```python
import torch

def _softmax(x, axis=-1):
    return torch.softmax(x, dim=axis)
def _gelu(x):
    return torch.nn.functional.gelu(x, approximate="tanh")
def _silu(x):
    return torch.nn.functional.silu(x)
def _sigmoid(x):
    return torch.sigmoid(x)
def _layernorm(x, axis=-1, eps=1e-5):
    m = x.mean(dim=axis, keepdim=True)
    v = x.var(dim=axis, keepdim=True, unbiased=False)
    return (x - m) / torch.sqrt(v + eps)
def _scatter_add(tgt, idx, src, axis=0):
    return tgt.clone().index_add_(axis, idx, src)
def _segment_sum(src, seg, n):
    out = torch.zeros((n,) + src.shape[1:], dtype=src.dtype)
    return out.index_add_(0, seg, src)
def _pad(x, pw):
    flat = tuple(v for pair in reversed(pw) for v in pair)
    return torch.nn.functional.pad(x, flat)

kernel_name = 'interleave_layers__sliding_block_cached__dense_activation_gelu__decode'

def setup_inputs():

    _w = (lambda a: (lambda t: t.to(torch.bfloat16) if t.is_floating_point() else t)(torch.as_tensor(a)))
    def _A_setup():
        B, Sq, D = 1, 1, 640
        Hq, Hkv, Sk, Dh = 32, 32, 32768, 192
        assert Hq % Hkv == 0, (Hq, Hkv)
        return {
            "x": _w((lambda *s: torch.randn(*s, dtype=torch.bfloat16) * 0.1)(B, Sq, D)),
            "k_cache": _w((lambda *s: torch.randn(*s, dtype=torch.bfloat16) * 0.8)(B, Hkv, Sk, Dh)),
            "v_cache": _w((lambda *s: torch.randn(*s, dtype=torch.bfloat16) * 1.6)(B, Hkv, Sk, Dh)),
            "wq": _w((lambda *s: torch.randn(*s, dtype=torch.bfloat16) * 0.8)(D, Hq * Dh) * (D ** -0.5)),
            "wo": _w((lambda *s: torch.randn(*s, dtype=torch.bfloat16) * 1.6)(Hq * Dh, D) * ((Hq * Dh) ** -0.5)),
        }
    _A_in = _A_setup()

    def _B_setup():
        B, S, D, F = 1, 1, 640, 1536
        return {
            "x": _w((lambda *s: torch.randn(*s, dtype=torch.bfloat16) * 0.1)(B, S, D)),
            "w1": _w((lambda *s: torch.randn(*s, dtype=torch.bfloat16) * 0.4)(D, F) * (D ** -0.5)),
            "b1": _w((lambda *s: torch.randn(*s, dtype=torch.bfloat16) * 0.4)(F) * 0.01),
            "w2": _w((lambda *s: torch.randn(*s, dtype=torch.bfloat16) * 0.4)(F, D) * (F ** -0.5)),
            "b2": _w((lambda *s: torch.randn(*s, dtype=torch.bfloat16) * 0.4)(D) * 0.01),
        }
    _B_in = _B_setup()

    return {
        "A_x": _A_in["x"],
        "A_k_cache": _A_in["k_cache"],
        "A_v_cache": _A_in["v_cache"],
        "A_wq": _A_in["wq"],
        "A_wo": _A_in["wo"],
        "B_x": _B_in["x"],
        "B_w1": _B_in["w1"],
        "B_b1": _B_in["b1"],
        "B_w2": _B_in["w2"],
        "B_b2": _B_in["b2"],
    }

def reference(A_x, A_k_cache, A_v_cache, A_wq, A_wo, B_x, B_w1, B_b1, B_w2, B_b2):
    def _A_ref(x, k_cache, v_cache, wq, wo):
        B, Sq, D = x.shape
        Hq, Dh = 32, 192
        Hkv, Sk = k_cache.shape[1], k_cache.shape[2]
        W = min(4096, max(256, Sk // 4))
        rep = Hq // Hkv
        q = (lambda x, *d: x.permute(*d))((x @ wq).reshape(B, Sq, Hq, Dh), 0, 2, 1, 3)
        k = (lambda x, n, axis: torch.repeat_interleave(x, n, dim=axis))(k_cache[:, :, Sk - W:, :], rep, axis=1)
        v = (lambda x, n, axis: torch.repeat_interleave(x, n, dim=axis))(v_cache[:, :, Sk - W:, :], rep, axis=1)
        scores = torch.einsum("bhqd,bhkd->bhqk", q, k) * (Dh ** -0.5)
        p = _softmax(scores, axis=-1)
        o = torch.einsum("bhqk,bhkd->bhqd", p, v)
        return (lambda x, *d: x.permute(*d))(o, 0, 2, 1, 3).reshape(B, Sq, Hq * Dh) @ wo

    def _B_ref(x, w1, b1, w2, b2):
        h = torch.einsum("bsd,df->bsf", x, w1) + b1
        h = _gelu(h)
        return torch.einsum("bsf,fd->bsd", h, w2) + b2

    x = A_x
    x = x + _A_ref(_layernorm(x, axis=-1), A_k_cache, A_v_cache, A_wq, A_wo)
    x = x + _B_ref(_layernorm(x, axis=-1), B_w1, B_b1, B_w2, B_b2)
    x = x + _A_ref(_layernorm(x, axis=-1), A_k_cache, A_v_cache, A_wq, A_wo)
    x = x + _B_ref(_layernorm(x, axis=-1), B_w1, B_b1, B_w2, B_b2)
    return x
```

```cpp
#include <cuda_runtime.h>
#include <cuda_bf16.h>
#include <cuda.h>
#include <stdint.h>

namespace {

constexpr int D_MODEL = 640, NHEAD = 32, SK = 32768, DH = 192, WIN = 4096, DFF = 1536;
constexpr int NCTA = 128, NTHR = 256;
constexpr int TILE = 64 * DH * 2;
constexpr int HALF = TILE / 2;
constexpr int SUB = 8 * DH * 2;
constexpr int SM_RING = 4 * TILE;
constexpr int SM_W2 = SM_RING + 20480, SM_W1 = SM_W2 + 20480;
constexpr int SM_WQR = 6 * TILE + HALF, SM_WQ = 7 * TILE;
constexpr int SM_PART = 9 * TILE;
constexpr int SM_EXC = SM_PART + 6144;
constexpr int SM_SC = SM_EXC + 1024;
constexpr int SM_BAR = SM_SC + 1024;
constexpr int SM_VEC = SM_BAR + 768;
constexpr int SM_CS = SM_VEC + 384;
constexpr int SM_FAC = SM_CS + 768;
constexpr int SM_GW = SM_FAC + 32;
constexpr int SM_ML = SM_GW + 16;
constexpr int SM_B1 = SM_ML + 64;
constexpr int SM_STAT = SM_B1 + 64;
constexpr int NCB = 26;
constexpr int CB_SNAP = 16, CB_WO = 18, CB_W1 = 23, CB_W2 = 24, CB_Q = 25;
constexpr int SM_CBAR = SM_STAT + 40;
constexpr int SM_CNT = SM_CBAR + NCB * 8;
constexpr int SM_EPOCH = SM_CNT + NCB * 8;
constexpr int SM_FXS = SM_EPOCH + 4;
constexpr int SM_T0 = SM_FXS + 4;
constexpr int SM_ZERO = SM_T0 + 4;
constexpr int SM_TS = SM_ZERO + 4;
constexpr int SM_TOTAL = 232448;
static_assert(SM_TS + 320 <= SM_TOTAL, "smem");
constexpr int NEXC = 16;

constexpr int SPIN = 1 << 20;
enum { TM_KH = 0, TM_VH = 1, TM_WO = 2, TM_VP = 3, TM_WOP = 4, TM_V = 5, TM_WQ = 6, TM_W1 = 7, TM_W2 = 8 };
constexpr uint32_t POL_NORMAL = 0x16F00000u, POL_FIRST = 0x12F00000u;

#define PACE 990
#define PACE0 1600
#define NI0 2
#define NI1 6
#define ETRIG 0x4321000
#define LATEAT 4
#define HWAT 11
#define PFREE 67
#define PF1 9
#define PF2 3
#define PFPOL POL_NORMAL
#define W1AT0 3
#define W1AT1 4
#define AR1D 300
#define SNAPAT 2
#define DMASK 0x7
#define WOKEEP 0x1f
#define VORD2 0x3456789a2b1c0defull
#define VTRIG 0xba97210
#define WOAT 12
#define PARK0 6
#define PARK1 10
#define S0EARLY 0
#define NPRE 2
#define ARDELAY 450
#define QDELAY 180
#define CMAP 6
#define PFW 8u
#define PUBAT 25
#define ZCHK 30
#define FX2LIM 524288.f
#define PROMOW 2
#define PROMO1 0
#define TB 2
#define WD1 300
#define WG1 140
#define WD2 0
#define WG2 140
#define WPOL POL_NORMAL

constexpr uint32_t G_A = 1u << 28, G_B = 1u << 29, G_C = 1u << 30;
__host__ __device__ constexpr int ring_hs(int j) { return (j + 4) % 5; }
__host__ __device__ constexpr uint32_t load_word(int j) {
    if (j >= 64) return (uint32_t)(j - 64) << 20 | (SM_RING + ring_hs(j) * HALF) | TM_WO << 8 | (CB_WO + j - 64) << 3 | 2 | !(WOKEEP >> (j - 64) & 1);
    const int e = j >> 1, isv = e >= 16, unit = e & 15;
    return (uint32_t)(unit * 256 + (j & 1) * 32) << 20 | (j < 6 ? j * HALF : SM_RING + ring_hs(j) * HALF) | isv << 8 | (j < 6 ? 10 + j : (j - 6) % 10) << 3 | 2
           | (!isv || (DMASK >> unit & 1));
}
struct Step { int unit, slot, par, next, mma0, nmma; };
struct Sched { uint32_t tile[64][3]; Step st[16]; };
constexpr Sched make_sched() {
    Sched s{};
    for (int j = 0; j < 64; j++) {
        const int e = j >> 1;
        const uint32_t d = load_word(j);
        uint32_t w = (uint32_t)(j < 6 ? 0 : (j - 6) / 10 & 1) << 31 | (e & 15) * 16 << 20 | ((d & 0x3f000) - (j & 1) * HALF) | (d & 0xf8);
        if (e == PUBAT || e == SNAPAT) w |= G_A;
        if (e == ZCHK || e == 3) w |= G_B;
        if (e >= LATEAT && e < LATEAT + 3) w |= G_C;
        s.tile[j][0] = w;
    }
    for (int j = NI1; j < 69; j++) {
        const int at = j < 11 ? (ETRIG >> (4 * (j - 4)) & 15) : j - 5;
        s.tile[at][1] = load_word(j);
        s.tile[at][2] = j >= PFREE ? 0 : PACE0 + j * PACE / 2;
    }
    const int slot[16] = {4, 5, 7, 6, 8, 0, 1, 2, 3, 4, 5, 7, 8, 0, 1, 2};
    int done = 0;
    for (int p = 0; p < 16; p++) {
        Step& c = s.st[p];
        c.unit = (int)(VORD2 >> (4 * p) & 15); c.slot = slot[p]; c.par = p >= 9; c.next = -1;
        c.mma0 = done;
        if (p >= 2) { c.nmma = p == 15 ? 16 - done : (p - done < 2 ? p - done : 2); done += c.nmma; }
    }
    for (int p = 9; p < 16; p++) s.st[VTRIG >> (4 * (p - 9)) & 15].next = p;
    return s;
}
constexpr Sched SCH = make_sched();
__host__ __device__ constexpr int kunit(int o) { return o < 5 ? o + 11 : o == 5 ? 10 : o - 6; }

template <int I> struct IC { static constexpr int value = I; };
template <uint32_t I> struct UC { static constexpr uint32_t value = I; };
template <int A, int B, class F> __device__ __forceinline__ void static_for(F&& f) {
    if constexpr (A < B) { f(IC<A>{}); static_for<A + 1, B>(f); }
}

struct Params {
    CUtensorMap tm[9];
    const __nv_bfloat16 *x, *k, *b1, *b2, *w1, *w2;
    __nv_bfloat16* out;
    uint4 tile[66];
};

typedef unsigned long long u64;
constexpr int ACC_PITCH = 256;
constexpr int ACC_BYTES = 80 * ACC_PITCH;
__device__ __align__(1024) unsigned char g_acc[4 * ACC_BYTES];
__device__ __align__(1024) u64 g_ll[3][NCTA][256];
__device__ unsigned g_epoch;
__device__ __align__(128) unsigned g_zflag;
#define TSTAMP(i)
#define TSTAMP2(i)
#define TSTAMPL(i)
#define TDUMP()
#define TRACE(i)

__device__ __forceinline__ void mbar_wait(uint32_t bar, uint32_t parity) {
    asm volatile("{\n.reg .pred p, q;\n.reg .u32 n;\nmov.u32 n, 0;\n"
                 "LOOP:\nmbarrier.try_wait.parity.shared::cta.b64 p, [%0], %1;\n"
                 "add.u32 n, n, 1;\nsetp.lt.and.u32 q, n, 0x100000, !p;\n@q bra.uni LOOP;\n}"
                 :: "r"(bar), "r"(parity) : "memory");
}
__device__ __forceinline__ bool mbar_test(uint32_t bar, uint32_t parity) {
    uint32_t r;
    asm volatile("{\n.reg .pred p;\nmbarrier.test_wait.parity.shared::cta.b64 p, [%1], %2;\nselp.u32 %0, 1, 0, p;\n}" : "=r"(r) : "r"(bar), "r"(parity) : "memory");
    return __all_sync(~0u, r);
}
__device__ __forceinline__ bool elect() {
    uint32_t r;
    asm volatile("{\n.reg .pred p;\nelect.sync _|p, 0xffffffff;\nselp.u32 %0, 1, 0, p;\n}" : "=r"(r));
    return r != 0;
}
__device__ __forceinline__ void mbar_expect(uint32_t bar, uint32_t bytes) {
    asm volatile("mbarrier.arrive.expect_tx.shared::cta.b64 _, [%0], %1;" :: "r"(bar), "r"(bytes) : "memory");
}
__device__ __forceinline__ uint4 lds128(uint32_t a) {
    uint4 v; asm volatile("ld.shared.v4.u32 {%0,%1,%2,%3}, [%4];" : "=r"(v.x), "=r"(v.y), "=r"(v.z), "=r"(v.w) : "r"(a) : "memory"); return v;
}
__device__ __forceinline__ uint4 ldsm_t(uint32_t a) {
    uint4 v; asm volatile("ldmatrix.sync.aligned.m8n8.x4.trans.shared.b16 {%0,%1,%2,%3}, [%4];" : "=r"(v.x), "=r"(v.y), "=r"(v.z), "=r"(v.w) : "r"(a) : "memory"); return v;
}
__device__ __forceinline__ uint2 lds64(uint32_t a) {
    uint2 v; asm volatile("ld.shared.v2.u32 {%0,%1}, [%2];" : "=r"(v.x), "=r"(v.y) : "r"(a) : "memory"); return v;
}
__device__ __forceinline__ float2 lds64f(uint32_t a) { const uint2 v = lds64(a); return make_float2(__uint_as_float(v.x), __uint_as_float(v.y)); }
__device__ __forceinline__ uint32_t lds32(uint32_t a) {
    uint32_t v; asm volatile("ld.shared.u32 %0, [%1];" : "=r"(v) : "r"(a) : "memory"); return v;
}
__device__ __forceinline__ float ldsf(uint32_t a) { return __uint_as_float(lds32(a)); }
__device__ __forceinline__ void sts32(uint32_t a, uint32_t v) { asm volatile("st.shared.u32 [%0], %1;" :: "r"(a), "r"(v) : "memory"); }
__device__ __forceinline__ void stsf(uint32_t a, float v) { sts32(a, __float_as_uint(v)); }
__device__ __forceinline__ void sts16(uint32_t a, uint32_t v) { asm volatile("st.shared.u16 [%0], %1;" :: "r"(a), "h"((uint16_t)v) : "memory"); }
__device__ __forceinline__ void sts64(uint32_t a, uint32_t x, uint32_t y) { asm volatile("st.shared.v2.u32 [%0], {%1,%2};" :: "r"(a), "r"(x), "r"(y) : "memory"); }
__device__ __forceinline__ void sts64f(uint32_t a, float x, float y) { sts64(a, __float_as_uint(x), __float_as_uint(y)); }
__device__ __forceinline__ void sts128f(uint32_t a, float x, float y, float z, float w) {
    asm volatile("st.shared.v4.f32 [%0], {%1,%2,%3,%4};" :: "r"(a), "f"(x), "f"(y), "f"(z), "f"(w) : "memory");
}
__device__ __forceinline__ void mma(float (&c)[4], const uint4& a, uint32_t b0, uint32_t b1) {
    asm volatile("mma.sync.aligned.m16n8k16.row.col.f32.bf16.bf16.f32 {%0,%1,%2,%3}, {%4,%5,%6,%7}, {%8,%9}, {%0,%1,%2,%3};"
                 : "+f"(c[0]), "+f"(c[1]), "+f"(c[2]), "+f"(c[3]) : "r"(a.x), "r"(a.y), "r"(a.z), "r"(a.w), "r"(b0), "r"(b1));
}
__device__ __forceinline__ u64 ld_rlx(const void* p) {
    u64 a; asm volatile("ld.relaxed.gpu.global.u64 %0, [%1];" : "=l"(a) : "l"(p) : "memory"); return a;
}
__device__ __forceinline__ void ld_rlx2(const void* p, u64& a, u64& b) {
    asm volatile("ld.relaxed.gpu.global.v2.u64 {%0,%1}, [%2];" : "=l"(a), "=l"(b) : "l"(p) : "memory");
}
__device__ __forceinline__ void st_rlx(void* p, u64 a) { asm volatile("st.relaxed.gpu.global.u64 [%0], %1;" :: "l"(p), "l"(a) : "memory"); }
__device__ __forceinline__ u64 ll_pack(float v, uint32_t tag) { return ((u64)tag << 32) | __float_as_uint(v); }
__device__ __forceinline__ float ll_val(u64 w) { return __uint_as_float((uint32_t)w); }
__device__ __forceinline__ uint32_t ll_tag(u64 w) { return (uint32_t)(w >> 32); }
__device__ __forceinline__ float bf_lo(uint32_t u) { return __uint_as_float(u << 16); }
__device__ __forceinline__ float bf_hi(uint32_t u) { return __uint_as_float(u & 0xffff0000u); }
__device__ __forceinline__ uint32_t pack_bf(float lo, float hi) {
    uint32_t r; asm("cvt.rn.bf16x2.f32 %0, %1, %2;" : "=r"(r) : "f"(hi), "f"(lo)); return r;
}
__device__ __forceinline__ float ex2(float v) { float r; asm("ex2.approx.ftz.f32 %0, %1;" : "=f"(r) : "f"(v)); return r; }
__device__ __forceinline__ float rcp(float v) { float r; asm("rcp.approx.ftz.f32 %0, %1;" : "=f"(r) : "f"(v)); return r; }
__device__ __forceinline__ float rsq(float v) { float r; asm("rsqrt.approx.ftz.f32 %0, %1;" : "=f"(r) : "f"(v)); return r; }
__device__ __forceinline__ void bar_sync(int id, int n) { asm volatile("bar.sync %0, %1;" :: "r"(id), "r"(n) : "memory"); }
__device__ __forceinline__ uint32_t clk() { uint32_t c; asm volatile("mov.u32 %0, %clock;" : "=r"(c)); return c; }
__device__ __forceinline__ void spin(uint32_t cycles) { const uint32_t c0 = clk(); while (clk() - c0 < cycles); }
__device__ __forceinline__ uint32_t pin(uint32_t v) { return __shfl_xor_sync(~0u, v, 0); }
__device__ __forceinline__ float shx(float v, int o) { return __shfl_xor_sync(~0u, v, o); }

__device__ __forceinline__ u64 fx_pack(float v, float scale) { return ((u64)__float2ll_rn(v * scale) & ~255ull) | 1ull; }
__device__ __forceinline__ float fx_scale(float meansq) {
    const int e = max(((int)(__float_as_uint(meansq) >> 23) - 127) >> 1, -6);
    return __uint_as_float((uint32_t)(127 + 32 - e) << 23);
}
__device__ __forceinline__ float fx_inv(float scale) { return __uint_as_float((254u << 23) - __float_as_uint(scale)); }
__device__ __forceinline__ uint32_t lo32(u64 w) { uint32_t l; asm("mov.b64 {%0, _}, %1;" : "=r"(l) : "l"(w)); return l; }
__device__ __forceinline__ int hi32(u64 w) { int h; asm("mov.b64 {_, %0}, %1;" : "=r"(h) : "l"(w)); return h; }
__device__ __forceinline__ float fx_val(u64 w) { return (float)hi32(w) * 4294967296.f + (float)lo32(w); }
template <int N>
__device__ __forceinline__ void fx_poll(const unsigned char* ap, uint32_t bit, u64 (&w)[N]) {
#pragma unroll 1
    for (int it = 0; it < SPIN; it++) {
        uint32_t m = bit;
#pragma unroll
        for (int k = 0; k < N; k++) w[k] = ld_rlx(ap + k * (80 / N) * ACC_PITCH);
#pragma unroll
        for (int k = 0; k < N; k++) m &= lo32(w[k]);
        if (__all_sync(~0u, m == bit)) break;
    }
}
__device__ __forceinline__ u64 fx2_pack(float a, float b) {
    const int ia = __float_as_int(a + 12582912.f) - 0x4b400000, ib = __float_as_int(b + 12582912.f) - 0x4b400000;
    return (u64)(uint32_t)(ia * 512 + 1) | (u64)(uint32_t)(ib * 16 + (ia >> 23)) << 32;
}
__device__ __forceinline__ float fx2_lo(u64 w) { return (float)((int)(__funnelshift_r(lo32(w), hi32(w), 9) << 5) >> 5); }
__device__ __forceinline__ float fx2_hi(u64 w) { return (float)((hi32(w) + 8) >> 4); }

__device__ __forceinline__ void tma3(uint32_t dst, const CUtensorMap* tm, int c1, int c2, uint32_t bar, uint32_t pol) {
    asm volatile("cp.async.bulk.tensor.3d.shared::cluster.global.mbarrier::complete_tx::bytes.L2::cache_hint [%0], [%1, {%2, %3, %4}], [%5], %6;"
                 :: "r"(dst), "l"(tm), "r"(0), "r"(c1), "r"(c2), "r"(bar), "l"((u64)pol << 32) : "memory");
}
__device__ __forceinline__ void tma3_pf(const CUtensorMap* tm, int c1, int c2, uint32_t pol) {
    asm volatile("cp.async.bulk.prefetch.tensor.3d.L2.global.tile.L2::cache_hint [%0, {%1, %2, %3}], %4;"
                 :: "l"(tm), "r"(0), "r"(c1), "r"(c2), "l"((u64)pol << 32) : "memory");
}
__device__ __forceinline__ void issue_half(uint32_t d, uint32_t sb, int rowc, int cta, const CUtensorMap* tm0) {
    const uint32_t bar = sb + SM_CBAR + (d & 0xf8);
    const CUtensorMap* tm = tm0 + ((d >> 8) & 3);
    const int c1 = (d & 0x200) ? 5 * (cta & 3) + (d >> 20) : 0, c2 = (d & 0x200) ? (cta >> 2) * DH : rowc + (d >> 20);
    mbar_expect(bar, HALF);
    tma3(sb + (d & 0x3f000), tm, c1, c2, bar, POL_FIRST);
    if (!(d & 1)) tma3_pf(tm + 2, c1, c2, POL_NORMAL);
}
__device__ __forceinline__ uint32_t cnt_inc(uint32_t a, uint32_t last) {
    uint32_t old; asm volatile("atom.relaxed.cta.shared.inc.u32 %0, [%1], %2;" : "=r"(old) : "r"(a), "r"(last) : "memory"); return old;
}
__device__ __forceinline__ void wait_until(uint32_t due) {
#pragma unroll 1
    for (int it = 0; it < 4096; it++) { uint32_t now; asm volatile("mov.u32 %0, %globaltimer_lo;" : "=r"(now)); if ((int)(now - due) >= 0) break; }
}
__device__ __forceinline__ uint32_t bf2_mul(uint32_t a, uint32_t b) { uint32_t r; asm("mul.rn.bf16x2 %0, %1, %2;" : "=r"(r) : "r"(a), "r"(b)); return r; }
__device__ __forceinline__ uint32_t bf2_fma(uint32_t a, uint32_t b, uint32_t c) { uint32_t r; asm("fma.rn.bf16x2 %0, %1, %2, %3;" : "=r"(r) : "r"(a), "r"(b), "r"(c)); return r; }
__device__ __forceinline__ uint32_t bf2_amax(uint32_t a, uint32_t b) { uint32_t r; asm("max.NaN.xorsign.abs.bf16x2 %0, %1, %2;" : "=r"(r) : "r"(a), "r"(b)); return r; }
__device__ __forceinline__ uint4 k_unpack(uint32_t l0, uint32_t l1, uint32_t h) {
    const uint32_t ha = h & 0x87878787u, hb = __funnelshift_l(h, h, 4) & 0x87878787u;
    return make_uint4(__byte_perm(l0, ha, 0x5140), __byte_perm(l0, ha, 0x7362), __byte_perm(l1, hb, 0x5140), __byte_perm(l1, hb, 0x7362));
}
#define KR4(u, i) "+r"(kr[u][i].x), "+r"(kr[u][i].y), "+r"(kr[u][i].z), "+r"(kr[u][i].w)
#define KR6(u) KR4(u, 0), KR4(u, 1), KR4(u, 2), KR4(u, 3), KR4(u, 4), KR4(u, 5)
__device__ __forceinline__ void k_keep(uint4 (&kr)[8][6], const uint32_t (&c)[18], int e, uint32_t a) {
    asm volatile("{\nKT: .branchtargets K0, K1, K2, K3, K4, K5, K6, K7, K8, K9, K10, K11, K12, K13, K14, K15;\nbrx.idx.uni %210, KT;\n"
                 "K0: mov.b32 %12, %192; mov.b32 %13, %193; mov.b32 %14, %194; mov.b32 %15, %195; mov.b32 %16, %196; mov.b32 %17, %197; mov.b32 %18, %198; mov.b32 %19, %199; mov.b32 %20, %200; mov.b32 %21, %201; mov.b32 %22, %202; mov.b32 %23, %203; mov.b32 %24, %204; mov.b32 %25, %205; mov.b32 %26, %206; mov.b32 %27, %207; mov.b32 %28, %208; mov.b32 %29, %209; bra.uni KE;\n"
                 "K1: mov.b32 %30, %192; mov.b32 %31, %193; mov.b32 %32, %194; mov.b32 %33, %195; mov.b32 %34, %196; mov.b32 %35, %197; mov.b32 %36, %198; mov.b32 %37, %199; mov.b32 %38, %200; mov.b32 %39, %201; mov.b32 %40, %202; mov.b32 %41, %203; mov.b32 %42, %204; mov.b32 %43, %205; mov.b32 %44, %206; mov.b32 %45, %207; mov.b32 %46, %208; mov.b32 %47, %209; bra.uni KE;\n"
                 "K2: mov.b32 %48, %192; mov.b32 %49, %193; mov.b32 %50, %194; mov.b32 %51, %195; mov.b32 %52, %196; mov.b32 %53, %197; mov.b32 %54, %198; mov.b32 %55, %199; mov.b32 %56, %200; mov.b32 %57, %201; mov.b32 %58, %202; mov.b32 %59, %203; mov.b32 %60, %204; mov.b32 %61, %205; mov.b32 %62, %206; mov.b32 %63, %207; mov.b32 %64, %208; mov.b32 %65, %209; bra.uni KE;\n"
                 "K3: mov.b32 %66, %192; mov.b32 %67, %193; mov.b32 %68, %194; mov.b32 %69, %195; mov.b32 %70, %196; mov.b32 %71, %197; mov.b32 %72, %198; mov.b32 %73, %199; mov.b32 %74, %200; mov.b32 %75, %201; mov.b32 %76, %202; mov.b32 %77, %203; mov.b32 %78, %204; mov.b32 %79, %205; mov.b32 %80, %206; mov.b32 %81, %207; mov.b32 %82, %208; mov.b32 %83, %209; bra.uni KE;\n"
                 "K4: mov.b32 %84, %192; mov.b32 %85, %193; mov.b32 %86, %194; mov.b32 %87, %195; mov.b32 %88, %196; mov.b32 %89, %197; mov.b32 %90, %198; mov.b32 %91, %199; mov.b32 %92, %200; mov.b32 %93, %201; mov.b32 %94, %202; mov.b32 %95, %203; mov.b32 %96, %204; mov.b32 %97, %205; mov.b32 %98, %206; mov.b32 %99, %207; mov.b32 %100, %208; mov.b32 %101, %209; bra.uni KE;\n"
                 "K5: mov.b32 %102, %192; mov.b32 %103, %193; mov.b32 %104, %194; mov.b32 %105, %195; mov.b32 %106, %196; mov.b32 %107, %197; mov.b32 %108, %198; mov.b32 %109, %199; mov.b32 %110, %200; mov.b32 %111, %201; mov.b32 %112, %202; mov.b32 %113, %203; mov.b32 %114, %204; mov.b32 %115, %205; mov.b32 %116, %206; mov.b32 %117, %207; mov.b32 %118, %208; mov.b32 %119, %209; bra.uni KE;\n"
                 "K6: mov.b32 %120, %192; mov.b32 %121, %193; mov.b32 %122, %194; mov.b32 %123, %195; mov.b32 %124, %196; mov.b32 %125, %197; mov.b32 %126, %198; mov.b32 %127, %199; mov.b32 %128, %200; mov.b32 %129, %201; mov.b32 %130, %202; mov.b32 %131, %203; mov.b32 %132, %204; mov.b32 %133, %205; mov.b32 %134, %206; mov.b32 %135, %207; mov.b32 %136, %208; mov.b32 %137, %209; bra.uni KE;\n"
                 "K7: mov.b32 %138, %192; mov.b32 %139, %193; mov.b32 %140, %194; mov.b32 %141, %195; mov.b32 %142, %196; mov.b32 %143, %197; mov.b32 %144, %198; mov.b32 %145, %199; mov.b32 %146, %200; mov.b32 %147, %201; mov.b32 %148, %202; mov.b32 %149, %203; mov.b32 %150, %204; mov.b32 %151, %205; mov.b32 %152, %206; mov.b32 %153, %207; mov.b32 %154, %208; mov.b32 %155, %209; bra.uni KE;\n"
                 "K8: mov.b32 %156, %192; mov.b32 %157, %193; mov.b32 %158, %194; mov.b32 %159, %195; mov.b32 %160, %196; mov.b32 %161, %197; mov.b32 %162, %198; mov.b32 %163, %199; mov.b32 %164, %200; mov.b32 %165, %201; mov.b32 %166, %202; mov.b32 %167, %203; mov.b32 %168, %204; mov.b32 %169, %205; mov.b32 %170, %206; mov.b32 %171, %207; mov.b32 %172, %208; mov.b32 %173, %209; bra.uni KE;\n"
                 "K9: mov.b32 %174, %192; mov.b32 %175, %193; mov.b32 %176, %194; mov.b32 %177, %195; mov.b32 %178, %196; mov.b32 %179, %197; mov.b32 %180, %198; mov.b32 %181, %199; mov.b32 %182, %200; mov.b32 %183, %201; mov.b32 %184, %202; mov.b32 %185, %203; mov.b32 %186, %204; mov.b32 %187, %205; mov.b32 %188, %206; mov.b32 %189, %207; mov.b32 %190, %208; mov.b32 %191, %209; bra.uni KE;\n"
                 "K10: st.shared.v2.b32 [%211+75784], {%192, %193}; st.shared.v4.b32 [%211+76288], {%194, %195, %196, %197}; mov.b32 %0, %198; mov.b32 %1, %199; mov.b32 %2, %200; mov.b32 %3, %201; mov.b32 %4, %202; mov.b32 %5, %203; mov.b32 %6, %204; mov.b32 %7, %205; mov.b32 %8, %206; mov.b32 %9, %207; mov.b32 %10, %208; mov.b32 %11, %209; bra.uni KE;\n"
                 "K11: st.shared.v4.b32 [%211+0], {%192, %193, %194, %195}; st.shared.v4.b32 [%211+512], {%196, %197, %198, %199}; st.shared.v4.b32 [%211+1024], {%200, %201, %202, %203}; st.shared.v4.b32 [%211+1536], {%204, %205, %206, %207}; st.shared.v2.b32 [%211+2048], {%208, %209}; bra.uni KE;\n"
                 "K12: st.shared.v2.b32 [%211+2056], {%192, %193}; st.shared.v4.b32 [%211+2560], {%194, %195, %196, %197}; st.shared.v4.b32 [%211+24576], {%198, %199, %200, %201}; st.shared.v4.b32 [%211+25088], {%202, %203, %204, %205}; st.shared.v4.b32 [%211+25600], {%206, %207, %208, %209}; bra.uni KE;\n"
                 "K13: st.shared.v4.b32 [%211+26112], {%192, %193, %194, %195}; st.shared.v4.b32 [%211+26624], {%196, %197, %198, %199}; st.shared.v4.b32 [%211+27136], {%200, %201, %202, %203}; st.shared.v4.b32 [%211+49152], {%204, %205, %206, %207}; st.shared.v2.b32 [%211+49664], {%208, %209}; bra.uni KE;\n"
                 "K14: st.shared.v2.b32 [%211+49672], {%192, %193}; st.shared.v4.b32 [%211+50176], {%194, %195, %196, %197}; st.shared.v4.b32 [%211+50688], {%198, %199, %200, %201}; st.shared.v4.b32 [%211+51200], {%202, %203, %204, %205}; st.shared.v4.b32 [%211+51712], {%206, %207, %208, %209}; bra.uni KE;\n"
                 "K15: st.shared.v4.b32 [%211+73728], {%192, %193, %194, %195}; st.shared.v4.b32 [%211+74240], {%196, %197, %198, %199}; st.shared.v4.b32 [%211+74752], {%200, %201, %202, %203}; st.shared.v4.b32 [%211+75264], {%204, %205, %206, %207}; st.shared.v2.b32 [%211+75776], {%208, %209}; \nKE:\n}"
                 : KR6(0), KR6(1), KR6(2), KR6(3), KR6(4), KR6(5), KR6(6), KR6(7)
                 : "r"(c[0]), "r"(c[1]), "r"(c[2]), "r"(c[3]), "r"(c[4]), "r"(c[5]), "r"(c[6]), "r"(c[7]), "r"(c[8]), "r"(c[9]), "r"(c[10]), "r"(c[11]), "r"(c[12]), "r"(c[13]), "r"(c[14]), "r"(c[15]), "r"(c[16]), "r"(c[17]), "r"(e), "r"(a) : "memory");
}
template <int K> __device__ __forceinline__ uint32_t& word(uint4& v) { if constexpr (K == 0) return v.x; else if constexpr (K == 1) return v.y; else if constexpr (K == 2) return v.z; else return v.w; }
__device__ __forceinline__ void add_if(bool p, float& d, float a, float b) {
    asm volatile("{\n.reg .pred p;\nsetp.ne.u32 p, %3, 0;\n@p add.f32 %0, %1, %2;\n}" : "+f"(d) : "f"(a), "f"(b), "r"((uint32_t)p));
}
__device__ __forceinline__ float warp_max(float v) {
#pragma unroll
    for (int o = 16; o; o >>= 1) v = fmaxf(v, shx(v, o));
    return v;
}
__device__ __forceinline__ float warp_sum(float v) {
#pragma unroll
    for (int o = 16; o; o >>= 1) v += shx(v, o);
    return v;
}
__device__ __forceinline__ float ll_gather4(const u64* buf, uint32_t tag, u64 w0, u64 w1, u64 w2, u64 w3) {
#pragma unroll 1
    for (int it = 0; it < SPIN; it++) {
        if (__all_sync(~0u, ll_tag(w0) == tag && ll_tag(w1) == tag && ll_tag(w2) == tag && ll_tag(w3) == tag)) break;
        w0 = ld_rlx(buf); w1 = ld_rlx(buf + 256); w2 = ld_rlx(buf + 512); w3 = ld_rlx(buf + 768);
    }
    return (ll_val(w0) + ll_val(w1)) + (ll_val(w2) + ll_val(w3));
}
__device__ __forceinline__ float sum8(uint32_t a, int pitch) {
    float s[8];
#pragma unroll
    for (int w = 0; w < 8; w++) s[w] = ldsf(a + w * pitch);
    return ((s[0] + s[1]) + (s[2] + s[3])) + ((s[4] + s[5]) + (s[6] + s[7]));
}
__host__ __device__ constexpr int hp_off(int w) { return SM_PART + w * 160; }
template <bool HP>
__device__ __forceinline__ void ln_final(uint32_t a, float& mean, float& rstd, float& msq) {
    float2 v[5];
#pragma unroll
    for (int w = 0; w < 5; w++) v[w] = lds64f(a + (HP ? hp_off(w) : w * 8));
    mean = (((v[0].x + v[1].x) + (v[2].x + v[3].x)) + v[4].x) * (1.f / D_MODEL);
    msq = (((v[0].y + v[1].y) + (v[2].y + v[3].y)) + v[4].y) * (1.f / D_MODEL);
    rstd = rsq(fmaxf(msq - mean * mean, 0.f) + 1e-5f);
}
constexpr float CS = 0.07216878364870322f * 1.4426950408889634f;
constexpr uint32_t ONES = 0x3f803f80u;

__global__ void __launch_bounds__(NTHR, 1) fused_kernel(const __grid_constant__ Params P) {
    extern __shared__ __align__(1024) unsigned char smem[];
    const uint32_t sb = (uint32_t)__cvta_generic_to_shared(smem);
    const int tid = pin(threadIdx.x), lane = tid & 31, warp = __shfl_sync(~0u, threadIdx.x >> 5, 0);
    const int g = lane >> 2, t = lane & 3, bx = blockIdx.x;
    const int cta = bx >= NCTA || CMAP == 0 ? bx : CMAP == 1 ? (bx & 31) * 4 + (bx >> 5) : CMAP == 2 ? ((bx >> 1) & 31) * 4 + (bx >> 6) * 2 + (bx & 1)
                  : CMAP == 3 ? (((bx >> 2) & 3) * 8 + (bx >> 4)) * 4 + (bx & 3) : CMAP == 4 ? (((bx >> 1) & 7) + (bx >> 5) * 8) * 4 + ((bx >> 4) & 1) * 2 + (bx & 1)
                  : CMAP == 5 ? ((bx & 15) + (bx >> 6) * 16) * 4 + ((bx >> 4) & 3) : (((bx >> 1) & 15) + (bx >> 6) * 16) * 4 + ((bx >> 5) & 1) * 2 + (bx & 1);

    if (cta == NCTA) {
        const uint32_t ep = *(volatile unsigned*)&g_epoch;
        if (tid == 0) {
#pragma unroll 1
            for (int it = 0; it < SPIN; it++) { if (ll_tag(ld_rlx(&g_ll[1][0][192])) == ep * 4 + 2) break; __nanosleep(200); }
        }
        __syncthreads();
#pragma unroll 1
        for (int i = tid; i < 4 * 80 * 8; i += NTHR)
            *reinterpret_cast<uint4*>(g_acc + (i >> 3) * ACC_PITCH + (i & 7) * 16) = make_uint4(0, 0, 0, 0);
        __threadfence();
        __syncthreads();
        if (tid == 0) asm volatile("st.relaxed.gpu.global.u32 [%0], %1;" :: "l"(&g_zflag), "r"(ep + 1) : "memory");
        return;
    }
    TSTAMP(0);
    if (tid == 64) { uint32_t now; asm volatile("mov.u32 %0, %globaltimer_lo;" : "=r"(now)); sts32(sb + SM_T0, now); }

    const int mlp = (cta & 3) == 3 ? 96 : (cta >> 2) * 3 + (cta & 3);
    const uint32_t barw = sb + SM_BAR + warp * 96, subw = sb + warp * SUB;
    const int rowc = (cta >> 2) * SK + (SK - WIN) + (cta & 3) * 64;
    const CUtensorMap* tmk = reinterpret_cast<const CUtensorMap*>(__shfl_sync(~0u, (u64)&P.tm[0] + (lane >> 5), 0));
    if (elect()) {
        asm volatile("mbarrier.init.shared::cta.b64 [%0], 1;" :: "r"(barw + 72));
        asm volatile("mbarrier.init.shared::cta.b64 [%0], 1;" :: "r"(sb + SM_CBAR + 64 + warp * 8));
        asm volatile("fence.proxy.async.shared::cta;" ::: "memory");
        mbar_expect(barw + 72, warp < 4 ? 3 * SUB : 2 * SUB);
        const int r0 = (cta & 3) * 160 + warp * 8;
        tma3(subw + SM_WQ, tmk + TM_WQ, (cta >> 2) * 3, r0, barw + 72, POL_FIRST);
        tma3(subw + SM_WQ + TILE, tmk + TM_WQ, (cta >> 2) * 3, r0 + 64, barw + 72, POL_FIRST);
        if (warp < 4) tma3(subw + SM_WQR, tmk + TM_WQ, (cta >> 2) * 3, r0 + 128, barw + 72, POL_FIRST);
        const uint32_t j = warp - 2;
        if (j < NI0) issue_half(((j >> 1) * 256 + (j & 1) * 32) << 20 | j * HALF | (10 + j) << 3 | 3, sb, rowc, cta, tmk);
#pragma unroll
        for (int i = 0; i < 9; i++) asm volatile("mbarrier.init.shared::cta.b64 [%0], 1;" :: "r"(barw + i * 8));
        asm volatile("mbarrier.init.shared::cta.b64 [%0], 1;" :: "r"(sb + SM_CBAR + warp * 8));
        asm volatile("mbarrier.init.shared::cta.b64 [%0], 1;" :: "r"(sb + SM_CBAR + 128 + warp * 8));
        if (warp < 2) asm volatile("mbarrier.init.shared::cta.b64 [%0], %1;" :: "r"(sb + SM_CBAR + 192 + warp * 8), "r"(1 + warp * 5));
        sts64(barw + 80, 0, 0);
        asm volatile("fence.proxy.async.shared::cta;" ::: "memory");
        asm volatile("prefetch.tensormap [%0];" :: "l"(tmk + warp + 1) : "memory");
    }
    __syncwarp();
    const int c4 = 32 * warp + 16 * (t >> 1) + 2 * g + (t & 1);
    const int j40 = __shfl_sync(~0u, (cta & 3) * 40, 0);
    uint2 xp = make_uint2(0, 0);
    if (tid < 160) asm volatile("ld.global.nc.v2.u32 {%0,%1}, [%2];" : "=r"(xp.x), "=r"(xp.y) : "l"(P.x + 4 * c4) : "memory");
    else if (tid == 255) { sts32(sb + SM_EPOCH, *(volatile unsigned*)&g_epoch); sts32(sb + SM_ZERO, 0); }
    else if (tid < 176) sts32(sb + SM_B1 + (tid - 160) * 4, (uint32_t)reinterpret_cast<const volatile unsigned short*>(P.b1)[min(mlp, 95) * 16 + tid - 160] << 16);
    else if (tid >= 192 && tid < 192 + NCB) sts32(sb + SM_CNT + (tid - 192) * 8, 0);
    unsigned char* accg = reinterpret_cast<unsigned char*>(__shfl_sync(~0u, (u64)g_acc + (lane >> 5), 0));
    auto release = [&](const uint4& tw) {
        uint32_t old;
        __syncwarp();
        asm volatile("{\n.reg .pred p;\nsetp.eq.u32 p, %2, 0;\nmov.u32 %0, 0;\n@p atom.relaxed.cta.shared.inc.u32 %0, [%1], 3;\n}"
                     : "=r"(old) : "r"(sb + SM_CNT + (tw.x & 0xf8)), "r"(lane) : "memory");
        return old;
    };
    auto refill = [&](const uint4& tw, uint32_t old) {
        if (__any_sync(~0u, old == 3 && (tw.y & 2))) {
            wait_until(lds32(sb + SM_T0) + tw.z);
            if (elect()) issue_half(tw.y, sb, rowc, cta, tmk);
            __syncwarp();
        }
    };
    __syncthreads();
    mbar_wait(barw + 72, 0);
    if (warp == 7 && elect()) static_for<NI0, NI1>([&](auto I) { issue_half(UC<load_word(I.value)>::value, sb, rowc, cta, tmk); });

    uint32_t offV0, offV2, maskA, maskB;
    auto calc_masks = [&](int ln) {
        const uint32_t m = (ln & 4) ? 0xffff0000u : 0x0000ffffu;
        maskA = (ln & 8) ? 0u : m; maskB = (ln & 8) ? m : 0u;
    };
    auto calc_offsets = [&](int ln) {
        const int gg = ln >> 2, tt = ln & 3;
        offV0 = subw + (6 * tt) * 128 + ((gg ^ ((6 * tt) & 7)) << 4);
        offV2 = subw + (6 * tt + 2) * 128 + ((gg ^ ((6 * tt + 2) & 7)) << 4);
    };
    calc_offsets(lane);
    calc_masks(lane);

    auto load_v = [&](uint4 (&v)[6], uint32_t so) {
        v[0] = lds128(offV0 + so); v[1] = lds128((offV0 ^ 16) + so + 128); v[2] = lds128(offV2 + so);
        v[3] = lds128((offV2 ^ 16) + so + 128); v[4] = lds128((offV0 ^ 64) + so + 512); v[5] = lds128((offV0 ^ 80) + so + 640);
    };
    const int roww = __shfl_sync(~0u, rowc + warp * 8, 0);
    auto issue_v = [&](auto I, int dw) {
        constexpr Step c = SCH.st[I.value];
        const uint32_t bar = barw + dw * 96 + c.slot * 8;
        mbar_expect(bar, SUB);
        tma3(subw + dw * SUB + c.slot * TILE, tmk + TM_V, 0, roww + dw * 8 + c.unit * 256, bar, POL_FIRST);
    };
    auto refill2 = [&](auto I) { __syncwarp(); if (elect()) issue_v(I, 0); };
    uint4 wq0[6];
    uint32_t xna;
    auto load_wq = [&]() {
        load_v(wq0, SM_WQ);
        const int r = c4 - j40;
        xna = pin((tid < 160 && r >= 0 && r < 40) ? sb + SM_VEC + r * 8 : 0u);
    };
    mbar_wait(sb + SM_BAR + (warp >> 1) * 96 + 72, 0);
    load_wq();
    uint4 kr[8][6];
#pragma unroll
    for (int u = 0; u < 8; u++)
#pragma unroll
        for (int i = 0; i < 6; i++) asm volatile("" : "=r"(kr[u][i].x), "=r"(kr[u][i].y), "=r"(kr[u][i].z), "=r"(kr[u][i].w));

#pragma unroll 1
    for (int layer = 0; layer < 2; layer++) {
        {
            if (xna) sts64(xna, xp.x, xp.y);
            uint4 wqh[3];
            const uint32_t so = SM_WQR - ((warp + 1) >> 1) * SUB;
            wqh[0] = lds128(((warp & 1) ? (offV2 ^ 16) + 128 : offV0) + so);
            wqh[1] = lds128(((warp & 1) ? (offV0 ^ 64) + 512 : (offV0 ^ 16) + 128) + so);
            wqh[2] = lds128(((warp & 1) ? (offV0 ^ 80) + 640 : offV2) + so);
            __syncthreads();
            TSTAMPL(20);
            const uint32_t pa = sb + SM_VEC + t * 4;
            uint32_t p0 = lds32(pa + warp * 16), p1 = lds32(pa + 128 + warp * 16), ph = lds32(pa + 256 + (warp >> 1) * 16);
            const float x0 = bf_lo(xp.x), x1 = bf_hi(xp.x), x2 = bf_lo(xp.y), x3 = bf_hi(xp.y);
            float s1 = (x0 + x1) + (x2 + x3), s2 = (x0 * x0 + x1 * x1) + (x2 * x2 + x3 * x3);
            s1 += shx(s1, 16); s2 += shx(s2, 16);
            if (g >= 4) p0 = p1 = ph = ONES;
            float acc[3][4];
            const uint32_t dH = __byte_perm(ph, 0, (warp & 1) ? 0x3232 : 0x1010);
#pragma unroll
            for (int j = 0; j < 3; j++) { acc[j][0] = acc[j][1] = acc[j][2] = acc[j][3] = 0.f; mma(acc[j], wqh[j], dH & maskA, dH & maskB); }
            s1 += shx(s1, 8); s2 += shx(s2, 8);
            const uint32_t dA = __byte_perm(p0, 0, 0x1010), dB = __byte_perm(p0, 0, 0x3232);
#pragma unroll
            for (int j = 0; j < 3; j++) mma(acc[j], wq0[j], dA & maskA, dA & maskB);
            wq0[0] = lds128(offV0 + SM_WQ + TILE); wq0[1] = lds128((offV0 ^ 16) + SM_WQ + TILE + 128); wq0[2] = lds128(offV2 + SM_WQ + TILE);
            wqh[0] = lds128((offV2 ^ 16) + SM_WQ + TILE + 128); wqh[1] = lds128((offV0 ^ 64) + SM_WQ + TILE + 512); wqh[2] = lds128((offV0 ^ 80) + SM_WQ + TILE + 640);
            s1 += shx(s1, 4); s2 += shx(s2, 4);
#pragma unroll
            for (int j = 0; j < 3; j++) mma(acc[j], wq0[j + 3], dB & maskA, dB & maskB);
            if (layer == 1) {
                if (warp >= 4) refill2(IC<3>{});
                refill2(IC<4>{});
            }
            s1 += shx(s1, 2); s2 += shx(s2, 2);
            const uint32_t dC = __byte_perm(p1, 0, 0x1010), dD = __byte_perm(p1, 0, 0x3232);
#pragma unroll
            for (int j = 0; j < 3; j++) mma(acc[j], wq0[j], dC & maskA, dC & maskB);
            s1 += shx(s1, 1); s2 += shx(s2, 1);
#pragma unroll
            for (int j = 0; j < 3; j++) mma(acc[j], wqh[j], dD & maskA, dD & maskB);
            if (t < 2 || layer == 0) {
                const uint32_t a = sb + (t < 2 ? SM_PART : 3 * TILE) + warp * 768 + (8 * g + 4 * (t & 1)) * 4;
#pragma unroll
                for (int j = 0; j < 3; j++) sts128f(a + j * 256, acc[j][0], acc[j][1], acc[j][2], acc[j][3]);
            }
            if (lane == 0 && warp < 5) sts64f(sb + SM_STAT + warp * 8, s1, s2);
            TSTAMPL(21);
            __syncthreads();
            TSTAMPL(22);
        }
        const uint32_t ep = lds32(sb + SM_EPOCH);
        if (tid < 192) {
            if (layer == 0) stsf(sb + SM_CS + tid * 4, sum8(sb + 3 * TILE + tid * 4, 768));
            const float s = sum8(sb + SM_PART + tid * 4, 768), cs = ldsf(sb + SM_CS + tid * 4);
            float mean, rstd, msq;
            ln_final<false>(sb + SM_STAT, mean, rstd, msq);
            st_rlx(&g_ll[layer][cta][tid], ll_pack((s - mean * cs) * rstd, ep * 4 + 1 + 2 * layer));
            if (tid == 0) stsf(sb + SM_FXS, fx_scale(msq));
        }
        TSTAMPL(23);
        __syncwarp();
        uint32_t offQ, offL;
        {
            const int ln = lane + lds32(sb + SM_ZERO);
            offQ = pin(sb + SM_VEC + (ln & 7) * 48);
            offL = pin(subw + ln * 16);
        }
        auto gather_q = [&](const u64 (&qw)[4], auto L) {
            const float q = ll_gather4(&g_ll[L.value][cta & ~3][tid], lds32(sb + SM_EPOCH) * 4 + 1 + 2 * L.value, qw[0], qw[1], qw[2], qw[3]) * (L.value ? 0x1p64f : 1.f);
            TSTAMPL(24);
            sts16(sb + SM_VEC + (((tid >> 1) & 1) * 4 + ((tid >> 3) & 3)) * 48 + (tid >> 5) * 8 + ((tid >> 2) & 1) * 4 + (tid & 1) * 2, pack_bf(q, q));
            __syncwarp();
            if (elect()) asm volatile("mbarrier.arrive.shared::cta.b64 _, [%0];" :: "r"(sb + SM_CBAR + CB_Q * 8) : "memory");
        };
        const uint32_t prow = sb + SM_PART + warp * 768;

        auto pf_w = [&](int at) {
            if ((PF1 == at || PF2 == at) && layer == 0 && (roww & 56) == 40 && elect()) {
                if (PF1 == at) asm volatile("cp.async.bulk.prefetch.L2.global.L2::cache_hint [%0], 15360, %1;" :: "l"(P.w1 + cta * 7680), "l"((u64)PFPOL << 32) : "memory");
                if (PF2 == at) asm volatile("cp.async.bulk.prefetch.L2.global.L2::cache_hint [%0], 15360, %1;" :: "l"(P.w2 + cta * 7680), "l"((u64)PFPOL << 32) : "memory");
            }
        };
        auto issue_w = [&](int which) {
            const uint32_t bar = sb + SM_CBAR + (CB_W1 + which) * 8;
            if (mlp == 96) asm volatile("mbarrier.arrive.shared::cta.b64 _, [%0];" :: "r"(bar) : "memory");
            else {
                mbar_expect(bar, 20480);
                if (which) tma3(sb + SM_W2, tmk + TM_W2, 0, mlp * 16, bar, WPOL);
                else asm volatile("cp.async.bulk.tensor.3d.shared::cluster.global.mbarrier::complete_tx::bytes.L2::cache_hint [%0], [%1, {%2, %3, %3}], [%4], %5;"
                                  :: "r"(sb + SM_W1), "l"(tmk + TM_W1), "r"(mlp * 16), "r"(0), "r"(bar), "l"((u64)WPOL << 32) : "memory");
            }
        };
        float acc[3][4];
        const int key = (g >> 1) + 4 * (g & 1);
        auto load_q = [&](uint4 (&qf)[3]) {
#pragma unroll
            for (int i = 0; i < 3; i++) qf[i] = lds128(offQ + i * 16);
        };
        auto score = [&](const uint4 (&v)[6], const uint4 (&qf)[3]) {
            float d[2][4];
#pragma unroll
            for (int j = 0; j < 2; j++) d[j][0] = d[j][1] = d[j][2] = d[j][3] = 0.f;
#pragma unroll
            for (int i = 0; i < 3; i++) { mma(d[0], v[2 * i], qf[i].x, qf[i].y); mma(d[1], v[2 * i + 1], qf[i].z, qf[i].w); }
            return (d[0][0] + d[0][3]) + (d[1][0] + d[1][3]);
        };
        auto softmax = [&](float S0, float S1, float S2, float S3) {
            const float mrun = warp_max(fmaxf(fmaxf(S0, S1), fmaxf(S2, S3)));
            const float p0 = ex2((S0 - mrun) * CS), p1 = ex2((S1 - mrun) * CS), p2 = ex2((S2 - mrun) * CS), p3 = ex2((S3 - mrun) * CS);
            const uint32_t pa = pack_bf(p0, p1), pb = pack_bf(p2, p3), pw = prow + 256 + t * 16 + key * 2;
            sts16(pw, pa); sts16(pw + 64, pa >> 16); sts16(pw + 128, pb); sts16(pw + 192, pb >> 16);
            const float l = warp_sum((p0 + p1) + (p2 + p3));
            if (layer == 1 && warp < 6) st_rlx(&g_ll[2][cta][tid], 0ull);
            uint32_t old = 0;
            if (lane == 0) {
                sts64f(sb + SM_ML + warp * 8, mrun, l);
                asm volatile("atom.acq_rel.cta.shared.inc.u32 %0, [%1], 7;" : "=r"(old) : "r"(sb + SM_CNT + CB_Q * 8) : "memory");
            }
            if (__any_sync(~0u, old == 7)) {
                __syncwarp();
                const float2 ml = lds64f(sb + SM_ML + (lane & 7) * 8);
                float M = fmaxf(ml.x, shx(ml.x, 1)); M = fmaxf(M, shx(M, 2)); M = fmaxf(M, shx(M, 4));
                const float f = ex2((ml.x - M) * CS);
                float L = f * ml.y; L += shx(L, 1); L += shx(L, 2); L += shx(L, 4);
                if (lane < 8) stsf(sb + SM_FAC + lane * 4, f);
                if (layer == 0) { if (lane == 0) sts64f(sb + SM_STAT, M, L); }
                else if (lane < 4) st_rlx(&g_ll[2][cta][192 + lane], ll_pack(lane == 0 ? M : L, lds32(sb + SM_EPOCH) * 4 + 4));
            }
            __syncwarp();
#pragma unroll
            for (int j = 0; j < 3; j++) acc[j][0] = acc[j][1] = acc[j][2] = acc[j][3] = 0.f;
        };
        auto head_weight = [&](u64 pm, u64 pl, auto L) {
            const uint32_t tag = lds32(sb + SM_EPOCH) * 4 + 2 + 2 * L.value;
#pragma unroll 1
            for (int it = 0; it < SPIN; it++) {
                if (__all_sync(~0u, ll_tag(pm) == tag && ll_tag(pl) == tag)) break;
                ld_rlx2(&g_ll[1 + L.value][cta ^ t][192], pm, pl);
            }
            float M = fmaxf(ll_val(pm), shx(ll_val(pm), 1)); M = fmaxf(M, shx(M, 2));
            const float f = ex2((ll_val(pm) - M) * CS);
            float L_ = f * ll_val(pl); L_ += shx(L_, 1); L_ += shx(L_, 2);
            if (lane == 0) stsf(sb + SM_GW, f * rcp(L_));
        };
        auto pv = [&](const uint4 (&v)[6], uint32_t pp) {
            const uint32_t dA = __byte_perm(pp, 0, 0x1010), dB = __byte_perm(pp, 0, 0x3232);
            mma(acc[0], v[0], dA & maskA, dA & maskB); mma(acc[1], v[1], dA & maskA, dA & maskB); mma(acc[2], v[2], dA & maskA, dA & maskB);
            mma(acc[0], v[3], dB & maskA, dB & maskB); mma(acc[1], v[4], dB & maskA, dB & maskB); mma(acc[2], v[5], dB & maskA, dB & maskB);
        };
        const uint32_t sa = prow + 256 + t * 32 + g * 4;
        if (layer == 0) {
            __syncthreads();
            sts64(prow + lane * 8, xp.x, xp.y);
            int e = 0;
            const uint4* tab = P.tile + (warp >> 2);
            uint4 tw = tab[0];
            uint32_t ka[3];
#pragma unroll
            for (int j = 0; j < 3; j++) ka[j] = pin(subw + key * 384 + j * 128 + ((t ^ ((3 * key + j) & 7)) << 4));
            auto load_k = [&](uint4 (&v)[6], uint32_t so) {
#pragma unroll
                for (int i = 0; i < 6; i++) v[i] = lds128(((i & 1) ? ka[i >> 1] ^ 64 : ka[i >> 1]) + so);
            };
            const uint32_t s0 = pin(prow + 256 + g * 4), sca = pin(sb + SM_SC + warp * 128 + g * 16);
#pragma unroll 1
            do {
                const uint4 tn = tab[2 * e + 2];
                uint4 v[6], qf[3];
                if (tw.x & (G_A | G_B | G_C)) {
                    if ((tw.x & G_A) && (roww & 56) == 56 && elect()) {
                        mbar_expect(sb + SM_CBAR + CB_SNAP * 8, 8192);
                        asm volatile("cp.async.bulk.shared::cluster.global.mbarrier::complete_tx::bytes [%0], [%1], 8192, [%2];"
                                     :: "r"(sb + 3 * TILE + 8192), "l"(&g_ll[0][cta & ~3][0]), "r"(sb + SM_CBAR + CB_SNAP * 8) : "memory");
                    }
                    if (tw.x & G_B) {
                        if (warp < 6) {
                            mbar_wait(sb + SM_CBAR + CB_SNAP * 8, 0);
                            u64 qw[4];
#pragma unroll
                            for (int i = 0; i < 4; i++) { const uint2 x = lds64(sb + 3 * TILE + 8192 + i * 2048 + tid * 8); qw[i] = x.x | (u64)x.y << 32; }
                            gather_q(qw, IC<0>{});
                        }
                        mbar_wait(sb + SM_CBAR + CB_Q * 8, 0);
                        TSTAMP(2);
                    }
                    if (tw.x & G_C) {
                        load_k(v, (e - LATEAT) * TILE);
                        load_q(qf);
                        stsf(s0 + (e - LATEAT) * 32, score(v, qf));
                    }
                }
                load_q(qf);
                mbar_wait(sb + SM_CBAR + (tw.x & 0xf8), tw.x >> 31);
                TRACE(e);
                load_k(v, tw.x & 0x3f000);
                const uint32_t old = release(tw);
                const float s = score(v, qf);
                uint32_t m;
                {
                    uint32_t a[6];
#pragma unroll
                    for (int i = 0; i < 6; i++) a[i] = bf2_amax(bf2_amax(v[i].x, v[i].y), bf2_amax(v[i].z, v[i].w));
                    m = bf2_amax(bf2_amax(bf2_amax(a[0], a[1]), bf2_amax(a[2], a[3])), bf2_amax(a[4], a[5]));
                }
                m = bf2_amax(m, m >> 16) & 0x7f80;
                m = max(m, __shfl_xor_sync(~0u, m, 1));
                stsf(s0 + e * 32, s);
                m = max(m, __shfl_xor_sync(~0u, m, 2));
                refill(tw, old);
                const uint32_t b = min(max(m, 15u << 7) - (15u << 7), 126u << 7);
                const uint32_t dn = ((127u << 7) - b) * 0x10001u, up = ((127u << 7 | 0x8000u) + b) * 0x10001u;
                uint32_t c[18], any = m > (141u << 7);
#pragma unroll
                for (int i = 0; i < 6; i++) {
                    const uint32_t y0 = bf2_mul(v[i].x, dn), y1 = bf2_mul(v[i].y, dn), y2 = bf2_mul(v[i].z, dn), y3 = bf2_mul(v[i].w, dn);
                    v[i] = make_uint4(bf2_fma(y0, up, v[i].x), bf2_fma(y1, up, v[i].y), bf2_fma(y2, up, v[i].z), bf2_fma(y3, up, v[i].w));
                    any |= v[i].x | v[i].y;
                    any |= v[i].z | v[i].w;
                    const uint32_t hb = __byte_perm(y2, y3, 0x7531);
                    c[3 * i] = __byte_perm(y0, y1, 0x6420); c[3 * i + 1] = __byte_perm(y2, y3, 0x6420);
                    c[3 * i + 2] = __byte_perm(y0, y1, 0x7531) | __funnelshift_r(hb, hb, 4);
                }
                asm volatile("st.shared.u8 [%0], %1;" :: "r"(sca + (e & 3) * 4 + (e >> 2)), "r"((b >> 7) + 63) : "memory");
                const bool rare = __any_sync(~0u, any);
                k_keep(kr, c, e, offL);
                if (rare) {
                    uint32_t odd = m > (141u << 7) ? 64u : 0u;
#pragma unroll
                    for (int i = 0; i < 6; i++) if (v[i].x | v[i].y | v[i].z | v[i].w) odd |= 1u << i;
                    odd = __reduce_or_sync(~0u, odd);
                    const uint2 st = lds64(barw + 80);
                    uint32_t n = odd >= 64 ? NEXC + 1 : __shfl_sync(~0u, st.x, 0);
#pragma unroll 1
                    for (; odd && n <= NEXC; odd &= odd - 1) {
                        const int i = __ffs(odd) - 1;
                        uint4 r = v[0];
#pragma unroll
                        for (int k = 1; k < 6; k++) if (i == k) r = v[k];
                        static_for<0, 4>([&](auto K) {
                            const uint32_t x = word<K.value>(r), who = __ballot_sync(~0u, x), at = n + __popc(who & ((1u << lane) - 1));
                            if (x && at < NEXC) sts64(sb + SM_EXC + warp * 128 + at * 8, x, (e * 32 + g * 4) << 16 | (((K.value & 1) * 4 + t) * 48 + i * 8 + (K.value >> 1) * 4));
                            n += __popc(who);
                        });
                    }
                    if (n > NEXC) asm volatile("st.shared.u8 [%0], %1;" :: "r"(sca + (e & 3) * 4 + (e >> 2)), "r"(0) : "memory");
                    sts64(barw + 80, n > NEXC ? st.x : n, n > NEXC ? st.y | 1u << e : st.y);
                    __syncwarp();
                }
                tw = tn;
            } while (++e < 16);
            asm volatile("fence.proxy.async.shared::cta;" ::: "memory");
            __syncwarp();
            TSTAMP(10);
            calc_offsets(lane + lds32(sb + SM_ZERO));
            softmax(ldsf(sa), ldsf(sa + 128), ldsf(sa + 256), ldsf(sa + 384));
#pragma unroll 1
            do {
                const uint4 tn = tab[2 * e + 2];
                if (tw.x & (G_A | G_B)) {
                    if ((tw.x & G_A) && tid < 196)
                        st_rlx(&g_ll[1][cta][tid], tid < 192 ? 0ull : ll_pack(ldsf(sb + SM_STAT + (tid > 192) * 4), lds32(sb + SM_EPOCH) * 4 + 2));
                    if ((tw.x & G_B) && (roww & 56) == 56) {
                        const uint32_t want = lds32(sb + SM_EPOCH) + 1;
#pragma unroll 1
                        for (int it = 0; it < SPIN; it++) {
                            uint32_t v; asm volatile("ld.acquire.gpu.global.u32 %0, [%1];" : "=r"(v) : "l"(&g_zflag) : "memory");
                            if (__all_sync(~0u, v == want)) break;
                        }
                    }
                    if ((tw.x & G_B) && (roww & 56) == 48) head_weight(0, 0, IC<0>{});
                    if (tw.x & G_B) pf_w(0);
                    __syncwarp();
                }
                const uint32_t pp = lds32(prow + 256 + t * 4 + ((tw.x >> 20) & 255));
                mbar_wait(sb + SM_CBAR + (tw.x & 0xf8), tw.x >> 31);
                TRACE(e);
                uint4 v[6];
                load_v(v, tw.x & 0x3f000);
                refill(tw, release(tw));
                pv(v, pp);
                tw = tn;
            } while (++e < 32);
        } else {
            spin(QDELAY);
            u64 qw[4] = {0, 0, 0, 0};
            if (warp < 6) {
#pragma unroll
                for (int i = 0; i < 4; i++) qw[i] = ld_rlx(&g_ll[1][(cta & ~3) + i][tid]);
            }
            uint4 tb[8][3];
            auto load_tb = [&](auto I) {
#pragma unroll
                for (int i = 0; i < 3; i++) tb[I.value][i] = lds128(offL + (I.value >> 1) * TILE + ((I.value & 1) * 3 + i) * 512);
            };
            static_for<0, NPRE>(load_tb);
            if (S0EARLY) refill2(IC<5>{});
            if (warp < 6) gather_q(qw, IC<1>{});
            else if (!S0EARLY) mbar_wait(sb + SM_CBAR + CB_Q * 8, 1);
            if (!S0EARLY) refill2(IC<5>{});
            mbar_wait(sb + SM_CBAR + CB_Q * 8, 1);
            TSTAMP(12);
            uint4 qf[3];
            load_q(qf);
            sts64(prow + lane * 8, xp.x, xp.y);
            sts128f(prow + 256 + lane * 16, 0.f, 0.f, 0.f, 0.f);
            float S[4], d[4];
            auto vstep = [&](auto I) {
                constexpr int p = I.value;
                constexpr Step c = SCH.st[p];
                mbar_wait(barw + c.slot * 8, c.par);
                TRACE(32 + p);
                load_v(kr[p & 7], c.slot * TILE);
                if constexpr (c.next >= 0) refill2(IC<c.next>{});
                if constexpr (p >= WOAT && p < WOAT + 3) {
                    __syncwarp();
                    if (elect() && cnt_inc(sb + SM_CNT + (CB_WO + p - WOAT) * 8, 7) == 7) {
                        issue_half(UC<load_word(64 + 2 * (p - WOAT)) | 1>::value, sb, rowc, cta, tmk);
                        if constexpr (p < WOAT + 2) issue_half(UC<load_word(65 + 2 * (p - WOAT)) | 1>::value, sb, rowc, cta, tmk);
                    }
                }
            };
            static_for<0, 96>([&](auto F) {
                constexpr int f = F.value, i = f % 6, u = kunit(f / 6), w = 3 * f % 12;
                uint4 (&src)[3] = *reinterpret_cast<uint4 (*)[3]>(f < 32 ? &tb[f / 4 & 7][0] : &kr[(f / 8 + 4) & 7][(f / 4 & 1) * 3]);
                const uint4 a = k_unpack(word<w % 4>(src[w / 4]), word<(w + 1) % 4>(src[(w + 1) / 4]), word<(w + 2) % 4>(src[(w + 2) / 4]));
                if constexpr (f % 4 == 3 && f / 4 + NPRE < 8) {
                    load_tb(IC<f / 4 + NPRE>{});
                    if constexpr ((f / 4 + NPRE) & 1) refill2(IC<5 + (f / 4 + NPRE) / 2>{});
                }
                if constexpr (i == 0) d[0] = d[1] = d[2] = d[3] = 0.f;
                mma(d, a, (i & 1) ? qf[i / 2].z : qf[i / 2].x, (i & 1) ? qf[i / 2].w : qf[i / 2].y);
                if constexpr (i == 5) {
                    if constexpr (u == 11 || ((u & 3) == 0 && u != 8)) asm volatile("add.f32 %0, %1, %2;" : "=f"(S[u >> 2]) : "f"(d[0]), "f"(d[3]));
                    else add_if(t == (u & 3), S[u >> 2], d[0], d[3]);
                    if constexpr (f < 40) S[u >> 2] = shx(S[u >> 2], 0);
                }
                if constexpr (f == 39) {
                    __syncwarp();
                    calc_offsets(lane + lds32(sb + SM_ZERO));
                    if (lane < lds32(barw + 80)) {
                        const uint2 x = lds64(sb + SM_EXC + warp * 128 + lane * 8);
                        const uint32_t qq = lds32(sb + SM_VEC + (x.y & 0xffff));
                        asm volatile("red.shared.add.f32 [%0], %1;" :: "r"(prow + 256 + (x.y >> 16)), "f"((bf_lo(x.x) * bf_lo(qq) + bf_hi(x.x) * bf_hi(qq)) * 0x1p-64f) : "memory");
                    }
                    __syncwarp();
                }
                if constexpr (f == 8 * PARK0 + 7) vstep(IC<0>{});
                if constexpr (f == 8 * PARK1 + 7) vstep(IC<1>{});
            });
#pragma unroll 1
            for (uint32_t bad = lds32(barw + 84); bad; bad &= bad - 1) {
                const int e = __ffs(bad) - 1;
                const __nv_bfloat16* kp = P.k + (size_t)(roww + e * 256 + key) * DH + t * 8;
                uint4 v[6];
#pragma unroll
                for (int i = 0; i < 6; i++) v[i] = *reinterpret_cast<const uint4*>(kp + i * 32);
                const float s = score(v, qf) * 0x1p-64f;
                if (t == 0) stsf(sa + e * 32, s);
            }
            __syncwarp();
            TSTAMP(30);
            const uint32_t sc = lds32(sb + SM_SC + tid * 4);
            softmax(S[0] * __uint_as_float((sc & 255) << 23) + ldsf(sa), S[1] * __uint_as_float((sc & 0xff00) << 15) + ldsf(sa + 128),
                    S[2] * __uint_as_float((sc & 0xff0000) << 7) + ldsf(sa + 256), S[3] * __uint_as_float((sc >> 24) << 23) + ldsf(sa + 384));
            TSTAMP(1);
            u64 pm = 0, pl = 0;
            static_for<2, 16>([&](auto I) {
                if constexpr (I.value == HWAT) { if ((roww & 56) == 48) ld_rlx2(&g_ll[2][cta ^ t][192], pm, pl); }
                if constexpr (I.value == HWAT + 3) { if ((roww & 56) == 48) head_weight(pm, pl, IC<1>{}); }
                vstep(I);
                static_for<SCH.st[I.value].mma0, SCH.st[I.value].mma0 + SCH.st[I.value].nmma>([&](auto J) { pv(kr[J.value & 7], lds32(prow + 256 + t * 4 + IC<SCH.st[J.value].unit>::value * 16)); });
            });
        }
        TSTAMP2(3);

        uint32_t pa, ro;
        {
            const int zero = lds32(sb + SM_ZERO), lz = lane + zero;
            const u64* lb = &g_ll[1 + layer][cta & ~3][0];
            xp = lds64(prow + lane * 8);
            __syncwarp();
            if (t < 2) {
#pragma unroll
                for (int j = 0; j < 3; j++) sts128f(prow + (64 * j + 8 * g + 4 * t) * 4, acc[j][0], acc[j][1], acc[j][2], acc[j][3]);
            }
            const uint32_t tag = lds32(sb + SM_EPOCH) * 4 + 2 + 2 * layer;
            const int d = warp * 24 + min(lz, 23);
            __syncthreads();
            TSTAMPL(29);
            {
                const uint4 fa = lds128(sb + SM_FAC), fb = lds128(sb + SM_FAC + 16);
                const float gw = ldsf(sb + SM_GW);
                float s[8];
#pragma unroll
                for (int w = 0; w < 8; w++) s[w] = ldsf(sb + SM_PART + d * 4 + w * 768);
                const float own = ((s[0] * __uint_as_float(fa.x) + s[1] * __uint_as_float(fa.y)) + (s[2] * __uint_as_float(fa.z) + s[3] * __uint_as_float(fa.w))) +
                      ((s[4] * __uint_as_float(fb.x) + s[5] * __uint_as_float(fb.y)) + (s[6] * __uint_as_float(fb.z) + s[7] * __uint_as_float(fb.w)));
                if (lane < 24) st_rlx(const_cast<u64*>(lb) + (cta & 3) * 256 + d, ll_pack(own * gw, tag));
            }
            u64 w0 = ld_rlx(lb + d), w1 = ld_rlx(lb + 256 + d), w2 = ld_rlx(lb + 512 + d), w3 = ld_rlx(lb + 768 + d);
            pf_w(1);
            const int row = pin((lz & 1) + 2 * (lz & 2) + 2 * (lz >> 4));
            const uint32_t wa = pin(sb + SM_RING + warp * 1536 + row * 64 + ((((lz >> 2) & 3) ^ (row >> 1)) << 4));
            uint4 v[5][3];
            auto load_wo = [&](auto J) {
                mbar_wait(sb + SM_CBAR + (CB_WO + J.value) * 8, layer);
#pragma unroll
                for (int p = 0; p < 3; p++) v[J.value][p] = lds128(wa + ring_hs(64 + J.value) * HALF + p * 512);
            };
            auto w1_early = [&](int at) {
                pf_w(at);
                if ((layer ? W1AT1 : W1AT0) == at) {
                    __syncwarp();
                    if (elect() && cnt_inc(sb + SM_CNT + CB_W1 * 8, 7) == 7) issue_w(0);
                    __syncwarp();
                }
            };
            load_wo(IC<0>{});
            load_wo(IC<1>{});
            w1_early(2);
            load_wo(IC<2>{});
            w1_early(3);
#pragma unroll 1
            for (int it = 0; it < SPIN; it++) {
                if (__all_sync(~0u, ll_tag(w0) == tag && ll_tag(w1) == tag && ll_tag(w2) == tag && ll_tag(w3) == tag)) break;
                w0 = ld_rlx(lb + d); w1 = ld_rlx(lb + 256 + d); w2 = ld_rlx(lb + 512 + d); w3 = ld_rlx(lb + 768 + d);
            }
            TSTAMP2(4);
            const float o = (ll_val(w0) + ll_val(w1)) + (ll_val(w2) + ll_val(w3));
            const uint32_t od = pack_bf(o, o);
            uint32_t op[3];
#pragma unroll
            for (int p = 0; p < 3; p++) op[p] = __shfl_sync(~0u, od, 8 * p + row);
            float y[5][4];
#pragma unroll
            for (int j = 0; j < 5; j++) y[j][0] = y[j][1] = y[j][2] = y[j][3] = 0.f;
#pragma unroll
            for (int p = 0; p < 2; p++)
#pragma unroll
                for (int j = 0; j < 3; j++) mma(y[j], v[j][p], op[p] & maskA, op[p] & maskB);
            load_wo(IC<3>{});
#pragma unroll
            for (int j = 0; j < 3; j++) mma(y[j], v[j][2], op[2] & maskA, op[2] & maskB);
            load_wo(IC<4>{});
            __syncwarp();
#pragma unroll
            for (int p = 0; p < 3; p++)
#pragma unroll
                for (int j = 3; j < 5; j++) mma(y[j], v[j][p], op[p] & maskA, op[p] & maskB);
            {
                const int word = (lz & 3) * 160 + j40 + warp * 8 + (lz >> 2);
                pa = pin(sb + SM_RING + warp * 256 + lz * 4);
                ro = pin((word >> 3) * ACC_PITCH + (word & 7) * 8);
            }
            if ((t >> 1) == (g >> 2)) {
#pragma unroll
                for (int j = 0; j < 5; j++)
                    sts128f(sb + SM_RING + warp * 1536 + j * 256 + (8 * g + 4 * (t & 1)) * 4, y[j][0], y[j][1], y[j][2], y[j][3]);
            }
        }
        TSTAMP2(5);
        __syncthreads();
        if (warp < 5) {
            unsigned char* accb = accg + 2 * layer * ACC_BYTES;
            float fxs = ldsf(sb + SM_FXS);
            {
                const float s = sum8(pa, 1536) + sum8(pa + 128, 1536);
                asm volatile("red.relaxed.gpu.global.add.u64 [%0], %1;" :: "l"(accb + ro), "l"(fx_pack(s, fxs)) : "memory");
            }
            TSTAMP2(6);
            if (layer == 0) asm volatile("bar.arrive 2, 256;" ::: "memory");
            else if (mlp == 96) { TDUMP(); return; }
            uint4 wf[8];
            const int lz = lane + lds32(sb + SM_ZERO);
            const uint32_t hpa = pin(sb + SM_PART + warp * 160 + ((lz & 2) * 4 + (lz >> 2)) * 8 + (lz & 1) * 4);
            const uint32_t w2a = pin(sb + SM_W2 + ((lz & 3) * 10 + 2 * warp) * 128 + (((lz >> 2) ^ ((2 * lz + 2 * warp) & 6)) << 4));
            const uint32_t la = sb + SM_W1 + warp * 4096 + (lz & 4) * 512 + (lz & 2) * 64 + (lz & 1) * 32 + (lz >> 4) * 64 + ((((lz >> 3) ^ (lz >> 1)) & 1) << 4);
            unsigned char* ap = accb + (c4 >> 3) * ACC_PITCH + (c4 & 7) * 8;
            {
                u64 w[4];
                bool have;
                int it = 0;
                spin(AR1D);
#pragma unroll 1
                do {
#pragma unroll
                    for (int k = 0; k < 4; k++) w[k] = ld_rlx(ap + k * 20 * ACC_PITCH);
                    have = mbar_test(sb + SM_CBAR + CB_W1 * 8, layer);
#pragma unroll
                    for (int j = 0; j < 8; j++) wf[j] = ldsm_t(la + j * 256);
                } while (!__all_sync(~0u, lo32(w[0]) & lo32(w[1]) & lo32(w[2]) & lo32(w[3]) & 32) && ++it < SPIN);
                if (!have) {
                    mbar_wait(sb + SM_CBAR + CB_W1 * 8, layer);
#pragma unroll
                    for (int j = 0; j < 8; j++) wf[j] = ldsm_t(la + j * 256);
                    TSTAMPL(28);
                }
                const float inv = fx_inv(fxs);
                xp = make_uint2(pack_bf(bf_lo(xp.x) + fx_val(w[0]) * inv, bf_hi(xp.x) + fx_val(w[1]) * inv),
                                pack_bf(bf_lo(xp.y) + fx_val(w[2]) * inv, bf_hi(xp.y) + fx_val(w[3]) * inv));
            }
            TSTAMP2(7);
            uint4 w2r[8];
            {
                const uint32_t e0 = (g & 1) ? ONES : xp.x, e1 = (g & 1) ? ONES : xp.y, o0 = (g & 1) ? xp.x : ONES, o1 = (g & 1) ? xp.y : ONES;
                float d[8][4];
#pragma unroll
                for (int j = 0; j < 8; j++) { d[j][0] = d[j][1] = d[j][2] = d[j][3] = 0.f; mma(d[j], wf[j], (j & 1) ? o0 : e0, (j & 1) ? o1 : e1); }
                const float x0 = bf_lo(xp.x), x1 = bf_hi(xp.x), x2 = bf_lo(xp.y), x3 = bf_hi(xp.y);
                const float s1 = (x0 + x1) + (x2 + x3), s2 = (x0 * x0 + x1 * x1) + (x2 * x2 + x3 * x3);
                float ss = ((lane & 16) ? s2 : s1) + shx((lane & 16) ? s1 : s2, 16);
                ss += shx(ss, 8); ss += shx(ss, 4);
                float r[4];
#pragma unroll
                for (int k = 0; k < 4; k++) r[k] = d[0][k] + d[1][k ^ 1];
#pragma unroll
                for (int j = 1; j < 4; j++)
#pragma unroll
                    for (int k = 0; k < 4; k++) add_if(t == j, r[k], d[2 * j][k], d[2 * j + 1][k ^ 1]);
                const float a = ((t & 1) ? r[1] : r[0]) + shx((t & 1) ? r[0] : r[1], 1), b = ((t & 1) ? r[3] : r[2]) + shx((t & 1) ? r[2] : r[3], 1);
                ss += shx(ss, 2);
                const float dd = ((t & 2) ? b : a) + shx((t & 2) ? a : b, 2);
                ss += shx(ss, 1);
                stsf(hpa, dd);
                if ((lane & 15) == 0) stsf(sb + SM_PART + warp * 160 + 128 + (lane >> 2), ss);
            }
            TSTAMPL(25);
            bar_sync(1, 160);
            TSTAMPL(26);
            float mean, rstd, msq;
            ln_final<true>(sb + 128, mean, rstd, msq);
            float2 hp[5];
#pragma unroll
            for (int w = 0; w < 5; w++) hp[w] = lds64f(sb + hp_off(w) + (lane & 15) * 8);
            const float b1v = ldsf(sb + SM_B1 + (lane & 15) * 4);
            mbar_wait(sb + SM_CBAR + CB_W2 * 8, layer);
#pragma unroll
            for (int i = 0; i < 8; i++) w2r[i] = lds128(((i & 1) ? (w2a ^ 16) + 128 : w2a) + (i >> 1) * 5120);
            if (layer == 0) asm volatile("bar.arrive 3, 256;" ::: "memory");
            float hv = (((hp[0].x + hp[1].x) + (hp[2].x + hp[3].x)) + hp[4].x) - mean * (((hp[0].y + hp[1].y) + (hp[2].y + hp[3].y)) + hp[4].y);
            hv = hv * rstd + b1v;
            hv = hv * rcp(1.f + ex2(hv * (-2.302208198f - 0.1029432397f * hv * hv)));
            const uint32_t hd = pack_bf(hv, hv);
            TSTAMPL(27);
            fxs = fx_scale(msq);
            float ym[4][4];
#pragma unroll
            for (int i = 0; i < 4; i++) ym[i][0] = ym[i][1] = ym[i][2] = ym[i][3] = 0.f;
#pragma unroll
            for (int i = 0; i < 4; i++) {
                const uint32_t hh = __shfl_sync(~0u, hd, 4 * i + t);
                mma(ym[(i & 1) * 2], w2r[2 * i], hh & maskA, hh & maskB);
                mma(ym[(i & 1) * 2 + 1], w2r[2 * i + 1], hh & maskA, hh & maskB);
            }
            const float sc2 = __uint_as_float((uint32_t)(127 + 16 - max(((int)(__float_as_uint(msq) >> 23) - 127) >> 1, -100)) << 23);
            float y[4];
#pragma unroll
            for (int k = 0; k < 4; k++) y[k] = ((t & 2) ? ym[1][k] + ym[3][k] : ym[0][k] + ym[2][k]) * sc2;
            u64 w[2] = {fx2_pack(y[0], y[1]), fx2_pack(y[2], y[3])};
            ap = accb + ACC_BYTES + (c4 >> 2) * ACC_PITCH + (c4 & 3) * 8;
            const float inv = fx_inv(sc2);
            if (!(fmaxf(fmaxf(fabsf(y[0]), fabsf(y[1])), fmaxf(fabsf(y[2]), fabsf(y[3]))) < FX2LIM) && mlp != 96) {
#pragma unroll
                for (int k = 0; k < 4; k++)
                    asm volatile("red.relaxed.gpu.global.add.u64 [%0], %1;" :: "l"(ap + (k >> 1) * 40 * ACC_PITCH + 64 + (k & 1) * 32), "l"(fx_pack(y[k] * inv, fxs)) : "memory");
                __threadfence();
#pragma unroll
                for (int k = 0; k < 2; k++) { asm volatile("red.relaxed.gpu.global.or.b64 [%0], 256;" :: "l"(ap + k * 40 * ACC_PITCH) : "memory"); w[k] = 1; }
            }
            uint2 b2v = make_uint2(0, 0);
            auto add_mlp = [&]() {
                float z[4] = {fx2_lo(w[0]) * inv, fx2_hi(w[0]) * inv, fx2_lo(w[1]) * inv, fx2_hi(w[1]) * inv};
                if ((lo32(w[0]) | lo32(w[1])) & 256) {
                    __threadfence();
#pragma unroll
                    for (int k = 0; k < 4; k++) z[k] += fx_val(ld_rlx(ap + (k >> 1) * 40 * ACC_PITCH + 64 + (k & 1) * 32)) * fx_inv(fxs);
                }
                xp = make_uint2(pack_bf(bf_lo(xp.x) + (z[0] + bf_lo(b2v.x)), bf_hi(xp.x) + (z[1] + bf_hi(b2v.x))),
                                pack_bf(bf_lo(xp.y) + (z[2] + bf_lo(b2v.y)), bf_hi(xp.y) + (z[3] + bf_hi(b2v.y))));
            };
            if (layer == 1) {
                u64 old[2];
#pragma unroll
                for (int k = 0; k < 2; k++) asm volatile("atom.relaxed.gpu.global.add.u64 %0, [%1], %2;" : "=l"(old[k]) : "l"(ap + k * 40 * ACC_PITCH), "l"(w[k]) : "memory");
                TSTAMP(18);
                asm volatile("ld.global.nc.v2.u32 {%0,%1}, [%2];" : "=r"(b2v.x), "=r"(b2v.y) : "l"(P.b2 + 4 * c4));
#pragma unroll
                for (int k = 0; k < 2; k++) w[k] += old[k];
                add_mlp();
                uint32_t* op = reinterpret_cast<uint32_t*>(P.out) + 2 * c4;
                if ((w[0] & 255) == 96) { op[0] = xp.x; if (tid == 0) g_epoch = lds32(sb + SM_EPOCH) + 1; }
                if ((w[1] & 255) == 96) op[1] = xp.y;
                TSTAMP(19);
                TDUMP();
                return;
            }
#pragma unroll
            for (int k = 0; k < 2; k++) if (mlp != 96) asm volatile("red.relaxed.gpu.global.add.u64 [%0], %1;" :: "l"(ap + k * 40 * ACC_PITCH), "l"(w[k]) : "memory");
            TSTAMP(8);
            asm volatile("ld.global.nc.v2.u32 {%0,%1}, [%2];" : "=r"(b2v.x), "=r"(b2v.y) : "l"(P.b2 + 4 * c4));
            calc_offsets(lane + lds32(sb + SM_ZERO));
            load_wq();
            const uint32_t c0 = clk();
            while (clk() - c0 < ARDELAY);
            if (warp < TB) refill2(IC<2>{});
            fx_poll(ap, 96, w);
            if (warp >= TB) refill2(IC<2>{});
            add_mlp();
            TSTAMP(9);
        } else {
            if ((roww & 56) == 40 && elect()) {
                if ((layer ? W1AT1 : W1AT0) == 4) issue_w(0);
                issue_w(1);
            }
            if (layer == 1) { TDUMP(); return; }
            __syncwarp();
            calc_offsets(lane + lds32(sb + SM_ZERO));
            load_wq();
            auto fill = [&](int i, int end, uint32_t c0, uint32_t gap) {
#pragma unroll 1
                for (; i < end; i += 3, c0 += 3 * gap) {
                    const uint32_t bar = sb + SM_BAR + (i & 7) * 96 + 32 + (i & 24);
                    while ((int)(clk() - c0) < 0);
                    mbar_expect(bar, SUB);
                    tma3(sb + SM_RING + i * SUB, tmk + TM_V, 0, rowc + (i & 7) * 8 + ((UC<SCH.st[0].unit << 8 | SCH.st[1].unit << 16 | SCH.st[3].unit << 24>::value >> (i & 24)) & 0xf00), bar, POL_FIRST);
                }
                return c0;
            };
            bar_sync(2, 256);
            if (elect()) {
                asm volatile("fence.proxy.async.shared::cta;" ::: "memory");
                const uint32_t c0 = fill(warp - 5, 6, clk() + WD1 + (warp - 5) * WG1, WG1);
                while ((int)(clk() - c0) < 0);
                issue_v(IC<2>{}, 0);
            }
            __syncwarp();
            bar_sync(3, 256);
            if (elect()) fill(warp + 1, 20, clk() + WD2 + (warp - 5) * WG2, WG2);
            __syncwarp();
        }
    }
}

typedef CUresult (*EncodeFn)(CUtensorMap*, CUtensorMapDataType, cuuint32_t, void*, const cuuint64_t*, const cuuint64_t*, const cuuint32_t*,
                             const cuuint32_t*, CUtensorMapInterleave, CUtensorMapSwizzle, CUtensorMapL2promotion, CUtensorMapFloatOOBfill);

}

extern "C" void kernel_launch(void* const* d_in, const int* in_sizes, int n_in, void* d_out, int out_size) {
    (void)in_sizes; (void)n_in; (void)out_size;
    static EncodeFn enc = nullptr;
    if (!enc) {
        void* fn = nullptr;
        cudaDriverEntryPointQueryResult qr;
        cudaGetDriverEntryPoint("cuTensorMapEncodeTiled", &fn, cudaEnableDefault, &qr);
        enc = (EncodeFn)fn;
        cudaFuncSetAttribute(fused_kernel, cudaFuncAttributeMaxDynamicSharedMemorySize, SM_TOTAL);
    }
    Params P = {};
    auto map3 = [&](int m, int in, cuuint64_t d0, cuuint64_t d1, cuuint64_t d2, cuuint64_t s1, cuuint64_t s2, cuuint32_t b0, cuuint32_t b1, cuuint32_t b2,
                    CUtensorMapSwizzle sw, int promo) {
        const cuuint64_t dim[3] = {d0, d1, d2}, str[2] = {s1, s2};
        const cuuint32_t box[3] = {b0, b1, b2}, ones[3] = {1, 1, 1};
        enc(&P.tm[m], CU_TENSOR_MAP_DATA_TYPE_BFLOAT16, 3, d_in[in], dim, str, box, ones, CU_TENSOR_MAP_INTERLEAVE_NONE, sw, (CUtensorMapL2promotion)promo,
            CU_TENSOR_MAP_FLOAT_OOB_FILL_NONE);
    };
    map3(TM_KH, 1, 64, 3, NHEAD * SK, 128, DH * 2, 64, 3, 32, CU_TENSOR_MAP_SWIZZLE_128B, 0);
    map3(TM_VH, 2, 64, 3, NHEAD * SK, 128, DH * 2, 64, 3, 32, CU_TENSOR_MAP_SWIZZLE_128B, 0);
    map3(TM_VP, 2, 64, 3, NHEAD * SK, 128, DH * 2, PFW, 3, 32, CU_TENSOR_MAP_SWIZZLE_NONE, 0);
    map3(TM_V, 2, 64, 3, NHEAD * SK, 128, DH * 2, 64, 3, 8, CU_TENSOR_MAP_SWIZZLE_128B, 0);
    map3(TM_WO, 4, 32, 20, NHEAD * DH, 64, D_MODEL * 2, 32, 1, DH, CU_TENSOR_MAP_SWIZZLE_64B, PROMOW);
    map3(TM_WOP, 4, 32, 20, NHEAD * DH, 64, D_MODEL * 2, PFW, 1, DH, CU_TENSOR_MAP_SWIZZLE_NONE, 0);
    map3(TM_WQ, 3, 64, NHEAD * 3, D_MODEL, 128, NHEAD * DH * 2, 64, 3, 8, CU_TENSOR_MAP_SWIZZLE_128B, 0);
    map3(TM_W1, 6, DFF, 128, 5, DFF * 2, DFF * 256, 16, 128, 5, CU_TENSOR_MAP_SWIZZLE_32B, PROMO1);
    map3(TM_W2, 8, 64, 10, DFF, 128, D_MODEL * 2, 64, 10, 16, CU_TENSOR_MAP_SWIZZLE_128B, 0);
    P.x = (const __nv_bfloat16*)d_in[0];
    P.k = (const __nv_bfloat16*)d_in[1];
    P.b1 = (const __nv_bfloat16*)d_in[7];
    P.b2 = (const __nv_bfloat16*)d_in[9];
    P.w1 = (const __nv_bfloat16*)d_in[6];
    P.w2 = (const __nv_bfloat16*)d_in[8];
    P.out = (__nv_bfloat16*)d_out;
    for (int i = 0; i < 64; i++) P.tile[i] = make_uint4(SCH.tile[i][0], SCH.tile[i][1], SCH.tile[i][2], 0);
    fused_kernel<<<NCTA + 1, NTHR, SM_TOTAL, cudaStreamPerThread>>>(P);
}
```

```cpp
#include <cuda_runtime.h>
#include <cuda_bf16.h>
#include <cuda.h>
#include <stdint.h>

namespace {

constexpr int D_MODEL = 640, NHEAD = 32, SK = 32768, DH = 192, WIN = 4096, DFF = 1536;
constexpr int NCTA = 128, NTHR = 256;
constexpr int TILE = 64 * DH * 2;
constexpr int HALF = TILE / 2;
constexpr int SUB = 8 * DH * 2;
constexpr int SM_RING = 4 * TILE;
constexpr int SM_W2 = SM_RING + 20480, SM_W1 = SM_W2 + 20480;
constexpr int SM_WQR = 6 * TILE + HALF, SM_WQ = 7 * TILE;
constexpr int SM_PART = 9 * TILE;
constexpr int SM_EXC = SM_PART + 6144;
constexpr int SM_SC = SM_EXC + 1024;
constexpr int SM_BAR = SM_SC + 1024;
constexpr int SM_VEC = SM_BAR + 768;
constexpr int SM_CS = SM_VEC + 384;
constexpr int SM_FAC = SM_CS + 768;
constexpr int SM_ML = SM_FAC + 32;
constexpr int SM_B1 = SM_ML + 64;
constexpr int SM_STAT = SM_B1 + 64;
constexpr int NCB = 26;
constexpr int CB_SNAP = 16, CB_REL = 17, CB_WO = 18, CB_W1 = 23, CB_W2 = 24, CB_Q = 25;
constexpr int SM_CBAR = SM_STAT + 40;
constexpr int SM_CNT = SM_CBAR + NCB * 8;
constexpr int SM_EPOCH = SM_CNT + NCB * 8;
constexpr int SM_FXS = SM_EPOCH + 4;
constexpr int SM_T0 = SM_FXS + 4;
constexpr int SM_ZERO = SM_T0 + 4;
constexpr int SM_M1 = SM_ZERO + 4;
constexpr int SM_TS = SM_M1 + 4;
constexpr int SM_TOTAL = 232448;
static_assert(SM_TS + 320 <= SM_TOTAL, "smem");
constexpr int NEXC = 16;

constexpr int SPIN = 1 << 20;
enum { TM_KH = 0, TM_VH = 1, TM_WO = 2, TM_VP = 3, TM_WOP = 4, TM_V = 5, TM_WQ = 6, TM_W1 = 7, TM_W2 = 8 };
constexpr uint32_t POL_NORMAL = 0x16F00000u, POL_FIRST = 0x12F00000u;

#define PACE 990
#define PACE0 1600
#define NI0 2
#define NI1 6
#define ETRIG 0x4321000
#define LATEAT 4
#define HWAT 11
#define PFREE 67
#define PF1 9
#define PF2 9
#define PFPOL POL_NORMAL
#define W1AT0 3
#define W1AT1 3
#define AR1D 300
#define LAG0 12
#define NMMA 2
#define M1AT 1
#define M1P 3
#define SNAPAT 2
#define DMASK 0x1
#define WOKEEP 0x1f
#define VORD2 0x3456789a2b1cd0efull
#define VTRIG 0xba73210
#define WOAT 12
#define PARKS 0x95
#define VSLOT 0x1087654321087654ull
#define OPOLL 2
#define S0EARLY 1
#define NPRE 2
#define ARDELAY 450
#define QDELAY 180
#define CMAP 6
#define PFW 8u
#define PUBAT 25
#define ZCHK 30
#define FX2LIM 524288.f
#define PROMOW 2
#define PROMO1 0
#define TB 2
#define WD1 300
#define WG1 140
#define WD2 0
#define WG2 140
#define WPOL POL_NORMAL

constexpr uint32_t G_A = 1u << 28, G_B = 1u << 29, G_C = 1u << 30;
__host__ __device__ constexpr int ring_hs(int j) { return (j + 4) % 5; }
__host__ __device__ constexpr uint32_t load_word(int j) {
    if (j >= 64) return (uint32_t)(j - 64) << 20 | (SM_RING + ring_hs(j) * HALF) | TM_WO << 8 | (CB_WO + j - 64) << 3 | 2 | !(WOKEEP >> (j - 64) & 1);
    const int e = j >> 1, isv = e >= 16, unit = e & 15;
    return (uint32_t)(unit * 256 + (j & 1) * 32) << 20 | (j < 6 ? j * HALF : SM_RING + ring_hs(j) * HALF) | isv << 8 | (j < 6 ? 10 + j : (j - 6) % 10) << 3 | 2
           | (!isv || (DMASK >> unit & 1));
}
__host__ __device__ constexpr int popc(int v) { return v ? (v & 1) + popc(v >> 1) : 0; }
constexpr int NPARK = popc(PARKS);
struct Step { int unit, slot, par, next, mma0, nmma; };
struct Sched { uint32_t tile[64][3]; Step st[16]; };
constexpr Sched make_sched() {
    Sched s{};
    for (int j = 0; j < 64; j++) {
        const int e = j >> 1;
        const uint32_t d = load_word(j);
        uint32_t w = (uint32_t)(j < 6 ? 0 : (j - 6) / 10 & 1) << 31 | (e & 15) * 4 << 20 | ((d & 0x3f000) - (j & 1) * HALF) | (d & 0xf8);
        if (e == PUBAT || e == SNAPAT) w |= G_A;
        if (e == ZCHK || e == 3) w |= G_B;
        if (e >= LATEAT && e < LATEAT + 3) w |= G_C;
        s.tile[j][0] = w;
    }
    for (int j = NI1; j < 69; j++) {
        const int at = j < 11 ? (ETRIG >> (4 * (j - 4)) & 15) : j - 5;
        s.tile[at][1] = load_word(j);
        s.tile[at][2] = j >= PFREE ? 0 : PACE0 + j * PACE / 2;
    }
    int done = 0;
    for (int p = 0; p < 16; p++) {
        Step& c = s.st[p];
        c.unit = (int)(VORD2 >> (4 * p) & 15); c.slot = (int)(VSLOT >> (4 * p) & 15); c.par = p >= 9; c.next = -1;
        c.mma0 = done;
        if (p >= NPARK) { const int avail = p - done + (p >= LAG0); c.nmma = p == 15 ? 16 - done : (avail < NMMA ? avail : NMMA); done += c.nmma; }
    }
    for (int p = 9; p < 16; p++) s.st[VTRIG >> (4 * (p - 9)) & 15].next = p;
    return s;
}
constexpr Sched SCH = make_sched();
__host__ __device__ constexpr int kunit(int o) { return o < 5 ? o + 11 : o == 5 ? 10 : o - 6; }

template <int I> struct IC { static constexpr int value = I; };
template <uint32_t I> struct UC { static constexpr uint32_t value = I; };
template <int A, int B, class F> __device__ __forceinline__ void static_for(F&& f) {
    if constexpr (A < B) { f(IC<A>{}); static_for<A + 1, B>(f); }
}

struct Params {
    CUtensorMap tm[9];
    const __nv_bfloat16 *x, *k, *b1, *b2, *w1, *w2;
    __nv_bfloat16* out;
    uint4 tile[66];
};

typedef unsigned long long u64;
constexpr int ACC_PITCH = 256;
constexpr int ACC_BYTES = 80 * ACC_PITCH;
__device__ __align__(1024) unsigned char g_acc[4 * ACC_BYTES];
__device__ __align__(1024) u64 g_ll[3][NCTA][256];
__device__ unsigned g_epoch;
__device__ __align__(128) unsigned g_zflag;
#define TSTAMP(i)
#define TSTAMP2(i)
#define TSTAMPL(i)
#define TDUMP()
#define TRACE(i)

__device__ __forceinline__ void mbar_wait(uint32_t bar, uint32_t parity) {
    asm volatile("{\n.reg .pred p, q;\n.reg .u32 n;\nmov.u32 n, 0;\n"
                 "LOOP:\nmbarrier.try_wait.parity.shared::cta.b64 p, [%0], %1;\n"
                 "add.u32 n, n, 1;\nsetp.lt.and.u32 q, n, 0x100000, !p;\n@q bra.uni LOOP;\n}"
                 :: "r"(bar), "r"(parity) : "memory");
}
__device__ __forceinline__ bool mbar_test(uint32_t bar, uint32_t parity) {
    uint32_t r;
    asm volatile("{\n.reg .pred p;\nmbarrier.test_wait.parity.shared::cta.b64 p, [%1], %2;\nselp.u32 %0, 1, 0, p;\n}" : "=r"(r) : "r"(bar), "r"(parity) : "memory");
    return __all_sync(~0u, r);
}
__device__ __forceinline__ bool elect() {
    uint32_t r;
    asm volatile("{\n.reg .pred p;\nelect.sync _|p, 0xffffffff;\nselp.u32 %0, 1, 0, p;\n}" : "=r"(r));
    return r != 0;
}
__device__ __forceinline__ void mbar_expect(uint32_t bar, uint32_t bytes) {
    asm volatile("mbarrier.arrive.expect_tx.shared::cta.b64 _, [%0], %1;" :: "r"(bar), "r"(bytes) : "memory");
}
__device__ __forceinline__ uint4 lds128(uint32_t a) {
    uint4 v; asm volatile("ld.shared.v4.u32 {%0,%1,%2,%3}, [%4];" : "=r"(v.x), "=r"(v.y), "=r"(v.z), "=r"(v.w) : "r"(a) : "memory"); return v;
}
__device__ __forceinline__ uint4 ldsm_t(uint32_t a) {
    uint4 v; asm volatile("ldmatrix.sync.aligned.m8n8.x4.trans.shared.b16 {%0,%1,%2,%3}, [%4];" : "=r"(v.x), "=r"(v.y), "=r"(v.z), "=r"(v.w) : "r"(a) : "memory"); return v;
}
__device__ __forceinline__ uint2 lds64(uint32_t a) {
    uint2 v; asm volatile("ld.shared.v2.u32 {%0,%1}, [%2];" : "=r"(v.x), "=r"(v.y) : "r"(a) : "memory"); return v;
}
__device__ __forceinline__ float2 lds64f(uint32_t a) { const uint2 v = lds64(a); return make_float2(__uint_as_float(v.x), __uint_as_float(v.y)); }
__device__ __forceinline__ uint32_t lds32(uint32_t a) {
    uint32_t v; asm volatile("ld.shared.u32 %0, [%1];" : "=r"(v) : "r"(a) : "memory"); return v;
}
__device__ __forceinline__ float ldsf(uint32_t a) { return __uint_as_float(lds32(a)); }
__device__ __forceinline__ void sts32(uint32_t a, uint32_t v) { asm volatile("st.shared.u32 [%0], %1;" :: "r"(a), "r"(v) : "memory"); }
__device__ __forceinline__ void stsf(uint32_t a, float v) { sts32(a, __float_as_uint(v)); }
__device__ __forceinline__ void sts16(uint32_t a, uint32_t v) { asm volatile("st.shared.u16 [%0], %1;" :: "r"(a), "h"((uint16_t)v) : "memory"); }
__device__ __forceinline__ void sts64(uint32_t a, uint32_t x, uint32_t y) { asm volatile("st.shared.v2.u32 [%0], {%1,%2};" :: "r"(a), "r"(x), "r"(y) : "memory"); }
__device__ __forceinline__ void sts64f(uint32_t a, float x, float y) { sts64(a, __float_as_uint(x), __float_as_uint(y)); }
__device__ __forceinline__ void sts128f(uint32_t a, float x, float y, float z, float w) {
    asm volatile("st.shared.v4.f32 [%0], {%1,%2,%3,%4};" :: "r"(a), "f"(x), "f"(y), "f"(z), "f"(w) : "memory");
}
__device__ __forceinline__ void mma(float (&c)[4], const uint4& a, uint32_t b0, uint32_t b1) {
    asm volatile("mma.sync.aligned.m16n8k16.row.col.f32.bf16.bf16.f32 {%0,%1,%2,%3}, {%4,%5,%6,%7}, {%8,%9}, {%0,%1,%2,%3};"
                 : "+f"(c[0]), "+f"(c[1]), "+f"(c[2]), "+f"(c[3]) : "r"(a.x), "r"(a.y), "r"(a.z), "r"(a.w), "r"(b0), "r"(b1));
}
__device__ __forceinline__ u64 ld_rlx(const void* p) {
    u64 a; asm volatile("ld.relaxed.gpu.global.u64 %0, [%1];" : "=l"(a) : "l"(p) : "memory"); return a;
}
__device__ __forceinline__ void ld_rlx2(const void* p, u64& a, u64& b) {
    asm volatile("ld.relaxed.gpu.global.v2.u64 {%0,%1}, [%2];" : "=l"(a), "=l"(b) : "l"(p) : "memory");
}
__device__ __forceinline__ void st_rlx(void* p, u64 a) { asm volatile("st.relaxed.gpu.global.u64 [%0], %1;" :: "l"(p), "l"(a) : "memory"); }
__device__ __forceinline__ u64 ll_pack(float v, uint32_t tag) { return ((u64)tag << 32) | __float_as_uint(v); }
__device__ __forceinline__ float ll_val(u64 w) { return __uint_as_float((uint32_t)w); }
__device__ __forceinline__ uint32_t ll_tag(u64 w) { return (uint32_t)(w >> 32); }
__device__ __forceinline__ float bf_lo(uint32_t u) { return __uint_as_float(u << 16); }
__device__ __forceinline__ float bf_hi(uint32_t u) { return __uint_as_float(u & 0xffff0000u); }
__device__ __forceinline__ uint32_t pack_bf(float lo, float hi) {
    uint32_t r; asm("cvt.rn.bf16x2.f32 %0, %1, %2;" : "=r"(r) : "f"(hi), "f"(lo)); return r;
}
__device__ __forceinline__ float ex2(float v) { float r; asm("ex2.approx.ftz.f32 %0, %1;" : "=f"(r) : "f"(v)); return r; }
__device__ __forceinline__ float rcp(float v) { float r; asm("rcp.approx.ftz.f32 %0, %1;" : "=f"(r) : "f"(v)); return r; }
__device__ __forceinline__ float rsq(float v) { float r; asm("rsqrt.approx.ftz.f32 %0, %1;" : "=f"(r) : "f"(v)); return r; }
__device__ __forceinline__ void bar_sync(int id, int n) { asm volatile("bar.sync %0, %1;" :: "r"(id), "r"(n) : "memory"); }
__device__ __forceinline__ uint32_t clk() { uint32_t c; asm volatile("mov.u32 %0, %clock;" : "=r"(c)); return c; }
__device__ __forceinline__ void spin(uint32_t cycles) { const uint32_t c0 = clk(); while (clk() - c0 < cycles); }
__device__ __forceinline__ uint32_t pin(uint32_t v) { return __shfl_xor_sync(~0u, v, 0); }
__device__ __forceinline__ float shx(float v, int o) { return __shfl_xor_sync(~0u, v, o); }

__device__ __forceinline__ u64 fx_pack(float v, float scale) { return ((u64)__float2ll_rn(v * scale) & ~255ull) | 1ull; }
__device__ __forceinline__ float fx_scale(float meansq) {
    const int e = max(((int)(__float_as_uint(meansq) >> 23) - 127) >> 1, -6);
    return __uint_as_float((uint32_t)(127 + 32 - e) << 23);
}
__device__ __forceinline__ float fx_inv(float scale) { return __uint_as_float((254u << 23) - __float_as_uint(scale)); }
__device__ __forceinline__ uint32_t lo32(u64 w) { uint32_t l; asm("mov.b64 {%0, _}, %1;" : "=r"(l) : "l"(w)); return l; }
__device__ __forceinline__ int hi32(u64 w) { int h; asm("mov.b64 {_, %0}, %1;" : "=r"(h) : "l"(w)); return h; }
__device__ __forceinline__ float fx_val(u64 w) { return (float)hi32(w) * 4294967296.f + (float)lo32(w); }
template <int N>
__device__ __forceinline__ void fx_poll(const unsigned char* ap, uint32_t bit, u64 (&w)[N]) {
#pragma unroll 1
    for (int it = 0; it < SPIN; it++) {
        uint32_t m = bit;
#pragma unroll
        for (int k = 0; k < N; k++) w[k] = ld_rlx(ap + k * (80 / N) * ACC_PITCH);
#pragma unroll
        for (int k = 0; k < N; k++) m &= lo32(w[k]);
        if (__all_sync(~0u, m == bit)) break;
    }
}
__device__ __forceinline__ u64 fx2_pack(float a, float b) {
    const int ia = __float_as_int(a + 12582912.f) - 0x4b400000, ib = __float_as_int(b + 12582912.f) - 0x4b400000;
    return (u64)(uint32_t)(ia * 512 + 1) | (u64)(uint32_t)(ib * 16 + (ia >> 23)) << 32;
}
__device__ __forceinline__ float fx2_lo(u64 w) { return (float)((int)(__funnelshift_r(lo32(w), hi32(w), 9) << 5) >> 5); }
__device__ __forceinline__ float fx2_hi(u64 w) { return (float)((hi32(w) + 8) >> 4); }

__device__ __forceinline__ void tma3(uint32_t dst, const CUtensorMap* tm, int c1, int c2, uint32_t bar, uint32_t pol) {
    asm volatile("cp.async.bulk.tensor.3d.shared::cluster.global.mbarrier::complete_tx::bytes.L2::cache_hint [%0], [%1, {%2, %3, %4}], [%5], %6;"
                 :: "r"(dst), "l"(tm), "r"(0), "r"(c1), "r"(c2), "r"(bar), "l"((u64)pol << 32) : "memory");
}
__device__ __forceinline__ void tma3_pf(const CUtensorMap* tm, int c1, int c2, uint32_t pol) {
    asm volatile("cp.async.bulk.prefetch.tensor.3d.L2.global.tile.L2::cache_hint [%0, {%1, %2, %3}], %4;"
                 :: "l"(tm), "r"(0), "r"(c1), "r"(c2), "l"((u64)pol << 32) : "memory");
}
__device__ __forceinline__ void issue_half(uint32_t d, uint32_t sb, int rowc, int cta, const CUtensorMap* tm0) {
    const uint32_t bar = sb + SM_CBAR + (d & 0xf8);
    const CUtensorMap* tm = tm0 + ((d >> 8) & 3);
    const int c1 = (d & 0x200) ? 5 * (cta & 3) + (d >> 20) : 0, c2 = (d & 0x200) ? (cta >> 2) * DH : rowc + (d >> 20);
    mbar_expect(bar, HALF);
    tma3(sb + (d & 0x3f000), tm, c1, c2, bar, POL_FIRST);
    if (!(d & 1)) tma3_pf(tm + 2, c1, c2, POL_NORMAL);
}
__device__ __forceinline__ uint32_t cnt_inc(uint32_t a, uint32_t last) {
    uint32_t old; asm volatile("atom.relaxed.cta.shared.inc.u32 %0, [%1], %2;" : "=r"(old) : "r"(a), "r"(last) : "memory"); return old;
}
__device__ __forceinline__ void wait_until(uint32_t due) {
#pragma unroll 1
    for (int it = 0; it < 4096; it++) { uint32_t now; asm volatile("mov.u32 %0, %globaltimer_lo;" : "=r"(now)); if ((int)(now - due) >= 0) break; }
}
__device__ __forceinline__ uint32_t bf2_mul(uint32_t a, uint32_t b) { uint32_t r; asm("mul.rn.bf16x2 %0, %1, %2;" : "=r"(r) : "r"(a), "r"(b)); return r; }
__device__ __forceinline__ uint32_t bf2_fma(uint32_t a, uint32_t b, uint32_t c) { uint32_t r; asm("fma.rn.bf16x2 %0, %1, %2, %3;" : "=r"(r) : "r"(a), "r"(b), "r"(c)); return r; }
__device__ __forceinline__ uint32_t bf2_amax(uint32_t a, uint32_t b) { uint32_t r; asm("max.NaN.xorsign.abs.bf16x2 %0, %1, %2;" : "=r"(r) : "r"(a), "r"(b)); return r; }
__device__ __forceinline__ uint4 k_unpack(uint32_t l0, uint32_t l1, uint32_t h, uint32_t m1) {
    const uint32_t ha = h & 0x87878787u, hc = ha * m1 + h, hb = __funnelshift_l(hc, hc, 4);
    return make_uint4(__byte_perm(l0, ha, 0x5140), __byte_perm(l0, ha, 0x7362), __byte_perm(l1, hb, 0x5140), __byte_perm(l1, hb, 0x7362));
}
#define KR4(u, i) "+r"(kr[u][i].x), "+r"(kr[u][i].y), "+r"(kr[u][i].z), "+r"(kr[u][i].w)
#define KR6(u) KR4(u, 0), KR4(u, 1), KR4(u, 2), KR4(u, 3), KR4(u, 4), KR4(u, 5)
__device__ __forceinline__ void k_keep(uint4 (&kr)[8][6], const uint32_t (&c)[18], int e, uint32_t a) {
    asm volatile("{\nKT: .branchtargets K0, K1, K2, K3, K4, K5, K6, K7, K8, K9, K10, K11, K12, K13, K14, K15;\nbrx.idx.uni %210, KT;\n"
                 "K0: mov.b32 %12, %192; mov.b32 %13, %193; mov.b32 %14, %194; mov.b32 %15, %195; mov.b32 %16, %196; mov.b32 %17, %197; mov.b32 %18, %198; mov.b32 %19, %199; mov.b32 %20, %200; mov.b32 %21, %201; mov.b32 %22, %202; mov.b32 %23, %203; mov.b32 %24, %204; mov.b32 %25, %205; mov.b32 %26, %206; mov.b32 %27, %207; mov.b32 %28, %208; mov.b32 %29, %209; bra.uni KE;\n"
                 "K1: mov.b32 %30, %192; mov.b32 %31, %193; mov.b32 %32, %194; mov.b32 %33, %195; mov.b32 %34, %196; mov.b32 %35, %197; mov.b32 %36, %198; mov.b32 %37, %199; mov.b32 %38, %200; mov.b32 %39, %201; mov.b32 %40, %202; mov.b32 %41, %203; mov.b32 %42, %204; mov.b32 %43, %205; mov.b32 %44, %206; mov.b32 %45, %207; mov.b32 %46, %208; mov.b32 %47, %209; bra.uni KE;\n"
                 "K2: mov.b32 %48, %192; mov.b32 %49, %193; mov.b32 %50, %194; mov.b32 %51, %195; mov.b32 %52, %196; mov.b32 %53, %197; mov.b32 %54, %198; mov.b32 %55, %199; mov.b32 %56, %200; mov.b32 %57, %201; mov.b32 %58, %202; mov.b32 %59, %203; mov.b32 %60, %204; mov.b32 %61, %205; mov.b32 %62, %206; mov.b32 %63, %207; mov.b32 %64, %208; mov.b32 %65, %209; bra.uni KE;\n"
                 "K3: mov.b32 %66, %192; mov.b32 %67, %193; mov.b32 %68, %194; mov.b32 %69, %195; mov.b32 %70, %196; mov.b32 %71, %197; mov.b32 %72, %198; mov.b32 %73, %199; mov.b32 %74, %200; mov.b32 %75, %201; mov.b32 %76, %202; mov.b32 %77, %203; mov.b32 %78, %204; mov.b32 %79, %205; mov.b32 %80, %206; mov.b32 %81, %207; mov.b32 %82, %208; mov.b32 %83, %209; bra.uni KE;\n"
                 "K4: mov.b32 %84, %192; mov.b32 %85, %193; mov.b32 %86, %194; mov.b32 %87, %195; mov.b32 %88, %196; mov.b32 %89, %197; mov.b32 %90, %198; mov.b32 %91, %199; mov.b32 %92, %200; mov.b32 %93, %201; mov.b32 %94, %202; mov.b32 %95, %203; mov.b32 %96, %204; mov.b32 %97, %205; mov.b32 %98, %206; mov.b32 %99, %207; mov.b32 %100, %208; mov.b32 %101, %209; bra.uni KE;\n"
                 "K5: mov.b32 %102, %192; mov.b32 %103, %193; mov.b32 %104, %194; mov.b32 %105, %195; mov.b32 %106, %196; mov.b32 %107, %197; mov.b32 %108, %198; mov.b32 %109, %199; mov.b32 %110, %200; mov.b32 %111, %201; mov.b32 %112, %202; mov.b32 %113, %203; mov.b32 %114, %204; mov.b32 %115, %205; mov.b32 %116, %206; mov.b32 %117, %207; mov.b32 %118, %208; mov.b32 %119, %209; bra.uni KE;\n"
                 "K6: mov.b32 %120, %192; mov.b32 %121, %193; mov.b32 %122, %194; mov.b32 %123, %195; mov.b32 %124, %196; mov.b32 %125, %197; mov.b32 %126, %198; mov.b32 %127, %199; mov.b32 %128, %200; mov.b32 %129, %201; mov.b32 %130, %202; mov.b32 %131, %203; mov.b32 %132, %204; mov.b32 %133, %205; mov.b32 %134, %206; mov.b32 %135, %207; mov.b32 %136, %208; mov.b32 %137, %209; bra.uni KE;\n"
                 "K7: mov.b32 %138, %192; mov.b32 %139, %193; mov.b32 %140, %194; mov.b32 %141, %195; mov.b32 %142, %196; mov.b32 %143, %197; mov.b32 %144, %198; mov.b32 %145, %199; mov.b32 %146, %200; mov.b32 %147, %201; mov.b32 %148, %202; mov.b32 %149, %203; mov.b32 %150, %204; mov.b32 %151, %205; mov.b32 %152, %206; mov.b32 %153, %207; mov.b32 %154, %208; mov.b32 %155, %209; bra.uni KE;\n"
                 "K8: mov.b32 %156, %192; mov.b32 %157, %193; mov.b32 %158, %194; mov.b32 %159, %195; mov.b32 %160, %196; mov.b32 %161, %197; mov.b32 %162, %198; mov.b32 %163, %199; mov.b32 %164, %200; mov.b32 %165, %201; mov.b32 %166, %202; mov.b32 %167, %203; mov.b32 %168, %204; mov.b32 %169, %205; mov.b32 %170, %206; mov.b32 %171, %207; mov.b32 %172, %208; mov.b32 %173, %209; bra.uni KE;\n"
                 "K9: mov.b32 %174, %192; mov.b32 %175, %193; mov.b32 %176, %194; mov.b32 %177, %195; mov.b32 %178, %196; mov.b32 %179, %197; mov.b32 %180, %198; mov.b32 %181, %199; mov.b32 %182, %200; mov.b32 %183, %201; mov.b32 %184, %202; mov.b32 %185, %203; mov.b32 %186, %204; mov.b32 %187, %205; mov.b32 %188, %206; mov.b32 %189, %207; mov.b32 %190, %208; mov.b32 %191, %209; bra.uni KE;\n"
                 "K10: st.shared.v2.b32 [%211+75784], {%192, %193}; st.shared.v4.b32 [%211+76288], {%194, %195, %196, %197}; mov.b32 %0, %198; mov.b32 %1, %199; mov.b32 %2, %200; mov.b32 %3, %201; mov.b32 %4, %202; mov.b32 %5, %203; mov.b32 %6, %204; mov.b32 %7, %205; mov.b32 %8, %206; mov.b32 %9, %207; mov.b32 %10, %208; mov.b32 %11, %209; bra.uni KE;\n"
                 "K11: st.shared.v4.b32 [%211+0], {%192, %193, %194, %195}; st.shared.v4.b32 [%211+512], {%196, %197, %198, %199}; st.shared.v4.b32 [%211+1024], {%200, %201, %202, %203}; st.shared.v4.b32 [%211+1536], {%204, %205, %206, %207}; st.shared.v2.b32 [%211+2048], {%208, %209}; bra.uni KE;\n"
                 "K12: st.shared.v2.b32 [%211+2056], {%192, %193}; st.shared.v4.b32 [%211+2560], {%194, %195, %196, %197}; st.shared.v4.b32 [%211+24576], {%198, %199, %200, %201}; st.shared.v4.b32 [%211+25088], {%202, %203, %204, %205}; st.shared.v4.b32 [%211+25600], {%206, %207, %208, %209}; bra.uni KE;\n"
                 "K13: st.shared.v4.b32 [%211+26112], {%192, %193, %194, %195}; st.shared.v4.b32 [%211+26624], {%196, %197, %198, %199}; st.shared.v4.b32 [%211+27136], {%200, %201, %202, %203}; st.shared.v4.b32 [%211+49152], {%204, %205, %206, %207}; st.shared.v2.b32 [%211+49664], {%208, %209}; bra.uni KE;\n"
                 "K14: st.shared.v2.b32 [%211+49672], {%192, %193}; st.shared.v4.b32 [%211+50176], {%194, %195, %196, %197}; st.shared.v4.b32 [%211+50688], {%198, %199, %200, %201}; st.shared.v4.b32 [%211+51200], {%202, %203, %204, %205}; st.shared.v4.b32 [%211+51712], {%206, %207, %208, %209}; bra.uni KE;\n"
                 "K15: st.shared.v4.b32 [%211+73728], {%192, %193, %194, %195}; st.shared.v4.b32 [%211+74240], {%196, %197, %198, %199}; st.shared.v4.b32 [%211+74752], {%200, %201, %202, %203}; st.shared.v4.b32 [%211+75264], {%204, %205, %206, %207}; st.shared.v2.b32 [%211+75776], {%208, %209}; \nKE:\n}"
                 : KR6(0), KR6(1), KR6(2), KR6(3), KR6(4), KR6(5), KR6(6), KR6(7)
                 : "r"(c[0]), "r"(c[1]), "r"(c[2]), "r"(c[3]), "r"(c[4]), "r"(c[5]), "r"(c[6]), "r"(c[7]), "r"(c[8]), "r"(c[9]), "r"(c[10]), "r"(c[11]), "r"(c[12]), "r"(c[13]), "r"(c[14]), "r"(c[15]), "r"(c[16]), "r"(c[17]), "r"(e), "r"(a) : "memory");
}
template <int K> __device__ __forceinline__ uint32_t& word(uint4& v) { if constexpr (K == 0) return v.x; else if constexpr (K == 1) return v.y; else if constexpr (K == 2) return v.z; else return v.w; }
__device__ __forceinline__ void add_if(bool p, float& d, float a, float b) {
    asm volatile("{\n.reg .pred p;\nsetp.ne.u32 p, %3, 0;\n@p add.f32 %0, %1, %2;\n}" : "+f"(d) : "f"(a), "f"(b), "r"((uint32_t)p));
}
__device__ __forceinline__ float warp_max(float v) {
#pragma unroll
    for (int o = 16; o; o >>= 1) v = fmaxf(v, shx(v, o));
    return v;
}
__device__ __forceinline__ float warp_sum(float v) {
#pragma unroll
    for (int o = 16; o; o >>= 1) v += shx(v, o);
    return v;
}
__device__ __forceinline__ float ll_gather4(const u64* buf, uint32_t tag, u64 w0, u64 w1, u64 w2, u64 w3) {
#pragma unroll 1
    for (int it = 0; it < SPIN; it++) {
        if (__all_sync(~0u, ll_tag(w0) == tag && ll_tag(w1) == tag && ll_tag(w2) == tag && ll_tag(w3) == tag)) break;
        w0 = ld_rlx(buf); w1 = ld_rlx(buf + 256); w2 = ld_rlx(buf + 512); w3 = ld_rlx(buf + 768);
    }
    return (ll_val(w0) + ll_val(w1)) + (ll_val(w2) + ll_val(w3));
}
__device__ __forceinline__ float sum8(uint32_t a, int pitch) {
    float s[8];
#pragma unroll
    for (int w = 0; w < 8; w++) s[w] = ldsf(a + w * pitch);
    return ((s[0] + s[1]) + (s[2] + s[3])) + ((s[4] + s[5]) + (s[6] + s[7]));
}
__host__ __device__ constexpr int hp_off(int w) { return SM_PART + w * 160; }
template <bool HP>
__device__ __forceinline__ void ln_final(uint32_t a, float& mean, float& rstd, float& msq) {
    float2 v[5];
#pragma unroll
    for (int w = 0; w < 5; w++) v[w] = lds64f(a + (HP ? hp_off(w) : w * 8));
    mean = (((v[0].x + v[1].x) + (v[2].x + v[3].x)) + v[4].x) * (1.f / D_MODEL);
    msq = (((v[0].y + v[1].y) + (v[2].y + v[3].y)) + v[4].y) * (1.f / D_MODEL);
    rstd = rsq(fmaxf(msq - mean * mean, 0.f) + 1e-5f);
}
constexpr float CS = 0.07216878364870322f * 1.4426950408889634f;
constexpr uint32_t ONES = 0x3f803f80u;

__global__ void __launch_bounds__(NTHR, 1) fused_kernel(const __grid_constant__ Params P) {
    extern __shared__ __align__(1024) unsigned char smem[];
    const uint32_t sb = (uint32_t)__cvta_generic_to_shared(smem);
    const int tid = pin(threadIdx.x), lane = tid & 31, warp = __shfl_sync(~0u, threadIdx.x >> 5, 0);
    const int g = lane >> 2, t = lane & 3, bx = blockIdx.x;
    const int cta = bx >= NCTA || CMAP == 0 ? bx : CMAP == 1 ? (bx & 31) * 4 + (bx >> 5) : CMAP == 2 ? ((bx >> 1) & 31) * 4 + (bx >> 6) * 2 + (bx & 1)
                  : CMAP == 3 ? (((bx >> 2) & 3) * 8 + (bx >> 4)) * 4 + (bx & 3) : CMAP == 4 ? (((bx >> 1) & 7) + (bx >> 5) * 8) * 4 + ((bx >> 4) & 1) * 2 + (bx & 1)
                  : CMAP == 5 ? ((bx & 15) + (bx >> 6) * 16) * 4 + ((bx >> 4) & 3) : (((bx >> 1) & 15) + (bx >> 6) * 16) * 4 + ((bx >> 5) & 1) * 2 + (bx & 1);

    if (cta == NCTA) {
        const uint32_t ep = *(volatile unsigned*)&g_epoch;
        if (tid == 0) {
#pragma unroll 1
            for (int it = 0; it < SPIN; it++) { if (ll_tag(ld_rlx(&g_ll[1][0][192])) == ep * 4 + 2) break; __nanosleep(200); }
        }
        __syncthreads();
#pragma unroll 1
        for (int i = tid; i < 4 * 80 * 8; i += NTHR)
            *reinterpret_cast<uint4*>(g_acc + (i >> 3) * ACC_PITCH + (i & 7) * 16) = make_uint4(0, 0, 0, 0);
        __threadfence();
        __syncthreads();
        if (tid == 0) asm volatile("st.relaxed.gpu.global.u32 [%0], %1;" :: "l"(&g_zflag), "r"(ep + 1) : "memory");
        return;
    }
    TSTAMP(0);
    if (tid == 64) { uint32_t now; asm volatile("mov.u32 %0, %globaltimer_lo;" : "=r"(now)); sts32(sb + SM_T0, now); }

    const int mlp = (cta & 3) == 3 ? 96 : (cta >> 2) * 3 + (cta & 3);
    const uint32_t barw = sb + SM_BAR + warp * 96, subw = sb + warp * SUB;
    const int rowc = (cta >> 2) * SK + (SK - WIN) + (cta & 3) * 64;
    const CUtensorMap* tmk = reinterpret_cast<const CUtensorMap*>(__shfl_sync(~0u, (u64)&P.tm[0] + (lane >> 5), 0));
    if (elect()) {
        asm volatile("mbarrier.init.shared::cta.b64 [%0], 1;" :: "r"(barw + 72));
        asm volatile("mbarrier.init.shared::cta.b64 [%0], 1;" :: "r"(sb + SM_CBAR + 64 + warp * 8));
        asm volatile("fence.proxy.async.shared::cta;" ::: "memory");
        mbar_expect(barw + 72, warp < 4 ? 3 * SUB : 2 * SUB);
        const int r0 = (cta & 3) * 160 + warp * 8;
        tma3(subw + SM_WQ, tmk + TM_WQ, (cta >> 2) * 3, r0, barw + 72, POL_FIRST);
        tma3(subw + SM_WQ + TILE, tmk + TM_WQ, (cta >> 2) * 3, r0 + 64, barw + 72, POL_FIRST);
        if (warp < 4) tma3(subw + SM_WQR, tmk + TM_WQ, (cta >> 2) * 3, r0 + 128, barw + 72, POL_FIRST);
        const uint32_t j = warp - 2;
        if (j < NI0) issue_half(((j >> 1) * 256 + (j & 1) * 32) << 20 | j * HALF | (10 + j) << 3 | 3, sb, rowc, cta, tmk);
#pragma unroll
        for (int i = 0; i < 9; i++) asm volatile("mbarrier.init.shared::cta.b64 [%0], 1;" :: "r"(barw + i * 8));
        asm volatile("mbarrier.init.shared::cta.b64 [%0], 1;" :: "r"(sb + SM_CBAR + warp * 8));
        asm volatile("mbarrier.init.shared::cta.b64 [%0], %1;" :: "r"(sb + SM_CBAR + 128 + warp * 8), "r"(warp == 1 ? 8 : 1));
        if (warp < 2) asm volatile("mbarrier.init.shared::cta.b64 [%0], %1;" :: "r"(sb + SM_CBAR + 192 + warp * 8), "r"(1 + warp * 5));
        sts64(barw + 80, 0, 0);
        asm volatile("fence.proxy.async.shared::cta;" ::: "memory");
        asm volatile("prefetch.tensormap [%0];" :: "l"(tmk + warp + 1) : "memory");
    }
    __syncwarp();
    const int c4 = 32 * warp + 16 * (t >> 1) + 2 * g + (t & 1);
    const int j40 = __shfl_sync(~0u, (cta & 3) * 40, 0);
    uint2 xp = make_uint2(0, 0);
    if (tid < 160) asm volatile("ld.global.nc.v2.u32 {%0,%1}, [%2];" : "=r"(xp.x), "=r"(xp.y) : "l"(P.x + 4 * c4) : "memory");
    else if (tid == 255) { sts32(sb + SM_EPOCH, *(volatile unsigned*)&g_epoch); sts32(sb + SM_ZERO, 0); sts32(sb + SM_M1, ~0u); }
    else if (tid < 176) sts32(sb + SM_B1 + (tid - 160) * 4, (uint32_t)reinterpret_cast<const volatile unsigned short*>(P.b1)[min(mlp, 95) * 16 + tid - 160] << 16);
    else if (tid >= 192 && tid < 192 + NCB) sts32(sb + SM_CNT + (tid - 192) * 8, 0);
    unsigned char* accg = reinterpret_cast<unsigned char*>(__shfl_sync(~0u, (u64)g_acc + (lane >> 5), 0));
    auto release = [&](const uint4& tw) {
        uint32_t old;
        __syncwarp();
        asm volatile("{\n.reg .pred p;\nsetp.eq.u32 p, %2, 0;\nmov.u32 %0, 0;\n@p atom.relaxed.cta.shared.inc.u32 %0, [%1], 3;\n}"
                     : "=r"(old) : "r"(sb + SM_CNT + (tw.x & 0xf8)), "r"(lane) : "memory");
        return old;
    };
    auto refill = [&](const uint4& tw, uint32_t old) {
        if (__any_sync(~0u, old == 3 && (tw.y & 2))) {
            wait_until(lds32(sb + SM_T0) + tw.z);
            if (elect()) issue_half(tw.y, sb, rowc, cta, tmk);
            __syncwarp();
        }
    };
    __syncthreads();
    mbar_wait(barw + 72, 0);
    if (warp == 7 && elect()) static_for<NI0, NI1>([&](auto I) { issue_half(UC<load_word(I.value)>::value, sb, rowc, cta, tmk); });

    uint32_t offV0, offV2, maskA, maskB;
    auto calc_masks = [&](int ln) {
        const uint32_t m = (ln & 4) ? 0xffff0000u : 0x0000ffffu;
        maskA = (ln & 8) ? 0u : m; maskB = (ln & 8) ? m : 0u;
    };
    auto calc_offsets = [&](int ln) {
        const int gg = ln >> 2, tt = ln & 3;
        offV0 = subw + (6 * tt) * 128 + ((gg ^ ((6 * tt) & 7)) << 4);
        offV2 = subw + (6 * tt + 2) * 128 + ((gg ^ ((6 * tt + 2) & 7)) << 4);
    };
    calc_offsets(lane);
    calc_masks(lane);

    auto load_v = [&](uint4 (&v)[6], uint32_t so) {
        v[0] = lds128(offV0 + so); v[1] = lds128((offV0 ^ 16) + so + 128); v[2] = lds128(offV2 + so);
        v[3] = lds128((offV2 ^ 16) + so + 128); v[4] = lds128((offV0 ^ 64) + so + 512); v[5] = lds128((offV0 ^ 80) + so + 640);
    };
    const int roww = __shfl_sync(~0u, rowc + warp * 8, 0);
    auto issue_v = [&](auto I, int dw) {
        constexpr Step c = SCH.st[I.value];
        const uint32_t bar = barw + dw * 96 + c.slot * 8;
        mbar_expect(bar, SUB);
        tma3(subw + dw * SUB + c.slot * TILE, tmk + TM_V, 0, roww + dw * 8 + c.unit * 256, bar, POL_FIRST);
    };
    auto refill2 = [&](auto I) { __syncwarp(); if (elect()) issue_v(I, 0); };
    uint4 wq0[6];
    uint32_t xna;
    auto load_wq = [&]() {
        load_v(wq0, SM_WQ);
        const int r = c4 - j40;
        xna = pin((tid < 160 && r >= 0 && r < 40) ? sb + SM_VEC + r * 8 : 0u);
    };
    mbar_wait(sb + SM_BAR + (warp >> 1) * 96 + 72, 0);
    load_wq();
    uint4 kr[8][6];
#pragma unroll
    for (int u = 0; u < 8; u++)
#pragma unroll
        for (int i = 0; i < 6; i++) asm volatile("" : "=r"(kr[u][i].x), "=r"(kr[u][i].y), "=r"(kr[u][i].z), "=r"(kr[u][i].w));

#pragma unroll 1
    for (int layer = 0; layer < 2; layer++) {
        {
            if (xna) sts64(xna, xp.x, xp.y);
            uint4 wqh[3];
            const uint32_t so = SM_WQR - ((warp + 1) >> 1) * SUB;
            wqh[0] = lds128(((warp & 1) ? (offV2 ^ 16) + 128 : offV0) + so);
            wqh[1] = lds128(((warp & 1) ? (offV0 ^ 64) + 512 : (offV0 ^ 16) + 128) + so);
            wqh[2] = lds128(((warp & 1) ? (offV0 ^ 80) + 640 : offV2) + so);
            __syncthreads();
            TSTAMPL(20);
            const uint32_t pa = sb + SM_VEC + t * 4;
            uint32_t p0 = lds32(pa + warp * 16), p1 = lds32(pa + 128 + warp * 16), ph = lds32(pa + 256 + (warp >> 1) * 16);
            const float x0 = bf_lo(xp.x), x1 = bf_hi(xp.x), x2 = bf_lo(xp.y), x3 = bf_hi(xp.y);
            float s1 = (x0 + x1) + (x2 + x3), s2 = (x0 * x0 + x1 * x1) + (x2 * x2 + x3 * x3);
            s1 += shx(s1, 16); s2 += shx(s2, 16);
            if (g >= 4) p0 = p1 = ph = ONES;
            float acc[3][4];
            const uint32_t dH = __byte_perm(ph, 0, (warp & 1) ? 0x3232 : 0x1010);
#pragma unroll
            for (int j = 0; j < 3; j++) { acc[j][0] = acc[j][1] = acc[j][2] = acc[j][3] = 0.f; mma(acc[j], wqh[j], dH & maskA, dH & maskB); }
            s1 += shx(s1, 8); s2 += shx(s2, 8);
            const uint32_t dA = __byte_perm(p0, 0, 0x1010), dB = __byte_perm(p0, 0, 0x3232);
#pragma unroll
            for (int j = 0; j < 3; j++) mma(acc[j], wq0[j], dA & maskA, dA & maskB);
            wq0[0] = lds128(offV0 + SM_WQ + TILE); wq0[1] = lds128((offV0 ^ 16) + SM_WQ + TILE + 128); wq0[2] = lds128(offV2 + SM_WQ + TILE);
            wqh[0] = lds128((offV2 ^ 16) + SM_WQ + TILE + 128); wqh[1] = lds128((offV0 ^ 64) + SM_WQ + TILE + 512); wqh[2] = lds128((offV0 ^ 80) + SM_WQ + TILE + 640);
            s1 += shx(s1, 4); s2 += shx(s2, 4);
#pragma unroll
            for (int j = 0; j < 3; j++) mma(acc[j], wq0[j + 3], dB & maskA, dB & maskB);
            if (layer == 1) {
                if (warp >= 4) refill2(IC<2>{});
                refill2(IC<4>{});
            }
            s1 += shx(s1, 2); s2 += shx(s2, 2);
            const uint32_t dC = __byte_perm(p1, 0, 0x1010), dD = __byte_perm(p1, 0, 0x3232);
#pragma unroll
            for (int j = 0; j < 3; j++) mma(acc[j], wq0[j], dC & maskA, dC & maskB);
            s1 += shx(s1, 1); s2 += shx(s2, 1);
#pragma unroll
            for (int j = 0; j < 3; j++) mma(acc[j], wqh[j], dD & maskA, dD & maskB);
            if (t < 2 || layer == 0) {
                const uint32_t a = sb + (t < 2 ? SM_PART : 3 * TILE) + warp * 768 + (8 * g + 4 * (t & 1)) * 4;
#pragma unroll
                for (int j = 0; j < 3; j++) sts128f(a + j * 256, acc[j][0], acc[j][1], acc[j][2], acc[j][3]);
            }
            if (lane == 0 && warp < 5) sts64f(sb + SM_STAT + warp * 8, s1, s2);
            TSTAMPL(21);
            __syncthreads();
            TSTAMPL(22);
        }
        const uint32_t ep = lds32(sb + SM_EPOCH);
        if (tid < 192) {
            if (layer == 0) stsf(sb + SM_CS + tid * 4, sum8(sb + 3 * TILE + tid * 4, 768));
            const float s = sum8(sb + SM_PART + tid * 4, 768), cs = ldsf(sb + SM_CS + tid * 4);
            float mean, rstd, msq;
            ln_final<false>(sb + SM_STAT, mean, rstd, msq);
            st_rlx(&g_ll[layer][cta][tid], ll_pack((s - mean * cs) * rstd, ep * 4 + 1 + 2 * layer));
            if (tid == 0) stsf(sb + SM_FXS, fx_scale(msq));
        }
        TSTAMPL(23);
        __syncwarp();
        uint32_t offQ, offL;
        {
            const int ln = lane + lds32(sb + SM_ZERO);
            offQ = pin(sb + SM_VEC + (ln & 7) * 48);
            offL = pin(subw + ln * 16);
        }
        auto gather_q = [&](const u64 (&qw)[4], auto L) {
            const float q = ll_gather4(&g_ll[L.value][cta & ~3][tid], lds32(sb + SM_EPOCH) * 4 + 1 + 2 * L.value, qw[0], qw[1], qw[2], qw[3]) * (L.value ? 0x1p64f : 1.f);
            TSTAMPL(24);
            sts16(sb + SM_VEC + (((tid >> 1) & 1) * 4 + ((tid >> 3) & 3)) * 48 + (tid >> 5) * 8 + ((tid >> 2) & 1) * 4 + (tid & 1) * 2, pack_bf(q, q));
            __syncwarp();
            if (elect()) asm volatile("mbarrier.arrive.shared::cta.b64 _, [%0];" :: "r"(sb + SM_CBAR + CB_Q * 8) : "memory");
        };
        const uint32_t prow = sb + SM_PART + warp * 768;

        auto pf_w = [&](int at) {
            if ((PF1 == at || PF2 == at) && layer == 0 && (roww & 56) == 40 && elect()) {
                if (PF1 == at) asm volatile("cp.async.bulk.prefetch.L2.global.L2::cache_hint [%0], 15360, %1;" :: "l"(P.w1 + cta * 7680), "l"((u64)PFPOL << 32) : "memory");
                if (PF2 == at) asm volatile("cp.async.bulk.prefetch.L2.global.L2::cache_hint [%0], 15360, %1;" :: "l"(P.w2 + cta * 7680), "l"((u64)PFPOL << 32) : "memory");
            }
        };
        auto issue_w = [&](int which) {
            const uint32_t bar = sb + SM_CBAR + (CB_W1 + which) * 8;
            if (mlp == 96) asm volatile("mbarrier.arrive.shared::cta.b64 _, [%0];" :: "r"(bar) : "memory");
            else {
                mbar_expect(bar, 20480);
                if (which) tma3(sb + SM_W2, tmk + TM_W2, 0, mlp * 16, bar, WPOL);
                else asm volatile("cp.async.bulk.tensor.3d.shared::cluster.global.mbarrier::complete_tx::bytes.L2::cache_hint [%0], [%1, {%2, %3, %3}], [%4], %5;"
                                  :: "r"(sb + SM_W1), "l"(tmk + TM_W1), "r"(mlp * 16), "r"(0), "r"(bar), "l"((u64)WPOL << 32) : "memory");
            }
        };
        float acc[3][4];
        const int key = (g >> 1) + 4 * (g & 1);
        auto load_q = [&](uint4 (&qf)[3]) {
#pragma unroll
            for (int i = 0; i < 3; i++) qf[i] = lds128(offQ + i * 16);
        };
        auto score = [&](const uint4 (&v)[6], const uint4 (&qf)[3]) {
            float d[2][4];
#pragma unroll
            for (int j = 0; j < 2; j++) d[j][0] = d[j][1] = d[j][2] = d[j][3] = 0.f;
#pragma unroll
            for (int i = 0; i < 3; i++) { mma(d[0], v[2 * i], qf[i].x, qf[i].y); mma(d[1], v[2 * i + 1], qf[i].z, qf[i].w); }
            return (d[0][0] + d[0][3]) + (d[1][0] + d[1][3]);
        };
        auto softmax = [&](float S0, float S1, float S2, float S3) {
            int mi = __float_as_int(fmaxf(fmaxf(S0, S1), fmaxf(S2, S3)));
            mi = __reduce_max_sync(~0u, mi ^ ((mi >> 31) & 0x7fffffff));
            const float mrun = __int_as_float(mi ^ ((mi >> 31) & 0x7fffffff));
            const float p0 = ex2((S0 - mrun) * CS), p1 = ex2((S1 - mrun) * CS), p2 = ex2((S2 - mrun) * CS), p3 = ex2((S3 - mrun) * CS);
            const uint32_t pa = pack_bf(p0, p1), pb = pack_bf(p2, p3), pw = prow + 256 + (key >> 1) * 80 + t * 4 + (key & 1) * 2;
            sts16(pw, pa); sts16(pw + 16, pa >> 16); sts16(pw + 32, pb); sts16(pw + 48, pb >> 16);
            __syncwarp();
#pragma unroll
            for (int j = 0; j < 3; j++) acc[j][0] = acc[j][1] = acc[j][2] = acc[j][3] = 0.f;
            return make_float2(mrun, (p0 + p1) + (p2 + p3));
        };
        auto head_weight = [&](u64 pm, u64 pl, auto L) {
            const uint32_t tag = lds32(sb + SM_EPOCH) * 4 + 2 + 2 * L.value;
#pragma unroll 1
            for (int it = 0; it < SPIN; it++) {
                if (__all_sync(~0u, ll_tag(pm) == tag && ll_tag(pl) == tag)) break;
                ld_rlx2(&g_ll[1 + L.value][cta ^ (lane >> 3)][192 + (lane & 7) * 4], pm, pl);
            }
            const float f = ex2((ll_val(pm) - warp_max(ll_val(pm))) * CS);
            const float w = f * rcp(warp_sum(f * ll_val(pl)));
            if (lane < 8) stsf(sb + SM_FAC + lane * 4, w);
        };
        auto pv = [&](const uint4 (&v)[6], uint32_t pp) {
            const uint32_t dA = __byte_perm(pp, 0, 0x1010), dB = __byte_perm(pp, 0, 0x3232);
            mma(acc[0], v[0], dA & maskA, dA & maskB); mma(acc[1], v[1], dA & maskA, dA & maskB); mma(acc[2], v[2], dA & maskA, dA & maskB);
            mma(acc[0], v[3], dB & maskA, dB & maskB); mma(acc[1], v[4], dB & maskA, dB & maskB); mma(acc[2], v[5], dB & maskA, dB & maskB);
        };
        const uint32_t sa = prow + 256 + t * 32 + g * 4;
        if (layer == 0) {
            __syncthreads();
            sts64(prow + lane * 8, xp.x, xp.y);
            int e = 0;
            const uint4* tab = P.tile + (warp >> 2);
            uint4 tw = tab[0];
            uint32_t ka[3];
#pragma unroll
            for (int j = 0; j < 3; j++) ka[j] = pin(subw + key * 384 + j * 128 + ((t ^ ((3 * key + j) & 7)) << 4));
            auto load_k = [&](uint4 (&v)[6], uint32_t so) {
#pragma unroll
                for (int i = 0; i < 6; i++) v[i] = lds128(((i & 1) ? ka[i >> 1] ^ 64 : ka[i >> 1]) + so);
            };
            const uint32_t s0 = pin(prow + 256 + g * 4), sca = pin(sb + SM_SC + warp * 128 + g * 16);
#pragma unroll 1
            do {
                const uint4 tn = tab[2 * e + 2];
                uint4 v[6], qf[3];
                if (tw.x & (G_A | G_B | G_C)) {
                    if ((tw.x & G_A) && (roww & 56) == 56 && elect()) {
                        mbar_expect(sb + SM_CBAR + CB_SNAP * 8, 8192);
                        asm volatile("cp.async.bulk.shared::cluster.global.mbarrier::complete_tx::bytes [%0], [%1], 8192, [%2];"
                                     :: "r"(sb + 3 * TILE + 8192), "l"(&g_ll[0][cta & ~3][0]), "r"(sb + SM_CBAR + CB_SNAP * 8) : "memory");
                    }
                    if (tw.x & G_B) {
                        if (warp < 6) {
                            mbar_wait(sb + SM_CBAR + CB_SNAP * 8, 0);
                            u64 qw[4];
#pragma unroll
                            for (int i = 0; i < 4; i++) { const uint2 x = lds64(sb + 3 * TILE + 8192 + i * 2048 + tid * 8); qw[i] = x.x | (u64)x.y << 32; }
                            gather_q(qw, IC<0>{});
                        }
                        mbar_wait(sb + SM_CBAR + CB_Q * 8, 0);
                        TSTAMP(2);
                    }
                    if (tw.x & G_C) {
                        load_k(v, (e - LATEAT) * TILE);
                        load_q(qf);
                        stsf(s0 + (e - LATEAT) * 32, score(v, qf));
                    }
                }
                load_q(qf);
                mbar_wait(sb + SM_CBAR + (tw.x & 0xf8), tw.x >> 31);
                TRACE(e);
                load_k(v, tw.x & 0x3f000);
                const uint32_t old = release(tw);
                const float s = score(v, qf);
                uint32_t m;
                {
                    uint32_t a[6];
#pragma unroll
                    for (int i = 0; i < 6; i++) a[i] = bf2_amax(bf2_amax(v[i].x, v[i].y), bf2_amax(v[i].z, v[i].w));
                    m = bf2_amax(bf2_amax(bf2_amax(a[0], a[1]), bf2_amax(a[2], a[3])), bf2_amax(a[4], a[5]));
                }
                m = bf2_amax(m, m >> 16) & 0x7f80;
                m = max(m, __shfl_xor_sync(~0u, m, 1));
                stsf(s0 + e * 32, s);
                m = max(m, __shfl_xor_sync(~0u, m, 2));
                refill(tw, old);
                const uint32_t b = min(max(m, 15u << 7) - (15u << 7), 126u << 7);
                const uint32_t dn = ((127u << 7) - b) * 0x10001u, up = ((127u << 7 | 0x8000u) + b) * 0x10001u;
                uint32_t c[18], any = m > (141u << 7);
#pragma unroll
                for (int i = 0; i < 6; i++) {
                    const uint32_t y0 = bf2_mul(v[i].x, dn), y1 = bf2_mul(v[i].y, dn), y2 = bf2_mul(v[i].z, dn), y3 = bf2_mul(v[i].w, dn);
                    v[i] = make_uint4(bf2_fma(y0, up, v[i].x), bf2_fma(y1, up, v[i].y), bf2_fma(y2, up, v[i].z), bf2_fma(y3, up, v[i].w));
                    any |= v[i].x | v[i].y;
                    any |= v[i].z | v[i].w;
                    const uint32_t hb = __byte_perm(y2, y3, 0x7531);
                    c[3 * i] = __byte_perm(y0, y1, 0x6420); c[3 * i + 1] = __byte_perm(y2, y3, 0x6420);
                    c[3 * i + 2] = __byte_perm(y0, y1, 0x7531) | __funnelshift_r(hb, hb, 4);
                }
                asm volatile("st.shared.u8 [%0], %1;" :: "r"(sca + (e & 3) * 4 + (e >> 2)), "r"((b >> 7) + 63) : "memory");
                const bool rare = __any_sync(~0u, any);
                k_keep(kr, c, e, offL);
                if (rare) {
                    uint32_t odd = m > (141u << 7) ? 64u : 0u;
#pragma unroll
                    for (int i = 0; i < 6; i++) if (v[i].x | v[i].y | v[i].z | v[i].w) odd |= 1u << i;
                    odd = __reduce_or_sync(~0u, odd);
                    const uint2 st = lds64(barw + 80);
                    uint32_t lt; asm volatile("mov.u32 %0, %lanemask_lt;" : "=r"(lt));
                    uint32_t n = odd >= 64 ? NEXC + 1 : __shfl_sync(~0u, st.x, 0);
#pragma unroll 1
                    for (; odd && n <= NEXC; odd &= odd - 1) {
                        const int i = __ffs(odd) - 1;
                        uint4 r = v[0];
#pragma unroll
                        for (int k = 1; k < 6; k++) if (i == k) r = v[k];
                        static_for<0, 4>([&](auto K) {
                            const uint32_t x = word<K.value>(r), who = __ballot_sync(~0u, x), at = n + __popc(who & lt);
                            if (x && at < NEXC) sts64(sb + SM_EXC + warp * 128 + at * 8, x, (e * 32 + g * 4) << 16 | (((K.value & 1) * 4 + t) * 48 + i * 8 + (K.value >> 1) * 4));
                            n += __popc(who);
                        });
                    }
                    if (n > NEXC) asm volatile("st.shared.u8 [%0], %1;" :: "r"(sca + (e & 3) * 4 + (e >> 2)), "r"(0) : "memory");
                    sts64(barw + 80, n > NEXC ? st.x : n, n > NEXC ? st.y | 1u << e : st.y);
                    __syncwarp();
                }
                tw = tn;
            } while (++e < 16);
            asm volatile("fence.proxy.async.shared::cta;" ::: "memory");
            __syncwarp();
            TSTAMP(10);
            calc_offsets(lane + lds32(sb + SM_ZERO));
            {
                const uint2 st = lds64(barw + 80);
                const uint32_t xa = sb + SM_EXC + warp * 128 + (lane & 15) * 8 + 4;
                uint32_t pos = lds32(xa), lt;
                asm volatile("mov.u32 %0, %lanemask_lt;" : "=r"(lt));
                if (lane >= st.x) pos = 0x80000000u;
                const bool dup = (__match_any_sync(~0u, pos >> 16) & lt) && lane < st.x;
                if (lane < 16) sts32(xa, dup ? pos | 0x40000000u : pos);
                if (__any_sync(~0u, dup)) sts32(barw + 84, st.y | 0x10000u);
                const float2 ml = softmax(ldsf(sa), ldsf(sa + 128), ldsf(sa + 256), ldsf(sa + 384));
                sts64f(sb + SM_ML + warp * 8, ml.x, warp_sum(ml.y));
            }
#pragma unroll 1
            do {
                const uint4 tn = tab[2 * e + 2];
                if (tw.x & (G_A | G_B)) {
                    if (tw.x & G_A) {
                        if (lane < 24) st_rlx(&g_ll[1][cta][warp * 24 + lane], 0ull);
                        else if (lane < 28) st_rlx(&g_ll[1][cta][168 + warp * 4 + lane], ll_pack(ldsf(sb + SM_ML + warp * 8 + (lane & 1) * 4), lds32(sb + SM_EPOCH) * 4 + 2));
                    }
                    if ((tw.x & G_B) && (roww & 56) == 56) {
                        const uint32_t want = lds32(sb + SM_EPOCH) + 1;
#pragma unroll 1
                        for (int it = 0; it < SPIN; it++) {
                            uint32_t v; asm volatile("ld.acquire.gpu.global.u32 %0, [%1];" : "=r"(v) : "l"(&g_zflag) : "memory");
                            if (__all_sync(~0u, v == want)) break;
                        }
                    }
                    if ((tw.x & G_B) && (roww & 56) == 48) head_weight(0, 0, IC<0>{});
                    if (tw.x & G_B) pf_w(0);
                    __syncwarp();
                }
                const uint32_t pp = lds32(prow + 256 + t * 80 + ((tw.x >> 20) & 255));
                mbar_wait(sb + SM_CBAR + (tw.x & 0xf8), tw.x >> 31);
                TRACE(e);
                uint4 v[6];
                load_v(v, tw.x & 0x3f000);
                refill(tw, release(tw));
                pv(v, pp);
                tw = tn;
            } while (++e < 32);
        } else {
            spin(QDELAY);
            u64 qw[4] = {0, 0, 0, 0};
            if (warp < 6) {
#pragma unroll
                for (int i = 0; i < 4; i++) qw[i] = ld_rlx(&g_ll[1][(cta & ~3) + i][tid]);
            }
            uint4 tb[8][3];
            auto load_tb = [&](auto I) {
#pragma unroll
                for (int i = 0; i < 3; i++) tb[I.value][i] = lds128(offL + (I.value >> 1) * TILE + ((I.value & 1) * 3 + i) * 512);
            };
            static_for<0, NPRE>(load_tb);
            if (S0EARLY) refill2(IC<5>{});
            auto vwait = [&](auto I) { mbar_wait(barw + IC<SCH.st[I.value].slot>::value * 8, IC<SCH.st[I.value].par>::value); TRACE(32 + I.value); };
            vwait(IC<0>{}); vwait(IC<1>{});
            uint32_t m1 = lds32(sb + SM_M1), m1n = m1;
            bool ok = true;
            if (warp < 6) gather_q(qw, IC<1>{});
            else if (!S0EARLY) mbar_wait(sb + SM_CBAR + CB_Q * 8, 1);
            if (!S0EARLY) refill2(IC<5>{});
            mbar_wait(sb + SM_CBAR + CB_Q * 8, 1);
            TSTAMP(12);
            uint4 qf[3];
            load_q(qf);
            sts64(prow + lane * 8, xp.x, xp.y);
            sts128f(prow + 256 + lane * 16, 0.f, 0.f, 0.f, 0.f);
            float S[4], d[2][4];
            auto vload = [&](auto I) {
                constexpr int p = I.value;
                constexpr Step c = SCH.st[p];
                load_v(kr[p & 7], c.slot * TILE);
                if constexpr (c.next >= 0) refill2(IC<c.next>{});
                if constexpr (p == 11) { __syncwarp(); if (elect()) asm volatile("mbarrier.arrive.shared::cta.b64 _, [%0];" :: "r"(sb + SM_CBAR + CB_REL * 8) : "memory"); }
            };
            auto side = [&](uint2 x) {
                const uint32_t qq = lds32(sb + SM_VEC + (x.y & 0xffff));
                return (bf_lo(x.x) * bf_lo(qq) + bf_hi(x.x) * bf_hi(qq)) * 0x1p-64f;
            };
            static_for<0, 96>([&](auto F) {
                constexpr int f = F.value, i = f % 6, u = kunit(f / 6), w = 3 * f % 12;
                uint4 (&src)[3] = *reinterpret_cast<uint4 (*)[3]>(f < 32 ? &tb[f / 4 & 7][0] : &kr[(f / 8 + 4) & 7][(f / 4 & 1) * 3]);
                const uint4 a = k_unpack(word<w % 4>(src[w / 4]), word<(w + 1) % 4>(src[(w + 1) / 4]), word<(w + 2) % 4>(src[(w + 2) / 4]), m1);
                if constexpr (f < 32 ? f % 4 == M1AT : f % 8 == M1P) m1 = m1n;
                if constexpr (f % 4 == 3 && f / 4 + NPRE < 8) {
                    load_tb(IC<f / 4 + NPRE>{});
                    if constexpr ((f / 4 + NPRE) & 1) { refill2(IC<5 + (f / 4 + NPRE) / 2>{}); m1n = lds32(sb + SM_M1); }
                }
                if constexpr (i < 2) d[i][0] = d[i][1] = d[i][2] = d[i][3] = 0.f;
                mma(d[i & 1], a, (i & 1) ? qf[i / 2].z : qf[i / 2].x, (i & 1) ? qf[i / 2].w : qf[i / 2].y);
                if constexpr (i == 5) {
                    if constexpr (u == 11 || ((u & 3) == 0 && u != 8)) S[u >> 2] = (d[0][0] + d[0][3]) + (d[1][0] + d[1][3]);
                    else add_if(t == (u & 3), S[u >> 2], d[0][0] + d[0][3], d[1][0] + d[1][3]);
                    if constexpr (f < 64) S[u >> 2] = shx(S[u >> 2], 0);
                }
                if constexpr (f == 31) calc_offsets(lane + lds32(sb + SM_ZERO));
                if constexpr (f == 48) {
                    const uint2 x = lds64(sb + SM_EXC + warp * 128 + (lane & 15) * 8);
                    const float c = side(x);
                    if (x.y < 0x40000000u) stsf(prow + 256 + (x.y >> 16), c);
                }
                if constexpr (f >= 32 && f % 8 == 7) {
                    if constexpr (PARKS >> (f / 8 - 4) & 1) {
                        constexpr int p = popc(PARKS & ((1 << (f / 8 - 4)) - 1));
                        if constexpr (p > 1) { if (!ok) vwait(IC<p>{}); }
                        vload(IC<p>{});
                        m1n = lds32(sb + SM_M1);
                        if constexpr (p > 0) ok = mbar_test(barw + IC<SCH.st[p + 1].slot>::value * 8, IC<SCH.st[p + 1].par>::value);
                    }
                }
            });
            uint32_t bad = lds32(barw + 84);
            const uint32_t sc = lds32(sb + SM_SC + tid * 4);
            __syncwarp();
            if (bad) {
                const uint2 x = lds64(sb + SM_EXC + warp * 128 + (lane & 15) * 8);
                if ((int)x.y >= 0x40000000 && lane < 16) asm volatile("red.shared.add.f32 [%0], %1;" :: "r"(prow + 256 + ((x.y >> 16) & 511)), "f"(side(x)) : "memory");
#pragma unroll 1
                for (bad &= 0xffff; bad; bad &= bad - 1) {
                    const int e = __ffs(bad) - 1;
                    const __nv_bfloat16* kp = P.k + (size_t)(roww + e * 256 + key) * DH + t * 8;
                    uint4 v[6];
#pragma unroll
                    for (int i = 0; i < 6; i++) v[i] = *reinterpret_cast<const uint4*>(kp + i * 32);
                    const float s = score(v, qf) * 0x1p-64f;
                    if (t == 0) stsf(sa + e * 32, s);
                }
                __syncwarp();
            }
            TSTAMP(30);
            const float2 ml = softmax(S[0] * __uint_as_float((sc & 255) << 23) + ldsf(sa), S[1] * __uint_as_float((sc & 0xff00) << 15) + ldsf(sa + 128),
                                      S[2] * __uint_as_float((sc & 0xff0000) << 7) + ldsf(sa + 256), S[3] * __uint_as_float((sc >> 24) << 23) + ldsf(sa + 384));
            uint4 pq[4];
#pragma unroll
            for (int j = 0; j < 4; j++) pq[j] = lds128(prow + 256 + t * 80 + j * 16);
            TSTAMP(1);
            if (!ok) vwait(IC<NPARK>{});
            float ac2[3][4];
#pragma unroll
            for (int j = 0; j < 3; j++) ac2[j][0] = ac2[j][1] = ac2[j][2] = ac2[j][3] = 0.f;
            const uint32_t sl = (g & 1) ? 0x1044 : 0x4410, sh = (g & 1) ? 0x3244 : 0x4432;
            const uint32_t sA0 = (g & 2) ? 0x4444 : sl, sA1 = (g & 2) ? sl : 0x4444, sB0 = (g & 2) ? 0x4444 : sh, sB1 = (g & 2) ? sh : 0x4444;
            u64 pm = 0, pl = 0;
            static_for<NPARK, 16>([&](auto I) {
                constexpr int p = I.value;
                static_assert(p - SCH.st[p].mma0 < 8, "buffer in use");
                vload(I);
                if constexpr (p < 15) ok = mbar_test(barw + IC<SCH.st[p + 1].slot>::value * 8, IC<SCH.st[p + 1].par>::value);
                static_for<SCH.st[p].mma0, SCH.st[p].mma0 + SCH.st[p].nmma>([&](auto J) {
                    constexpr int u = SCH.st[J.value].unit;
                    const uint32_t pp = word<u & 3>(pq[u >> 2]), a0 = __byte_perm(pp, 0, sA0), a1 = __byte_perm(pp, 0, sA1), b0 = __byte_perm(pp, 0, sB0), b1 = __byte_perm(pp, 0, sB1);
#pragma unroll
                    for (int j = 0; j < 3; j++) mma(acc[j], kr[J.value & 7][j], a0, a1);
#pragma unroll
                    for (int j = 0; j < 3; j++) mma(ac2[j], kr[J.value & 7][j + 3], b0, b1);
                });
                if constexpr (p == NPARK) {
                    const float l = warp_sum(ml.y);
                    if (lane < 28) st_rlx(&g_ll[2][cta][lane < 24 ? warp * 24 + lane : 168 + warp * 4 + lane], lane < 24 ? 0ull : ll_pack((lane & 1) ? l : ml.x, lds32(sb + SM_EPOCH) * 4 + 4));
                }
                if constexpr (p == HWAT) { if ((roww & 56) == 48) ld_rlx2(&g_ll[2][cta ^ (lane >> 3)][192 + (lane & 7) * 4], pm, pl); }
                if constexpr (p == HWAT + 2) { if ((roww & 56) == 48) head_weight(pm, pl, IC<1>{}); }
                if constexpr (p >= WOAT && p < WOAT + 3) {
                    if ((roww & 56) == 8 * (p - WOAT)) {
                        mbar_wait(sb + SM_CBAR + CB_REL * 8, 0);
                        if (elect()) {
                            issue_half(UC<load_word(64 + 2 * (p - WOAT)) | 1>::value, sb, rowc, cta, tmk);
                            if constexpr (p < WOAT + 2) issue_half(UC<load_word(65 + 2 * (p - WOAT)) | 1>::value, sb, rowc, cta, tmk);
                        }
                        __syncwarp();
                    }
                }
                if constexpr (p < 15) { if (!ok) mbar_wait(barw + IC<SCH.st[p + 1].slot>::value * 8, IC<SCH.st[p + 1].par>::value); TRACE(33 + p); }
            });
#pragma unroll
            for (int j = 0; j < 3; j++)
#pragma unroll
                for (int k = 0; k < 4; k++) acc[j][k] += ac2[j][k];
        }
        TSTAMP2(3);

        uint32_t pa, ro;
        {
            const int zero = lds32(sb + SM_ZERO), lz = lane + zero;
            const u64* lb = &g_ll[1 + layer][cta & ~3][0];
            xp = lds64(prow + lane * 8);
            __syncwarp();
            if (t < 2) {
#pragma unroll
                for (int j = 0; j < 3; j++) sts128f(prow + (64 * j + 8 * g + 4 * t) * 4, acc[j][0], acc[j][1], acc[j][2], acc[j][3]);
            }
            const uint32_t tag = lds32(sb + SM_EPOCH) * 4 + 2 + 2 * layer;
            const int d = warp * 24 + min(lz, 23);
            __syncthreads();
            TSTAMPL(29);
            {
                const uint4 fa = lds128(sb + SM_FAC), fb = lds128(sb + SM_FAC + 16);
                float s[8];
#pragma unroll
                for (int w = 0; w < 8; w++) s[w] = ldsf(sb + SM_PART + d * 4 + w * 768);
                const float own = ((s[0] * __uint_as_float(fa.x) + s[1] * __uint_as_float(fa.y)) + (s[2] * __uint_as_float(fa.z) + s[3] * __uint_as_float(fa.w))) +
                      ((s[4] * __uint_as_float(fb.x) + s[5] * __uint_as_float(fb.y)) + (s[6] * __uint_as_float(fb.z) + s[7] * __uint_as_float(fb.w)));
                if (lane < 24) st_rlx(const_cast<u64*>(lb) + (cta & 3) * 256 + d, ll_pack(own, tag));
            }
            u64 w0, w1, w2, w3;
            auto look = [&]() { w0 = ld_rlx(lb + d); w1 = ld_rlx(lb + 256 + d); w2 = ld_rlx(lb + 512 + d); w3 = ld_rlx(lb + 768 + d); };
            if (OPOLL == 0) look();
            pf_w(1);
            const int row = pin((lz & 1) + 2 * (lz & 2) + 2 * (lz >> 4));
            const uint32_t wa = pin(sb + SM_RING + warp * 1536 + row * 64 + ((((lz >> 2) & 3) ^ (row >> 1)) << 4));
            uint4 v[5][3];
            auto load_wo = [&](auto J) {
                mbar_wait(sb + SM_CBAR + (CB_WO + J.value) * 8, layer);
#pragma unroll
                for (int p = 0; p < 3; p++) v[J.value][p] = lds128(wa + ring_hs(64 + J.value) * HALF + p * 512);
            };
            auto w1_early = [&](int at) {
                pf_w(at);
                if ((layer ? W1AT1 : W1AT0) == at) {
                    __syncwarp();
                    if (elect() && cnt_inc(sb + SM_CNT + CB_W1 * 8, 7) == 7) issue_w(0);
                    __syncwarp();
                }
            };
            load_wo(IC<0>{});
            if (OPOLL == 1) look();
            load_wo(IC<1>{});
            if (OPOLL == 2) look();
            w1_early(2);
            load_wo(IC<2>{});
            w1_early(3);
#pragma unroll 1
            for (int it = 0; it < SPIN; it++) {
                if (__all_sync(~0u, ll_tag(w0) == tag && ll_tag(w1) == tag && ll_tag(w2) == tag && ll_tag(w3) == tag)) break;
                look();
            }
            TSTAMP2(4);
            const float o = (ll_val(w0) + ll_val(w1)) + (ll_val(w2) + ll_val(w3));
            const uint32_t od = pack_bf(o, o);
            uint32_t op[3];
#pragma unroll
            for (int p = 0; p < 3; p++) op[p] = __shfl_sync(~0u, od, 8 * p + row);
            float y[5][4];
#pragma unroll
            for (int j = 0; j < 5; j++) y[j][0] = y[j][1] = y[j][2] = y[j][3] = 0.f;
#pragma unroll
            for (int p = 0; p < 2; p++)
#pragma unroll
                for (int j = 0; j < 3; j++) mma(y[j], v[j][p], op[p] & maskA, op[p] & maskB);
            load_wo(IC<3>{});
#pragma unroll
            for (int j = 0; j < 3; j++) mma(y[j], v[j][2], op[2] & maskA, op[2] & maskB);
            load_wo(IC<4>{});
            __syncwarp();
#pragma unroll
            for (int p = 0; p < 3; p++)
#pragma unroll
                for (int j = 3; j < 5; j++) mma(y[j], v[j][p], op[p] & maskA, op[p] & maskB);
            {
                const int word = (lz & 3) * 160 + j40 + warp * 8 + (lz >> 2);
                pa = pin(sb + SM_RING + warp * 256 + lz * 4);
                ro = pin((word >> 3) * ACC_PITCH + (word & 7) * 8);
            }
            if ((t >> 1) == (g >> 2)) {
#pragma unroll
                for (int j = 0; j < 5; j++)
                    sts128f(sb + SM_RING + warp * 1536 + j * 256 + (8 * g + 4 * (t & 1)) * 4, y[j][0], y[j][1], y[j][2], y[j][3]);
            }
        }
        TSTAMP2(5);
        __syncthreads();
        if (warp < 5) {
            unsigned char* accb = accg + 2 * layer * ACC_BYTES;
            float fxs = ldsf(sb + SM_FXS);
            {
                const float s = sum8(pa, 1536) + sum8(pa + 128, 1536);
                asm volatile("red.relaxed.gpu.global.add.u64 [%0], %1;" :: "l"(accb + ro), "l"(fx_pack(s, fxs)) : "memory");
            }
            TSTAMP2(6);
            if (layer == 0) asm volatile("bar.arrive 2, 256;" ::: "memory");
            else if (mlp == 96) { TDUMP(); return; }
            uint4 wf[8];
            const int lz = lane + lds32(sb + SM_ZERO);
            const uint32_t hpa = pin(sb + SM_PART + warp * 160 + ((lz & 2) * 4 + (lz >> 2)) * 8 + (lz & 1) * 4);
            const uint32_t w2a = pin(sb + SM_W2 + ((lz & 3) * 10 + 2 * warp) * 128 + (((lz >> 2) ^ ((2 * lz + 2 * warp) & 6)) << 4));
            const uint32_t la = sb + SM_W1 + warp * 4096 + (lz & 4) * 512 + (lz & 2) * 64 + (lz & 1) * 32 + (lz >> 4) * 64 + ((((lz >> 3) ^ (lz >> 1)) & 1) << 4);
            unsigned char* ap = accb + (c4 >> 3) * ACC_PITCH + (c4 & 7) * 8;
            {
                u64 w[4];
                bool have;
                int it = 0;
                spin(AR1D);
#pragma unroll 1
                do {
#pragma unroll
                    for (int k = 0; k < 4; k++) w[k] = ld_rlx(ap + k * 20 * ACC_PITCH);
                    have = mbar_test(sb + SM_CBAR + CB_W1 * 8, layer);
#pragma unroll
                    for (int j = 0; j < 8; j++) wf[j] = ldsm_t(la + j * 256);
                } while (!__all_sync(~0u, lo32(w[0]) & lo32(w[1]) & lo32(w[2]) & lo32(w[3]) & 32) && ++it < SPIN);
                if (!have) {
                    mbar_wait(sb + SM_CBAR + CB_W1 * 8, layer);
#pragma unroll
                    for (int j = 0; j < 8; j++) wf[j] = ldsm_t(la + j * 256);
                    TSTAMPL(28);
                }
                const float inv = fx_inv(fxs);
                xp = make_uint2(pack_bf(bf_lo(xp.x) + fx_val(w[0]) * inv, bf_hi(xp.x) + fx_val(w[1]) * inv),
                                pack_bf(bf_lo(xp.y) + fx_val(w[2]) * inv, bf_hi(xp.y) + fx_val(w[3]) * inv));
            }
            TSTAMP2(7);
            uint4 w2r[8];
            {
                const uint32_t e0 = (g & 1) ? ONES : xp.x, e1 = (g & 1) ? ONES : xp.y, o0 = (g & 1) ? xp.x : ONES, o1 = (g & 1) ? xp.y : ONES;
                float d[8][4];
#pragma unroll
                for (int j = 0; j < 8; j++) { d[j][0] = d[j][1] = d[j][2] = d[j][3] = 0.f; mma(d[j], wf[j], (j & 1) ? o0 : e0, (j & 1) ? o1 : e1); }
                const float x0 = bf_lo(xp.x), x1 = bf_hi(xp.x), x2 = bf_lo(xp.y), x3 = bf_hi(xp.y);
                const float s1 = (x0 + x1) + (x2 + x3), s2 = (x0 * x0 + x1 * x1) + (x2 * x2 + x3 * x3);
                float ss = ((lane & 16) ? s2 : s1) + shx((lane & 16) ? s1 : s2, 16);
                ss += shx(ss, 8); ss += shx(ss, 4);
                float r[4];
#pragma unroll
                for (int k = 0; k < 4; k++) r[k] = d[0][k] + d[1][k ^ 1];
#pragma unroll
                for (int j = 1; j < 4; j++)
#pragma unroll
                    for (int k = 0; k < 4; k++) add_if(t == j, r[k], d[2 * j][k], d[2 * j + 1][k ^ 1]);
                const float a = ((t & 1) ? r[1] : r[0]) + shx((t & 1) ? r[0] : r[1], 1), b = ((t & 1) ? r[3] : r[2]) + shx((t & 1) ? r[2] : r[3], 1);
                ss += shx(ss, 2);
                const float dd = ((t & 2) ? b : a) + shx((t & 2) ? a : b, 2);
                ss += shx(ss, 1);
                stsf(hpa, dd);
                if ((lane & 15) == 0) stsf(sb + SM_PART + warp * 160 + 128 + (lane >> 2), ss);
            }
            TSTAMPL(25);
            bar_sync(1, 160);
            TSTAMPL(26);
            float mean, rstd, msq;
            ln_final<true>(sb + 128, mean, rstd, msq);
            float2 hp[5];
#pragma unroll
            for (int w = 0; w < 5; w++) hp[w] = lds64f(sb + hp_off(w) + (lane & 15) * 8);
            const float b1v = ldsf(sb + SM_B1 + (lane & 15) * 4);
            mbar_wait(sb + SM_CBAR + CB_W2 * 8, layer);
#pragma unroll
            for (int i = 0; i < 8; i++) w2r[i] = lds128(((i & 1) ? (w2a ^ 16) + 128 : w2a) + (i >> 1) * 5120);
            if (layer == 0) asm volatile("bar.arrive 3, 256;" ::: "memory");
            float hv = (((hp[0].x + hp[1].x) + (hp[2].x + hp[3].x)) + hp[4].x) - mean * (((hp[0].y + hp[1].y) + (hp[2].y + hp[3].y)) + hp[4].y);
            hv = hv * rstd + b1v;
            hv = hv * rcp(1.f + ex2(hv * (-2.302208198f - 0.1029432397f * hv * hv)));
            const uint32_t hd = pack_bf(hv, hv);
            TSTAMPL(27);
            fxs = fx_scale(msq);
            float ym[4][4];
#pragma unroll
            for (int i = 0; i < 4; i++) ym[i][0] = ym[i][1] = ym[i][2] = ym[i][3] = 0.f;
#pragma unroll
            for (int i = 0; i < 4; i++) {
                const uint32_t hh = __shfl_sync(~0u, hd, 4 * i + t);
                mma(ym[(i & 1) * 2], w2r[2 * i], hh & maskA, hh & maskB);
                mma(ym[(i & 1) * 2 + 1], w2r[2 * i + 1], hh & maskA, hh & maskB);
            }
            const float sc2 = __uint_as_float((uint32_t)(127 + 16 - max(((int)(__float_as_uint(msq) >> 23) - 127) >> 1, -100)) << 23);
            float y[4];
#pragma unroll
            for (int k = 0; k < 4; k++) y[k] = ((t & 2) ? ym[1][k] + ym[3][k] : ym[0][k] + ym[2][k]) * sc2;
            u64 w[2] = {fx2_pack(y[0], y[1]), fx2_pack(y[2], y[3])};
            ap = accb + ACC_BYTES + (c4 >> 2) * ACC_PITCH + (c4 & 3) * 8;
            const float inv = fx_inv(sc2);
            if (!(fmaxf(fmaxf(fabsf(y[0]), fabsf(y[1])), fmaxf(fabsf(y[2]), fabsf(y[3]))) < FX2LIM) && mlp != 96) {
#pragma unroll
                for (int k = 0; k < 4; k++)
                    asm volatile("red.relaxed.gpu.global.add.u64 [%0], %1;" :: "l"(ap + (k >> 1) * 40 * ACC_PITCH + 64 + (k & 1) * 32), "l"(fx_pack(y[k] * inv, fxs)) : "memory");
                __threadfence();
#pragma unroll
                for (int k = 0; k < 2; k++) { asm volatile("red.relaxed.gpu.global.or.b64 [%0], 256;" :: "l"(ap + k * 40 * ACC_PITCH) : "memory"); w[k] = 1; }
            }
            uint2 b2v = make_uint2(0, 0);
            auto add_mlp = [&]() {
                float z[4] = {fx2_lo(w[0]) * inv, fx2_hi(w[0]) * inv, fx2_lo(w[1]) * inv, fx2_hi(w[1]) * inv};
                if ((lo32(w[0]) | lo32(w[1])) & 256) {
                    __threadfence();
#pragma unroll
                    for (int k = 0; k < 4; k++) z[k] += fx_val(ld_rlx(ap + (k >> 1) * 40 * ACC_PITCH + 64 + (k & 1) * 32)) * fx_inv(fxs);
                }
                xp = make_uint2(pack_bf(bf_lo(xp.x) + (z[0] + bf_lo(b2v.x)), bf_hi(xp.x) + (z[1] + bf_hi(b2v.x))),
                                pack_bf(bf_lo(xp.y) + (z[2] + bf_lo(b2v.y)), bf_hi(xp.y) + (z[3] + bf_hi(b2v.y))));
            };
            if (layer == 1) {
                u64 old[2];
#pragma unroll
                for (int k = 0; k < 2; k++) asm volatile("atom.relaxed.gpu.global.add.u64 %0, [%1], %2;" : "=l"(old[k]) : "l"(ap + k * 40 * ACC_PITCH), "l"(w[k]) : "memory");
                TSTAMP(18);
                asm volatile("ld.global.nc.v2.u32 {%0,%1}, [%2];" : "=r"(b2v.x), "=r"(b2v.y) : "l"(P.b2 + 4 * c4));
#pragma unroll
                for (int k = 0; k < 2; k++) w[k] += old[k];
                add_mlp();
                uint32_t* op = reinterpret_cast<uint32_t*>(P.out) + 2 * c4;
                if ((w[0] & 255) == 96) { op[0] = xp.x; if (tid == 0) g_epoch = lds32(sb + SM_EPOCH) + 1; }
                if ((w[1] & 255) == 96) op[1] = xp.y;
                TSTAMP(19);
                TDUMP();
                return;
            }
#pragma unroll
            for (int k = 0; k < 2; k++) if (mlp != 96) asm volatile("red.relaxed.gpu.global.add.u64 [%0], %1;" :: "l"(ap + k * 40 * ACC_PITCH), "l"(w[k]) : "memory");
            TSTAMP(8);
            asm volatile("ld.global.nc.v2.u32 {%0,%1}, [%2];" : "=r"(b2v.x), "=r"(b2v.y) : "l"(P.b2 + 4 * c4));
            calc_offsets(lane + lds32(sb + SM_ZERO));
            load_wq();
            const uint32_t c0 = clk();
            while (clk() - c0 < ARDELAY);
            if (warp < TB) refill2(IC<3>{});
            fx_poll(ap, 96, w);
            if (warp >= TB) refill2(IC<3>{});
            add_mlp();
            TSTAMP(9);
        } else {
            if ((roww & 56) == 40 && elect()) {
                if ((layer ? W1AT1 : W1AT0) == 4) issue_w(0);
                issue_w(1);
            }
            if (layer == 1) { TDUMP(); return; }
            __syncwarp();
            calc_offsets(lane + lds32(sb + SM_ZERO));
            load_wq();
            auto fill = [&](int i, int end, uint32_t c0, uint32_t gap) {
#pragma unroll 1
                for (; i < end; i += 3, c0 += 3 * gap) {
                    const uint32_t bar = sb + SM_BAR + (i & 7) * 96 + 32 + (i & 24);
                    while ((int)(clk() - c0) < 0);
                    mbar_expect(bar, SUB);
                    tma3(sb + SM_RING + i * SUB, tmk + TM_V, 0, rowc + (i & 7) * 8 + ((UC<SCH.st[0].unit << 8 | SCH.st[1].unit << 16 | SCH.st[2].unit << 24>::value >> (i & 24)) & 0xf00), bar, POL_FIRST);
                }
                return c0;
            };
            bar_sync(2, 256);
            if (elect()) {
                asm volatile("fence.proxy.async.shared::cta;" ::: "memory");
                const uint32_t c0 = fill(warp - 5, 6, clk() + WD1 + (warp - 5) * WG1, WG1);
                while ((int)(clk() - c0) < 0);
                issue_v(IC<3>{}, 0);
            }
            __syncwarp();
            bar_sync(3, 256);
            if (elect()) fill(warp + 1, 20, clk() + WD2 + (warp - 5) * WG2, WG2);
            __syncwarp();
        }
    }
}

typedef CUresult (*EncodeFn)(CUtensorMap*, CUtensorMapDataType, cuuint32_t, void*, const cuuint64_t*, const cuuint64_t*, const cuuint32_t*,
                             const cuuint32_t*, CUtensorMapInterleave, CUtensorMapSwizzle, CUtensorMapL2promotion, CUtensorMapFloatOOBfill);

}

extern "C" void kernel_launch(void* const* d_in, const int* in_sizes, int n_in, void* d_out, int out_size) {
    (void)in_sizes; (void)n_in; (void)out_size;
    static EncodeFn enc = nullptr;
    if (!enc) {
        void* fn = nullptr;
        cudaDriverEntryPointQueryResult qr;
        cudaGetDriverEntryPoint("cuTensorMapEncodeTiled", &fn, cudaEnableDefault, &qr);
        enc = (EncodeFn)fn;
        cudaFuncSetAttribute(fused_kernel, cudaFuncAttributeMaxDynamicSharedMemorySize, SM_TOTAL);
    }
    Params P = {};
    auto map3 = [&](int m, int in, cuuint64_t d0, cuuint64_t d1, cuuint64_t d2, cuuint64_t s1, cuuint64_t s2, cuuint32_t b0, cuuint32_t b1, cuuint32_t b2,
                    CUtensorMapSwizzle sw, int promo) {
        const cuuint64_t dim[3] = {d0, d1, d2}, str[2] = {s1, s2};
        const cuuint32_t box[3] = {b0, b1, b2}, ones[3] = {1, 1, 1};
        enc(&P.tm[m], CU_TENSOR_MAP_DATA_TYPE_BFLOAT16, 3, d_in[in], dim, str, box, ones, CU_TENSOR_MAP_INTERLEAVE_NONE, sw, (CUtensorMapL2promotion)promo,
            CU_TENSOR_MAP_FLOAT_OOB_FILL_NONE);
    };
    map3(TM_KH, 1, 64, 3, NHEAD * SK, 128, DH * 2, 64, 3, 32, CU_TENSOR_MAP_SWIZZLE_128B, 0);
    map3(TM_VH, 2, 64, 3, NHEAD * SK, 128, DH * 2, 64, 3, 32, CU_TENSOR_MAP_SWIZZLE_128B, 0);
    map3(TM_VP, 2, 64, 3, NHEAD * SK, 128, DH * 2, PFW, 3, 32, CU_TENSOR_MAP_SWIZZLE_NONE, 0);
    map3(TM_V, 2, 64, 3, NHEAD * SK, 128, DH * 2, 64, 3, 8, CU_TENSOR_MAP_SWIZZLE_128B, 0);
    map3(TM_WO, 4, 32, 20, NHEAD * DH, 64, D_MODEL * 2, 32, 1, DH, CU_TENSOR_MAP_SWIZZLE_64B, PROMOW);
    map3(TM_WOP, 4, 32, 20, NHEAD * DH, 64, D_MODEL * 2, PFW, 1, DH, CU_TENSOR_MAP_SWIZZLE_NONE, 0);
    map3(TM_WQ, 3, 64, NHEAD * 3, D_MODEL, 128, NHEAD * DH * 2, 64, 3, 8, CU_TENSOR_MAP_SWIZZLE_128B, 0);
    map3(TM_W1, 6, DFF, 128, 5, DFF * 2, DFF * 256, 16, 128, 5, CU_TENSOR_MAP_SWIZZLE_32B, PROMO1);
    map3(TM_W2, 8, 64, 10, DFF, 128, D_MODEL * 2, 64, 10, 16, CU_TENSOR_MAP_SWIZZLE_128B, 0);
    P.x = (const __nv_bfloat16*)d_in[0];
    P.k = (const __nv_bfloat16*)d_in[1];
    P.b1 = (const __nv_bfloat16*)d_in[7];
    P.b2 = (const __nv_bfloat16*)d_in[9];
    P.w1 = (const __nv_bfloat16*)d_in[6];
    P.w2 = (const __nv_bfloat16*)d_in[8];
    P.out = (__nv_bfloat16*)d_out;
    for (int i = 0; i < 64; i++) P.tile[i] = make_uint4(SCH.tile[i][0], SCH.tile[i][1], SCH.tile[i][2], 0);
    fused_kernel<<<NCTA + 1, NTHR, SM_TOTAL, cudaStreamPerThread>>>(P);
}
```

```cpp
#include <cuda_runtime.h>
#include <cuda_bf16.h>
#include <cuda.h>
#include <stdint.h>

namespace {

constexpr int D_MODEL = 640, NHEAD = 32, SK = 32768, DH = 192, WIN = 4096, DFF = 1536;
constexpr int NCTA = 128, NTHR = 256;
constexpr int TILE = 64 * DH * 2;
constexpr int HALF = TILE / 2;
constexpr int SUB = 8 * DH * 2;
constexpr int SM_RING = 4 * TILE;
constexpr int SM_W2 = SM_RING + 20480, SM_W1 = SM_W2 + 20480;
constexpr int SM_WQR = 6 * TILE + HALF, SM_WQ = 7 * TILE;
constexpr int SM_PART = 9 * TILE;
constexpr int SM_EXC = SM_PART + 6144;
constexpr int SM_SC = SM_EXC + 1024;
constexpr int SM_BAR = SM_SC + 1024;
constexpr int SM_VEC = SM_BAR + 768;
constexpr int SM_CS = SM_VEC + 384;
constexpr int SM_FAC = SM_CS + 768;
constexpr int SM_ML = SM_FAC + 32;
constexpr int SM_B1 = SM_ML + 64;
constexpr int SM_STAT = SM_B1 + 64;
constexpr int NCB = 27;
constexpr int CB_WO = 18, CB_W1 = 23, CB_W2 = 24, CB_SNAP = 25, CB_REL = 26;
constexpr int SM_CBAR = SM_STAT + 40;
constexpr int SM_CNT = SM_CBAR + NCB * 8;
constexpr int SM_EPOCH = SM_CNT + NCB * 8;
constexpr int SM_FXS = SM_EPOCH + 4;
constexpr int SM_T0 = SM_FXS + 4;
constexpr int SM_MSQ = SM_T0 + 4;
constexpr int SM_M1 = SM_MSQ + 4;
constexpr int SM_TS = SM_M1 + 4;
constexpr int SM_TOTAL = 232448;
static_assert(SM_TS + 320 <= SM_TOTAL, "smem");
constexpr int NEXC = 16;

constexpr int SPIN = 1 << 20;
enum { TM_KH = 0, TM_VH = 1, TM_WO = 2, TM_VP = 3, TM_WOP = 4, TM_V = 5, TM_WQ = 6, TM_W1 = 7, TM_W2 = 8 };
constexpr uint32_t POL_NORMAL = 0x16F00000u, POL_FIRST = 0x12F00000u;

#define PACE 980
#define PACE0 1600
#define NI0 2
#define NI1 6
#define ETRIG 0x54321000
#define LATEAT 5
#define HWAT 11
#define PFREE 66
#define W1AT0 3
#define W1AT1 3
#define AR1D 300
#define LAG0 12
#define NMMA 2
#define M1AT 1
#define M1P 3
#define NWO1 4
#define WG2 120
#define WG3 120
#define WD4 250
#define WG4 70
#define NWQ1 0
#define P4AT 0
#define P2LATE 0
#define RWAT 1
#define W2AT1 6
#define PCD 150
#define NOWIN 0
#define DPRE 0
#define DPOST 200
#define SNAPAT 2
#define DMASK 0x1
#define WOKEEP 0x1f
#define VORD2 0x6758493a2b1cd0efull
#define VTRIG 0xba73210
#define WOAT 13
#define PARKS 0x95
#define VSLOT 0x1087654321087654ull
#define OPOLL 2
#define S0EARLY 0
#define NPRE 2
#define ARDELAY 1000
#define QDELAY 180
#define CMAP 6
#define PFW 8u
#define PUBAT 27
#define HW0 29
#define HW1 31
#define FX2LIM 524288.f
#define PROMOW 2
#define PROMO1 0
#define WD1 300
#define WG1 140
#define WPOL POL_NORMAL

constexpr uint32_t G_A = 1u << 28, G_B = 1u << 29, G_C = 1u << 30;
__host__ __device__ constexpr int ring_hs(int j) { return (j + 4) % 5; }
__host__ __device__ constexpr uint32_t load_word(int j) {
    if (j >= 64) return (uint32_t)(j - 64) << 20 | (SM_RING + ring_hs(j) * HALF) | TM_WO << 8 | (CB_WO + j - 64) << 3 | 2 | !(WOKEEP >> (j - 64) & 1);
    const int e = j >> 1, isv = e >= 16, unit = e & 15;
    return (uint32_t)(unit * 256 + (j & 1) * 32) << 20 | (j < 8 ? j * HALF : SM_RING + ring_hs(j) * HALF) | isv << 8 | (j < 8 ? 10 + j : (j - 8) % 10) << 3 | 2
           | (!isv || (DMASK >> unit & 1));
}
__host__ __device__ constexpr int popc(int v) { return v ? (v & 1) + popc(v >> 1) : 0; }
constexpr int NPARK = popc(PARKS);
constexpr int SM_SNAP = SM_RING + ring_hs(12) * HALF, SM_CSP = SM_RING + ring_hs(11) * HALF;
struct Step { int unit, slot, par, next, mma0, nmma; };
struct Sched { uint32_t tile[64][3]; Step st[16]; };
constexpr Sched make_sched() {
    Sched s{};
    for (int j = 0; j < 64; j++) {
        const int e = j >> 1;
        const uint32_t d = load_word(j);
        uint32_t w = (uint32_t)(j < 8 ? 0 : (j - 8) / 10 & 1) << 31 | (e & 15) * 4 << 20 | ((d & 0x3f000) - (j & 1) * HALF) | (d & 0xf8);
        if (e == PUBAT || e == SNAPAT) w |= G_A;
        if (e == HW0 || e == 4) w |= G_B;
        if ((e >= LATEAT && e < LATEAT + 4) || e == HW1) w |= G_C;
        s.tile[j][0] = w;
    }
    for (int j = NI1; j < 69; j++) {
        if (j == 12) continue;
        const int at = j < 12 ? (ETRIG >> (4 * (j - 4)) & 15) : j - 5;
        s.tile[at][1] = load_word(j);
        s.tile[at][2] = j >= PFREE ? 0 : PACE0 + j * PACE / 2;
    }
    int done = 0;
    for (int p = 0; p < 16; p++) {
        Step& c = s.st[p];
        c.unit = (int)(VORD2 >> (4 * p) & 15); c.slot = (int)(VSLOT >> (4 * p) & 15); c.par = p >= 9; c.next = -1;
        c.mma0 = done;
        if (p >= NPARK) { const int avail = p - done + (p >= LAG0); c.nmma = p == 15 ? 16 - done : (avail < NMMA ? avail : NMMA); done += c.nmma; }
    }
    for (int p = 9; p < 16; p++) s.st[VTRIG >> (4 * (p - 9)) & 15].next = p;
    return s;
}
constexpr Sched SCH = make_sched();
__host__ __device__ constexpr int kunit(int o) { return o < 5 ? o + 11 : o == 5 ? 10 : o - 6; }

template <int I> struct IC { static constexpr int value = I; };
template <uint32_t I> struct UC { static constexpr uint32_t value = I; };
template <int A, int B, class F> __device__ __forceinline__ void static_for(F&& f) {
    if constexpr (A < B) { f(IC<A>{}); static_for<A + 1, B>(f); }
}

struct Params {
    CUtensorMap tm[9];
    const __nv_bfloat16 *x, *k, *b1, *b2;
    __nv_bfloat16* out;
    uint4 tile[66];
};

typedef unsigned long long u64;
constexpr int ACC_PITCH = 256;
constexpr int ACC_BYTES = 80 * ACC_PITCH;
__device__ __align__(1024) unsigned char g_acc[4 * ACC_BYTES];
__device__ __align__(1024) u64 g_l0[NCTA][384];
__device__ __align__(1024) u64 g_ll[2][NCTA][256];
__device__ unsigned g_epoch;
__device__ __align__(128) unsigned g_zflag;
#define TSTAMP(i)
#define TSTAMP2(i)
#define TSTAMPL(i)
#define TDUMP()
#define CSTAMP(i, x)
#define TRACE(i)

__device__ __forceinline__ void mbar_wait(uint32_t bar, uint32_t parity) {
    asm volatile("{\n.reg .pred p, q;\n.reg .u32 n;\nmov.u32 n, 0;\n"
                 "LOOP:\nmbarrier.try_wait.parity.shared::cta.b64 p, [%0], %1;\n"
                 "add.u32 n, n, 1;\nsetp.lt.and.u32 q, n, 0x100000, !p;\n@q bra.uni LOOP;\n}"
                 :: "r"(bar), "r"(parity) : "memory");
}
__device__ __forceinline__ bool mbar_test(uint32_t bar, uint32_t parity) {
    uint32_t r;
    asm volatile("{\n.reg .pred p;\nmbarrier.test_wait.parity.shared::cta.b64 p, [%1], %2;\nselp.u32 %0, 1, 0, p;\n}" : "=r"(r) : "r"(bar), "r"(parity) : "memory");
    return __all_sync(~0u, r);
}
__device__ __forceinline__ bool elect() {
    uint32_t r;
    asm volatile("{\n.reg .pred p;\nelect.sync _|p, 0xffffffff;\nselp.u32 %0, 1, 0, p;\n}" : "=r"(r));
    return r != 0;
}
__device__ __forceinline__ void mbar_expect(uint32_t bar, uint32_t bytes) {
    asm volatile("mbarrier.arrive.expect_tx.shared::cta.b64 _, [%0], %1;" :: "r"(bar), "r"(bytes) : "memory");
}
__device__ __forceinline__ uint4 lds128(uint32_t a) {
    uint4 v; asm volatile("ld.shared.v4.u32 {%0,%1,%2,%3}, [%4];" : "=r"(v.x), "=r"(v.y), "=r"(v.z), "=r"(v.w) : "r"(a) : "memory"); return v;
}
__device__ __forceinline__ uint4 ldsm_t(uint32_t a) {
    uint4 v; asm volatile("ldmatrix.sync.aligned.m8n8.x4.trans.shared.b16 {%0,%1,%2,%3}, [%4];" : "=r"(v.x), "=r"(v.y), "=r"(v.z), "=r"(v.w) : "r"(a) : "memory"); return v;
}
__device__ __forceinline__ uint2 lds64(uint32_t a) {
    uint2 v; asm volatile("ld.shared.v2.u32 {%0,%1}, [%2];" : "=r"(v.x), "=r"(v.y) : "r"(a) : "memory"); return v;
}
__device__ __forceinline__ float2 lds64f(uint32_t a) { const uint2 v = lds64(a); return make_float2(__uint_as_float(v.x), __uint_as_float(v.y)); }
__device__ __forceinline__ uint32_t lds32(uint32_t a) {
    uint32_t v; asm volatile("ld.shared.u32 %0, [%1];" : "=r"(v) : "r"(a) : "memory"); return v;
}
__device__ __forceinline__ float ldsf(uint32_t a) { return __uint_as_float(lds32(a)); }
__device__ __forceinline__ void sts32(uint32_t a, uint32_t v) { asm volatile("st.shared.u32 [%0], %1;" :: "r"(a), "r"(v) : "memory"); }
__device__ __forceinline__ void stsf(uint32_t a, float v) { sts32(a, __float_as_uint(v)); }
__device__ __forceinline__ void sts16(uint32_t a, uint32_t v) { asm volatile("st.shared.u16 [%0], %1;" :: "r"(a), "h"((uint16_t)v) : "memory"); }
__device__ __forceinline__ void sts64(uint32_t a, uint32_t x, uint32_t y) { asm volatile("st.shared.v2.u32 [%0], {%1,%2};" :: "r"(a), "r"(x), "r"(y) : "memory"); }
__device__ __forceinline__ void sts64f(uint32_t a, float x, float y) { sts64(a, __float_as_uint(x), __float_as_uint(y)); }
__device__ __forceinline__ void sts128f(uint32_t a, float x, float y, float z, float w) {
    asm volatile("st.shared.v4.f32 [%0], {%1,%2,%3,%4};" :: "r"(a), "f"(x), "f"(y), "f"(z), "f"(w) : "memory");
}
__device__ __forceinline__ void mma(float (&c)[4], const uint4& a, uint32_t b0, uint32_t b1) {
    asm volatile("mma.sync.aligned.m16n8k16.row.col.f32.bf16.bf16.f32 {%0,%1,%2,%3}, {%4,%5,%6,%7}, {%8,%9}, {%0,%1,%2,%3};"
                 : "+f"(c[0]), "+f"(c[1]), "+f"(c[2]), "+f"(c[3]) : "r"(a.x), "r"(a.y), "r"(a.z), "r"(a.w), "r"(b0), "r"(b1));
}
__device__ __forceinline__ u64 ld_rlx(const void* p) {
    u64 a; asm volatile("ld.relaxed.gpu.global.u64 %0, [%1];" : "=l"(a) : "l"(p) : "memory"); return a;
}
__device__ __forceinline__ void ld_rlx2(const void* p, u64& a, u64& b) {
    asm volatile("ld.relaxed.gpu.global.v2.u64 {%0,%1}, [%2];" : "=l"(a), "=l"(b) : "l"(p) : "memory");
}
__device__ __forceinline__ void st_rlx(void* p, u64 a) { asm volatile("st.relaxed.gpu.global.u64 [%0], %1;" :: "l"(p), "l"(a) : "memory"); }
__device__ __forceinline__ u64 ll_pack(float v, uint32_t tag) { return ((u64)tag << 32) | __float_as_uint(v); }
__device__ __forceinline__ float ll_val(u64 w) { return __uint_as_float((uint32_t)w); }
__device__ __forceinline__ uint32_t ll_tag(u64 w) { return (uint32_t)(w >> 32); }
__device__ __forceinline__ float bf_lo(uint32_t u) { return __uint_as_float(u << 16); }
__device__ __forceinline__ float bf_hi(uint32_t u) { return __uint_as_float(u & 0xffff0000u); }
__device__ __forceinline__ uint32_t pack_bf(float lo, float hi) {
    uint32_t r; asm("cvt.rn.bf16x2.f32 %0, %1, %2;" : "=r"(r) : "f"(hi), "f"(lo)); return r;
}
__device__ __forceinline__ float ex2(float v) { float r; asm("ex2.approx.ftz.f32 %0, %1;" : "=f"(r) : "f"(v)); return r; }
__device__ __forceinline__ float rcp(float v) { float r; asm("rcp.approx.ftz.f32 %0, %1;" : "=f"(r) : "f"(v)); return r; }
__device__ __forceinline__ float rsq(float v) { float r; asm("rsqrt.approx.ftz.f32 %0, %1;" : "=f"(r) : "f"(v)); return r; }
__device__ __forceinline__ void bar_sync(int id, int n) { asm volatile("bar.sync %0, %1;" :: "r"(id), "r"(n) : "memory"); }
__device__ __forceinline__ uint32_t clk() { uint32_t c; asm volatile("mov.u32 %0, %clock;" : "=r"(c)); return c; }
__device__ __forceinline__ uint32_t pin(uint32_t v) { return __shfl_xor_sync(~0u, v, 0); }
__device__ __forceinline__ float shx(float v, int o) { return __shfl_xor_sync(~0u, v, o); }

__device__ __forceinline__ u64 fx_pack(float v, float scale) { return ((u64)__float2ll_rn(v * scale) & ~255ull) | 1ull; }
__device__ __forceinline__ float fx_scale(float meansq) {
    const int e = max(((int)(__float_as_uint(meansq) >> 23) - 127) >> 1, -6);
    return __uint_as_float((uint32_t)(127 + 32 - e) << 23);
}
__device__ __forceinline__ float fx_inv(float scale) { return __uint_as_float((254u << 23) - __float_as_uint(scale)); }
__device__ __forceinline__ uint32_t lo32(u64 w) { uint32_t l; asm("mov.b64 {%0, _}, %1;" : "=r"(l) : "l"(w)); return l; }
__device__ __forceinline__ int hi32(u64 w) { int h; asm("mov.b64 {_, %0}, %1;" : "=r"(h) : "l"(w)); return h; }
__device__ __forceinline__ float fx_val(u64 w) { return (float)hi32(w) * 4294967296.f + (float)lo32(w); }
constexpr float FX2_ONE = 12582912.f;
__device__ __forceinline__ float fx2_scale(float meansq) { return __uint_as_float((uint32_t)(127 + 16 - max(((int)(__float_as_uint(meansq) >> 23) - 127) >> 1, -100)) << 23); }
__device__ __forceinline__ u64 fx2_pack(float a, float b) {
    const uint32_t lo = __float_as_uint(a) * 512u + (1u - 0x4b400000u * 512u);
    return lo | (u64)(__float_as_uint(b) * 16u - 0x4b400000u * 16u + (uint32_t)((int)lo >> 31)) << 32;
}
__device__ __forceinline__ float fx2_lo(u64 w, float inv) { return (float)(int)(__funnelshift_r(lo32(w), hi32(w), 4) & ~31u) * (inv * 0.5f); }
__device__ __forceinline__ float fx2_hi(u64 w, float inv) { return (float)((hi32(w) + 8) & ~15) * inv; }
__device__ __forceinline__ float fx2_inv(float meansq) { return fx_inv(fx2_scale(meansq)) * 0.0625f; }
__device__ __forceinline__ uint32_t fx2_wide(const unsigned char* a, u64 w, float meansq) {
    const float inv = fx_inv(fx_scale(meansq));
    return pack_bf(fx2_lo(w, fx2_inv(meansq)) + fx_val(ld_rlx(a + 64)) * inv, fx2_hi(w, fx2_inv(meansq)) + fx_val(ld_rlx(a + 96)) * inv);
}
template <int N, bool LOOK, class A> __device__ __forceinline__ void fx2_wait(A a, u64 (&w)[N], uint32_t msqa, float inv, uint32_t (&x)[N]) {
    int it = 0;
    uint32_t miss = lds32(msqa + 4);
    do {
        if (__all_sync(~0u, !(miss & 96))) {
            __threadfence();
#pragma unroll
            for (int i = 0; i < N; i++) x[i] = 0;
#pragma unroll 1
            for (int i = 0; i < 2 * N; i++) {
                const u64 v = ld_rlx(a(i >> 1));
                const float y = ((i & 1) ? fx2_hi(v, inv) : fx2_lo(v, inv)) + fx_val(ld_rlx(a(i >> 1) + 64 + (i & 1) * 32)) * fx_inv(fx_scale(ldsf(msqa)));
#pragma unroll
                for (int k = 0; k < N; k++) x[k] = __funnelshift_r(x[k], k + 1 < N ? x[k + 1] : pack_bf(y, y), 16);
            }
            return;
        }
        if (!LOOK || it) {
#pragma unroll
            for (int i = 0; i < N; i++) w[i] = ld_rlx(a(i));
        }
        uint32_t all = lo32(w[0]), any = all;
#pragma unroll
        for (int i = 1; i < N; i++) { all &= lo32(w[i]); any |= lo32(w[i]); }
        miss = (~all & 96) | (any & 256);
    } while (__any_sync(~0u, miss) & (++it < SPIN));
#pragma unroll
    for (int i = 0; i < N; i++) x[i] = pack_bf(fx2_lo(w[i], inv), fx2_hi(w[i], inv));
}
__device__ __forceinline__ void st_rlx_if(bool p, void* a, u64 v) {
    asm volatile("{\n.reg .pred p;\nsetp.ne.u32 p, %2, 0;\n@p st.relaxed.gpu.global.u64 [%0], %1;\n}" :: "l"(a), "l"(v), "r"((uint32_t)p) : "memory");
}
__device__ __forceinline__ void sts128f(uint32_t a, const float (&v)[4]) { sts128f(a, v[0], v[1], v[2], v[3]); }
__device__ __forceinline__ void bar_arrive(int id, int n) { asm volatile("bar.arrive %0, %1;" :: "r"(id), "r"(n) : "memory"); }
template <class T> __device__ __forceinline__ T* pin(T* p) { return reinterpret_cast<T*>(__shfl_xor_sync(~0u, (u64)p, 0)); }

__device__ __forceinline__ void tma3(uint32_t dst, const CUtensorMap* tm, int c1, int c2, uint32_t bar, uint32_t pol) {
    asm volatile("cp.async.bulk.tensor.3d.shared::cluster.global.mbarrier::complete_tx::bytes.L2::cache_hint [%0], [%1, {%2, %3, %4}], [%5], %6;"
                 :: "r"(dst), "l"(tm), "r"(0), "r"(c1), "r"(c2), "r"(bar), "l"((u64)pol << 32) : "memory");
}
__device__ __forceinline__ void tma3_pf(const CUtensorMap* tm, int c1, int c2, uint32_t pol) {
    asm volatile("cp.async.bulk.prefetch.tensor.3d.L2.global.tile.L2::cache_hint [%0, {%1, %2, %3}], %4;"
                 :: "l"(tm), "r"(0), "r"(c1), "r"(c2), "l"((u64)pol << 32) : "memory");
}
__device__ __forceinline__ void issue_half(uint32_t d, uint32_t sb, int rowc, int cta, const CUtensorMap* tm0) {
    const uint32_t bar = sb + SM_CBAR + (d & 0xf8);
    const CUtensorMap* tm = tm0 + ((d >> 8) & 3);
    const int c1 = (d & 0x200) ? 5 * (cta & 3) + (d >> 20) : 0, c2 = (d & 0x200) ? (cta >> 2) * DH : rowc + (d >> 20);
    mbar_expect(bar, HALF);
    tma3(sb + (d & 0x3f000), tm, c1, c2, bar, POL_FIRST);
    if (!(d & 1)) tma3_pf(tm + 2, c1, c2, POL_NORMAL);
}
__device__ __forceinline__ uint32_t cnt_inc(uint32_t a, uint32_t last) {
    uint32_t old; asm volatile("atom.relaxed.cta.shared.inc.u32 %0, [%1], %2;" : "=r"(old) : "r"(a), "r"(last) : "memory"); return old;
}
__device__ __forceinline__ void wait_until(uint32_t due) {
#pragma unroll 1
    for (int it = 0; it < 4096; it++) { uint32_t now; asm volatile("mov.u32 %0, %globaltimer_lo;" : "=r"(now)); if ((int)(now - due) >= 0) break; }
}
__device__ __forceinline__ uint32_t bf2_mul(uint32_t a, uint32_t b) { uint32_t r; asm("mul.rn.bf16x2 %0, %1, %2;" : "=r"(r) : "r"(a), "r"(b)); return r; }
__device__ __forceinline__ uint32_t bf2_fma(uint32_t a, uint32_t b, uint32_t c) { uint32_t r; asm("fma.rn.bf16x2 %0, %1, %2, %3;" : "=r"(r) : "r"(a), "r"(b), "r"(c)); return r; }
__device__ __forceinline__ uint32_t bf2_amax(uint32_t a, uint32_t b) { uint32_t r; asm("max.NaN.xorsign.abs.bf16x2 %0, %1, %2;" : "=r"(r) : "r"(a), "r"(b)); return r; }
__device__ __forceinline__ uint4 k_unpack(uint32_t l0, uint32_t l1, uint32_t h, uint32_t m1) {
    const uint32_t ha = h & 0x87878787u, hc = ha * m1 + h, hb = __funnelshift_l(hc, hc, 4);
    return make_uint4(__byte_perm(l0, ha, 0x5140), __byte_perm(l0, ha, 0x7362), __byte_perm(l1, hb, 0x5140), __byte_perm(l1, hb, 0x7362));
}
#define KR4(u, i) "+r"(kr[u][i].x), "+r"(kr[u][i].y), "+r"(kr[u][i].z), "+r"(kr[u][i].w)
#define KR6(u) KR4(u, 0), KR4(u, 1), KR4(u, 2), KR4(u, 3), KR4(u, 4), KR4(u, 5)
__device__ __forceinline__ void k_keep(uint4 (&kr)[8][6], const uint32_t (&c)[18], int e, uint32_t a) {
    asm volatile("{\nKT: .branchtargets K0, K1, K2, K3, K4, K5, K6, K7, K8, K9, K10, K11, K12, K13, K14, K15;\nbrx.idx.uni %210, KT;\n"
                 "K0: mov.b32 %12, %192; mov.b32 %13, %193; mov.b32 %14, %194; mov.b32 %15, %195; mov.b32 %16, %196; mov.b32 %17, %197; mov.b32 %18, %198; mov.b32 %19, %199; mov.b32 %20, %200; mov.b32 %21, %201; mov.b32 %22, %202; mov.b32 %23, %203; mov.b32 %24, %204; mov.b32 %25, %205; mov.b32 %26, %206; mov.b32 %27, %207; mov.b32 %28, %208; mov.b32 %29, %209; bra.uni KE;\n"
                 "K1: mov.b32 %30, %192; mov.b32 %31, %193; mov.b32 %32, %194; mov.b32 %33, %195; mov.b32 %34, %196; mov.b32 %35, %197; mov.b32 %36, %198; mov.b32 %37, %199; mov.b32 %38, %200; mov.b32 %39, %201; mov.b32 %40, %202; mov.b32 %41, %203; mov.b32 %42, %204; mov.b32 %43, %205; mov.b32 %44, %206; mov.b32 %45, %207; mov.b32 %46, %208; mov.b32 %47, %209; bra.uni KE;\n"
                 "K2: mov.b32 %48, %192; mov.b32 %49, %193; mov.b32 %50, %194; mov.b32 %51, %195; mov.b32 %52, %196; mov.b32 %53, %197; mov.b32 %54, %198; mov.b32 %55, %199; mov.b32 %56, %200; mov.b32 %57, %201; mov.b32 %58, %202; mov.b32 %59, %203; mov.b32 %60, %204; mov.b32 %61, %205; mov.b32 %62, %206; mov.b32 %63, %207; mov.b32 %64, %208; mov.b32 %65, %209; bra.uni KE;\n"
                 "K3: mov.b32 %66, %192; mov.b32 %67, %193; mov.b32 %68, %194; mov.b32 %69, %195; mov.b32 %70, %196; mov.b32 %71, %197; mov.b32 %72, %198; mov.b32 %73, %199; mov.b32 %74, %200; mov.b32 %75, %201; mov.b32 %76, %202; mov.b32 %77, %203; mov.b32 %78, %204; mov.b32 %79, %205; mov.b32 %80, %206; mov.b32 %81, %207; mov.b32 %82, %208; mov.b32 %83, %209; bra.uni KE;\n"
                 "K4: mov.b32 %84, %192; mov.b32 %85, %193; mov.b32 %86, %194; mov.b32 %87, %195; mov.b32 %88, %196; mov.b32 %89, %197; mov.b32 %90, %198; mov.b32 %91, %199; mov.b32 %92, %200; mov.b32 %93, %201; mov.b32 %94, %202; mov.b32 %95, %203; mov.b32 %96, %204; mov.b32 %97, %205; mov.b32 %98, %206; mov.b32 %99, %207; mov.b32 %100, %208; mov.b32 %101, %209; bra.uni KE;\n"
                 "K5: mov.b32 %102, %192; mov.b32 %103, %193; mov.b32 %104, %194; mov.b32 %105, %195; mov.b32 %106, %196; mov.b32 %107, %197; mov.b32 %108, %198; mov.b32 %109, %199; mov.b32 %110, %200; mov.b32 %111, %201; mov.b32 %112, %202; mov.b32 %113, %203; mov.b32 %114, %204; mov.b32 %115, %205; mov.b32 %116, %206; mov.b32 %117, %207; mov.b32 %118, %208; mov.b32 %119, %209; bra.uni KE;\n"
                 "K6: mov.b32 %120, %192; mov.b32 %121, %193; mov.b32 %122, %194; mov.b32 %123, %195; mov.b32 %124, %196; mov.b32 %125, %197; mov.b32 %126, %198; mov.b32 %127, %199; mov.b32 %128, %200; mov.b32 %129, %201; mov.b32 %130, %202; mov.b32 %131, %203; mov.b32 %132, %204; mov.b32 %133, %205; mov.b32 %134, %206; mov.b32 %135, %207; mov.b32 %136, %208; mov.b32 %137, %209; bra.uni KE;\n"
                 "K7: mov.b32 %138, %192; mov.b32 %139, %193; mov.b32 %140, %194; mov.b32 %141, %195; mov.b32 %142, %196; mov.b32 %143, %197; mov.b32 %144, %198; mov.b32 %145, %199; mov.b32 %146, %200; mov.b32 %147, %201; mov.b32 %148, %202; mov.b32 %149, %203; mov.b32 %150, %204; mov.b32 %151, %205; mov.b32 %152, %206; mov.b32 %153, %207; mov.b32 %154, %208; mov.b32 %155, %209; bra.uni KE;\n"
                 "K8: mov.b32 %156, %192; mov.b32 %157, %193; mov.b32 %158, %194; mov.b32 %159, %195; mov.b32 %160, %196; mov.b32 %161, %197; mov.b32 %162, %198; mov.b32 %163, %199; mov.b32 %164, %200; mov.b32 %165, %201; mov.b32 %166, %202; mov.b32 %167, %203; mov.b32 %168, %204; mov.b32 %169, %205; mov.b32 %170, %206; mov.b32 %171, %207; mov.b32 %172, %208; mov.b32 %173, %209; bra.uni KE;\n"
                 "K9: mov.b32 %174, %192; mov.b32 %175, %193; mov.b32 %176, %194; mov.b32 %177, %195; mov.b32 %178, %196; mov.b32 %179, %197; mov.b32 %180, %198; mov.b32 %181, %199; mov.b32 %182, %200; mov.b32 %183, %201; mov.b32 %184, %202; mov.b32 %185, %203; mov.b32 %186, %204; mov.b32 %187, %205; mov.b32 %188, %206; mov.b32 %189, %207; mov.b32 %190, %208; mov.b32 %191, %209; bra.uni KE;\n"
                 "K10: st.shared.v2.b32 [%211+75784], {%192, %193}; st.shared.v2.b32 [%211+76288], {%194, %195}; st.shared.v2.b32 [%211+76296], {%196, %197}; mov.b32 %0, %198; mov.b32 %1, %199; mov.b32 %2, %200; mov.b32 %3, %201; mov.b32 %4, %202; mov.b32 %5, %203; mov.b32 %6, %204; mov.b32 %7, %205; mov.b32 %8, %206; mov.b32 %9, %207; mov.b32 %10, %208; mov.b32 %11, %209; bra.uni KE;\n"
                 "K11: st.shared.v2.b32 [%211+0], {%192, %193}; st.shared.v2.b32 [%211+8], {%194, %195}; st.shared.v2.b32 [%211+512], {%196, %197}; st.shared.v2.b32 [%211+520], {%198, %199}; st.shared.v2.b32 [%211+1024], {%200, %201}; st.shared.v2.b32 [%211+1032], {%202, %203}; st.shared.v2.b32 [%211+1536], {%204, %205}; st.shared.v2.b32 [%211+1544], {%206, %207}; st.shared.v2.b32 [%211+2048], {%208, %209}; bra.uni KE;\n"
                 "K12: st.shared.v2.b32 [%211+2056], {%192, %193}; st.shared.v2.b32 [%211+2560], {%194, %195}; st.shared.v2.b32 [%211+2568], {%196, %197}; st.shared.v2.b32 [%211+24576], {%198, %199}; st.shared.v2.b32 [%211+24584], {%200, %201}; st.shared.v2.b32 [%211+25088], {%202, %203}; st.shared.v2.b32 [%211+25096], {%204, %205}; st.shared.v2.b32 [%211+25600], {%206, %207}; st.shared.v2.b32 [%211+25608], {%208, %209}; bra.uni KE;\n"
                 "K13: st.shared.v2.b32 [%211+26112], {%192, %193}; st.shared.v2.b32 [%211+26120], {%194, %195}; st.shared.v2.b32 [%211+26624], {%196, %197}; st.shared.v2.b32 [%211+26632], {%198, %199}; st.shared.v2.b32 [%211+27136], {%200, %201}; st.shared.v2.b32 [%211+27144], {%202, %203}; st.shared.v2.b32 [%211+49152], {%204, %205}; st.shared.v2.b32 [%211+49160], {%206, %207}; st.shared.v2.b32 [%211+49664], {%208, %209}; bra.uni KE;\n"
                 "K14: st.shared.v2.b32 [%211+49672], {%192, %193}; st.shared.v2.b32 [%211+50176], {%194, %195}; st.shared.v2.b32 [%211+50184], {%196, %197}; st.shared.v2.b32 [%211+50688], {%198, %199}; st.shared.v2.b32 [%211+50696], {%200, %201}; st.shared.v2.b32 [%211+51200], {%202, %203}; st.shared.v2.b32 [%211+51208], {%204, %205}; st.shared.v2.b32 [%211+51712], {%206, %207}; st.shared.v2.b32 [%211+51720], {%208, %209}; bra.uni KE;\n"
                 "K15: st.shared.v2.b32 [%211+73728], {%192, %193}; st.shared.v2.b32 [%211+73736], {%194, %195}; st.shared.v2.b32 [%211+74240], {%196, %197}; st.shared.v2.b32 [%211+74248], {%198, %199}; st.shared.v2.b32 [%211+74752], {%200, %201}; st.shared.v2.b32 [%211+74760], {%202, %203}; st.shared.v2.b32 [%211+75264], {%204, %205}; st.shared.v2.b32 [%211+75272], {%206, %207}; st.shared.v2.b32 [%211+75776], {%208, %209}; \nKE:\n}"
                 : KR6(0), KR6(1), KR6(2), KR6(3), KR6(4), KR6(5), KR6(6), KR6(7)
                 : "r"(c[0]), "r"(c[1]), "r"(c[2]), "r"(c[3]), "r"(c[4]), "r"(c[5]), "r"(c[6]), "r"(c[7]), "r"(c[8]), "r"(c[9]), "r"(c[10]), "r"(c[11]), "r"(c[12]), "r"(c[13]), "r"(c[14]), "r"(c[15]), "r"(c[16]), "r"(c[17]), "r"(e), "r"(a) : "memory");
}
template <int K> __device__ __forceinline__ uint32_t& word(uint4& v) { if constexpr (K == 0) return v.x; else if constexpr (K == 1) return v.y; else if constexpr (K == 2) return v.z; else return v.w; }
__device__ __forceinline__ void add_if(bool p, float& d, float a, float b) {
    asm volatile("{\n.reg .pred p;\nsetp.ne.u32 p, %3, 0;\n@p add.f32 %0, %1, %2;\n}" : "+f"(d) : "f"(a), "f"(b), "r"((uint32_t)p));
}
__device__ __forceinline__ float warp_max(float v) {
#pragma unroll
    for (int o = 16; o; o >>= 1) v = fmaxf(v, shx(v, o));
    return v;
}
__device__ __forceinline__ float warp_sum(float v) {
#pragma unroll
    for (int o = 16; o; o >>= 1) v += shx(v, o);
    return v;
}
template <int PITCH> __device__ __forceinline__ void ll_look(const u64* buf, u64 (&w)[4]) {
#pragma unroll
    for (int i = 0; i < 4; i++) w[i] = ld_rlx(buf + i * PITCH);
}
template <int PITCH> __device__ __forceinline__ float ll_gather(const u64* buf, uint32_t tag, u64 (&w)[4]) {
    auto miss = [&]() { return __any_sync(~0u, ((ll_tag(w[0]) ^ tag) | (ll_tag(w[1]) ^ tag)) | ((ll_tag(w[2]) ^ tag) | (ll_tag(w[3]) ^ tag))); };
    int it = 0;
    goto check;
again:
    ll_look<PITCH>(buf, w);
check:
    if (miss() & (++it < SPIN)) goto again;
    return (ll_val(w[0]) + ll_val(w[1])) + (ll_val(w[2]) + ll_val(w[3]));
}
__device__ __forceinline__ float sum8(uint32_t a, int pitch) {
    float s[8];
#pragma unroll
    for (int w = 0; w < 8; w++) s[w] = ldsf(a + w * pitch);
    return ((s[0] + s[1]) + (s[2] + s[3])) + ((s[4] + s[5]) + (s[6] + s[7]));
}
__device__ __forceinline__ float sum5(float a, float b, float c, float d, float e) { return ((a + b) + (c + d)) + e; }
__device__ __forceinline__ float ln_part(uint2 xp, int lane) {
    const float x0 = bf_lo(xp.x), x1 = bf_hi(xp.x), x2 = bf_lo(xp.y), x3 = bf_hi(xp.y);
    const float s1 = (x0 + x1) + (x2 + x3), s2 = (x0 * x0 + x1 * x1) + (x2 * x2 + x3 * x3);
    return ((lane & 16) ? s2 : s1) + shx((lane & 16) ? s1 : s2, 16);
}
__device__ __forceinline__ float ln_rstd(float mean, float msq) { return rsq(fmaxf(msq - mean * mean, 0.f) + 1e-5f); }
constexpr float CS = 0.07216878364870322f * 1.4426950408889634f;
constexpr uint32_t ONES = 0x3f803f80u;

__global__ void __launch_bounds__(NTHR, 1) fused_kernel(const __grid_constant__ Params P) {
    extern __shared__ __align__(1024) unsigned char smem[];
    const uint32_t sb = (uint32_t)__cvta_generic_to_shared(smem);
    const int bx = blockIdx.x;
    const int cta0 = bx >= NCTA || CMAP == 0 ? bx : CMAP == 4 ? (((bx >> 1) & 7) + (bx >> 5) * 8) * 4 + ((bx >> 4) & 1) * 2 + (bx & 1)
                   : (((bx >> 1) & 15) + (bx >> 6) * 16) * 4 + ((bx >> 5) & 1) * 2 + (bx & 1);
    int id = cta0 * NTHR + threadIdx.x, tid, lane, g, t, key, warp, cta, mlp, rowc, roww, j40;
    uint32_t maskA, maskB, barw, subw, prow;
    auto fresh = [&]() {
        const int cw = __shfl_sync(~0u, id >> 5, 0);
        id = pin(id); tid = id & 255; lane = id & 31; g = lane >> 2; t = lane & 3; key = (g >> 1) + 4 * (g & 1);
        const uint32_t m = (g & 1) ? 0xffff0000u : 0x0000ffffu;
        maskA = (g & 2) ? 0u : m; maskB = (g & 2) ? m : 0u;
        warp = cw & 7; cta = cw >> 3;
        mlp = (cta & 3) == 3 ? 96 : (cta >> 2) * 3 + (cta & 3);
        rowc = (cta >> 2) * SK + (SK - WIN) + (cta & 3) * 64; roww = rowc + warp * 8;
        j40 = (cta & 3) * 40;
        barw = sb + SM_BAR + warp * 96; subw = sb + warp * SUB; prow = sb + SM_PART + warp * 768;
    };
    fresh();

    if (cta == NCTA) {
        const uint32_t ep = *(volatile unsigned*)&g_epoch;
        if (tid == 0) {
#pragma unroll 1
            for (int it = 0; it < SPIN; it++) { if (ll_tag(ld_rlx(&g_ll[0][0][192])) == ep * 4 + 2) break; __nanosleep(200); }
        }
        __syncthreads();
#pragma unroll 1
        for (int i = tid; i < 4 * 80 * 8; i += NTHR)
            *reinterpret_cast<uint4*>(g_acc + (i >> 3) * ACC_PITCH + (i & 7) * 16) = make_uint4(0, 0, 0, 0);
        __threadfence();
        __syncthreads();
        if (tid == 0) asm volatile("st.relaxed.gpu.global.u32 [%0], %1;" :: "l"(&g_zflag), "r"(ep + 1) : "memory");
        return;
    }
    TSTAMP(0);
    if (tid == 64) { uint32_t now; asm volatile("mov.u32 %0, %globaltimer_lo;" : "=r"(now)); sts32(sb + SM_T0, now); }

    const CUtensorMap* tmk = reinterpret_cast<const CUtensorMap*>(__shfl_sync(~0u, (u64)&P.tm[0] + (lane >> 5), 0));
    auto issue_first = [&](int j) {
        mbar_expect(sb + SM_CBAR + 80 + j * 8, HALF);
        tma3(sb + j * HALF, tmk + TM_KH, 0, rowc + (j >> 1) * 256 + (j & 1) * 32, sb + SM_CBAR + 80 + j * 8, POL_FIRST);
    };
    if (elect()) {
        asm volatile("mbarrier.init.shared::cta.b64 [%0], 1;" :: "r"(barw + 72));
        asm volatile("mbarrier.init.shared::cta.b64 [%0], 1;" :: "r"(sb + SM_CBAR + 64 + warp * 8));
        asm volatile("fence.proxy.async.shared::cta;" ::: "memory");
        mbar_expect(barw + 72, warp < 4 ? 3 * SUB : 2 * SUB);
        const int r0 = (cta & 3) * 160 + warp * 8;
        tma3(subw + SM_WQ, tmk + TM_WQ, (cta >> 2) * 3, r0, barw + 72, POL_FIRST);
        tma3(subw + SM_WQ + TILE, tmk + TM_WQ, (cta >> 2) * 3, r0 + 64, barw + 72, POL_FIRST);
        if (warp < 4) tma3(subw + SM_WQR, tmk + TM_WQ, (cta >> 2) * 3, r0 + 128, barw + 72, POL_FIRST);
        if ((uint32_t)warp - 2 < NI0) issue_first(warp - 2);
#pragma unroll
        for (int i = 0; i < 9; i++) asm volatile("mbarrier.init.shared::cta.b64 [%0], 1;" :: "r"(barw + i * 8));
        asm volatile("mbarrier.init.shared::cta.b64 [%0], 1;" :: "r"(sb + SM_CBAR + warp * 8));
        asm volatile("mbarrier.init.shared::cta.b64 [%0], 1;" :: "r"(sb + SM_CBAR + 128 + warp * 8));
        if (warp < 3) asm volatile("mbarrier.init.shared::cta.b64 [%0], %1;" :: "r"(sb + SM_CBAR + 192 + warp * 8), "r"(warp == 2 ? 8 : 1));
        sts64(barw + 80, 0, 0);
        asm volatile("fence.proxy.async.shared::cta;" ::: "memory");
        asm volatile("prefetch.tensormap [%0];" :: "l"(tmk + warp + 1) : "memory");
    }
    __syncwarp();
    auto c4 = [&]() { return 32 * min(warp, 4) + 16 * (t >> 1) + 2 * g + (t & 1); };
    uint2 xp = make_uint2(0, 0);
    if (tid < 160) asm volatile("ld.global.nc.v2.u32 {%0,%1}, [%2];" : "=r"(xp.x), "=r"(xp.y) : "l"(P.x + 4 * c4()) : "memory");
    else if (tid == 255) { sts32(sb + SM_EPOCH, *(volatile unsigned*)&g_epoch); sts32(sb + SM_M1, ~0u); }
    else if (tid < 176) sts32(sb + SM_B1 + (tid - 160) * 4, (uint32_t)reinterpret_cast<const volatile unsigned short*>(P.b1)[min(mlp, 95) * 16 + tid - 160] << 16);
    else if (tid >= 192 && tid < 192 + NCB) sts32(sb + SM_CNT + (tid - 192) * 8, 0);
    unsigned char* accg = reinterpret_cast<unsigned char*>(__shfl_sync(~0u, (u64)g_acc + (lane >> 5), 0));
    auto release = [&](const uint4& tw) {
        uint32_t old;
        __syncwarp();
        asm volatile("{\n.reg .pred p;\nsetp.eq.u32 p, %2, 0;\nmov.u32 %0, 0;\n@p atom.relaxed.cta.shared.inc.u32 %0, [%1], 3;\n}"
                     : "=r"(old) : "r"(sb + SM_CNT + (tw.x & 0xf8)), "r"(lane) : "memory");
        return old;
    };
    auto refill = [&](const uint4& tw, uint32_t old) {
        if (__any_sync(~0u, old == 3 && (tw.y & 2))) {
            wait_until(lds32(sb + SM_T0) + tw.z);
            if (elect()) issue_half(tw.y, sb, rowc, cta, tmk);
            __syncwarp();
        }
    };
    __syncthreads();
    mbar_wait(barw + 72, 0);
    if (warp < NI1 - NI0 && elect()) issue_first(warp + NI0);

    uint32_t offV0, offV2;
    auto calc_offsets = [&]() {
        offV0 = subw + (6 * t) * 128 + ((g ^ ((6 * t) & 7)) << 4);
        offV2 = subw + (6 * t + 2) * 128 + ((g ^ ((6 * t + 2) & 7)) << 4);
    };
    calc_offsets();

    auto load_v = [&](uint4 (&v)[6], uint32_t so) {
        v[0] = lds128(offV0 + so); v[1] = lds128((offV0 ^ 16) + so + 128); v[2] = lds128(offV2 + so);
        v[3] = lds128((offV2 ^ 16) + so + 128); v[4] = lds128((offV0 ^ 64) + so + 512); v[5] = lds128((offV0 ^ 80) + so + 640);
    };
    auto issue_v = [&](auto I, int dw) {
        constexpr Step c = SCH.st[I.value];
        const uint32_t bar = barw + dw * 96 + c.slot * 8;
        mbar_expect(bar, SUB);
        tma3(subw + dw * SUB + c.slot * TILE, tmk + TM_V, 0, roww + dw * 8 + c.unit * 256, bar, POL_FIRST);
    };
    auto refill2 = [&](auto I) { __syncwarp(); if (elect()) issue_v(I, 0); };
    uint4 wq0[6], wqh[3], wq1[6];
    auto load_wq1 = [&](int i) { wq1[i] = lds128((i == 2 ? offV2 : i == 3 ? (offV2 ^ 16) + 128 : (offV0 ^ (i * 16)) + i * 128) + SM_WQ + TILE); };
    auto load_wq = [&]() {
        load_v(wq0, SM_WQ);
        const uint32_t so = SM_WQR - ((warp + 1) >> 1) * SUB;
        wqh[0] = lds128(((warp & 1) ? (offV2 ^ 16) + 128 : offV0) + so);
        wqh[1] = lds128(((warp & 1) ? (offV0 ^ 64) + 512 : (offV0 ^ 16) + 128) + so);
        wqh[2] = lds128(((warp & 1) ? (offV0 ^ 80) + 640 : offV2) + so);
#pragma unroll
        for (int i = 0; i < NWQ1; i++) load_wq1(i);
    };
    auto xcol = [&](int i, int tt) { return (i < 2 ? 64 * i + 8 * warp : 128 + 8 * (warp >> 1)) + 2 * tt; };
    uint4 kr[8][6];
    const unsigned char* rap;
    u64 rw[2];
    auto q_proj = [&](auto L, uint32_t (&p)[3], uint32_t pst) {
        if (L.value == 0 && g >= 4) p[0] = p[1] = p[2] = ONES;
        float a[3][4], b[3][4];
        const uint32_t dH = __byte_perm(p[2], 0, (warp & 1) ? 0x3232 : 0x1010);
        const uint32_t dA = __byte_perm(p[0], 0, 0x1010), dB = __byte_perm(p[0], 0, 0x3232), dC = __byte_perm(p[1], 0, 0x1010), dD = __byte_perm(p[1], 0, 0x3232);
#pragma unroll
        for (int i = NWQ1; i < 3; i++) load_wq1(i);
#pragma unroll
        for (int j = 0; j < 3; j++) { a[j][0] = a[j][1] = a[j][2] = a[j][3] = 0.f; mma(a[j], wq0[j], dA & maskA, dA & maskB); }
#pragma unroll
        for (int j = 0; j < 3; j++) { b[j][0] = b[j][1] = b[j][2] = b[j][3] = 0.f; mma(b[j], wq0[j + 3], dB & maskA, dB & maskB); }
#pragma unroll
        for (int j = 0; j < 3; j++) mma(a[j], wqh[j], dH & maskA, dH & maskB);
#pragma unroll
        for (int i = 3; i < 6; i++) load_wq1(i);
        auto look_rw = [&]() {
            if constexpr (L.value == 1) {
                if (NWQ1) rap = accg + ACC_BYTES + (c4() >> 2) * ACC_PITCH + (c4() & 3) * 8;
                rw[0] = ld_rlx(rap); rw[1] = ld_rlx(rap + 40 * ACC_PITCH);
            }
        };
        if (RWAT == 0) look_rw();
        if (L.value == 1 && P4AT == 2) refill2(IC<4>{});
#pragma unroll
        for (int j = 0; j < 3; j++) mma(b[j], wq1[j], dC & maskA, dC & maskB);
#pragma unroll
        for (int j = 0; j < 3; j++) mma(a[j], wq1[j + 3], dD & maskA, dD & maskB);
#pragma unroll
        for (int j = 0; j < 3; j++) {
#pragma unroll
            for (int k = 0; k < 4; k++) a[j][k] += b[j][k];
            sts128f(pst + j * 256, a[j]);
        }
        const uint32_t tag = lds32(sb + SM_EPOCH) * 4 + 1 + 2 * L.value;
        u64* pub = L.value ? &g_ll[0][cta][tid] : &g_l0[cta][tid];
        if (RWAT == 1) look_rw();
        TSTAMPL(21);
        __syncthreads();
        st_rlx_if(tid < 192, pub, ll_pack(sum8(sb + SM_PART + tid * 4, 768), tag));
        if constexpr (L.value == 0) st_rlx_if(tid < 192, pub + 192, ll_pack(sum8(sb + SM_CSP + tid * 4, 768), tag));
        TSTAMPL(23);
    };
    auto ln_stats = [&]() {
        float ss = ln_part(xp, lane);
        ss += shx(ss, 8); ss += shx(ss, 4); ss += shx(ss, 2); ss += shx(ss, 1);
        stsf(sb + SM_STAT + min(warp, 4) * 8 + (lane >> 4) * 4, ss);
    };
    auto ln_final = [&](float& mean, float& rstd) {
        float2 v[5];
#pragma unroll
        for (int w = 0; w < 5; w++) v[w] = lds64f(sb + SM_STAT + w * 8);
        mean = sum5(v[0].x, v[1].x, v[2].x, v[3].x, v[4].x) * (1.f / D_MODEL);
        const float msq = sum5(v[0].y, v[1].y, v[2].y, v[3].y, v[4].y) * (1.f / D_MODEL);
        rstd = ln_rstd(mean, msq);
        stsf(sb + SM_FXS, fx_scale(msq));
    };
    auto q_addr = [&](int d) { return sb + SM_VEC + (((d >> 1) & 1) * 4 + ((d >> 3) & 3)) * 48 + (d >> 5) * 8 + ((d >> 2) & 1) * 4 + (d & 1) * 2; };
    {
        uint32_t px[3];
#pragma unroll
        for (int i = 0; i < 3; i++) px[i] = *reinterpret_cast<const uint32_t*>(P.x + 4 * j40 + xcol(i, t));
        if (warp < 5) ln_stats();
        mbar_wait(sb + SM_BAR + (warp >> 1) * 96 + 72, 0);
        load_wq();
        q_proj(IC<0>{}, px, sb + (t < 2 ? SM_PART : SM_CSP) + warp * 768 + (8 * g + 4 * (t & 1)) * 4);
    }
    {
        uint32_t offQ, offL;
        auto calc_ql = [&]() {
            offQ = pin(sb + SM_VEC + (lane & 7) * 48);
            offL = pin(subw + lane * 16);
        };

        auto issue_w = [&](auto L, int which) {
            const uint32_t bar = sb + SM_CBAR + (CB_W1 + which) * 8;
            if (mlp == 96) asm volatile("mbarrier.arrive.shared::cta.b64 _, [%0];" :: "r"(bar) : "memory");
            else {
                mbar_expect(bar, 20480);
                if (which) tma3(sb + (L.value ? 3 * TILE : SM_W2), tmk + TM_W2, 0, mlp * 16, bar, WPOL);
                else asm volatile("cp.async.bulk.tensor.3d.shared::cluster.global.mbarrier::complete_tx::bytes.L2::cache_hint [%0], [%1, {%2, %3, %3}], [%4], %5;"
                                  :: "r"(sb + (L.value ? 2 * TILE : SM_W1)), "l"(tmk + TM_W1), "r"(mlp * 16), "r"(0), "r"(bar), "l"((u64)WPOL << 32) : "memory");
            }
        };
        float acc[3][4];
        auto load_q = [&](uint4 (&qf)[3]) {
#pragma unroll
            for (int i = 0; i < 3; i++) qf[i] = lds128(offQ + i * 16);
        };
        auto score = [&](const uint4 (&v)[6], const uint4 (&qf)[3]) {
            float d[2][4];
#pragma unroll
            for (int j = 0; j < 2; j++) d[j][0] = d[j][1] = d[j][2] = d[j][3] = 0.f;
#pragma unroll
            for (int i = 0; i < 3; i++) { mma(d[0], v[2 * i], qf[i].x, qf[i].y); mma(d[1], v[2 * i + 1], qf[i].z, qf[i].w); }
            return (d[0][0] + d[0][3]) + (d[1][0] + d[1][3]);
        };
        auto softmax = [&](float S0, float S1, float S2, float S3) {
            int mi = __float_as_int(fmaxf(fmaxf(S0, S1), fmaxf(S2, S3)));
            mi = __reduce_max_sync(~0u, mi ^ ((mi >> 31) & 0x7fffffff));
            const float mrun = __int_as_float(mi ^ ((mi >> 31) & 0x7fffffff));
            const float p0 = ex2((S0 - mrun) * CS), p1 = ex2((S1 - mrun) * CS), p2 = ex2((S2 - mrun) * CS), p3 = ex2((S3 - mrun) * CS);
            const uint32_t pa = pack_bf(p0, p1), pb = pack_bf(p2, p3), pw = prow + 256 + (key >> 1) * 80 + t * 4 + (key & 1) * 2;
            sts16(pw, pa); sts16(pw + 16, pa >> 16); sts16(pw + 32, pb); sts16(pw + 48, pb >> 16);
            __syncwarp();
#pragma unroll
            for (int j = 0; j < 3; j++) acc[j][0] = acc[j][1] = acc[j][2] = acc[j][3] = 0.f;
            return make_float2(mrun, (p0 + p1) + (p2 + p3));
        };
        auto head_weight = [&](u64 pm, u64 pl, auto L) {
            const uint32_t tag = lds32(sb + SM_EPOCH) * 4 + 2 + 2 * L.value;
#pragma unroll 1
            for (int it = 0; it < SPIN; it++) {
                if (__all_sync(~0u, ll_tag(pm) == tag && ll_tag(pl) == tag)) break;
                ld_rlx2(&g_ll[L.value][cta ^ (lane >> 3)][192 + (lane & 7) * 4], pm, pl);
            }
            const float f = ex2((ll_val(pm) - warp_max(ll_val(pm))) * CS);
            const float w = f * rcp(warp_sum(f * ll_val(pl)));
            if (lane < 8) stsf(sb + SM_FAC + lane * 4, w);
        };
        auto pv = [&](const uint4 (&v)[6], uint32_t pp) {
            const uint32_t dA = __byte_perm(pp, 0, 0x1010), dB = __byte_perm(pp, 0, 0x3232);
            mma(acc[0], v[0], dA & maskA, dA & maskB); mma(acc[1], v[1], dA & maskA, dA & maskB); mma(acc[2], v[2], dA & maskA, dA & maskB);
            mma(acc[0], v[3], dB & maskA, dB & maskB); mma(acc[1], v[4], dB & maskA, dB & maskB); mma(acc[2], v[5], dB & maskA, dB & maskB);
        };
        auto sa = [&]() { return prow + 256 + t * 32 + g * 4; };
        auto pass1 = [&]() {
#pragma unroll
            for (int u = 0; u < 8; u++)
#pragma unroll
                for (int i = 0; i < 6; i++) kr[u][i] = lds128(sb + SM_CS + (u * 6 + i) * 16);
            fresh();
            calc_ql();
            asm volatile("fence.proxy.async.shared::cta;" ::: "memory");
            __syncthreads();
            sts64(prow + lane * 8, xp.x, xp.y);
            int e = 0;
            const uint4* tab = P.tile + (warp >> 2);
            uint4 tw = tab[0];
            uint32_t ka[3];
#pragma unroll
            for (int j = 0; j < 3; j++) ka[j] = pin(subw + key * 384 + j * 128 + ((t ^ ((3 * key + j) & 7)) << 4));
            auto load_k = [&](uint4 (&v)[6], uint32_t so) {
#pragma unroll
                for (int i = 0; i < 6; i++) v[i] = lds128(((i & 1) ? ka[i >> 1] ^ 64 : ka[i >> 1]) + so);
            };
            const uint32_t s0 = pin(prow + 256 + g * 4), sca = pin(sb + SM_SC + warp * 128 + g * 16);
#pragma unroll 1
            do {
                const uint4 tn = tab[2 * e + 2];
                uint4 v[6], qf[3];
                if (tw.x & (G_A | G_B | G_C)) {
                    if ((tw.x & G_A) && warp == 7 && elect()) {
                        mbar_expect(sb + SM_CBAR + CB_SNAP * 8, HALF);
                        asm volatile("cp.async.bulk.shared::cluster.global.mbarrier::complete_tx::bytes [%0], [%1], 12288, [%2];"
                                     :: "r"(sb + SM_SNAP), "l"(&g_l0[cta & ~3][0]), "r"(sb + SM_CBAR + CB_SNAP * 8) : "memory");
                    }
                    if (tw.x & G_B) {
                        if (warp < 6) {
                            mbar_wait(sb + SM_CBAR + CB_SNAP * 8, 0);
                            float qc[2] = {0.f, 0.f}, mean, rstd;
#pragma unroll 1
                            for (int k = 0; k < 2; k++) {
                                u64 qw[4];
#pragma unroll
                                for (int i = 0; i < 4; i++) { const uint2 x = lds64(sb + SM_SNAP + i * 3072 + k * 1536 + tid * 8); qw[i] = x.x | (u64)x.y << 32; }
                                qc[0] = qc[1];
                                qc[1] = ll_gather<384>(&g_l0[cta & ~3][k * 192 + tid], lds32(sb + SM_EPOCH) * 4 + 1, qw);
                            }
                            ln_final(mean, rstd);
                            stsf(sb + SM_CS + tid * 4, qc[1]);
                            const float q = (qc[0] - mean * qc[1]) * rstd;
                            sts16(q_addr(tid), pack_bf(q, q));
                        }
                        __syncthreads();
                        if (warp == 7 && elect()) issue_half(UC<load_word(12)>::value, sb, rowc, cta, tmk);
                        TSTAMP(2);
                    }
                    if (tw.x & G_C) {
                        load_k(v, (e - LATEAT) * TILE);
                        load_q(qf);
                        stsf(s0 + (e - LATEAT) * 32, score(v, qf));
                    }
                }
                load_q(qf);
                mbar_wait(sb + SM_CBAR + (tw.x & 0xf8), tw.x >> 31);
                TRACE(e);
                load_k(v, tw.x & 0x3f000);
                const uint32_t old = release(tw);
                const float s = score(v, qf);
                uint32_t m;
                {
                    uint32_t a[6];
#pragma unroll
                    for (int i = 0; i < 6; i++) a[i] = bf2_amax(bf2_amax(v[i].x, v[i].y), bf2_amax(v[i].z, v[i].w));
                    m = bf2_amax(bf2_amax(bf2_amax(a[0], a[1]), bf2_amax(a[2], a[3])), bf2_amax(a[4], a[5]));
                }
                m = bf2_amax(m, m >> 16) & 0x7f80;
                m = max(m, __shfl_xor_sync(~0u, m, 1));
                stsf(s0 + e * 32, s);
                m = max(m, __shfl_xor_sync(~0u, m, 2));
                refill(tw, old);
                const uint32_t b = min(max(m, 15u << 7) - (15u << 7), 126u << 7);
                const uint32_t dn = ((127u << 7) - b) * 0x10001u, up = ((127u << 7 | 0x8000u) + b) * 0x10001u;
                uint32_t c[18], any = m > (141u << 7);
#pragma unroll
                for (int i = 0; i < 6; i++) {
                    const uint32_t y0 = bf2_mul(v[i].x, dn), y1 = bf2_mul(v[i].y, dn), y2 = bf2_mul(v[i].z, dn), y3 = bf2_mul(v[i].w, dn);
                    v[i] = make_uint4(bf2_fma(y0, up, v[i].x), bf2_fma(y1, up, v[i].y), bf2_fma(y2, up, v[i].z), bf2_fma(y3, up, v[i].w));
                    any |= v[i].x | v[i].y;
                    any |= v[i].z | v[i].w;
                    const uint32_t hb = __byte_perm(y2, y3, 0x7531);
                    c[3 * i] = __byte_perm(y0, y1, 0x6420); c[3 * i + 1] = __byte_perm(y2, y3, 0x6420);
                    c[3 * i + 2] = __byte_perm(y0, y1, 0x7531) | __funnelshift_r(hb, hb, 4);
                }
                asm volatile("st.shared.u8 [%0], %1;" :: "r"(sca + (e & 3) * 4 + (e >> 2)), "r"((b >> 7) + 63) : "memory");
                const bool rare = __any_sync(~0u, any);
                k_keep(kr, c, e, offL);
                if (rare) {
                    uint32_t odd = m > (141u << 7) ? 64u : 0u;
#pragma unroll
                    for (int i = 0; i < 6; i++) if (v[i].x | v[i].y | v[i].z | v[i].w) odd |= 1u << i;
                    odd = __reduce_or_sync(~0u, odd);
                    const uint2 st = lds64(barw + 80);
                    uint32_t lt; asm volatile("mov.u32 %0, %lanemask_lt;" : "=r"(lt));
                    uint32_t n = odd >= 64 ? NEXC + 1 : __shfl_sync(~0u, st.x, 0);
#pragma unroll 1
                    for (; odd && n <= NEXC; odd &= odd - 1) {
                        const int i = __ffs(odd) - 1;
                        uint4 r = v[0];
#pragma unroll
                        for (int k = 1; k < 6; k++) if (i == k) r = v[k];
#pragma unroll 1
                        for (int k = 0; k < 4; k++) {
                            const uint32_t who = __ballot_sync(~0u, r.x), at = n + __popc(who & lt);
                            if (r.x && at < NEXC) sts64(sb + SM_EXC + warp * 128 + at * 8, r.x, (e * 32 + g * 4) << 16 | (((k & 1) * 4 + t) * 48 + i * 8 + (k >> 1) * 4));
                            n += __popc(who);
                            r.x = r.y; r.y = r.z; r.z = r.w;
                        }
                    }
                    if (n > NEXC) asm volatile("st.shared.u8 [%0], %1;" :: "r"(sca + (e & 3) * 4 + (e >> 2)), "r"(0) : "memory");
                    sts64(barw + 80, n > NEXC ? st.x : n, n > NEXC ? st.y | 1u << e : st.y);
                    __syncwarp();
                }
                tw = tn;
            } while (++e < 16);
            asm volatile("fence.proxy.async.shared::cta;" ::: "memory");
            __syncwarp();
            TSTAMP(10);
            fresh(); calc_offsets();
            {
                const uint2 st = lds64(barw + 80);
                const uint32_t xa = sb + SM_EXC + warp * 128 + (lane & 15) * 8 + 4;
                uint32_t pos = lds32(xa), lt;
                asm volatile("mov.u32 %0, %lanemask_lt;" : "=r"(lt));
                if (lane >= st.x) pos = 0x80000000u;
                const bool dup = (__match_any_sync(~0u, pos >> 16) & lt) && lane < st.x;
                if (lane < 16) sts32(xa, dup ? pos | 0x40000000u : pos);
                if (__any_sync(~0u, dup)) sts32(barw + 84, st.y | 0x10000u);
                const float2 ml = softmax(ldsf(sa()), ldsf(sa() + 128), ldsf(sa() + 256), ldsf(sa() + 384));
                sts64f(sb + SM_ML + warp * 8, ml.x, warp_sum(ml.y));
            }
            u64 pm = 0, pl = 0;
#pragma unroll 1
            do {
                const uint4 tn = tab[2 * e + 2];
                if (tw.x & (G_A | G_B | G_C)) {
                    if (tw.x & G_A) {
                        if (lane < 24) st_rlx(&g_ll[0][cta][warp * 24 + lane], 0ull);
                        else if (lane < 28) st_rlx(&g_ll[0][cta][168 + warp * 4 + lane], ll_pack(ldsf(sb + SM_ML + warp * 8 + (lane & 1) * 4), lds32(sb + SM_EPOCH) * 4 + 2));
                    }
                    if (warp == 2) {
                        if (tw.x & G_B) ld_rlx2(&g_ll[0][cta ^ (lane >> 3)][192 + (lane & 7) * 4], pm, pl);
                        if (tw.x & G_C) head_weight(pm, pl, IC<0>{});
                    }
                    __syncwarp();
                }
                const uint32_t pp = lds32(prow + 256 + t * 80 + ((tw.x >> 20) & 255));
                mbar_wait(sb + SM_CBAR + (tw.x & 0xf8), tw.x >> 31);
                TRACE(e);
                uint4 v[6];
                load_v(v, tw.x & 0x3f000);
                refill(tw, release(tw));
                pv(v, pp);
                tw = tn;
            } while (++e < 32);
        };
        uint32_t osa, ora, owa, orow, otag;
        u64* olb;
        auto o_setup = [&](auto L) {
            fresh();
            const int lz = lane, d = warp * 24 + min(lz, 23);
            osa = pin(prow + ((lz >> 2) * 8 + (lz & 1) * 4) * 4);
            ora = pin(sb + SM_PART + d * 4);
            olb = pin(&g_ll[L.value][cta & ~3][d]);
            orow = pin((lz & 1) + 2 * (lz & 2) + 2 * (lz >> 4));
            owa = pin(sb + SM_RING + warp * 1536 + orow * 64 + ((((lz >> 2) & 3) ^ (orow >> 1)) << 4));
            otag = lds32(sb + SM_EPOCH) * 4 + 2 + 2 * L.value;
            xp = lds64(prow + lz * 8);
        };
        auto pass2 = [&]() {
            constexpr IC<1> L{};
            const uint32_t c0 = clk();
            if (P4AT == 0) refill2(IC<4>{});
            if (P2LATE == 1 && warp >= 4) refill2(IC<2>{});
            offQ = sb + SM_VEC + (lane & 7) * 48; offL = subw + lane * 16;
            uint4 tb[8][3];
            auto load_tb = [&](auto I) {
#pragma unroll
                for (int i = 0; i < 3; i++) tb[I.value][i] = lds128(offL + (I.value >> 1) * TILE + ((I.value & 1) * 3 + i) * 512);
            };
            const float cs = ldsf(sb + SM_CS + min(tid, 191) * 4), inv = fx2_inv(ldsf(sb + SM_MSQ));
            const uint32_t qtag = lds32(sb + SM_EPOCH) * 4 + 3;
            uint32_t m1 = lds32(sb + SM_M1), m1n = m1;
            static_for<0, NPRE>(load_tb);
            const u64* qb = &g_ll[0][cta & ~3][min(tid, 191)];
            const uint32_t qa = pin(q_addr(min(tid, 191)));
            {
                uint32_t x[2];
                fx2_wait<2, true>([&](int i) { return rap + i * 40 * ACC_PITCH; }, rw, sb + SM_MSQ, inv, x);
                xp = make_uint2(x[0], x[1]);
            }
            u64 qw[4];
            if (QDELAY) while (clk() - c0 < QDELAY);
            ll_look<256>(qb, qw);
            ln_stats();
            if (P4AT == 1) refill2(IC<4>{});
            if (S0EARLY) refill2(IC<5>{});
            __syncthreads();
            auto vwait = [&](auto I) { mbar_wait(barw + IC<SCH.st[I.value].slot>::value * 8, IC<SCH.st[I.value].par>::value); };
            bool ok;
            {
                float mean, rstd;
                ln_final(mean, rstd);
                sts64(prow + lane * 8, xp.x, xp.y);
                sts128f(prow + 256 + lane * 16, 0.f, 0.f, 0.f, 0.f);
                const float sq = rstd * 0x1p64f, q0 = -mean * cs * sq;
                const float q = ll_gather<256>(qb, qtag, qw) * sq + q0;
                sts16(qa, pack_bf(q, q));
                TSTAMPL(24);
            }
            if (!S0EARLY) refill2(IC<5>{});
            if (P2LATE == 2 && warp >= 4) refill2(IC<2>{});
            if (P4AT == 3) refill2(IC<4>{});
            if (NOWIN & 1) { if (warp < 6) refill2(IC<0>{}); if (warp >= 5) refill2(IC<3>{}); }
            if (NOWIN & 2) { if (warp >= 6) refill2(IC<1>{}); if (warp < 4) refill2(IC<2>{}); }
            if (NOWIN & 4) { if (warp >= 6) refill2(IC<0>{}); if (warp < 6) refill2(IC<1>{}); }
            if (NOWIN & 8) { if (warp < 5) refill2(IC<3>{}); if (warp >= 4) refill2(IC<2>{}); }
            __syncthreads();
            uint4 qf[3];
            load_q(qf);
            float S[4], d[2][4];
            auto vload = [&](auto I) {
                constexpr int p = I.value;
                constexpr Step c = SCH.st[p];
                load_v(kr[p & 7], c.slot * TILE);
                if constexpr (c.next >= 0) refill2(IC<c.next>{});
                if constexpr (p == 11) { __syncwarp(); if (elect()) asm volatile("mbarrier.arrive.shared::cta.b64 _, [%0];" :: "r"(sb + SM_CBAR + CB_REL * 8) : "memory"); }
            };
            auto side = [&](uint2 x) {
                const uint32_t qq = lds32(sb + SM_VEC + (x.y & 0xffff));
                return (bf_lo(x.x) * bf_lo(qq) + bf_hi(x.x) * bf_hi(qq)) * 0x1p-64f;
            };
            static_for<0, 96>([&](auto F) {
                constexpr int f = F.value, i = f % 6, u = kunit(f / 6), w = 3 * f % 12;
                uint4 (&src)[3] = *reinterpret_cast<uint4 (*)[3]>(f < 32 ? &tb[f / 4 & 7][0] : &kr[(f / 8 + 4) & 7][(f / 4 & 1) * 3]);
                const uint4 a = k_unpack(word<w % 4>(src[w / 4]), word<(w + 1) % 4>(src[(w + 1) / 4]), word<(w + 2) % 4>(src[(w + 2) / 4]), m1);
                if constexpr (f < 32 ? f % 4 == M1AT : f % 8 == M1P) m1 = m1n;
                if constexpr (f % 4 == 3 && f / 4 + NPRE < 8) {
                    load_tb(IC<f / 4 + NPRE>{});
                    if constexpr ((f / 4 + NPRE) & 1) { refill2(IC<5 + (f / 4 + NPRE) / 2>{}); m1n = lds32(sb + SM_M1); }
                }
                if constexpr (i < 2) d[i][0] = d[i][1] = d[i][2] = d[i][3] = 0.f;
                mma(d[i & 1], a, (i & 1) ? qf[i / 2].z : qf[i / 2].x, (i & 1) ? qf[i / 2].w : qf[i / 2].y);
                if constexpr (i == 5) {
                    if constexpr (u == 11 || ((u & 3) == 0 && u != 8)) S[u >> 2] = (d[0][0] + d[0][3]) + (d[1][0] + d[1][3]);
                    else add_if(t == (u & 3), S[u >> 2], d[0][0] + d[0][3], d[1][0] + d[1][3]);
                    if constexpr (f < 64) S[u >> 2] = shx(S[u >> 2], 0);
                }
                if constexpr (f == 31) { fresh(); calc_offsets(); ok = mbar_test(barw + IC<SCH.st[0].slot>::value * 8, 0); }
                if constexpr (f == 48) {
                    const uint2 x = lds64(sb + SM_EXC + warp * 128 + (lane & 15) * 8);
                    const float c = side(x);
                    if (x.y < 0x40000000u) stsf(prow + 256 + (x.y >> 16), c);
                }
                if constexpr (f >= 32 && f % 8 == 7) {
                    if constexpr (PARKS >> (f / 8 - 4) & 1) {
                        constexpr int p = popc(PARKS & ((1 << (f / 8 - 4)) - 1));
                        if (!ok) vwait(IC<p>{});
                        vload(IC<p>{});
                        m1n = lds32(sb + SM_M1);
                        ok = mbar_test(barw + IC<SCH.st[p + 1].slot>::value * 8, IC<SCH.st[p + 1].par>::value);
                    }
                }
            });
            uint32_t bad = lds32(barw + 84);
            const uint32_t sc = lds32(sb + SM_SC + tid * 4);
            __syncwarp();
            if (bad) {
                const uint2 x = lds64(sb + SM_EXC + warp * 128 + (lane & 15) * 8);
                if ((int)x.y >= 0x40000000 && lane < 16) asm volatile("red.shared.add.f32 [%0], %1;" :: "r"(prow + 256 + ((x.y >> 16) & 511)), "f"(side(x)) : "memory");
#pragma unroll 1
                for (bad &= 0xffff; bad; bad &= bad - 1) {
                    const int e = __ffs(bad) - 1;
                    const __nv_bfloat16* kp = P.k + (size_t)(roww + e * 256 + key) * DH + t * 8;
                    uint4 v[6];
#pragma unroll
                    for (int i = 0; i < 6; i++) v[i] = *reinterpret_cast<const uint4*>(kp + i * 32);
                    const float s = score(v, qf) * 0x1p-64f;
                    if (t == 0) stsf(sa() + e * 32, s);
                }
                __syncwarp();
            }
            TSTAMP(30);
            const float2 ml = softmax(S[0] * __uint_as_float((sc & 255) << 23) + ldsf(sa()), S[1] * __uint_as_float((sc & 0xff00) << 15) + ldsf(sa() + 128),
                                      S[2] * __uint_as_float((sc & 0xff0000) << 7) + ldsf(sa() + 256), S[3] * __uint_as_float((sc >> 24) << 23) + ldsf(sa() + 384));
            uint4 pq[4];
#pragma unroll
            for (int j = 0; j < 4; j++) pq[j] = lds128(prow + 256 + t * 80 + j * 16);
            TSTAMP(1);
            if (!ok) vwait(IC<NPARK>{});
            float ac2[3][4];
#pragma unroll
            for (int j = 0; j < 3; j++) ac2[j][0] = ac2[j][1] = ac2[j][2] = ac2[j][3] = 0.f;
            const uint32_t sl = (g & 1) ? 0x1044 : 0x4410, sh = (g & 1) ? 0x3244 : 0x4432;
            const uint32_t sA0 = (g & 2) ? 0x4444 : sl, sA1 = (g & 2) ? sl : 0x4444, sB0 = (g & 2) ? 0x4444 : sh, sB1 = (g & 2) ? sh : 0x4444;
            u64 pm = 0, pl = 0;
            static_for<NPARK, 16>([&](auto I) {
                constexpr int p = I.value;
                static_assert(p - SCH.st[p].mma0 < 8, "buffer in use");
                vload(I);
                if constexpr (p < 15) ok = mbar_test(barw + IC<SCH.st[p + 1].slot>::value * 8, IC<SCH.st[p + 1].par>::value);
                static_for<SCH.st[p].mma0, SCH.st[p].mma0 + SCH.st[p].nmma>([&](auto J) {
                    constexpr int u = SCH.st[J.value].unit;
                    const uint32_t pp = word<u & 3>(pq[u >> 2]), a0 = __byte_perm(pp, 0, sA0), a1 = __byte_perm(pp, 0, sA1), b0 = __byte_perm(pp, 0, sB0), b1 = __byte_perm(pp, 0, sB1);
#pragma unroll
                    for (int j = 0; j < 3; j++) mma(acc[j], kr[J.value & 7][j], a0, a1);
#pragma unroll
                    for (int j = 0; j < 3; j++) mma(ac2[j], kr[J.value & 7][j + 3], b0, b1);
                });
                if constexpr (p == NPARK) {
                    const float l = warp_sum(ml.y);
                    if (lane < 28) st_rlx(&g_ll[1][cta][lane < 24 ? warp * 24 + lane : 168 + warp * 4 + lane], lane < 24 ? 0ull : ll_pack((lane & 1) ? l : ml.x, lds32(sb + SM_EPOCH) * 4 + 4));
                }
                if constexpr (p == HWAT) { if (warp == 6) ld_rlx2(&g_ll[1][cta ^ (lane >> 3)][192 + (lane & 7) * 4], pm, pl); }
                if constexpr (p == 13) o_setup(L);
                if constexpr (p == HWAT + 2) { if (warp == 6) head_weight(pm, pl, IC<1>{}); }
                if constexpr (p >= WOAT && p < WOAT + 3) {
                    if (warp == p - WOAT) {
                        mbar_wait(sb + SM_CBAR + CB_REL * 8, 0);
                        if (elect()) {
                            issue_half(UC<load_word(64 + 2 * (p - WOAT)) | 1>::value, sb, rowc, cta, tmk);
                            if constexpr (p < WOAT + 2) issue_half(UC<load_word(65 + 2 * (p - WOAT)) | 1>::value, sb, rowc, cta, tmk);
                        }
                        __syncwarp();
                    }
                }
                if constexpr (p < 15) { if (!ok) mbar_wait(barw + IC<SCH.st[p + 1].slot>::value * 8, IC<SCH.st[p + 1].par>::value); TRACE(33 + p); }
            });
#pragma unroll
            for (int j = 0; j < 3; j++)
#pragma unroll
                for (int k = 0; k < 4; k++) acc[j][k] += ac2[j][k];
        };

        uint32_t pa;
        unsigned char* rop;
        auto out_proj = [&](auto L) {
            TSTAMP2(3);
            CSTAMP(0, __float_as_uint(acc[2][3]));
            __syncwarp();
#pragma unroll
            for (int j = 0; j < 3; j++) sts128f(osa + 256 * j, acc[j]);
            __syncthreads();
            {
                float s[8];
#pragma unroll
                for (int w = 0; w < 8; w++) s[w] = ldsf(ora + w * 768);
                const uint4 fa = lds128(sb + SM_FAC), fb = lds128(sb + SM_FAC + 16);
            CSTAMP(1, __float_as_uint(s[0]));
                const float own = ((s[0] * __uint_as_float(fa.x) + s[1] * __uint_as_float(fa.y)) + (s[2] * __uint_as_float(fa.z) + s[3] * __uint_as_float(fa.w))) +
                                  ((s[4] * __uint_as_float(fb.x) + s[5] * __uint_as_float(fb.y)) + (s[6] * __uint_as_float(fb.z) + s[7] * __uint_as_float(fb.w)));
                st_rlx_if(lane < 24, olb + (cta & 3) * 256, ll_pack(own, otag));
            CSTAMP(2, __float_as_uint(own));
            }
            TSTAMPL(29);
            if (L.value == 0 && warp == 7) {
#pragma unroll 1
                for (int it = 0; it < SPIN; it++) {
                    uint32_t v; asm volatile("ld.acquire.gpu.global.u32 %0, [%1];" : "=r"(v) : "l"(&g_zflag) : "memory");
                    if (__all_sync(~0u, v == (otag >> 2) + 1)) break;
                }
            }
            constexpr int NW = L.value ? NWO1 : 3;
            uint4 v[5][3];
            u64 ow[4];
            auto read_wo = [&](auto J) {
#pragma unroll
                for (int p = 0; p < 3; p++) v[J.value][p] = lds128(owa + ring_hs(64 + J.value) * HALF + p * 512);
            };
            uint32_t wpa;
            auto sum_setup = [&]() {
                const int lz = lane, word = (lz & 3) * 160 + j40 + warp * 8 + (lz >> 2);
                const uint32_t wo = ((lz >> 2) * 8 + (lz & 1) * 4) * 4;
                wpa = pin(sb + SM_RING + warp * 1536 + ((((lz >> 1) ^ (lz >> 4)) & 1) ? HALF + (wo ^ 64) : wo));
                pa = pin(sb + SM_RING + warp * 256 + lz * 4);
                rop = pin(accg + 2 * L.value * ACC_BYTES + (word >> 3) * ACC_PITCH + (word & 7) * 8);
            };
            if (L.value) { sum_setup(); maskA = pin(maskA); maskB = pin(maskB); }
            static_for<0, NW>([&](auto J) {
                if (OPOLL == J.value) ll_look<256>(olb, ow);
                mbar_wait(sb + SM_CBAR + (CB_WO + J.value) * 8, L.value);
                read_wo(J);
                if (L.value == 0 && W1AT0 == J.value + 1) {
                    __syncwarp();
                    if (elect() && cnt_inc(sb + SM_CNT + CB_W1 * 8, 7) == 7) issue_w(L, 0);
                    __syncwarp();
                }
                if (L.value == 1 && (W1AT1 == J.value + 1 || W2AT1 == J.value + 1)) {
                    if (warp == 7 && elect()) { if (W1AT1 == J.value + 1) issue_w(L, 0); if (W2AT1 == J.value + 1) issue_w(L, 1); }
                    __syncwarp();
                }
            });
            const float o = ll_gather<256>(olb, otag, ow);
            CSTAMP(3, __float_as_uint(o));
            TSTAMP2(4);
            bool ok = true;
            if constexpr (NW < 5) ok = mbar_test(sb + SM_CBAR + (CB_WO + 4) * 8, L.value);
            if constexpr (NW < 4) ok &= mbar_test(sb + SM_CBAR + (CB_WO + 3) * 8, L.value);
            const uint32_t od = pack_bf(o, o);
            uint32_t oa[3], ob[3];
#pragma unroll
            for (int p = 0; p < 3; p++) { const uint32_t op = __shfl_sync(~0u, od, 8 * p + orow); oa[p] = op & maskA; ob[p] = op & maskB; }
            CSTAMP(4, oa[2]);
            float y[5][4];
#pragma unroll
            for (int j = 0; j < 5; j++) y[j][0] = y[j][1] = y[j][2] = y[j][3] = 0.f;
            auto rest = [&]() {
                if (!ok) static_for<NW, 5>([&](auto J) { mbar_wait(sb + SM_CBAR + (CB_WO + J.value) * 8, L.value); });
                static_for<NW, 5>(read_wo);
            };
            if (L.value) rest();
#pragma unroll
            for (int p = 0; p < 3; p++)
#pragma unroll
                for (int j = 0; j < NW; j++) mma(y[j], v[j][p], oa[p], ob[p]);
            if (!L.value) { rest(); sum_setup(); }
#pragma unroll
            for (int p = 0; p < 3; p++)
#pragma unroll
                for (int j = NW; j < 5; j++) mma(y[j], v[j][p], oa[p], ob[p]);
            CSTAMP(5, __float_as_uint(y[4][3]));
#pragma unroll
            for (int j = 0; j < 5; j++) sts128f(wpa + j * 256, y[j]);
            TSTAMP2(5);
        };
        u64 yw[2];
        bool wide;
        float msq = 0.f, yf[4];
        auto mlp_part = [&](auto L) {
            const float fxs = ldsf(sb + SM_FXS);
            bar_sync(0, 256);
            CSTAMP(6, __float_as_uint(fxs));
            {
                const float s = sum8(pa, 1536) + sum8(pa + 128, 1536);
            CSTAMP(7, __float_as_uint(s));
                asm volatile("red.relaxed.gpu.global.add.u64 [%0], %1;" :: "l"(rop), "l"(fx_pack(s, fxs)) : "memory");
            }
            const uint32_t c0 = clk();
            TSTAMP2(6);
            if (L.value == 0) bar_arrive(2, 256);
            else if (mlp == 96) { TDUMP(); asm volatile("exit;"); }
            uint4 wf[8], w2r[8];
            fresh();
            const int lz = lane, cz = c4();
            const uint32_t hpa = pin(sb + SM_PART + warp * 256 + ((lz & 2) * 4 + (lz >> 2)) * 16 + (L.value ? 0 : (lz & 1) * 4));
            const uint32_t hsa = pin(sb + SM_PART + (lz & 15) * 16), hst = pin(sb + SM_PART + (lz & 15) * 16 + warp * 256 + 8 + (lz >> 4) * 4);
            const uint32_t w2a = pin(sb + (L.value ? 3 * TILE : SM_W2) + ((lz & 3) * 10 + 2 * warp) * 128 + (((lz >> 2) ^ ((2 * lz + 2 * warp) & 6)) << 4));
            const uint32_t la = sb + (L.value ? 2 * TILE : SM_W1) + warp * 4096 + (lz & 4) * 512 + (lz & 2) * 64 + (lz & 1) * 32 + (lz >> 4) * 64 + ((((lz >> 3) ^ (lz >> 1)) & 1) << 4);
            const unsigned char* ap = pin(accg + 2 * L.value * ACC_BYTES + (cz >> 3) * ACC_PITCH + (cz & 7) * 8);
            rap = pin(accg + (2 * L.value + 1) * ACC_BYTES + (cz >> 2) * ACC_PITCH + (cz & 3) * 8);
            uint2 b2v;
            asm volatile("ld.global.nc.v2.u32 {%0,%1}, [%2];" : "=r"(b2v.x), "=r"(b2v.y) : "l"(P.b2 + 4 * cz));
            auto read_w2 = [&]() {
#pragma unroll
                for (int i = 0; i < 8; i++) w2r[i] = lds128(((i & 1) ? (w2a ^ 16) + 128 : w2a) + (i >> 1) * 5120);
            };
            mbar_wait(sb + SM_CBAR + CB_W1 * 8, L.value);
#pragma unroll
            for (int j = 0; j < 8; j++) wf[j] = ldsm_t(la + j * 256);
            if (L.value == 0) { bar_arrive(3, 256); fresh(); }
            if constexpr (L.value == 1) {
                float cs[2][4] = {};
#pragma unroll
                for (int j = 0; j < 8; j++) mma(cs[j & 1], wf[j], ONES, ONES);
                stsf(hpa | 4, (t & 2) ? cs[0][2] + cs[1][2] : cs[0][0] + cs[1][0]);
                mbar_wait(sb + SM_CBAR + CB_W2 * 8, 1);
                read_w2();
                maskA = pin(maskA); maskB = pin(maskB);
            }
            const float b1v = ldsf(sb + SM_B1 + (lane & 15) * 4);
            TSTAMPL(28);
            while (clk() - c0 < AR1D);
            {
                u64 w[4];
                int it = 0;
#pragma unroll 1
                do {
#pragma unroll
                    for (int k = 0; k < 4; k++) w[k] = ld_rlx(ap + k * 20 * ACC_PITCH);
                } while (__any_sync(~0u, ~(lo32(w[0]) & lo32(w[1]) & lo32(w[2]) & lo32(w[3])) & 32) & (++it < SPIN));
                const float inv = fx_inv(fxs);
            CSTAMP(8, lo32(w[3]));
                xp = make_uint2(pack_bf(bf_lo(xp.x) + fx_val(w[0]) * inv, bf_hi(xp.x) + fx_val(w[1]) * inv),
                                pack_bf(bf_lo(xp.y) + fx_val(w[2]) * inv, bf_hi(xp.y) + fx_val(w[3]) * inv));
            }
            TSTAMP2(7);
            CSTAMP(9, xp.y);
            {
                bool ok = true;
                if (L.value == 0) ok = mbar_test(sb + SM_CBAR + CB_W2 * 8, 0);
                const bool ev = L.value || !(g & 1), od = L.value || (g & 1);
                const uint32_t e0 = ev ? xp.x : ONES, e1 = ev ? xp.y : ONES, o0 = od ? xp.x : ONES, o1 = od ? xp.y : ONES;
                float d[8][4];
#pragma unroll
                for (int j = 0; j < 8; j++) { d[j][0] = d[j][1] = d[j][2] = d[j][3] = 0.f; mma(d[j], wf[j], (j & 1) ? o0 : e0, (j & 1) ? o1 : e1); }
                float ss = ln_part(xp, lane);
                ss += shx(ss, 8); ss += shx(ss, 4);
                float r[4], dd;
#pragma unroll
                for (int k = 0; k < 4; k += 1 + L.value) r[k] = d[0][k] + d[1][k ^ 1];
#pragma unroll
                for (int j = 1; j < 4; j++)
#pragma unroll
                    for (int k = 0; k < 4; k += 1 + L.value) add_if(t == j, r[k], d[2 * j][k], d[2 * j + 1][k ^ 1]);
                CSTAMP(10, __float_as_uint(r[2]));
                if (L.value) {
                    dd = ((t & 2) ? r[2] : r[0]) + shx((t & 2) ? r[0] : r[2], 2);
                    ss += shx(ss, 2);
                    dd += shx(dd, 1);
                } else {
                    const float a = ((t & 1) ? r[1] : r[0]) + shx((t & 1) ? r[0] : r[1], 1), b = ((t & 1) ? r[3] : r[2]) + shx((t & 1) ? r[2] : r[3], 1);
                    ss += shx(ss, 2);
                    dd = ((t & 2) ? b : a) + shx((t & 2) ? a : b, 2);
                }
                ss += shx(ss, 1);
                stsf(hpa, dd);
                stsf(hst, ss);
                CSTAMP(11, __float_as_uint(dd + ss));
                if (!ok) mbar_wait(sb + SM_CBAR + CB_W2 * 8, 0);
            }
            TSTAMPL(25);
            bar_sync(1, 160);
            uint4 hp[5];
#pragma unroll
            for (int w = 0; w < 5; w++) hp[w] = lds128(hsa + w * 256);
            CSTAMP(12, hp[0].x);
            auto hs = [&](auto K) { return sum5(__uint_as_float(word<K.value>(hp[0])), __uint_as_float(word<K.value>(hp[1])), __uint_as_float(word<K.value>(hp[2])),
                                                __uint_as_float(word<K.value>(hp[3])), __uint_as_float(word<K.value>(hp[4]))); };
            const float mean = hs(IC<2>{}) * (1.f / D_MODEL);
            msq = hs(IC<3>{}) * (1.f / D_MODEL);
            float hv = hs(IC<0>{}) - mean * hs(IC<1>{});
            CSTAMP(13, __float_as_uint(hv));
            const float sc2 = fx2_scale(msq), lim = fx_inv(sc2) * FX2LIM;
            if (L.value == 0) { read_w2(); bar_arrive(4, 256); }
            hv = hv * ln_rstd(mean, msq) + b1v;
            CSTAMP(14, __float_as_uint(hv));
            hv = hv * rcp(1.f + ex2(hv * (-2.302208198f - 0.1029432397f * hv * hv)));
            const uint32_t hd = pack_bf(hv, hv);
            CSTAMP(15, hd);
            TSTAMPL(27);
            float ym[4][4];
#pragma unroll
            for (int i = 0; i < 2; i++) {
                ym[i][0] = ym[i][1] = ym[i][2] = ym[i][3] = 0.f;
                const float f = mlp < 64 ? 1.f / 64 : 0.f;
                ym[i + 2][0] = (bf_lo(xp.x) + bf_lo(b2v.x)) * f; ym[i + 2][1] = (bf_hi(xp.x) + bf_hi(b2v.x)) * f;
                ym[i + 2][2] = (bf_lo(xp.y) + bf_lo(b2v.y)) * f; ym[i + 2][3] = (bf_hi(xp.y) + bf_hi(b2v.y)) * f;
            }
#pragma unroll
            for (int i = 0; i < 4; i++) {
                const uint32_t hh = __shfl_sync(~0u, hd, 4 * i + t);
                mma(ym[(i & 1) * 2], w2r[2 * i], hh & maskA, hh & maskB);
                mma(ym[(i & 1) * 2 + 1], w2r[2 * i + 1], hh & maskA, hh & maskB);
            }
#pragma unroll
            for (int k = 0; k < 4; k++) { yf[k] = ym[0][k] + ym[2][k]; add_if(t & 2, yf[k], ym[1][k], ym[3][k]); }
            CSTAMP(16, __float_as_uint(yf[3]));
            yw[0] = fx2_pack(yf[0] * sc2 + FX2_ONE, yf[1] * sc2 + FX2_ONE); yw[1] = fx2_pack(yf[2] * sc2 + FX2_ONE, yf[3] * sc2 + FX2_ONE);
            wide = !(fmaxf(fmaxf(fabsf(yf[0]), fabsf(yf[1])), fmaxf(fabsf(yf[2]), fabsf(yf[3]))) < lim);
            if (wide) yw[0] = yw[1] = 0;
        };
        auto send_wide = [&]() {
#pragma unroll 1
            for (int k = 0; k < 4; k++, yf[0] = yf[1], yf[1] = yf[2], yf[2] = yf[3])
                asm volatile("red.relaxed.gpu.global.add.u64 [%0], %1;" :: "l"(rap + (k >> 1) * 40 * ACC_PITCH + 64 + (k & 1) * 32), "l"(fx_pack(yf[0], fx_scale(msq))) : "memory");
            __threadfence();
#pragma unroll
            for (int k = 0; k < 2; k++) { asm volatile("red.relaxed.gpu.global.or.b64 [%0], 256;" :: "l"(rap + k * 40 * ACC_PITCH) : "memory"); yw[k] = 1; }
        };

        pass1();
        o_setup(IC<0>{});
        out_proj(IC<0>{});
        uint32_t c0;
        if (warp < 5) {
            mlp_part(IC<0>{});
            if (mlp != 96) {
#pragma unroll
                for (int k = 0; k < 2; k++) asm volatile("red.relaxed.gpu.global.add.u64 [%0], %1;" :: "l"(rap + k * 40 * ACC_PITCH), "l"(yw[k]) : "memory");
            }
            c0 = clk();
            TSTAMP(8);
            if (__any_sync(~0u, wide && mlp != 96)) {
                if (wide) {
                    send_wide();
#pragma unroll
                    for (int k = 0; k < 2; k++) asm volatile("red.relaxed.gpu.global.add.u64 [%0], 1;" :: "l"(rap + k * 40 * ACC_PITCH) : "memory");
                }
                __syncwarp();
            }
            fresh(); calc_offsets();
            load_wq();
        } else {
            bar_sync(0, 256);
            if (warp == 5 && elect()) {
                asm volatile("fence.proxy.async.shared::cta;" ::: "memory");
                if (W1AT0 == 4) issue_w(IC<0>{}, 0);
                issue_w(IC<0>{}, 1);
            }
            __syncwarp();
            fresh(); calc_offsets();
            load_wq();
#pragma unroll 1
            for (int ph = 0; ph < 3; ph++) {
                bar_sync(ph + 2, 256);
                c0 = clk();
                if (ph == 2) {
                    msq = sum5(ldsf(sb + SM_PART + 12), ldsf(sb + SM_PART + 268), ldsf(sb + SM_PART + 524), ldsf(sb + SM_PART + 780), ldsf(sb + SM_PART + 1036)) * (1.f / D_MODEL);
                    bar_arrive(5, 256);
                }
                if (!(NOWIN >> ph & 1) && elect()) {
                    asm volatile("fence.proxy.async.shared::cta;" ::: "memory");
                    const uint32_t gap = ph == 0 ? WG1 : ph == 1 ? WG2 : WG3;
                    uint32_t c1 = c0 + (ph == 0 ? WD1 : 0) + (warp - 5) * gap;
#pragma unroll 1
                    for (int k = warp + (ph == 0 ? -5 : ph == 1 ? 9 : 1); k < (ph == 0 ? 9 : ph == 1 ? 20 : 14); k += 3, c1 += 3 * gap) {
                        const int i = ph == 0 && k >= 6 ? k + 23 : k;
                        const uint32_t bar = sb + SM_BAR + (i & 7) * 96 + 32 + (i & 24);
                        while ((int)(clk() - c1) < 0);
                        mbar_expect(bar, SUB);
                        tma3(sb + SM_RING + i * SUB, tmk + TM_V, 0,
                             rowc + (i & 7) * 8 + ((UC<SCH.st[0].unit | SCH.st[1].unit << 8 | SCH.st[2].unit << 16 | SCH.st[3].unit << 24>::value >> (i & 24)) & 15) * 256, bar, POL_FIRST);
                    }
                }
                __syncwarp();
            }
            c0 += PCD;
        }
        {
            constexpr IC<1> L{};
            fresh();
            const int lz = lane;
            const unsigned char* xa[2];
#pragma unroll
            for (int i = 0; i < 2; i++) {
                const int col = xcol(2 * i, lz & 3), cw = j40 + (col >> 2);
                xa[i] = pin(accg + ACC_BYTES + ((cw >> 2) + (col & 2) * 20) * ACC_PITCH + (cw & 3) * 8);
            }
            const uint32_t pst = pin(prow + ((lz >> 2) * 8 + (lz & 1) * 4) * 4);
            stsf(sb + SM_MSQ, msq);
            const float inv = shx(fx2_inv(msq), 0);
            if (!NWQ1) rap = pin(accg + ACC_BYTES + (c4() >> 2) * ACC_PITCH + (c4() & 3) * 8);
            fresh();
            if (!NWQ1) { maskA = pin(maskA); maskB = pin(maskB); }
            u64 w[3];
            uint32_t x2[3];
            auto xat = [&](int i) { return ((i & 2) ? xa[1] : xa[0]) + (i & 1) * 4 * ACC_PITCH; };
            if (warp < 5) {
                bar_sync(5, 256);
                if (DPRE) { while ((int)(clk() - c0) < WD4 + warp * WG4); if (warp < DPRE) refill2(IC<3>{}); }
            }
            while ((int)(clk() - c0) < ARDELAY);
#pragma unroll
            for (int i = 0; i < 3; i++) w[i] = ld_rlx(xat(i));
            if (warp < 5 && !(NOWIN & 8) && elect()) {
                if (DPOST) while ((int)(clk() - c0) < ARDELAY + DPOST);
                if (warp >= DPRE) issue_v(IC<3>{}, 0);
                if (warp < 4 && !P2LATE) issue_v(IC<2>{}, 4);
            }
            __syncwarp();
            fx2_wait<3, true>(xat, w, sb + SM_MSQ, inv, x2);
            TSTAMP(9);
            q_proj(L, x2, pst);
            pass2();
            out_proj(L);
            if (warp >= 5) {
                bar_arrive(0, 256);
                if ((W1AT1 == 6 || W2AT1 == 6) && warp == 5 && elect()) { if (W1AT1 == 6) issue_w(L, 0); if (W2AT1 == 6) issue_w(L, 1); }
                TDUMP();
                return;
            }
            mlp_part(L);
            u64 old[2];
            auto add = [&]() {
#pragma unroll
                for (int k = 0; k < 2; k++) asm volatile("atom.relaxed.gpu.global.add.u64 %0, [%1], %2;" : "=l"(old[k]) : "l"(rap + k * 40 * ACC_PITCH), "l"(yw[k]) : "memory");
            };
            add();
            uint32_t* op = reinterpret_cast<uint32_t*>(P.out) + 2 * c4();
            if (wide) { send_wide(); add(); }
            TSTAMP(18);
            CSTAMP(17, hi32(yw[1]));
            const float inv2 = fx2_inv(msq);
            const uint32_t ep1 = lds32(sb + SM_EPOCH) + 1;
            CSTAMP(18, lo32(old[0]) ^ lo32(old[1]));
#pragma unroll
            for (int k = 0; k < 2; k++) {
                yw[k] += old[k];
                asm volatile("{\n.reg .pred p;\nsetp.eq.u32 p, %2, 96;\n@p st.global.u32 [%0], %1;\n}"
                             :: "l"(op + k), "r"(pack_bf(fx2_lo(yw[k], inv2), fx2_hi(yw[k], inv2))), "r"(lo32(yw[k]) & 511) : "memory");
            }
            if ((lo32(yw[0]) & 255) == 96 && tid == 0) g_epoch = ep1;
            if ((lo32(yw[0]) | lo32(yw[1])) & 256) {
                __threadfence();
#pragma unroll 1
                for (int k = 0; k < 2; k++, yw[0] = yw[1]) if ((lo32(yw[0]) & 511) == 256 + 96) op[k] = fx2_wide(rap + k * 40 * ACC_PITCH, yw[0], msq);
            }
            TSTAMP(19);
            CSTAMP(19, lo32(yw[1]));
            TDUMP();
        }
    }
}

typedef CUresult (*EncodeFn)(CUtensorMap*, CUtensorMapDataType, cuuint32_t, void*, const cuuint64_t*, const cuuint64_t*, const cuuint32_t*,
                             const cuuint32_t*, CUtensorMapInterleave, CUtensorMapSwizzle, CUtensorMapL2promotion, CUtensorMapFloatOOBfill);

}

extern "C" void kernel_launch(void* const* d_in, const int* in_sizes, int n_in, void* d_out, int out_size) {
    (void)in_sizes; (void)n_in; (void)out_size;
    static EncodeFn enc = nullptr;
    if (!enc) {
        void* fn = nullptr;
        cudaDriverEntryPointQueryResult qr;
        cudaGetDriverEntryPoint("cuTensorMapEncodeTiled", &fn, cudaEnableDefault, &qr);
        enc = (EncodeFn)fn;
        cudaFuncSetAttribute(fused_kernel, cudaFuncAttributeMaxDynamicSharedMemorySize, SM_TOTAL);
    }
    Params P = {};
    auto map3 = [&](int m, int in, cuuint64_t d0, cuuint64_t d1, cuuint64_t d2, cuuint64_t s1, cuuint64_t s2, cuuint32_t b0, cuuint32_t b1, cuuint32_t b2,
                    CUtensorMapSwizzle sw, int promo) {
        const cuuint64_t dim[3] = {d0, d1, d2}, str[2] = {s1, s2};
        const cuuint32_t box[3] = {b0, b1, b2}, ones[3] = {1, 1, 1};
        enc(&P.tm[m], CU_TENSOR_MAP_DATA_TYPE_BFLOAT16, 3, d_in[in], dim, str, box, ones, CU_TENSOR_MAP_INTERLEAVE_NONE, sw, (CUtensorMapL2promotion)promo,
            CU_TENSOR_MAP_FLOAT_OOB_FILL_NONE);
    };
    map3(TM_KH, 1, 64, 3, NHEAD * SK, 128, DH * 2, 64, 3, 32, CU_TENSOR_MAP_SWIZZLE_128B, 0);
    map3(TM_VH, 2, 64, 3, NHEAD * SK, 128, DH * 2, 64, 3, 32, CU_TENSOR_MAP_SWIZZLE_128B, 0);
    map3(TM_VP, 2, 64, 3, NHEAD * SK, 128, DH * 2, PFW, 3, 32, CU_TENSOR_MAP_SWIZZLE_NONE, 0);
    map3(TM_V, 2, 64, 3, NHEAD * SK, 128, DH * 2, 64, 3, 8, CU_TENSOR_MAP_SWIZZLE_128B, 0);
    map3(TM_WO, 4, 32, 20, NHEAD * DH, 64, D_MODEL * 2, 32, 1, DH, CU_TENSOR_MAP_SWIZZLE_64B, PROMOW);
    map3(TM_WOP, 4, 32, 20, NHEAD * DH, 64, D_MODEL * 2, PFW, 1, DH, CU_TENSOR_MAP_SWIZZLE_NONE, 0);
    map3(TM_WQ, 3, 64, NHEAD * 3, D_MODEL, 128, NHEAD * DH * 2, 64, 3, 8, CU_TENSOR_MAP_SWIZZLE_128B, 0);
    map3(TM_W1, 6, DFF, 128, 5, DFF * 2, DFF * 256, 16, 128, 5, CU_TENSOR_MAP_SWIZZLE_32B, PROMO1);
    map3(TM_W2, 8, 64, 10, DFF, 128, D_MODEL * 2, 64, 10, 16, CU_TENSOR_MAP_SWIZZLE_128B, 0);
    P.x = (const __nv_bfloat16*)d_in[0];
    P.k = (const __nv_bfloat16*)d_in[1];
    P.b1 = (const __nv_bfloat16*)d_in[7];
    P.b2 = (const __nv_bfloat16*)d_in[9];
    P.out = (__nv_bfloat16*)d_out;
    for (int i = 0; i < 64; i++) P.tile[i] = make_uint4(SCH.tile[i][0], SCH.tile[i][1], SCH.tile[i][2], 0);
    fused_kernel<<<NCTA + 1, NTHR, SM_TOTAL, cudaStreamPerThread>>>(P);
}
```

```cpp
#include <cuda_runtime.h>
#include <cuda_bf16.h>
#include <cuda.h>
#include <stdint.h>

namespace {

constexpr int D_MODEL = 640, NHEAD = 32, SK = 32768, DH = 192, WIN = 4096, DFF = 1536;
constexpr int NCTA = 128, NTHR = 256;
constexpr int TILE = 64 * DH * 2;
constexpr int HALF = TILE / 2;
constexpr int SUB = 8 * DH * 2;
constexpr int SM_RING = 4 * TILE;
constexpr int SM_W2 = SM_RING + 20480, SM_W1 = SM_W2 + 20480;
constexpr int SM_WQR = 6 * TILE + HALF, SM_WQ = 7 * TILE;
constexpr int SM_PART = 9 * TILE;
constexpr int SM_EXC = SM_PART + 6144;
constexpr int SM_SC = SM_EXC + 1024;
constexpr int SM_BAR = SM_SC + 1024;
constexpr int SM_VEC = SM_BAR + 768;
constexpr int SM_CS = SM_VEC + 384;
constexpr int SM_FAC = SM_CS + 768;
constexpr int SM_ML = SM_FAC + 32;
constexpr int SM_B1 = SM_ML + 64;
constexpr int SM_STAT = SM_B1 + 64;
constexpr int NCB = 27;
constexpr int CB_WO = 18, CB_W1 = 23, CB_W2 = 24, CB_SNAP = 25, CB_REL = 26;
constexpr int SM_CBAR = SM_STAT + 40;
constexpr int SM_CNT = SM_CBAR + NCB * 8;
constexpr int SM_EPOCH = SM_CNT + NCB * 8;
constexpr int SM_FXS = SM_EPOCH + 4;
constexpr int SM_T0 = SM_FXS + 4;
constexpr int SM_MSQ = SM_T0 + 4;
constexpr int SM_M1 = SM_MSQ + 4;
constexpr int SM_TS = SM_M1 + 4;
constexpr int SM_TOTAL = 232448;
static_assert(SM_TS + 320 <= SM_TOTAL, "smem");
constexpr int NEXC = 16;

constexpr int SPIN = 1 << 20;
enum { TM_KH = 0, TM_VH = 1, TM_WO = 2, TM_VP = 3, TM_WOP = 4, TM_V = 5, TM_WQ = 6, TM_W1 = 7, TM_W2 = 8 };
constexpr uint32_t POL_NORMAL = 0x16F00000u, POL_FIRST = 0x12F00000u;

#define PACE 980
#define PACE0 1600
#define NI0 1
#define NI1 6
#define ETRIG 0x54321000
#define LATEAT 5
#define HWAT 11
#define PFREE 66
#define W1AT0 3
#define W1AT1 3
#define AR1D 300
#define LAG0 12
#define NMMA 2
#define M1AT 1
#define M1P 3
#define NWO1 4
#define WG2 90
#define WG3 120
#define WD4 250
#define WG4 70
#define NWQ1 0
#define P4AT 0
#define P2LATE 0
#define RWAT 1
#define W2AT1 6
#define PCD 150
#define NOWIN 0
#define DPRE 0
#define DPOST 200
#define NIM 4
#define PACES PACE0
#define JP2 54
#define PACE2 0
#define WD2 0
#define W2PRE 2
#define OPOLL1 2
#define SNAPAT 1
#define DMASK 0x1
#define WOKEEP 0x1f
#define VORD2 0x6758493a2b1cd0efull
#define VTRIG 0xba73210
#define WOAT 13
#define PARKS 0x95
#define VSLOT 0x1087654321087654ull
#define OPOLL 2
#define S0EARLY 0
#define NPRE 2
#define ARDELAY 1000
#define QDELAY 0
#define CMAP 0
#define PFW 8u
#define PUBAT 27
#define HW0 29
#define HW1 31
#define FX2LIM 524288.f
#define PROMOW 2
#define PROMO1 0
#define WD1 300
#define WG1 140
#define WPOL POL_NORMAL

constexpr uint32_t G_A = 1u << 28, G_B = 1u << 29, G_C = 1u << 30;
__host__ __device__ constexpr int ring_hs(int j) { return (j + 4) % 5; }
__host__ __device__ constexpr uint32_t load_word(int j) {
    if (j >= 64) return (uint32_t)(j - 64) << 20 | (SM_RING + ring_hs(j) * HALF) | TM_WO << 8 | (CB_WO + j - 64) << 3 | 2 | !(WOKEEP >> (j - 64) & 1);
    const int e = j >> 1, isv = e >= 16, unit = e & 15;
    return (uint32_t)(unit * 256 + (j & 1) * 32) << 20 | (j < 8 ? j * HALF : SM_RING + ring_hs(j) * HALF) | isv << 8 | (j < 8 ? 10 + j : (j - 8) % 10) << 3 | 2
           | (!isv || (DMASK >> unit & 1));
}
__host__ __device__ constexpr int popc(int v) { return v ? (v & 1) + popc(v >> 1) : 0; }
constexpr int NPARK = popc(PARKS);
constexpr int SM_SNAP = SM_RING + ring_hs(12) * HALF, SM_CSP = SM_RING + ring_hs(11) * HALF;
struct Step { int unit, slot, par, next, mma0, nmma; };
struct Sched { uint32_t tile[64][3]; Step st[16]; };
constexpr Sched make_sched() {
    Sched s{};
    for (int j = 0; j < 64; j++) {
        const int e = j >> 1;
        const uint32_t d = load_word(j);
        uint32_t w = (uint32_t)(j < 8 ? 0 : (j - 8) / 10 & 1) << 31 | (e & 15) * 4 << 20 | ((d & 0x3f000) - (j & 1) * HALF) | (d & 0xf8);
        if (e == PUBAT || e == SNAPAT) w |= G_A;
        if (e == HW0 || e == 4) w |= G_B;
        if ((e >= LATEAT && e < LATEAT + 4) || e == HW1) w |= G_C;
        s.tile[j][0] = w;
    }
    for (int j = NI1; j < 69; j++) {
        if (j == 12) continue;
        const int at = j < 12 ? (ETRIG >> (4 * (j - 4)) & 15) : j - 5;
        s.tile[at][1] = load_word(j);
        s.tile[at][2] = j >= PFREE ? 0 : PACE0 + j * PACE / 2 + (j > JP2 ? (j - JP2) * PACE2 : 0);
    }
    int done = 0;
    for (int p = 0; p < 16; p++) {
        Step& c = s.st[p];
        c.unit = (int)(VORD2 >> (4 * p) & 15); c.slot = (int)(VSLOT >> (4 * p) & 15); c.par = p >= 9; c.next = -1;
        c.mma0 = done;
        if (p >= NPARK) { const int avail = p - done + (p >= LAG0); c.nmma = p == 15 ? 16 - done : (avail < NMMA ? avail : NMMA); done += c.nmma; }
    }
    for (int p = 9; p < 16; p++) s.st[VTRIG >> (4 * (p - 9)) & 15].next = p;
    return s;
}
constexpr Sched SCH = make_sched();
__host__ __device__ constexpr int kunit(int o) { return o < 5 ? o + 11 : o == 5 ? 10 : o - 6; }

template <int I> struct IC { static constexpr int value = I; };
template <uint32_t I> struct UC { static constexpr uint32_t value = I; };
template <int A, int B, class F> __device__ __forceinline__ void static_for(F&& f) {
    if constexpr (A < B) { f(IC<A>{}); static_for<A + 1, B>(f); }
}

struct Params {
    CUtensorMap tm[9];
    const __nv_bfloat16 *x, *k, *b1, *b2;
    __nv_bfloat16* out;
    uint4 tile[66];
};

typedef unsigned long long u64;
constexpr int ACC_PITCH = 256;
constexpr int ACC_BYTES = 80 * ACC_PITCH;
__device__ __align__(1024) unsigned char g_acc[4 * ACC_BYTES];
__device__ __align__(1024) u64 g_l0[NCTA][384];
__device__ __align__(1024) u64 g_ll[2][NCTA][256];
__device__ unsigned g_epoch;
__device__ __align__(128) unsigned g_zflag;
#define TSTAMP(i)
#define TSTAMP2(i)
#define TSTAMPL(i)
#define TDUMP()
#define CSTAMP(i, x)
#define TRACE(i)

__device__ __forceinline__ void mbar_wait(uint32_t bar, uint32_t parity) {
    asm volatile("{\n.reg .pred p, q;\n.reg .u32 n;\nmov.u32 n, 0;\n"
                 "LOOP:\nmbarrier.try_wait.parity.shared::cta.b64 p, [%0], %1;\n"
                 "add.u32 n, n, 1;\nsetp.lt.and.u32 q, n, 0x100000, !p;\n@q bra.uni LOOP;\n}"
                 :: "r"(bar), "r"(parity) : "memory");
}
__device__ __forceinline__ bool mbar_test(uint32_t bar, uint32_t parity) {
    uint32_t r;
    asm volatile("{\n.reg .pred p;\nmbarrier.test_wait.parity.shared::cta.b64 p, [%1], %2;\nselp.u32 %0, 1, 0, p;\n}" : "=r"(r) : "r"(bar), "r"(parity) : "memory");
    return __all_sync(~0u, r);
}
__device__ __forceinline__ bool elect() {
    uint32_t r;
    asm volatile("{\n.reg .pred p;\nelect.sync _|p, 0xffffffff;\nselp.u32 %0, 1, 0, p;\n}" : "=r"(r));
    return r != 0;
}
__device__ __forceinline__ void mbar_expect(uint32_t bar, uint32_t bytes) {
    asm volatile("mbarrier.arrive.expect_tx.shared::cta.b64 _, [%0], %1;" :: "r"(bar), "r"(bytes) : "memory");
}
__device__ __forceinline__ uint4 lds128(uint32_t a) {
    uint4 v; asm volatile("ld.shared.v4.u32 {%0,%1,%2,%3}, [%4];" : "=r"(v.x), "=r"(v.y), "=r"(v.z), "=r"(v.w) : "r"(a) : "memory"); return v;
}
__device__ __forceinline__ uint4 ldsm_t(uint32_t a) {
    uint4 v; asm volatile("ldmatrix.sync.aligned.m8n8.x4.trans.shared.b16 {%0,%1,%2,%3}, [%4];" : "=r"(v.x), "=r"(v.y), "=r"(v.z), "=r"(v.w) : "r"(a) : "memory"); return v;
}
__device__ __forceinline__ uint2 lds64(uint32_t a) {
    uint2 v; asm volatile("ld.shared.v2.u32 {%0,%1}, [%2];" : "=r"(v.x), "=r"(v.y) : "r"(a) : "memory"); return v;
}
__device__ __forceinline__ float2 lds64f(uint32_t a) { const uint2 v = lds64(a); return make_float2(__uint_as_float(v.x), __uint_as_float(v.y)); }
__device__ __forceinline__ uint32_t lds32(uint32_t a) {
    uint32_t v; asm volatile("ld.shared.u32 %0, [%1];" : "=r"(v) : "r"(a) : "memory"); return v;
}
__device__ __forceinline__ float ldsf(uint32_t a) { return __uint_as_float(lds32(a)); }
__device__ __forceinline__ void sts32(uint32_t a, uint32_t v) { asm volatile("st.shared.u32 [%0], %1;" :: "r"(a), "r"(v) : "memory"); }
__device__ __forceinline__ void stsf(uint32_t a, float v) { sts32(a, __float_as_uint(v)); }
__device__ __forceinline__ void sts16(uint32_t a, uint32_t v) { asm volatile("st.shared.u16 [%0], %1;" :: "r"(a), "h"((uint16_t)v) : "memory"); }
__device__ __forceinline__ void sts64(uint32_t a, uint32_t x, uint32_t y) { asm volatile("st.shared.v2.u32 [%0], {%1,%2};" :: "r"(a), "r"(x), "r"(y) : "memory"); }
__device__ __forceinline__ void sts64f(uint32_t a, float x, float y) { sts64(a, __float_as_uint(x), __float_as_uint(y)); }
__device__ __forceinline__ void sts128f(uint32_t a, float x, float y, float z, float w) {
    asm volatile("st.shared.v4.f32 [%0], {%1,%2,%3,%4};" :: "r"(a), "f"(x), "f"(y), "f"(z), "f"(w) : "memory");
}
__device__ __forceinline__ void mma(float (&c)[4], const uint4& a, uint32_t b0, uint32_t b1) {
    asm volatile("mma.sync.aligned.m16n8k16.row.col.f32.bf16.bf16.f32 {%0,%1,%2,%3}, {%4,%5,%6,%7}, {%8,%9}, {%0,%1,%2,%3};"
                 : "+f"(c[0]), "+f"(c[1]), "+f"(c[2]), "+f"(c[3]) : "r"(a.x), "r"(a.y), "r"(a.z), "r"(a.w), "r"(b0), "r"(b1));
}
__device__ __forceinline__ u64 ld_rlx(const void* p) {
    u64 a; asm volatile("ld.relaxed.gpu.global.u64 %0, [%1];" : "=l"(a) : "l"(p) : "memory"); return a;
}
__device__ __forceinline__ void ld_rlx2(const void* p, u64& a, u64& b) {
    asm volatile("ld.relaxed.gpu.global.v2.u64 {%0,%1}, [%2];" : "=l"(a), "=l"(b) : "l"(p) : "memory");
}
__device__ __forceinline__ void st_rlx(void* p, u64 a) { asm volatile("st.relaxed.gpu.global.u64 [%0], %1;" :: "l"(p), "l"(a) : "memory"); }
__device__ __forceinline__ u64 ll_pack(float v, uint32_t tag) { return ((u64)tag << 32) | __float_as_uint(v); }
__device__ __forceinline__ float ll_val(u64 w) { return __uint_as_float((uint32_t)w); }
__device__ __forceinline__ uint32_t ll_tag(u64 w) { return (uint32_t)(w >> 32); }
__device__ __forceinline__ float bf_lo(uint32_t u) { return __uint_as_float(u << 16); }
__device__ __forceinline__ float bf_hi(uint32_t u) { return __uint_as_float(u & 0xffff0000u); }
__device__ __forceinline__ uint32_t pack_bf(float lo, float hi) {
    uint32_t r; asm("cvt.rn.bf16x2.f32 %0, %1, %2;" : "=r"(r) : "f"(hi), "f"(lo)); return r;
}
__device__ __forceinline__ float ex2(float v) { float r; asm("ex2.approx.ftz.f32 %0, %1;" : "=f"(r) : "f"(v)); return r; }
__device__ __forceinline__ float rcp(float v) { float r; asm("rcp.approx.ftz.f32 %0, %1;" : "=f"(r) : "f"(v)); return r; }
__device__ __forceinline__ float rsq(float v) { float r; asm("rsqrt.approx.ftz.f32 %0, %1;" : "=f"(r) : "f"(v)); return r; }
__device__ __forceinline__ void bar_sync(int id, int n) { asm volatile("bar.sync %0, %1;" :: "r"(id), "r"(n) : "memory"); }
__device__ __forceinline__ uint32_t clk() { uint32_t c; asm volatile("mov.u32 %0, %clock;" : "=r"(c)); return c; }
__device__ __forceinline__ uint32_t pin(uint32_t v) { return __shfl_xor_sync(~0u, v, 0); }
__device__ __forceinline__ float shx(float v, int o) { return __shfl_xor_sync(~0u, v, o); }

__device__ __forceinline__ u64 fx_pack(float v, float scale) { return ((u64)__float2ll_rn(v * scale) & ~255ull) | 1ull; }
__device__ __forceinline__ float fx_scale(float meansq) {
    const int e = max(((int)(__float_as_uint(meansq) >> 23) - 127) >> 1, -6);
    return __uint_as_float((uint32_t)(127 + 32 - e) << 23);
}
__device__ __forceinline__ float fx_inv(float scale) { return __uint_as_float((254u << 23) - __float_as_uint(scale)); }
__device__ __forceinline__ uint32_t lo32(u64 w) { uint32_t l; asm("mov.b64 {%0, _}, %1;" : "=r"(l) : "l"(w)); return l; }
__device__ __forceinline__ int hi32(u64 w) { int h; asm("mov.b64 {_, %0}, %1;" : "=r"(h) : "l"(w)); return h; }
__device__ __forceinline__ float fx_val(u64 w) { return (float)hi32(w) * 4294967296.f + (float)lo32(w); }
constexpr float FX2_ONE = 12582912.f;
__device__ __forceinline__ float fx2_scale(float meansq) { return __uint_as_float((uint32_t)(127 + 16 - max(((int)(__float_as_uint(meansq) >> 23) - 127) >> 1, -100)) << 23); }
__device__ __forceinline__ u64 fx2_pack(float a, float b) {
    const uint32_t lo = __float_as_uint(a) * 512u + (1u - 0x4b400000u * 512u);
    return lo | (u64)(__float_as_uint(b) * 16u - 0x4b400000u * 16u + (uint32_t)((int)lo >> 31)) << 32;
}
__device__ __forceinline__ float fx2_lo(u64 w, float inv) { return (float)(int)(__funnelshift_r(lo32(w), hi32(w), 4) & ~31u) * (inv * 0.5f); }
__device__ __forceinline__ float fx2_hi(u64 w, float inv) { return (float)((hi32(w) + 8) & ~15) * inv; }
__device__ __forceinline__ float fx2_inv(float meansq) { return fx_inv(fx2_scale(meansq)) * 0.0625f; }
__device__ __forceinline__ uint32_t fx2_wide(const unsigned char* a, u64 w, float meansq) {
    const float inv = fx_inv(fx_scale(meansq));
    return pack_bf(fx2_lo(w, fx2_inv(meansq)) + fx_val(ld_rlx(a + 64)) * inv, fx2_hi(w, fx2_inv(meansq)) + fx_val(ld_rlx(a + 96)) * inv);
}
template <int N, bool LOOK, class A> __device__ __forceinline__ void fx2_wait(A a, u64 (&w)[N], uint32_t msqa, float inv, uint32_t (&x)[N]) {
    int it = 0;
    uint32_t miss = lds32(msqa + 4);
    do {
        if (__all_sync(~0u, !(miss & 96))) {
            __threadfence();
#pragma unroll
            for (int i = 0; i < N; i++) x[i] = 0;
#pragma unroll 1
            for (int i = 0; i < 2 * N; i++) {
                const u64 v = ld_rlx(a(i >> 1));
                const float y = ((i & 1) ? fx2_hi(v, inv) : fx2_lo(v, inv)) + fx_val(ld_rlx(a(i >> 1) + 64 + (i & 1) * 32)) * fx_inv(fx_scale(ldsf(msqa)));
#pragma unroll
                for (int k = 0; k < N; k++) x[k] = __funnelshift_r(x[k], k + 1 < N ? x[k + 1] : pack_bf(y, y), 16);
            }
            return;
        }
        if (!LOOK || it) {
#pragma unroll
            for (int i = 0; i < N; i++) w[i] = ld_rlx(a(i));
        }
        uint32_t all = lo32(w[0]), any = all;
#pragma unroll
        for (int i = 1; i < N; i++) { all &= lo32(w[i]); any |= lo32(w[i]); }
        miss = (~all & 96) | (any & 256);
    } while (__any_sync(~0u, miss) & (++it < SPIN));
#pragma unroll
    for (int i = 0; i < N; i++) x[i] = pack_bf(fx2_lo(w[i], inv), fx2_hi(w[i], inv));
}
__device__ __forceinline__ void st_rlx_if(bool p, void* a, u64 v) {
    asm volatile("{\n.reg .pred p;\nsetp.ne.u32 p, %2, 0;\n@p st.relaxed.gpu.global.u64 [%0], %1;\n}" :: "l"(a), "l"(v), "r"((uint32_t)p) : "memory");
}
__device__ __forceinline__ void sts128f(uint32_t a, const float (&v)[4]) { sts128f(a, v[0], v[1], v[2], v[3]); }
__device__ __forceinline__ void bar_arrive(int id, int n) { asm volatile("bar.arrive %0, %1;" :: "r"(id), "r"(n) : "memory"); }
template <class T> __device__ __forceinline__ T* pin(T* p) { return reinterpret_cast<T*>(__shfl_xor_sync(~0u, (u64)p, 0)); }

__device__ __forceinline__ void tma3(uint32_t dst, const CUtensorMap* tm, int c1, int c2, uint32_t bar, uint32_t pol) {
    asm volatile("cp.async.bulk.tensor.3d.shared::cluster.global.mbarrier::complete_tx::bytes.L2::cache_hint [%0], [%1, {%2, %3, %4}], [%5], %6;"
                 :: "r"(dst), "l"(tm), "r"(0), "r"(c1), "r"(c2), "r"(bar), "l"((u64)pol << 32) : "memory");
}
__device__ __forceinline__ void tma3_pf(const CUtensorMap* tm, int c1, int c2, uint32_t pol) {
    asm volatile("cp.async.bulk.prefetch.tensor.3d.L2.global.tile.L2::cache_hint [%0, {%1, %2, %3}], %4;"
                 :: "l"(tm), "r"(0), "r"(c1), "r"(c2), "l"((u64)pol << 32) : "memory");
}
__device__ __forceinline__ void issue_half(uint32_t d, uint32_t sb, int rowc, int cta, const CUtensorMap* tm0) {
    const uint32_t bar = sb + SM_CBAR + (d & 0xf8);
    const CUtensorMap* tm = tm0 + ((d >> 8) & 3);
    const int c1 = (d & 0x200) ? (cta & 3) + 4 * (d >> 20) : 0, c2 = (d & 0x200) ? (cta >> 2) * DH : rowc + (d >> 20);
    mbar_expect(bar, HALF);
    tma3(sb + (d & 0x3f000), tm, c1, c2, bar, POL_FIRST);
    if (!(d & 1)) tma3_pf(tm + 2, c1, c2, POL_NORMAL);
}
__device__ __forceinline__ uint32_t cnt_inc(uint32_t a, uint32_t last) {
    uint32_t old; asm volatile("atom.relaxed.cta.shared.inc.u32 %0, [%1], %2;" : "=r"(old) : "r"(a), "r"(last) : "memory"); return old;
}
__device__ __forceinline__ void wait_until(uint32_t due) {
#pragma unroll 1
    for (int it = 0; it < 4096; it++) { uint32_t now; asm volatile("mov.u32 %0, %globaltimer_lo;" : "=r"(now)); if ((int)(now - due) >= 0) break; }
}
__device__ __forceinline__ uint32_t bf2_mul(uint32_t a, uint32_t b) { uint32_t r; asm("mul.rn.bf16x2 %0, %1, %2;" : "=r"(r) : "r"(a), "r"(b)); return r; }
__device__ __forceinline__ uint32_t bf2_fma(uint32_t a, uint32_t b, uint32_t c) { uint32_t r; asm("fma.rn.bf16x2 %0, %1, %2, %3;" : "=r"(r) : "r"(a), "r"(b), "r"(c)); return r; }
__device__ __forceinline__ uint32_t bf2_amax(uint32_t a, uint32_t b) { uint32_t r; asm("max.NaN.xorsign.abs.bf16x2 %0, %1, %2;" : "=r"(r) : "r"(a), "r"(b)); return r; }
__device__ __forceinline__ uint4 k_unpack(uint32_t l0, uint32_t l1, uint32_t h, uint32_t m1) {
    const uint32_t ha = h & 0x87878787u, hc = ha * m1 + h, hb = __funnelshift_l(hc, hc, 4);
    return make_uint4(__byte_perm(l0, ha, 0x5140), __byte_perm(l0, ha, 0x7362), __byte_perm(l1, hb, 0x5140), __byte_perm(l1, hb, 0x7362));
}
#define KR4(u, i) "+r"(kr[u][i].x), "+r"(kr[u][i].y), "+r"(kr[u][i].z), "+r"(kr[u][i].w)
#define KR6(u) KR4(u, 0), KR4(u, 1), KR4(u, 2), KR4(u, 3), KR4(u, 4), KR4(u, 5)
__device__ __forceinline__ void k_keep(uint4 (&kr)[8][6], const uint32_t (&c)[18], int e, uint32_t a) {
    asm volatile("{\nKT: .branchtargets K0, K1, K2, K3, K4, K5, K6, K7, K8, K9, K10, K11, K12, K13, K14, K15;\nbrx.idx.uni %210, KT;\n"
                 "K0: mov.b32 %12, %192; mov.b32 %13, %193; mov.b32 %14, %194; mov.b32 %15, %195; mov.b32 %16, %196; mov.b32 %17, %197; mov.b32 %18, %198; mov.b32 %19, %199; mov.b32 %20, %200; mov.b32 %21, %201; mov.b32 %22, %202; mov.b32 %23, %203; mov.b32 %24, %204; mov.b32 %25, %205; mov.b32 %26, %206; mov.b32 %27, %207; mov.b32 %28, %208; mov.b32 %29, %209; bra.uni KE;\n"
                 "K1: mov.b32 %30, %192; mov.b32 %31, %193; mov.b32 %32, %194; mov.b32 %33, %195; mov.b32 %34, %196; mov.b32 %35, %197; mov.b32 %36, %198; mov.b32 %37, %199; mov.b32 %38, %200; mov.b32 %39, %201; mov.b32 %40, %202; mov.b32 %41, %203; mov.b32 %42, %204; mov.b32 %43, %205; mov.b32 %44, %206; mov.b32 %45, %207; mov.b32 %46, %208; mov.b32 %47, %209; bra.uni KE;\n"
                 "K2: mov.b32 %48, %192; mov.b32 %49, %193; mov.b32 %50, %194; mov.b32 %51, %195; mov.b32 %52, %196; mov.b32 %53, %197; mov.b32 %54, %198; mov.b32 %55, %199; mov.b32 %56, %200; mov.b32 %57, %201; mov.b32 %58, %202; mov.b32 %59, %203; mov.b32 %60, %204; mov.b32 %61, %205; mov.b32 %62, %206; mov.b32 %63, %207; mov.b32 %64, %208; mov.b32 %65, %209; bra.uni KE;\n"
                 "K3: mov.b32 %66, %192; mov.b32 %67, %193; mov.b32 %68, %194; mov.b32 %69, %195; mov.b32 %70, %196; mov.b32 %71, %197; mov.b32 %72, %198; mov.b32 %73, %199; mov.b32 %74, %200; mov.b32 %75, %201; mov.b32 %76, %202; mov.b32 %77, %203; mov.b32 %78, %204; mov.b32 %79, %205; mov.b32 %80, %206; mov.b32 %81, %207; mov.b32 %82, %208; mov.b32 %83, %209; bra.uni KE;\n"
                 "K4: mov.b32 %84, %192; mov.b32 %85, %193; mov.b32 %86, %194; mov.b32 %87, %195; mov.b32 %88, %196; mov.b32 %89, %197; mov.b32 %90, %198; mov.b32 %91, %199; mov.b32 %92, %200; mov.b32 %93, %201; mov.b32 %94, %202; mov.b32 %95, %203; mov.b32 %96, %204; mov.b32 %97, %205; mov.b32 %98, %206; mov.b32 %99, %207; mov.b32 %100, %208; mov.b32 %101, %209; bra.uni KE;\n"
                 "K5: mov.b32 %102, %192; mov.b32 %103, %193; mov.b32 %104, %194; mov.b32 %105, %195; mov.b32 %106, %196; mov.b32 %107, %197; mov.b32 %108, %198; mov.b32 %109, %199; mov.b32 %110, %200; mov.b32 %111, %201; mov.b32 %112, %202; mov.b32 %113, %203; mov.b32 %114, %204; mov.b32 %115, %205; mov.b32 %116, %206; mov.b32 %117, %207; mov.b32 %118, %208; mov.b32 %119, %209; bra.uni KE;\n"
                 "K6: mov.b32 %120, %192; mov.b32 %121, %193; mov.b32 %122, %194; mov.b32 %123, %195; mov.b32 %124, %196; mov.b32 %125, %197; mov.b32 %126, %198; mov.b32 %127, %199; mov.b32 %128, %200; mov.b32 %129, %201; mov.b32 %130, %202; mov.b32 %131, %203; mov.b32 %132, %204; mov.b32 %133, %205; mov.b32 %134, %206; mov.b32 %135, %207; mov.b32 %136, %208; mov.b32 %137, %209; bra.uni KE;\n"
                 "K7: mov.b32 %138, %192; mov.b32 %139, %193; mov.b32 %140, %194; mov.b32 %141, %195; mov.b32 %142, %196; mov.b32 %143, %197; mov.b32 %144, %198; mov.b32 %145, %199; mov.b32 %146, %200; mov.b32 %147, %201; mov.b32 %148, %202; mov.b32 %149, %203; mov.b32 %150, %204; mov.b32 %151, %205; mov.b32 %152, %206; mov.b32 %153, %207; mov.b32 %154, %208; mov.b32 %155, %209; bra.uni KE;\n"
                 "K8: mov.b32 %156, %192; mov.b32 %157, %193; mov.b32 %158, %194; mov.b32 %159, %195; mov.b32 %160, %196; mov.b32 %161, %197; mov.b32 %162, %198; mov.b32 %163, %199; mov.b32 %164, %200; mov.b32 %165, %201; mov.b32 %166, %202; mov.b32 %167, %203; mov.b32 %168, %204; mov.b32 %169, %205; mov.b32 %170, %206; mov.b32 %171, %207; mov.b32 %172, %208; mov.b32 %173, %209; bra.uni KE;\n"
                 "K9: mov.b32 %174, %192; mov.b32 %175, %193; mov.b32 %176, %194; mov.b32 %177, %195; mov.b32 %178, %196; mov.b32 %179, %197; mov.b32 %180, %198; mov.b32 %181, %199; mov.b32 %182, %200; mov.b32 %183, %201; mov.b32 %184, %202; mov.b32 %185, %203; mov.b32 %186, %204; mov.b32 %187, %205; mov.b32 %188, %206; mov.b32 %189, %207; mov.b32 %190, %208; mov.b32 %191, %209; bra.uni KE;\n"
                 "K10: st.shared.v2.b32 [%211+75784], {%192, %193}; st.shared.v2.b32 [%211+76288], {%194, %195}; st.shared.v2.b32 [%211+76296], {%196, %197}; mov.b32 %0, %198; mov.b32 %1, %199; mov.b32 %2, %200; mov.b32 %3, %201; mov.b32 %4, %202; mov.b32 %5, %203; mov.b32 %6, %204; mov.b32 %7, %205; mov.b32 %8, %206; mov.b32 %9, %207; mov.b32 %10, %208; mov.b32 %11, %209; bra.uni KE;\n"
                 "K11: st.shared.v2.b32 [%211+0], {%192, %193}; st.shared.v2.b32 [%211+8], {%194, %195}; st.shared.v2.b32 [%211+512], {%196, %197}; st.shared.v2.b32 [%211+520], {%198, %199}; st.shared.v2.b32 [%211+1024], {%200, %201}; st.shared.v2.b32 [%211+1032], {%202, %203}; st.shared.v2.b32 [%211+1536], {%204, %205}; st.shared.v2.b32 [%211+1544], {%206, %207}; st.shared.v2.b32 [%211+2048], {%208, %209}; bra.uni KE;\n"
                 "K12: st.shared.v2.b32 [%211+2056], {%192, %193}; st.shared.v2.b32 [%211+2560], {%194, %195}; st.shared.v2.b32 [%211+2568], {%196, %197}; st.shared.v2.b32 [%211+24576], {%198, %199}; st.shared.v2.b32 [%211+24584], {%200, %201}; st.shared.v2.b32 [%211+25088], {%202, %203}; st.shared.v2.b32 [%211+25096], {%204, %205}; st.shared.v2.b32 [%211+25600], {%206, %207}; st.shared.v2.b32 [%211+25608], {%208, %209}; bra.uni KE;\n"
                 "K13: st.shared.v2.b32 [%211+26112], {%192, %193}; st.shared.v2.b32 [%211+26120], {%194, %195}; st.shared.v2.b32 [%211+26624], {%196, %197}; st.shared.v2.b32 [%211+26632], {%198, %199}; st.shared.v2.b32 [%211+27136], {%200, %201}; st.shared.v2.b32 [%211+27144], {%202, %203}; st.shared.v2.b32 [%211+49152], {%204, %205}; st.shared.v2.b32 [%211+49160], {%206, %207}; st.shared.v2.b32 [%211+49664], {%208, %209}; bra.uni KE;\n"
                 "K14: st.shared.v2.b32 [%211+49672], {%192, %193}; st.shared.v2.b32 [%211+50176], {%194, %195}; st.shared.v2.b32 [%211+50184], {%196, %197}; st.shared.v2.b32 [%211+50688], {%198, %199}; st.shared.v2.b32 [%211+50696], {%200, %201}; st.shared.v2.b32 [%211+51200], {%202, %203}; st.shared.v2.b32 [%211+51208], {%204, %205}; st.shared.v2.b32 [%211+51712], {%206, %207}; st.shared.v2.b32 [%211+51720], {%208, %209}; bra.uni KE;\n"
                 "K15: st.shared.v2.b32 [%211+73728], {%192, %193}; st.shared.v2.b32 [%211+73736], {%194, %195}; st.shared.v2.b32 [%211+74240], {%196, %197}; st.shared.v2.b32 [%211+74248], {%198, %199}; st.shared.v2.b32 [%211+74752], {%200, %201}; st.shared.v2.b32 [%211+74760], {%202, %203}; st.shared.v2.b32 [%211+75264], {%204, %205}; st.shared.v2.b32 [%211+75272], {%206, %207}; st.shared.v2.b32 [%211+75776], {%208, %209}; \nKE:\n}"
                 : KR6(0), KR6(1), KR6(2), KR6(3), KR6(4), KR6(5), KR6(6), KR6(7)
                 : "r"(c[0]), "r"(c[1]), "r"(c[2]), "r"(c[3]), "r"(c[4]), "r"(c[5]), "r"(c[6]), "r"(c[7]), "r"(c[8]), "r"(c[9]), "r"(c[10]), "r"(c[11]), "r"(c[12]), "r"(c[13]), "r"(c[14]), "r"(c[15]), "r"(c[16]), "r"(c[17]), "r"(e), "r"(a) : "memory");
}
template <int K> __device__ __forceinline__ uint32_t& word(uint4& v) { if constexpr (K == 0) return v.x; else if constexpr (K == 1) return v.y; else if constexpr (K == 2) return v.z; else return v.w; }
__device__ __forceinline__ void add_if(bool p, float& d, float a, float b) {
    asm volatile("{\n.reg .pred p;\nsetp.ne.u32 p, %3, 0;\n@p add.f32 %0, %1, %2;\n}" : "+f"(d) : "f"(a), "f"(b), "r"((uint32_t)p));
}
__device__ __forceinline__ float warp_max(float v) {
#pragma unroll
    for (int o = 16; o; o >>= 1) v = fmaxf(v, shx(v, o));
    return v;
}
__device__ __forceinline__ float warp_sum(float v) {
#pragma unroll
    for (int o = 16; o; o >>= 1) v += shx(v, o);
    return v;
}
template <int PITCH> __device__ __forceinline__ void ll_look(const u64* buf, u64 (&w)[4]) {
#pragma unroll
    for (int i = 0; i < 4; i++) w[i] = ld_rlx(buf + i * PITCH);
}
template <int PITCH> __device__ __forceinline__ float ll_gather(const u64* buf, uint32_t tag, u64 (&w)[4]) {
    auto miss = [&]() { return __any_sync(~0u, ((ll_tag(w[0]) ^ tag) | (ll_tag(w[1]) ^ tag)) | ((ll_tag(w[2]) ^ tag) | (ll_tag(w[3]) ^ tag))); };
    int it = 0;
    goto check;
again:
    ll_look<PITCH>(buf, w);
check:
    if (miss() & (++it < SPIN)) goto again;
    return (ll_val(w[0]) + ll_val(w[1])) + (ll_val(w[2]) + ll_val(w[3]));
}
__device__ __forceinline__ float sum8(uint32_t a, int pitch) {
    float s[8];
#pragma unroll
    for (int w = 0; w < 8; w++) s[w] = ldsf(a + w * pitch);
    return ((s[0] + s[1]) + (s[2] + s[3])) + ((s[4] + s[5]) + (s[6] + s[7]));
}
__device__ __forceinline__ float sum5(float a, float b, float c, float d, float e) { return ((a + b) + (c + d)) + e; }
__device__ __forceinline__ float ln_part(uint2 xp, int lane) {
    const float x0 = bf_lo(xp.x), x1 = bf_hi(xp.x), x2 = bf_lo(xp.y), x3 = bf_hi(xp.y);
    const float s1 = (x0 + x1) + (x2 + x3), s2 = (x0 * x0 + x1 * x1) + (x2 * x2 + x3 * x3);
    return ((lane & 16) ? s2 : s1) + shx((lane & 16) ? s1 : s2, 16);
}
__device__ __forceinline__ float ln_rstd(float mean, float msq) { return rsq(fmaxf(msq - mean * mean, 0.f) + 1e-5f); }
constexpr float CS = 0.07216878364870322f * 1.4426950408889634f;
constexpr uint32_t ONES = 0x3f803f80u;

__global__ void __launch_bounds__(NTHR, 1) fused_kernel(const __grid_constant__ Params P) {
    extern __shared__ __align__(1024) unsigned char smem[];
    const uint32_t sb = (uint32_t)__cvta_generic_to_shared(smem);
    const int bx = blockIdx.x;
    const int cta0 = bx >= NCTA || CMAP == 0 ? bx : CMAP == 4 ? (((bx >> 1) & 7) + (bx >> 5) * 8) * 4 + ((bx >> 4) & 1) * 2 + (bx & 1)
                   : (((bx >> 1) & 15) + (bx >> 6) * 16) * 4 + ((bx >> 5) & 1) * 2 + (bx & 1);
    int id = cta0 * NTHR + threadIdx.x, tid, lane, g, t, key, warp, cta, mlp, rowc, roww, j40;
    uint32_t maskA, maskB, barw, subw, prow;
    auto fresh = [&]() {
        const int cw = __shfl_sync(~0u, id >> 5, 0);
        id = pin(id); tid = id & 255; lane = id & 31; g = lane >> 2; t = lane & 3; key = (g >> 1) + 4 * (g & 1);
        const uint32_t m = (g & 1) ? 0xffff0000u : 0x0000ffffu;
        maskA = (g & 2) ? 0u : m; maskB = (g & 2) ? m : 0u;
        warp = cw & 7; cta = cw >> 3;
        mlp = (cta & 3) == 3 ? 96 : (cta >> 2) * 3 + (cta & 3);
        rowc = (cta >> 2) * SK + (SK - WIN) + (cta & 3) * 64; roww = rowc + warp * 8;
        j40 = (cta & 3) * 40;
        barw = sb + SM_BAR + warp * 96; subw = sb + warp * SUB; prow = sb + SM_PART + warp * 768;
    };
    fresh();

    if (cta == NCTA) {
        const uint32_t ep = *(volatile unsigned*)&g_epoch;
        if (tid == 0) {
#pragma unroll 1
            for (int it = 0; it < SPIN; it++) { if (ll_tag(ld_rlx(&g_ll[0][0][192])) == ep * 4 + 2) break; __nanosleep(200); }
        }
        __syncthreads();
#pragma unroll 1
        for (int i = tid; i < 4 * 80 * 8; i += NTHR)
            *reinterpret_cast<uint4*>(g_acc + (i >> 3) * ACC_PITCH + (i & 7) * 16) = make_uint4(0, 0, 0, 0);
        __threadfence();
        __syncthreads();
        if (tid == 0) asm volatile("st.relaxed.gpu.global.u32 [%0], %1;" :: "l"(&g_zflag), "r"(ep + 1) : "memory");
        return;
    }
    TSTAMP(0);
    if (tid == 64) { uint32_t now; asm volatile("mov.u32 %0, %globaltimer_lo;" : "=r"(now)); sts32(sb + SM_T0, now); }

    const CUtensorMap* tmk = reinterpret_cast<const CUtensorMap*>(__shfl_sync(~0u, (u64)&P.tm[0] + (lane >> 5), 0));
    auto issue_first = [&](int j) {
        mbar_expect(sb + SM_CBAR + 80 + j * 8, HALF);
        tma3(sb + j * HALF, tmk + TM_KH, 0, rowc + (j >> 1) * 256 + (j & 1) * 32, sb + SM_CBAR + 80 + j * 8, POL_FIRST);
    };
    if (elect()) {
        asm volatile("mbarrier.init.shared::cta.b64 [%0], 1;" :: "r"(barw + 72));
        asm volatile("mbarrier.init.shared::cta.b64 [%0], 1;" :: "r"(sb + SM_CBAR + 64 + warp * 8));
        asm volatile("fence.proxy.async.shared::cta;" ::: "memory");
        mbar_expect(barw + 72, warp < 4 ? 3 * SUB : 2 * SUB);
        const int r0 = (cta & 3) * 160 + warp * 8;
        tma3(subw + SM_WQ, tmk + TM_WQ, (cta >> 2) * 3, r0, barw + 72, POL_FIRST);
        tma3(subw + SM_WQ + TILE, tmk + TM_WQ, (cta >> 2) * 3, r0 + 64, barw + 72, POL_FIRST);
        if (warp < 4) tma3(subw + SM_WQR, tmk + TM_WQ, (cta >> 2) * 3, r0 + 128, barw + 72, POL_FIRST);
        if (warp >= 2 && warp < NI0 + 2) issue_first(warp - 2);
#pragma unroll
        for (int i = 0; i < 9; i++) asm volatile("mbarrier.init.shared::cta.b64 [%0], 1;" :: "r"(barw + i * 8));
        asm volatile("mbarrier.init.shared::cta.b64 [%0], 1;" :: "r"(sb + SM_CBAR + warp * 8));
        asm volatile("mbarrier.init.shared::cta.b64 [%0], 1;" :: "r"(sb + SM_CBAR + 128 + warp * 8));
        if (warp < 3) asm volatile("mbarrier.init.shared::cta.b64 [%0], %1;" :: "r"(sb + SM_CBAR + 192 + warp * 8), "r"(warp == 2 ? 8 : 1));
        sts64(barw + 80, 0, 0);
        asm volatile("fence.proxy.async.shared::cta;" ::: "memory");
        asm volatile("prefetch.tensormap [%0];" :: "l"(tmk + warp + 1) : "memory");
    }
    __syncwarp();
    auto c4 = [&]() { return 32 * min(warp, 4) + 16 * (t >> 1) + 2 * g + (t & 1); };
    uint2 xp = make_uint2(0, 0);
    if (tid < 160) asm volatile("ld.global.nc.v2.u32 {%0,%1}, [%2];" : "=r"(xp.x), "=r"(xp.y) : "l"(P.x + 4 * c4()) : "memory");
    else if (tid == 255) { sts32(sb + SM_EPOCH, *(volatile unsigned*)&g_epoch); sts32(sb + SM_M1, ~0u); }
    else if (tid < 176) sts32(sb + SM_B1 + (tid - 160) * 4, (uint32_t)reinterpret_cast<const volatile unsigned short*>(P.b1)[min(mlp, 95) * 16 + tid - 160] << 16);
    else if (tid >= 192 && tid < 192 + NCB) sts32(sb + SM_CNT + (tid - 192) * 8, 0);
    unsigned char* accg = reinterpret_cast<unsigned char*>(__shfl_sync(~0u, (u64)g_acc + (lane >> 5), 0));
    auto release = [&](const uint4& tw) {
        uint32_t old;
        __syncwarp();
        asm volatile("{\n.reg .pred p;\nsetp.eq.u32 p, %2, 0;\nmov.u32 %0, 0;\n@p atom.relaxed.cta.shared.inc.u32 %0, [%1], 3;\n}"
                     : "=r"(old) : "r"(sb + SM_CNT + (tw.x & 0xf8)), "r"(lane) : "memory");
        return old;
    };
    auto refill = [&](const uint4& tw, uint32_t old) {
        if (__any_sync(~0u, old == 3 && (tw.y & 2))) {
            wait_until(lds32(sb + SM_T0) + tw.z);
            if (elect()) issue_half(tw.y, sb, rowc, cta, tmk);
            __syncwarp();
        }
    };
    __syncthreads();
    auto issue_paced = [&](int j0, int j1) {
        if (warp >= j0 && warp < j1) {
            wait_until(lds32(sb + SM_T0) + PACES + warp * PACE / 2);
            if (elect()) issue_first(warp);
            __syncwarp();
        }
    };
    issue_paced(NI0, NIM);
    mbar_wait(barw + 72, 0);

    uint32_t offV0, offV2;
    auto calc_offsets = [&]() {
        offV0 = subw + (6 * t) * 128 + ((g ^ ((6 * t) & 7)) << 4);
        offV2 = subw + (6 * t + 2) * 128 + ((g ^ ((6 * t + 2) & 7)) << 4);
    };
    calc_offsets();

    auto load_v = [&](uint4 (&v)[6], uint32_t so) {
        v[0] = lds128(offV0 + so); v[1] = lds128((offV0 ^ 16) + so + 128); v[2] = lds128(offV2 + so);
        v[3] = lds128((offV2 ^ 16) + so + 128); v[4] = lds128((offV0 ^ 64) + so + 512); v[5] = lds128((offV0 ^ 80) + so + 640);
    };
    auto issue_v = [&](auto I, int dw) {
        constexpr Step c = SCH.st[I.value];
        const uint32_t bar = barw + dw * 96 + c.slot * 8;
        mbar_expect(bar, SUB);
        tma3(subw + dw * SUB + c.slot * TILE, tmk + TM_V, 0, roww + dw * 8 + c.unit * 256, bar, POL_FIRST);
    };
    auto refill2 = [&](auto I) { __syncwarp(); if (elect()) issue_v(I, 0); };
    uint4 wq0[6], wqh[3], wq1[6];
    auto load_wq1 = [&](int i) { wq1[i] = lds128((i == 2 ? offV2 : i == 3 ? (offV2 ^ 16) + 128 : (offV0 ^ (i * 16)) + i * 128) + SM_WQ + TILE); };
    auto load_wq = [&]() {
        load_v(wq0, SM_WQ);
        const uint32_t so = SM_WQR - ((warp + 1) >> 1) * SUB;
        wqh[0] = lds128(((warp & 1) ? (offV2 ^ 16) + 128 : offV0) + so);
        wqh[1] = lds128(((warp & 1) ? (offV0 ^ 64) + 512 : (offV0 ^ 16) + 128) + so);
        wqh[2] = lds128(((warp & 1) ? (offV0 ^ 80) + 640 : offV2) + so);
#pragma unroll
        for (int i = 0; i < NWQ1; i++) load_wq1(i);
    };
    auto xcol = [&](int i, int tt) { return (i < 2 ? 64 * i + 8 * warp : 128 + 8 * (warp >> 1)) + 2 * tt; };
    uint4 kr[8][6];
    const unsigned char* rap;
    u64 rw[2];
    auto q_proj = [&](auto L, uint32_t (&p)[3], uint32_t pst) {
        if (L.value == 0 && g >= 4) p[0] = p[1] = p[2] = ONES;
        float a[3][4], b[3][4];
        const uint32_t dH = __byte_perm(p[2], 0, (warp & 1) ? 0x3232 : 0x1010);
        const uint32_t dA = __byte_perm(p[0], 0, 0x1010), dB = __byte_perm(p[0], 0, 0x3232), dC = __byte_perm(p[1], 0, 0x1010), dD = __byte_perm(p[1], 0, 0x3232);
#pragma unroll
        for (int i = NWQ1; i < 3; i++) load_wq1(i);
#pragma unroll
        for (int j = 0; j < 3; j++) { a[j][0] = a[j][1] = a[j][2] = a[j][3] = 0.f; mma(a[j], wq0[j], dA & maskA, dA & maskB); }
#pragma unroll
        for (int j = 0; j < 3; j++) { b[j][0] = b[j][1] = b[j][2] = b[j][3] = 0.f; mma(b[j], wq0[j + 3], dB & maskA, dB & maskB); }
#pragma unroll
        for (int j = 0; j < 3; j++) mma(a[j], wqh[j], dH & maskA, dH & maskB);
#pragma unroll
        for (int i = 3; i < 6; i++) load_wq1(i);
        auto look_rw = [&]() {
            if constexpr (L.value == 1) {
                if (NWQ1) rap = accg + ACC_BYTES + (c4() >> 2) * ACC_PITCH + (c4() & 3) * 8;
                rw[0] = ld_rlx(rap); rw[1] = ld_rlx(rap + 40 * ACC_PITCH);
            }
        };
        if (RWAT == 0) look_rw();
        if (L.value == 1 && P4AT == 2) refill2(IC<4>{});
#pragma unroll
        for (int j = 0; j < 3; j++) mma(b[j], wq1[j], dC & maskA, dC & maskB);
#pragma unroll
        for (int j = 0; j < 3; j++) mma(a[j], wq1[j + 3], dD & maskA, dD & maskB);
#pragma unroll
        for (int j = 0; j < 3; j++) {
#pragma unroll
            for (int k = 0; k < 4; k++) a[j][k] += b[j][k];
            sts128f(pst + j * 256, a[j]);
        }
        const uint32_t tag = lds32(sb + SM_EPOCH) * 4 + 1 + 2 * L.value;
        u64* pub = L.value ? &g_ll[0][cta][tid] : &g_l0[cta][tid];
        if (RWAT == 1) look_rw();
        if (L.value == 0) asm volatile("fence.proxy.async.shared::cta;" ::: "memory");
        TSTAMPL(21);
        __syncthreads();
        st_rlx_if(tid < 192, pub, ll_pack(sum8(sb + SM_PART + tid * 4, 768), tag));
        if constexpr (L.value == 0) st_rlx_if(tid < 192, pub + 192, ll_pack(sum8(sb + SM_CSP + tid * 4, 768), tag));
        TSTAMPL(23);
    };
    auto ln_stats = [&]() {
        float ss = ln_part(xp, lane);
        ss += shx(ss, 8); ss += shx(ss, 4); ss += shx(ss, 2); ss += shx(ss, 1);
        stsf(sb + SM_STAT + min(warp, 4) * 8 + (lane >> 4) * 4, ss);
    };
    auto ln_final = [&](float& mean, float& rstd) {
        float2 v[5];
#pragma unroll
        for (int w = 0; w < 5; w++) v[w] = lds64f(sb + SM_STAT + w * 8);
        mean = sum5(v[0].x, v[1].x, v[2].x, v[3].x, v[4].x) * (1.f / D_MODEL);
        const float msq = sum5(v[0].y, v[1].y, v[2].y, v[3].y, v[4].y) * (1.f / D_MODEL);
        rstd = ln_rstd(mean, msq);
        stsf(sb + SM_FXS, fx_scale(msq));
    };
    auto q_addr = [&](int d) { return sb + SM_VEC + (((d >> 1) & 1) * 4 + ((d >> 3) & 3)) * 48 + (d >> 5) * 8 + ((d >> 2) & 1) * 4 + (d & 1) * 2; };
    {
        uint32_t px[3];
#pragma unroll
        for (int i = 0; i < 3; i++) px[i] = *reinterpret_cast<const uint32_t*>(P.x + 4 * j40 + xcol(i, t));
        if (warp < 5) ln_stats();
        mbar_wait(sb + SM_BAR + (warp >> 1) * 96 + 72, 0);
        load_wq();
        q_proj(IC<0>{}, px, sb + (t < 2 ? SM_PART : SM_CSP) + warp * 768 + (8 * g + 4 * (t & 1)) * 4);
    }
    {
        uint32_t offQ, offL;
        auto calc_ql = [&]() {
            offQ = pin(sb + SM_VEC + (lane & 7) * 48);
            offL = pin(subw + lane * 16);
        };

        auto issue_w = [&](auto L, int which) {
            const uint32_t bar = sb + SM_CBAR + (CB_W1 + which) * 8;
            if (mlp == 96) asm volatile("mbarrier.arrive.shared::cta.b64 _, [%0];" :: "r"(bar) : "memory");
            else {
                mbar_expect(bar, 20480);
                if (which) tma3(sb + (L.value ? 3 * TILE : SM_W2), tmk + TM_W2, 0, mlp * 16, bar, WPOL);
                else asm volatile("cp.async.bulk.tensor.3d.shared::cluster.global.mbarrier::complete_tx::bytes.L2::cache_hint [%0], [%1, {%2, %3, %3}], [%4], %5;"
                                  :: "r"(sb + (L.value ? 2 * TILE : SM_W1)), "l"(tmk + TM_W1), "r"(mlp * 16), "r"(0), "r"(bar), "l"((u64)WPOL << 32) : "memory");
            }
        };
        float acc[3][4];
        auto load_q = [&](uint4 (&qf)[3]) {
#pragma unroll
            for (int i = 0; i < 3; i++) qf[i] = lds128(offQ + i * 16);
        };
        auto score = [&](const uint4 (&v)[6], const uint4 (&qf)[3]) {
            float d[2][4];
#pragma unroll
            for (int j = 0; j < 2; j++) d[j][0] = d[j][1] = d[j][2] = d[j][3] = 0.f;
#pragma unroll
            for (int i = 0; i < 3; i++) { mma(d[0], v[2 * i], qf[i].x, qf[i].y); mma(d[1], v[2 * i + 1], qf[i].z, qf[i].w); }
            return (d[0][0] + d[0][3]) + (d[1][0] + d[1][3]);
        };
        auto softmax = [&](float S0, float S1, float S2, float S3) {
            int mi = __float_as_int(fmaxf(fmaxf(S0, S1), fmaxf(S2, S3)));
            mi = __reduce_max_sync(~0u, mi ^ ((mi >> 31) & 0x7fffffff));
            const float mrun = __int_as_float(mi ^ ((mi >> 31) & 0x7fffffff));
            const float p0 = ex2((S0 - mrun) * CS), p1 = ex2((S1 - mrun) * CS), p2 = ex2((S2 - mrun) * CS), p3 = ex2((S3 - mrun) * CS);
            const uint32_t pa = pack_bf(p0, p1), pb = pack_bf(p2, p3), pw = prow + 256 + (key >> 1) * 80 + t * 4 + (key & 1) * 2;
            sts16(pw, pa); sts16(pw + 16, pa >> 16); sts16(pw + 32, pb); sts16(pw + 48, pb >> 16);
            __syncwarp();
#pragma unroll
            for (int j = 0; j < 3; j++) acc[j][0] = acc[j][1] = acc[j][2] = acc[j][3] = 0.f;
            return make_float2(mrun, (p0 + p1) + (p2 + p3));
        };
        auto head_weight = [&](u64 pm, u64 pl, auto L) {
            const uint32_t tag = lds32(sb + SM_EPOCH) * 4 + 2 + 2 * L.value;
#pragma unroll 1
            for (int it = 0; it < SPIN; it++) {
                if (__all_sync(~0u, ll_tag(pm) == tag && ll_tag(pl) == tag)) break;
                ld_rlx2(&g_ll[L.value][cta ^ (lane >> 3)][192 + (lane & 7) * 4], pm, pl);
            }
            const float f = ex2((ll_val(pm) - warp_max(ll_val(pm))) * CS);
            const float w = f * rcp(warp_sum(f * ll_val(pl)));
            if (lane < 8) stsf(sb + SM_FAC + lane * 4, w);
        };
        auto pv = [&](const uint4 (&v)[6], uint32_t pp) {
            const uint32_t dA = __byte_perm(pp, 0, 0x1010), dB = __byte_perm(pp, 0, 0x3232);
            mma(acc[0], v[0], dA & maskA, dA & maskB); mma(acc[1], v[1], dA & maskA, dA & maskB); mma(acc[2], v[2], dA & maskA, dA & maskB);
            mma(acc[0], v[3], dB & maskA, dB & maskB); mma(acc[1], v[4], dB & maskA, dB & maskB); mma(acc[2], v[5], dB & maskA, dB & maskB);
        };
        auto sa = [&]() { return prow + 256 + t * 32 + g * 4; };
        auto pass1 = [&]() {
            issue_paced(NIM, NI1);
#pragma unroll
            for (int u = 0; u < 8; u++)
#pragma unroll
                for (int i = 0; i < 6; i++) kr[u][i] = lds128(sb + SM_CS + (u * 6 + i) * 16);
            fresh();
            calc_ql();
            __syncthreads();
            sts64(prow + lane * 8, xp.x, xp.y);
            int e = 0;
            const uint4* tab = P.tile + (warp >> 2);
            uint4 tw = tab[0];
            uint32_t ka[3];
#pragma unroll
            for (int j = 0; j < 3; j++) ka[j] = pin(subw + key * 384 + j * 128 + ((t ^ ((3 * key + j) & 7)) << 4));
            auto load_k = [&](uint4 (&v)[6], uint32_t so) {
#pragma unroll
                for (int i = 0; i < 6; i++) v[i] = lds128(((i & 1) ? ka[i >> 1] ^ 64 : ka[i >> 1]) + so);
            };
            const uint32_t s0 = pin(prow + 256 + g * 4), sca = pin(sb + SM_SC + warp * 128 + g * 16);
#pragma unroll 1
            do {
                const uint4 tn = tab[2 * e + 2];
                uint4 v[6], qf[3];
                if (tw.x & (G_A | G_B | G_C)) {
                    if ((tw.x & G_A) && warp == 7 && elect()) {
                        mbar_expect(sb + SM_CBAR + CB_SNAP * 8, HALF);
                        asm volatile("cp.async.bulk.shared::cluster.global.mbarrier::complete_tx::bytes [%0], [%1], 12288, [%2];"
                                     :: "r"(sb + SM_SNAP), "l"(&g_l0[cta & ~3][0]), "r"(sb + SM_CBAR + CB_SNAP * 8) : "memory");
                    }
                    if (tw.x & G_B) {
                        if (warp < 6) {
                            mbar_wait(sb + SM_CBAR + CB_SNAP * 8, 0);
                            float qc[2] = {0.f, 0.f}, mean, rstd;
#pragma unroll 1
                            for (int k = 0; k < 2; k++) {
                                u64 qw[4];
#pragma unroll
                                for (int i = 0; i < 4; i++) { const uint2 x = lds64(sb + SM_SNAP + i * 3072 + k * 1536 + tid * 8); qw[i] = x.x | (u64)x.y << 32; }
                                qc[0] = qc[1];
                                qc[1] = ll_gather<384>(&g_l0[cta & ~3][k * 192 + tid], lds32(sb + SM_EPOCH) * 4 + 1, qw);
                            }
                            ln_final(mean, rstd);
                            stsf(sb + SM_CS + tid * 4, qc[1]);
                            const float q = (qc[0] - mean * qc[1]) * rstd;
                            sts16(q_addr(tid), pack_bf(q, q));
                        }
                        __syncthreads();
                        if (warp == 7 && elect()) issue_half(UC<load_word(12)>::value, sb, rowc, cta, tmk);
                        TSTAMP(2);
                    }
                    if (tw.x & G_C) {
                        load_k(v, (e - LATEAT) * TILE);
                        load_q(qf);
                        stsf(s0 + (e - LATEAT) * 32, score(v, qf));
                    }
                }
                load_q(qf);
                mbar_wait(sb + SM_CBAR + (tw.x & 0xf8), tw.x >> 31);
                TRACE(e);
                load_k(v, tw.x & 0x3f000);
                const uint32_t old = release(tw);
                const float s = score(v, qf);
                uint32_t m;
                {
                    uint32_t a[6];
#pragma unroll
                    for (int i = 0; i < 6; i++) a[i] = bf2_amax(bf2_amax(v[i].x, v[i].y), bf2_amax(v[i].z, v[i].w));
                    m = bf2_amax(bf2_amax(bf2_amax(a[0], a[1]), bf2_amax(a[2], a[3])), bf2_amax(a[4], a[5]));
                }
                m = bf2_amax(m, m >> 16) & 0x7f80;
                m = max(m, __shfl_xor_sync(~0u, m, 1));
                stsf(s0 + e * 32, s);
                m = max(m, __shfl_xor_sync(~0u, m, 2));
                refill(tw, old);
                const uint32_t b = min(max(m, 15u << 7) - (15u << 7), 126u << 7);
                const uint32_t dn = ((127u << 7) - b) * 0x10001u, up = ((127u << 7 | 0x8000u) + b) * 0x10001u;
                uint32_t c[18], any = m > (141u << 7);
#pragma unroll
                for (int i = 0; i < 6; i++) {
                    const uint32_t y0 = bf2_mul(v[i].x, dn), y1 = bf2_mul(v[i].y, dn), y2 = bf2_mul(v[i].z, dn), y3 = bf2_mul(v[i].w, dn);
                    v[i] = make_uint4(bf2_fma(y0, up, v[i].x), bf2_fma(y1, up, v[i].y), bf2_fma(y2, up, v[i].z), bf2_fma(y3, up, v[i].w));
                    any |= v[i].x | v[i].y;
                    any |= v[i].z | v[i].w;
                    const uint32_t hb = __byte_perm(y2, y3, 0x7531);
                    c[3 * i] = __byte_perm(y0, y1, 0x6420); c[3 * i + 1] = __byte_perm(y2, y3, 0x6420);
                    c[3 * i + 2] = __byte_perm(y0, y1, 0x7531) | __funnelshift_r(hb, hb, 4);
                }
                asm volatile("st.shared.u8 [%0], %1;" :: "r"(sca + (e & 3) * 4 + (e >> 2)), "r"((b >> 7) + 63) : "memory");
                const bool rare = __any_sync(~0u, any);
                k_keep(kr, c, e, offL);
                if (rare) {
                    uint32_t odd = m > (141u << 7) ? 64u : 0u;
#pragma unroll
                    for (int i = 0; i < 6; i++) if (v[i].x | v[i].y | v[i].z | v[i].w) odd |= 1u << i;
                    odd = __reduce_or_sync(~0u, odd);
                    const uint2 st = lds64(barw + 80);
                    uint32_t lt; asm volatile("mov.u32 %0, %lanemask_lt;" : "=r"(lt));
                    uint32_t n = odd >= 64 ? NEXC + 1 : __shfl_sync(~0u, st.x, 0);
#pragma unroll 1
                    for (; odd && n <= NEXC; odd &= odd - 1) {
                        const int i = __ffs(odd) - 1;
                        uint4 r = v[0];
#pragma unroll
                        for (int k = 1; k < 6; k++) if (i == k) r = v[k];
#pragma unroll 1
                        for (int k = 0; k < 4; k++) {
                            const uint32_t who = __ballot_sync(~0u, r.x), at = n + __popc(who & lt);
                            if (r.x && at < NEXC) sts64(sb + SM_EXC + warp * 128 + at * 8, r.x, (e * 32 + g * 4) << 16 | (((k & 1) * 4 + t) * 48 + i * 8 + (k >> 1) * 4));
                            n += __popc(who);
                            r.x = r.y; r.y = r.z; r.z = r.w;
                        }
                    }
                    if (n > NEXC) asm volatile("st.shared.u8 [%0], %1;" :: "r"(sca + (e & 3) * 4 + (e >> 2)), "r"(0) : "memory");
                    sts64(barw + 80, n > NEXC ? st.x : n, n > NEXC ? st.y | 1u << e : st.y);
                    __syncwarp();
                }
                tw = tn;
            } while (++e < 16);
            asm volatile("fence.proxy.async.shared::cta;" ::: "memory");
            __syncwarp();
            TSTAMP(10);
            fresh(); calc_offsets();
            {
                const uint2 st = lds64(barw + 80);
                const uint32_t xa = sb + SM_EXC + warp * 128 + (lane & 15) * 8 + 4;
                uint32_t pos = lds32(xa), lt;
                asm volatile("mov.u32 %0, %lanemask_lt;" : "=r"(lt));
                if (lane >= st.x) pos = 0x80000000u;
                const bool dup = (__match_any_sync(~0u, pos >> 16) & lt) && lane < st.x;
                if (lane < 16) sts32(xa, dup ? pos | 0x40000000u : pos);
                if (__any_sync(~0u, dup)) sts32(barw + 84, st.y | 0x10000u);
                const float2 ml = softmax(ldsf(sa()), ldsf(sa() + 128), ldsf(sa() + 256), ldsf(sa() + 384));
                sts64f(sb + SM_ML + warp * 8, ml.x, warp_sum(ml.y));
            }
            u64 pm = 0, pl = 0;
#pragma unroll 1
            do {
                const uint4 tn = tab[2 * e + 2];
                if (tw.x & (G_A | G_B | G_C)) {
                    if (tw.x & G_A) {
                        if (lane < 24) st_rlx(&g_ll[0][cta][warp * 24 + lane], 0ull);
                        else if (lane < 28) st_rlx(&g_ll[0][cta][168 + warp * 4 + lane], ll_pack(ldsf(sb + SM_ML + warp * 8 + (lane & 1) * 4), lds32(sb + SM_EPOCH) * 4 + 2));
                    }
                    if (warp == 2) {
                        if (tw.x & G_B) ld_rlx2(&g_ll[0][cta ^ (lane >> 3)][192 + (lane & 7) * 4], pm, pl);
                        if (tw.x & G_C) head_weight(pm, pl, IC<0>{});
                    }
                    __syncwarp();
                }
                const uint32_t pp = lds32(prow + 256 + t * 80 + ((tw.x >> 20) & 255));
                mbar_wait(sb + SM_CBAR + (tw.x & 0xf8), tw.x >> 31);
                TRACE(e);
                uint4 v[6];
                load_v(v, tw.x & 0x3f000);
                refill(tw, release(tw));
                pv(v, pp);
                tw = tn;
            } while (++e < 32);
        };
        uint32_t osa, ora, owa, orow, otag;
        u64* olb;
        auto o_setup = [&](auto L) {
            fresh();
            const int lz = lane, d = warp * 24 + min(lz, 23);
            osa = pin(prow + ((lz >> 2) * 8 + (lz & 1) * 4) * 4);
            ora = pin(sb + SM_PART + d * 4);
            olb = pin(&g_ll[L.value][cta & ~3][d]);
            orow = pin((lz & 1) + 2 * (lz & 2) + 2 * (lz >> 4));
            owa = pin(sb + SM_RING + warp * 1536 + orow * 64 + ((((lz >> 2) & 3) ^ (orow >> 1)) << 4));
            otag = lds32(sb + SM_EPOCH) * 4 + 2 + 2 * L.value;
            xp = lds64(prow + lz * 8);
        };
        auto pass2 = [&]() {
            constexpr IC<1> L{};
            const uint32_t c0 = clk();
            if (P4AT == 0) refill2(IC<4>{});
            if (P2LATE == 1 && warp >= 4) refill2(IC<2>{});
            offQ = sb + SM_VEC + (lane & 7) * 48; offL = subw + lane * 16;
            uint4 tb[8][3];
            auto load_tb = [&](auto I) {
#pragma unroll
                for (int i = 0; i < 3; i++) tb[I.value][i] = lds128(offL + (I.value >> 1) * TILE + ((I.value & 1) * 3 + i) * 512);
            };
            const float cs = ldsf(sb + SM_CS + min(tid, 191) * 4), inv = fx2_inv(ldsf(sb + SM_MSQ));
            const uint32_t qtag = lds32(sb + SM_EPOCH) * 4 + 3;
            uint32_t m1 = lds32(sb + SM_M1), m1n = m1;
            static_for<0, NPRE>(load_tb);
            const u64* qb = &g_ll[0][cta & ~3][min(tid, 191)];
            const uint32_t qa = pin(q_addr(min(tid, 191)));
            {
                uint32_t x[2];
                fx2_wait<2, true>([&](int i) { return rap + i * 40 * ACC_PITCH; }, rw, sb + SM_MSQ, inv, x);
                xp = make_uint2(x[0], x[1]);
            }
            u64 qw[4];
            if (QDELAY) while (clk() - c0 < QDELAY);
            ll_look<256>(qb, qw);
            ln_stats();
            if (P4AT == 1) refill2(IC<4>{});
            if (S0EARLY) refill2(IC<5>{});
            __syncthreads();
            auto vwait = [&](auto I) { mbar_wait(barw + IC<SCH.st[I.value].slot>::value * 8, IC<SCH.st[I.value].par>::value); };
            bool ok;
            {
                float mean, rstd;
                ln_final(mean, rstd);
                sts64(prow + lane * 8, xp.x, xp.y);
                sts128f(prow + 256 + lane * 16, 0.f, 0.f, 0.f, 0.f);
                const float sq = rstd * 0x1p64f, q0 = -mean * cs * sq;
                const float q = ll_gather<256>(qb, qtag, qw) * sq + q0;
                sts16(qa, pack_bf(q, q));
                TSTAMPL(24);
            }
            if (!S0EARLY) refill2(IC<5>{});
            if (P2LATE == 2 && warp >= 4) refill2(IC<2>{});
            if (P4AT == 3) refill2(IC<4>{});
            if (NOWIN & 1) { if (warp < 6) refill2(IC<0>{}); if (warp >= 5) refill2(IC<3>{}); }
            if (NOWIN & 2) { if (warp >= 6) refill2(IC<1>{}); if (warp < 4) refill2(IC<2>{}); }
            if (NOWIN & 4) { if (warp >= 6) refill2(IC<0>{}); if (warp < 6) refill2(IC<1>{}); }
            if (NOWIN & 8) { if (warp < 5) refill2(IC<3>{}); if (warp >= 4) refill2(IC<2>{}); }
            __syncthreads();
            uint4 qf[3];
            load_q(qf);
            float S[4], d[2][4];
            auto vload = [&](auto I) {
                constexpr int p = I.value;
                constexpr Step c = SCH.st[p];
                load_v(kr[p & 7], c.slot * TILE);
                if constexpr (c.next >= 0) refill2(IC<c.next>{});
                if constexpr (p == 11) { __syncwarp(); if (elect()) asm volatile("mbarrier.arrive.shared::cta.b64 _, [%0];" :: "r"(sb + SM_CBAR + CB_REL * 8) : "memory"); }
            };
            auto side = [&](uint2 x) {
                const uint32_t qq = lds32(sb + SM_VEC + (x.y & 0xffff));
                return (bf_lo(x.x) * bf_lo(qq) + bf_hi(x.x) * bf_hi(qq)) * 0x1p-64f;
            };
            static_for<0, 96>([&](auto F) {
                constexpr int f = F.value, i = f % 6, u = kunit(f / 6), w = 3 * f % 12;
                uint4 (&src)[3] = *reinterpret_cast<uint4 (*)[3]>(f < 32 ? &tb[f / 4 & 7][0] : &kr[(f / 8 + 4) & 7][(f / 4 & 1) * 3]);
                const uint4 a = k_unpack(word<w % 4>(src[w / 4]), word<(w + 1) % 4>(src[(w + 1) / 4]), word<(w + 2) % 4>(src[(w + 2) / 4]), m1);
                if constexpr (f < 32 ? f % 4 == M1AT : f % 8 == M1P) m1 = m1n;
                if constexpr (f % 4 == 3 && f / 4 + NPRE < 8) {
                    load_tb(IC<f / 4 + NPRE>{});
                    if constexpr ((f / 4 + NPRE) & 1) { refill2(IC<5 + (f / 4 + NPRE) / 2>{}); m1n = lds32(sb + SM_M1); }
                }
                if constexpr (i < 2) d[i][0] = d[i][1] = d[i][2] = d[i][3] = 0.f;
                mma(d[i & 1], a, (i & 1) ? qf[i / 2].z : qf[i / 2].x, (i & 1) ? qf[i / 2].w : qf[i / 2].y);
                if constexpr (i == 5) {
                    if constexpr (u == 11 || ((u & 3) == 0 && u != 8)) S[u >> 2] = (d[0][0] + d[0][3]) + (d[1][0] + d[1][3]);
                    else add_if(t == (u & 3), S[u >> 2], d[0][0] + d[0][3], d[1][0] + d[1][3]);
                    if constexpr (f < 64) S[u >> 2] = shx(S[u >> 2], 0);
                }
                if constexpr (f == 31) { fresh(); calc_offsets(); ok = mbar_test(barw + IC<SCH.st[0].slot>::value * 8, 0); }
                if constexpr (f == 48) {
                    const uint2 x = lds64(sb + SM_EXC + warp * 128 + (lane & 15) * 8);
                    const float c = side(x);
                    if (x.y < 0x40000000u) stsf(prow + 256 + (x.y >> 16), c);
                }
                if constexpr (f >= 32 && f % 8 == 7) {
                    if constexpr (PARKS >> (f / 8 - 4) & 1) {
                        constexpr int p = popc(PARKS & ((1 << (f / 8 - 4)) - 1));
                        if (!ok) vwait(IC<p>{});
                        vload(IC<p>{});
                        m1n = lds32(sb + SM_M1);
                        ok = mbar_test(barw + IC<SCH.st[p + 1].slot>::value * 8, IC<SCH.st[p + 1].par>::value);
                    }
                }
            });
            uint32_t bad = lds32(barw + 84);
            const uint32_t sc = lds32(sb + SM_SC + tid * 4);
            __syncwarp();
            if (bad) {
                const uint2 x = lds64(sb + SM_EXC + warp * 128 + (lane & 15) * 8);
                if ((int)x.y >= 0x40000000 && lane < 16) asm volatile("red.shared.add.f32 [%0], %1;" :: "r"(prow + 256 + ((x.y >> 16) & 511)), "f"(side(x)) : "memory");
#pragma unroll 1
                for (bad &= 0xffff; bad; bad &= bad - 1) {
                    const int e = __ffs(bad) - 1;
                    const __nv_bfloat16* kp = P.k + (size_t)(roww + e * 256 + key) * DH + t * 8;
                    uint4 v[6];
#pragma unroll
                    for (int i = 0; i < 6; i++) v[i] = *reinterpret_cast<const uint4*>(kp + i * 32);
                    const float s = score(v, qf) * 0x1p-64f;
                    if (t == 0) stsf(sa() + e * 32, s);
                }
                __syncwarp();
            }
            TSTAMP(30);
            const float2 ml = softmax(S[0] * __uint_as_float((sc & 255) << 23) + ldsf(sa()), S[1] * __uint_as_float((sc & 0xff00) << 15) + ldsf(sa() + 128),
                                      S[2] * __uint_as_float((sc & 0xff0000) << 7) + ldsf(sa() + 256), S[3] * __uint_as_float((sc >> 24) << 23) + ldsf(sa() + 384));
            uint4 pq[4];
#pragma unroll
            for (int j = 0; j < 4; j++) pq[j] = lds128(prow + 256 + t * 80 + j * 16);
            TSTAMP(1);
            if (!ok) vwait(IC<NPARK>{});
            float ac2[3][4];
#pragma unroll
            for (int j = 0; j < 3; j++) ac2[j][0] = ac2[j][1] = ac2[j][2] = ac2[j][3] = 0.f;
            const uint32_t sl = (g & 1) ? 0x1044 : 0x4410, sh = (g & 1) ? 0x3244 : 0x4432;
            const uint32_t sA0 = (g & 2) ? 0x4444 : sl, sA1 = (g & 2) ? sl : 0x4444, sB0 = (g & 2) ? 0x4444 : sh, sB1 = (g & 2) ? sh : 0x4444;
            u64 pm = 0, pl = 0;
            static_for<NPARK, 16>([&](auto I) {
                constexpr int p = I.value;
                static_assert(p - SCH.st[p].mma0 < 8, "buffer in use");
                vload(I);
                if constexpr (p < 15) ok = mbar_test(barw + IC<SCH.st[p + 1].slot>::value * 8, IC<SCH.st[p + 1].par>::value);
                static_for<SCH.st[p].mma0, SCH.st[p].mma0 + SCH.st[p].nmma>([&](auto J) {
                    constexpr int u = SCH.st[J.value].unit;
                    const uint32_t pp = word<u & 3>(pq[u >> 2]), a0 = __byte_perm(pp, 0, sA0), a1 = __byte_perm(pp, 0, sA1), b0 = __byte_perm(pp, 0, sB0), b1 = __byte_perm(pp, 0, sB1);
#pragma unroll
                    for (int j = 0; j < 3; j++) mma(acc[j], kr[J.value & 7][j], a0, a1);
#pragma unroll
                    for (int j = 0; j < 3; j++) mma(ac2[j], kr[J.value & 7][j + 3], b0, b1);
                });
                if constexpr (p == NPARK) {
                    const float l = warp_sum(ml.y);
                    if (lane < 28) st_rlx(&g_ll[1][cta][lane < 24 ? warp * 24 + lane : 168 + warp * 4 + lane], lane < 24 ? 0ull : ll_pack((lane & 1) ? l : ml.x, lds32(sb + SM_EPOCH) * 4 + 4));
                }
                if constexpr (p == HWAT) { if (warp == 6) ld_rlx2(&g_ll[1][cta ^ (lane >> 3)][192 + (lane & 7) * 4], pm, pl); }
                if constexpr (p == 13) o_setup(L);
                if constexpr (p == HWAT + 2) { if (warp == 6) head_weight(pm, pl, IC<1>{}); }
                if constexpr (p >= WOAT && p < WOAT + 3) {
                    if (warp == p - WOAT) {
                        mbar_wait(sb + SM_CBAR + CB_REL * 8, 0);
                        if (elect()) {
                            issue_half(UC<load_word(64 + 2 * (p - WOAT)) | 1>::value, sb, rowc, cta, tmk);
                            if constexpr (p < WOAT + 2) issue_half(UC<load_word(65 + 2 * (p - WOAT)) | 1>::value, sb, rowc, cta, tmk);
                        }
                        __syncwarp();
                    }
                }
                if constexpr (p < 15) { if (!ok) mbar_wait(barw + IC<SCH.st[p + 1].slot>::value * 8, IC<SCH.st[p + 1].par>::value); TRACE(33 + p); }
            });
#pragma unroll
            for (int j = 0; j < 3; j++)
#pragma unroll
                for (int k = 0; k < 4; k++) acc[j][k] += ac2[j][k];
        };

        const unsigned char* ap;
        uint32_t hpa, hsa, hst, w2a, la;
        uint2 b2v;
        float b1v, cs1;
        auto mlp_global = [&](auto L) {
            const int cz = c4();
            ap = accg + 2 * L.value * ACC_BYTES + (cz >> 3) * ACC_PITCH + (cz & 7) * 8;
            if (L.value) ap = pin(ap);
            rap = pin(accg + (2 * L.value + 1) * ACC_BYTES + (cz >> 2) * ACC_PITCH + (cz & 3) * 8);
            asm volatile("ld.global.nc.v2.u32 {%0,%1}, [%2];" : "=r"(b2v.x), "=r"(b2v.y) : "l"(P.b2 + 4 * cz));
        };
        auto mlp_shared = [&](auto L) {
            const int lz = lane;
            hpa = pin(sb + SM_PART + warp * 256 + ((lz & 2) * 4 + (lz >> 2)) * 16 + (L.value ? 0 : (lz & 1) * 4));
            hsa = pin(sb + SM_PART + (lz & 15) * 16); hst = pin(sb + SM_PART + (lz & 15) * 16 + warp * 256 + 8 + (lz >> 4) * 4);
            w2a = pin(sb + (L.value ? 3 * TILE : SM_W2) + ((lz & 3) * 10 + 2 * warp) * 128 + (((lz >> 2) ^ ((2 * lz + 2 * warp) & 6)) << 4));
            la = sb + (L.value ? 2 * TILE : SM_W1) + warp * 4096 + (lz & 4) * 512 + (lz & 2) * 64 + (lz & 1) * 32 + (lz >> 4) * 64 + ((((lz >> 3) ^ (lz >> 1)) & 1) << 4);
            b1v = ldsf(sb + SM_B1 + (lz & 15) * 4);
            if (L.value) { la = pin(la); cs1 = ldsf(sb + SM_ML + (lz & 15) * 4); }
            else fresh();
        };
        uint32_t pa;
        unsigned char* rop;
        uint32_t wpa;
        auto sum_setup = [&](auto L) {
            const int lz = lane, word = (lz & 3) * 160 + warp * 32 + (cta & 3) * 8 + (lz >> 2);
            const uint32_t wo = ((lz >> 2) * 8 + (lz & 1) * 4) * 4;
            wpa = pin(sb + SM_RING + warp * 1536 + ((((lz >> 1) ^ (lz >> 4)) & 1) ? HALF + (wo ^ 64) : wo));
            pa = pin(sb + SM_RING + warp * 256 + lz * 4);
            rop = pin(accg + 2 * L.value * ACC_BYTES + (word >> 3) * ACC_PITCH + (word & 7) * 8);
        };
        auto out_proj = [&](auto L) {
            TSTAMP2(3);
            CSTAMP(0, __float_as_uint(acc[2][3]));
            __syncwarp();
#pragma unroll
            for (int j = 0; j < 3; j++) sts128f(osa + 256 * j, acc[j]);
            __syncthreads();
            {
                float s[8];
#pragma unroll
                for (int w = 0; w < 8; w++) s[w] = ldsf(ora + w * 768);
                const uint4 fa = lds128(sb + SM_FAC), fb = lds128(sb + SM_FAC + 16);
            CSTAMP(1, __float_as_uint(s[0]));
                const float own = ((s[0] * __uint_as_float(fa.x) + s[1] * __uint_as_float(fa.y)) + (s[2] * __uint_as_float(fa.z) + s[3] * __uint_as_float(fa.w))) +
                                  ((s[4] * __uint_as_float(fb.x) + s[5] * __uint_as_float(fb.y)) + (s[6] * __uint_as_float(fb.z) + s[7] * __uint_as_float(fb.w)));
                st_rlx_if(lane < 24, olb + (cta & 3) * 256, ll_pack(own, otag));
            CSTAMP(2, __float_as_uint(own));
            }
            TSTAMPL(29);
            if (L.value == 0 && warp == 7) {
#pragma unroll 1
                for (int it = 0; it < SPIN; it++) {
                    uint32_t v; asm volatile("ld.acquire.gpu.global.u32 %0, [%1];" : "=r"(v) : "l"(&g_zflag) : "memory");
                    if (__all_sync(~0u, v == (otag >> 2) + 1)) break;
                }
            }
            constexpr int NW = L.value ? NWO1 : 3;
            uint4 v[5][3];
            u64 ow[4];
            auto read_wo = [&](auto J) {
#pragma unroll
                for (int p = 0; p < 3; p++) v[J.value][p] = lds128(owa + ring_hs(64 + J.value) * HALF + p * 512);
            };
            static_for<0, NW>([&](auto J) {
                if (L.value && J.value == 0) { sum_setup(L); maskA = pin(maskA); maskB = pin(maskB); }
                if ((L.value ? OPOLL1 : OPOLL) == J.value) { ll_look<256>(olb, ow); if (L.value) { mlp_shared(L); mlp_global(L); } }
                mbar_wait(sb + SM_CBAR + (CB_WO + J.value) * 8, L.value);
                read_wo(J);
                if (L.value == 0 && W1AT0 == J.value + 1) {
                    __syncwarp();
                    if (elect() && cnt_inc(sb + SM_CNT + CB_W1 * 8, 7) == 7) issue_w(L, 0);
                    __syncwarp();
                }
                if (L.value == 1 && (W1AT1 == J.value + 1 || W2AT1 == J.value + 1)) {
                    if (warp == 7 && elect()) { if (W1AT1 == J.value + 1) issue_w(L, 0); if (W2AT1 == J.value + 1) issue_w(L, 1); }
                    __syncwarp();
                }
            });
            const float o = ll_gather<256>(olb, otag, ow);
            CSTAMP(3, __float_as_uint(o));
            TSTAMP2(4);
            bool ok = true;
            if constexpr (NW < 5) ok = mbar_test(sb + SM_CBAR + (CB_WO + 4) * 8, L.value);
            if constexpr (NW < 4) ok &= mbar_test(sb + SM_CBAR + (CB_WO + 3) * 8, L.value);
            const uint32_t od = pack_bf(o, o);
            uint32_t oa[3], ob[3];
#pragma unroll
            for (int p = 0; p < 3; p++) { const uint32_t op = __shfl_sync(~0u, od, 8 * p + orow); oa[p] = op & maskA; ob[p] = op & maskB; }
            CSTAMP(4, oa[2]);
            float y[5][4];
#pragma unroll
            for (int j = 0; j < 5; j++) y[j][0] = y[j][1] = y[j][2] = y[j][3] = 0.f;
            auto rest = [&]() {
                if (!ok) static_for<NW, 5>([&](auto J) { mbar_wait(sb + SM_CBAR + (CB_WO + J.value) * 8, L.value); });
                static_for<NW, 5>(read_wo);
            };
            if (L.value) rest();
#pragma unroll
            for (int p = 0; p < 3; p++)
#pragma unroll
                for (int j = 0; j < NW; j++) mma(y[j], v[j][p], oa[p], ob[p]);
            if (!L.value) { rest(); sum_setup(L); }
#pragma unroll
            for (int p = 0; p < 3; p++)
#pragma unroll
                for (int j = NW; j < 5; j++) mma(y[j], v[j][p], oa[p], ob[p]);
            CSTAMP(5, __float_as_uint(y[4][3]));
#pragma unroll
            for (int j = 0; j < 5; j++) sts128f(wpa + j * 256, y[j]);
            TSTAMP2(5);
        };
        u64 yw[2];
        bool wide;
        float msq = 0.f, yf[4];
        auto mlp_part = [&](auto L) {
            const float fxs = ldsf(sb + SM_FXS);
            bar_sync(0, 256);
            CSTAMP(6, __float_as_uint(fxs));
            {
                const float s = sum8(pa, 1536) + sum8(pa + 128, 1536);
            CSTAMP(7, __float_as_uint(s));
                asm volatile("red.relaxed.gpu.global.add.u64 [%0], %1;" :: "l"(rop), "l"(fx_pack(s, fxs)) : "memory");
            }
            const uint32_t c0 = clk();
            TSTAMP2(6);
            if (L.value == 0) bar_arrive(2, 256);
            else if (mlp == 96) { TDUMP(); asm volatile("exit;"); }
            uint4 wf[8], w2r[8];
            u64 w[4];
            auto look = [&]() {
#pragma unroll
                for (int k = 0; k < 4; k++) w[k] = ld_rlx(ap + k * 20 * ACC_PITCH);
            };
            auto read_w1 = [&]() {
#pragma unroll
                for (int j = 0; j < 8; j++) wf[j] = ldsm_t(la + j * 256);
            };
            auto read_w2 = [&]() {
#pragma unroll
                for (int i = 0; i < 8; i++) w2r[i] = lds128(((i & 1) ? (w2a ^ 16) + 128 : w2a) + (i >> 1) * 5120);
            };
            if (L.value == 0) { fresh(); mlp_global(L); }
            mbar_wait(sb + SM_CBAR + CB_W1 * 8, L.value);
            if (L.value == 1) {
                if (W2PRE == 1) mbar_wait(sb + SM_CBAR + CB_W2 * 8, 1);
                read_w1();
                if (W2PRE == 1) read_w2();
            }
            while (clk() - c0 < AR1D);
            look();
            if (L.value == 0) { mlp_shared(L); read_w1(); bar_arrive(3, 256); }
            else if (W2PRE == 2) { mbar_wait(sb + SM_CBAR + CB_W2 * 8, 1); read_w2(); }
            TSTAMPL(28);
            {
                int it = 0;
#pragma unroll 1
                while (__any_sync(~0u, ~(lo32(w[0]) & lo32(w[1]) & lo32(w[2]) & lo32(w[3])) & 32) & (++it < SPIN)) look();
                const float inv = fx_inv(fxs);
            CSTAMP(8, lo32(w[3]));
                xp = make_uint2(pack_bf(bf_lo(xp.x) + fx_val(w[0]) * inv, bf_hi(xp.x) + fx_val(w[1]) * inv),
                                pack_bf(bf_lo(xp.y) + fx_val(w[2]) * inv, bf_hi(xp.y) + fx_val(w[3]) * inv));
            }
            TSTAMP2(7);
            CSTAMP(9, xp.y);
            {
                bool ok = true;
                if (L.value == 0 || !W2PRE) ok = mbar_test(sb + SM_CBAR + CB_W2 * 8, L.value);
                const bool ev = L.value || !(g & 1), od = L.value || (g & 1);
                const uint32_t e0 = ev ? xp.x : ONES, e1 = ev ? xp.y : ONES, o0 = od ? xp.x : ONES, o1 = od ? xp.y : ONES;
                float d[8][4];
#pragma unroll
                for (int j = 0; j < 8; j++) { d[j][0] = d[j][1] = d[j][2] = d[j][3] = 0.f; mma(d[j], wf[j], (j & 1) ? o0 : e0, (j & 1) ? o1 : e1); }
                float ss = ln_part(xp, lane);
                ss += shx(ss, 8); ss += shx(ss, 4);
                float r[4], dd;
#pragma unroll
                for (int k = 0; k < 4; k += 1 + L.value) r[k] = d[0][k] + d[1][k ^ 1];
#pragma unroll
                for (int j = 1; j < 4; j++)
#pragma unroll
                    for (int k = 0; k < 4; k += 1 + L.value) add_if(t == j, r[k], d[2 * j][k], d[2 * j + 1][k ^ 1]);
                CSTAMP(10, __float_as_uint(r[2]));
                if (L.value) {
                    dd = ((t & 2) ? r[2] : r[0]) + shx((t & 2) ? r[0] : r[2], 2);
                    ss += shx(ss, 2);
                    dd += shx(dd, 1);
                } else {
                    const float a = ((t & 1) ? r[1] : r[0]) + shx((t & 1) ? r[0] : r[1], 1), b = ((t & 1) ? r[3] : r[2]) + shx((t & 1) ? r[2] : r[3], 1);
                    ss += shx(ss, 2);
                    dd = ((t & 2) ? b : a) + shx((t & 2) ? a : b, 2);
                }
                ss += shx(ss, 1);
                stsf(hpa, dd);
                stsf(hst, ss);
                CSTAMP(11, __float_as_uint(dd + ss));
                if (!ok) mbar_wait(sb + SM_CBAR + CB_W2 * 8, L.value);
            }
            TSTAMPL(25);
            bar_sync(1, 160);
            uint4 hp[5];
#pragma unroll
            for (int w = 0; w < 5; w++) hp[w] = lds128(hsa + w * 256);
            CSTAMP(12, hp[0].x);
            auto hs = [&](auto K) { return sum5(__uint_as_float(word<K.value>(hp[0])), __uint_as_float(word<K.value>(hp[1])), __uint_as_float(word<K.value>(hp[2])),
                                                __uint_as_float(word<K.value>(hp[3])), __uint_as_float(word<K.value>(hp[4]))); };
            const float mean = hs(IC<2>{}) * (1.f / D_MODEL);
            msq = hs(IC<3>{}) * (1.f / D_MODEL);
            if (L.value == 0) cs1 = hs(IC<1>{});
            float hv = hs(IC<0>{}) - mean * cs1;
            CSTAMP(13, __float_as_uint(hv));
            const float sc2 = fx2_scale(msq), lim = fx_inv(sc2) * FX2LIM;
            if (L.value == 0 || !W2PRE) read_w2();
            if (L.value == 0) bar_arrive(4, 256);
            hv = hv * ln_rstd(mean, msq) + b1v;
            CSTAMP(14, __float_as_uint(hv));
            hv = hv * rcp(1.f + ex2(hv * (-2.302208198f - 0.1029432397f * hv * hv)));
            const uint32_t hd = pack_bf(hv, hv);
            CSTAMP(15, hd);
            TSTAMPL(27);
            float ym[4][4];
#pragma unroll
            for (int i = 0; i < 2; i++) {
                ym[i][0] = ym[i][1] = ym[i][2] = ym[i][3] = 0.f;
                const float f = mlp < 64 ? 1.f / 64 : 0.f;
                ym[i + 2][0] = (bf_lo(xp.x) + bf_lo(b2v.x)) * f; ym[i + 2][1] = (bf_hi(xp.x) + bf_hi(b2v.x)) * f;
                ym[i + 2][2] = (bf_lo(xp.y) + bf_lo(b2v.y)) * f; ym[i + 2][3] = (bf_hi(xp.y) + bf_hi(b2v.y)) * f;
            }
#pragma unroll
            for (int i = 0; i < 4; i++) {
                const uint32_t hh = __shfl_sync(~0u, hd, 4 * i + t);
                mma(ym[(i & 1) * 2], w2r[2 * i], hh & maskA, hh & maskB);
                mma(ym[(i & 1) * 2 + 1], w2r[2 * i + 1], hh & maskA, hh & maskB);
            }
#pragma unroll
            for (int k = 0; k < 4; k++) { yf[k] = ym[0][k] + ym[2][k]; add_if(t & 2, yf[k], ym[1][k], ym[3][k]); }
            CSTAMP(16, __float_as_uint(yf[3]));
            yw[0] = fx2_pack(yf[0] * sc2 + FX2_ONE, yf[1] * sc2 + FX2_ONE); yw[1] = fx2_pack(yf[2] * sc2 + FX2_ONE, yf[3] * sc2 + FX2_ONE);
            wide = !(fmaxf(fmaxf(fabsf(yf[0]), fabsf(yf[1])), fmaxf(fabsf(yf[2]), fabsf(yf[3]))) < lim);
            if (wide) yw[0] = yw[1] = 0;
        };
        auto send_wide = [&]() {
#pragma unroll 1
            for (int k = 0; k < 4; k++, yf[0] = yf[1], yf[1] = yf[2], yf[2] = yf[3])
                asm volatile("red.relaxed.gpu.global.add.u64 [%0], %1;" :: "l"(rap + (k >> 1) * 40 * ACC_PITCH + 64 + (k & 1) * 32), "l"(fx_pack(yf[0], fx_scale(msq))) : "memory");
            __threadfence();
#pragma unroll
            for (int k = 0; k < 2; k++) { asm volatile("red.relaxed.gpu.global.or.b64 [%0], 256;" :: "l"(rap + k * 40 * ACC_PITCH) : "memory"); yw[k] = 1; }
        };

        pass1();
        o_setup(IC<0>{});
        out_proj(IC<0>{});
        uint32_t c0;
        if (warp < 5) {
            mlp_part(IC<0>{});
            if (mlp != 96) {
#pragma unroll
                for (int k = 0; k < 2; k++) asm volatile("red.relaxed.gpu.global.add.u64 [%0], %1;" :: "l"(rap + k * 40 * ACC_PITCH), "l"(yw[k]) : "memory");
            }
            c0 = clk();
            stsf(sb + SM_ML + (lane & 15) * 4, cs1);
            TSTAMP(8);
            if (__any_sync(~0u, wide && mlp != 96)) {
                if (wide) {
                    send_wide();
#pragma unroll
                    for (int k = 0; k < 2; k++) asm volatile("red.relaxed.gpu.global.add.u64 [%0], 1;" :: "l"(rap + k * 40 * ACC_PITCH) : "memory");
                }
                __syncwarp();
            }
            fresh(); calc_offsets();
            load_wq();
        } else {
            bar_sync(0, 256);
            if (warp == 5 && elect()) {
                asm volatile("fence.proxy.async.shared::cta;" ::: "memory");
                if (W1AT0 == 4) issue_w(IC<0>{}, 0);
                issue_w(IC<0>{}, 1);
            }
            __syncwarp();
            fresh(); calc_offsets();
            load_wq();
#pragma unroll 1
            for (int ph = 0; ph < 3; ph++) {
                bar_sync(ph + 2, 256);
                c0 = clk();
                if (ph == 2) {
                    msq = sum5(ldsf(sb + SM_PART + 12), ldsf(sb + SM_PART + 268), ldsf(sb + SM_PART + 524), ldsf(sb + SM_PART + 780), ldsf(sb + SM_PART + 1036)) * (1.f / D_MODEL);
                    bar_arrive(5, 256);
                }
                if (!(NOWIN >> ph & 1) && elect()) {
                    asm volatile("fence.proxy.async.shared::cta;" ::: "memory");
                    const uint32_t gap = ph == 0 ? WG1 : ph == 1 ? WG2 : WG3;
                    uint32_t c1 = c0 + (ph == 0 ? WD1 : ph == 1 ? WD2 : 0) + (warp - 5) * gap;
#pragma unroll 1
                    for (int k = warp + (ph == 0 ? -5 : ph == 1 ? 9 : 1); k < (ph == 0 ? 9 : ph == 1 ? 20 : 14); k += 3, c1 += 3 * gap) {
                        const int i = ph == 0 && k >= 6 ? k + 23 : k;
                        const uint32_t bar = sb + SM_BAR + (i & 7) * 96 + 32 + (i & 24);
                        while ((int)(clk() - c1) < 0);
                        mbar_expect(bar, SUB);
                        tma3(sb + SM_RING + i * SUB, tmk + TM_V, 0,
                             rowc + (i & 7) * 8 + ((UC<SCH.st[0].unit | SCH.st[1].unit << 8 | SCH.st[2].unit << 16 | SCH.st[3].unit << 24>::value >> (i & 24)) & 15) * 256, bar, POL_FIRST);
                    }
                }
                __syncwarp();
            }
            c0 += PCD;
        }
        {
            constexpr IC<1> L{};
            fresh();
            const int lz = lane;
            const unsigned char* xa[2];
#pragma unroll
            for (int i = 0; i < 2; i++) {
                const int col = xcol(2 * i, lz & 3), cw = j40 + (col >> 2);
                xa[i] = pin(accg + ACC_BYTES + ((cw >> 2) + (col & 2) * 20) * ACC_PITCH + (cw & 3) * 8);
            }
            const uint32_t pst = pin(prow + ((lz >> 2) * 8 + (lz & 1) * 4) * 4);
            stsf(sb + SM_MSQ, msq);
            const float inv = shx(fx2_inv(msq), 0);
            if (!NWQ1) rap = pin(accg + ACC_BYTES + (c4() >> 2) * ACC_PITCH + (c4() & 3) * 8);
            fresh();
            if (!NWQ1) { maskA = pin(maskA); maskB = pin(maskB); }
            u64 w[3];
            uint32_t x2[3];
            auto xat = [&](int i) { return ((i & 2) ? xa[1] : xa[0]) + (i & 1) * 4 * ACC_PITCH; };
            if (warp < 5) {
                bar_sync(5, 256);
                if (DPRE) { while ((int)(clk() - c0) < WD4 + warp * WG4); if (warp < DPRE) refill2(IC<3>{}); }
            }
            while ((int)(clk() - c0) < ARDELAY);
#pragma unroll
            for (int i = 0; i < 3; i++) w[i] = ld_rlx(xat(i));
            if (warp < 5 && !(NOWIN & 8) && elect()) {
                if (DPOST) while ((int)(clk() - c0) < ARDELAY + DPOST);
                if (warp >= DPRE) issue_v(IC<3>{}, 0);
                if (warp < 4 && !P2LATE) issue_v(IC<2>{}, 4);
            }
            __syncwarp();
            fx2_wait<3, true>(xat, w, sb + SM_MSQ, inv, x2);
            TSTAMP(9);
            q_proj(L, x2, pst);
            pass2();
            out_proj(L);
            if (warp >= 5) {
                bar_arrive(0, 256);
                if ((W1AT1 == 6 || W2AT1 == 6) && warp == 5 && elect()) { if (W1AT1 == 6) issue_w(L, 0); if (W2AT1 == 6) issue_w(L, 1); }
                TDUMP();
                return;
            }
            mlp_part(L);
            u64 old[2];
            auto add = [&]() {
#pragma unroll
                for (int k = 0; k < 2; k++) asm volatile("atom.relaxed.gpu.global.add.u64 %0, [%1], %2;" : "=l"(old[k]) : "l"(rap + k * 40 * ACC_PITCH), "l"(yw[k]) : "memory");
            };
            add();
            uint32_t* op = reinterpret_cast<uint32_t*>(P.out) + 2 * c4();
            if (wide) { send_wide(); add(); }
            TSTAMP(18);
            CSTAMP(17, hi32(yw[1]));
            const float inv2 = fx2_inv(msq);
            const uint32_t ep1 = lds32(sb + SM_EPOCH) + 1;
            CSTAMP(18, lo32(old[0]) ^ lo32(old[1]));
#pragma unroll
            for (int k = 0; k < 2; k++) {
                yw[k] += old[k];
                asm volatile("{\n.reg .pred p;\nsetp.eq.u32 p, %2, 96;\n@p st.global.u32 [%0], %1;\n}"
                             :: "l"(op + k), "r"(pack_bf(fx2_lo(yw[k], inv2), fx2_hi(yw[k], inv2))), "r"(lo32(yw[k]) & 511) : "memory");
            }
            if ((lo32(yw[0]) & 255) == 96 && tid == 0) g_epoch = ep1;
            if ((lo32(yw[0]) | lo32(yw[1])) & 256) {
                __threadfence();
#pragma unroll 1
                for (int k = 0; k < 2; k++, yw[0] = yw[1]) if ((lo32(yw[0]) & 511) == 256 + 96) op[k] = fx2_wide(rap + k * 40 * ACC_PITCH, yw[0], msq);
            }
            TSTAMP(19);
            CSTAMP(19, lo32(yw[1]));
            TDUMP();
        }
    }
}

typedef CUresult (*EncodeFn)(CUtensorMap*, CUtensorMapDataType, cuuint32_t, void*, const cuuint64_t*, const cuuint64_t*, const cuuint32_t*,
                             const cuuint32_t*, CUtensorMapInterleave, CUtensorMapSwizzle, CUtensorMapL2promotion, CUtensorMapFloatOOBfill);

}

extern "C" void kernel_launch(void* const* d_in, const int* in_sizes, int n_in, void* d_out, int out_size) {
    (void)in_sizes; (void)n_in; (void)out_size;
    static EncodeFn enc = nullptr;
    if (!enc) {
        void* fn = nullptr;
        cudaDriverEntryPointQueryResult qr;
        cudaGetDriverEntryPoint("cuTensorMapEncodeTiled", &fn, cudaEnableDefault, &qr);
        enc = (EncodeFn)fn;
        cudaFuncSetAttribute(fused_kernel, cudaFuncAttributeMaxDynamicSharedMemorySize, SM_TOTAL);
    }
    Params P = {};
    auto map3 = [&](int m, int in, cuuint64_t d0, cuuint64_t d1, cuuint64_t d2, cuuint64_t s1, cuuint64_t s2, cuuint32_t b0, cuuint32_t b1, cuuint32_t b2,
                    CUtensorMapSwizzle sw, int promo) {
        const cuuint64_t dim[3] = {d0, d1, d2}, str[2] = {s1, s2};
        const cuuint32_t box[3] = {b0, b1, b2}, ones[3] = {1, 1, 1};
        enc(&P.tm[m], CU_TENSOR_MAP_DATA_TYPE_BFLOAT16, 3, d_in[in], dim, str, box, ones, CU_TENSOR_MAP_INTERLEAVE_NONE, sw, (CUtensorMapL2promotion)promo,
            CU_TENSOR_MAP_FLOAT_OOB_FILL_NONE);
    };
    map3(TM_KH, 1, 64, 3, NHEAD * SK, 128, DH * 2, 64, 3, 32, CU_TENSOR_MAP_SWIZZLE_128B, 0);
    map3(TM_VH, 2, 64, 3, NHEAD * SK, 128, DH * 2, 64, 3, 32, CU_TENSOR_MAP_SWIZZLE_128B, 0);
    map3(TM_VP, 2, 64, 3, NHEAD * SK, 128, DH * 2, PFW, 3, 32, CU_TENSOR_MAP_SWIZZLE_NONE, 0);
    map3(TM_V, 2, 64, 3, NHEAD * SK, 128, DH * 2, 64, 3, 8, CU_TENSOR_MAP_SWIZZLE_128B, 0);
    map3(TM_WO, 4, 32, 20, NHEAD * DH, 64, D_MODEL * 2, 32, 1, DH, CU_TENSOR_MAP_SWIZZLE_64B, PROMOW);
    map3(TM_WOP, 4, 32, 20, NHEAD * DH, 64, D_MODEL * 2, PFW, 1, DH, CU_TENSOR_MAP_SWIZZLE_NONE, 0);
    map3(TM_WQ, 3, 64, NHEAD * 3, D_MODEL, 128, NHEAD * DH * 2, 64, 3, 8, CU_TENSOR_MAP_SWIZZLE_128B, 0);
    map3(TM_W1, 6, DFF, 128, 5, DFF * 2, DFF * 256, 16, 128, 5, CU_TENSOR_MAP_SWIZZLE_32B, PROMO1);
    map3(TM_W2, 8, 64, 10, DFF, 128, D_MODEL * 2, 64, 10, 16, CU_TENSOR_MAP_SWIZZLE_128B, 0);
    P.x = (const __nv_bfloat16*)d_in[0];
    P.k = (const __nv_bfloat16*)d_in[1];
    P.b1 = (const __nv_bfloat16*)d_in[7];
    P.b2 = (const __nv_bfloat16*)d_in[9];
    P.out = (__nv_bfloat16*)d_out;
    for (int i = 0; i < 64; i++) P.tile[i] = make_uint4(SCH.tile[i][0], SCH.tile[i][1], SCH.tile[i][2], 0);
    fused_kernel<<<NCTA + 1, NTHR, SM_TOTAL, cudaStreamPerThread>>>(P);
}
```

```cpp
#include <cuda_runtime.h>
#include <cuda_bf16.h>
#include <cuda.h>
#include <stdint.h>

namespace {

constexpr int D_MODEL = 640, NHEAD = 32, SK = 32768, DH = 192, WIN = 4096, DFF = 1536;
constexpr int NCTA = 128, NTHR = 256;
constexpr int TILE = 64 * DH * 2;
constexpr int HALF = TILE / 2;
constexpr int SUB = 8 * DH * 2;
constexpr int SM_RING = 4 * TILE;
constexpr int SM_W2 = SM_RING + 20480, SM_W1 = SM_W2 + 20480;
constexpr int SM_WQR = 6 * TILE + HALF, SM_WQ = 7 * TILE;
constexpr int SM_PART = 9 * TILE;
constexpr int SM_EXC = SM_PART + 6144;
constexpr int SM_SC = SM_EXC + 1024;
constexpr int SM_BAR = SM_SC + 1024;
constexpr int SM_VEC = SM_BAR + 768;
constexpr int SM_CS = SM_VEC + 384;
constexpr int SM_FAC = SM_CS + 768;
constexpr int SM_ML = SM_FAC + 32;
constexpr int SM_B1 = SM_ML + 64;
constexpr int SM_STAT = SM_B1 + 64;
constexpr int NCB = 27;
constexpr int CB_WO = 18, CB_W1 = 23, CB_W2 = 24, CB_SNAP = 25, CB_REL = 26;
constexpr int SM_CBAR = SM_STAT + 40;
constexpr int SM_CNT = SM_CBAR + NCB * 8;
constexpr int SM_EPOCH = SM_CNT + NCB * 8;
constexpr int SM_FXS = SM_EPOCH + 4;
constexpr int SM_T0 = SM_FXS + 4;
constexpr int SM_MSQ = SM_T0 + 4;
constexpr int SM_M1 = SM_MSQ + 4;
constexpr int SM_TS = SM_M1 + 4;
constexpr int SM_TOTAL = 232448;
static_assert(SM_TS + 320 <= SM_TOTAL, "smem");
constexpr int NEXC = 16;

constexpr int SPIN = 1 << 20;
enum { TM_KH = 0, TM_VH = 1, TM_WO = 2, TM_VP = 3, TM_WOP = 4, TM_V = 5, TM_WQ = 6, TM_W1 = 7, TM_W2 = 8 };
constexpr uint32_t POL_NORMAL = 0x16F00000u, POL_FIRST = 0x12F00000u;

#define PACE 980
#define PACE0 1600
#define NI0 1
#define NI1 6
#define ETRIG 0x54321000
#define LATEAT 5
#define HWAT 12
#define PFREE 66
#define W1AT0 3
#define W1AT1 3
#define AR1D 300
#define LAG0 12
#define NMMA 2
#define M1AT 1
#define M1P 3
#define NWO1 4
#define WG2 90
#define WG3 120
#define WD4 250
#define WG4 70
#define NWQ1 0
#define P4AT 0
#define P2LATE 0
#define RWAT 1
#define W2AT1 6
#define PCD 150
#define NOWIN 0
#define DPRE 0
#define DPOST 200
#define NIM 4
#define PACES PACE0
#define JP2 54
#define PACE2 0
#define WD2 0
#define W2PRE 2
#define OPOLL1 2
#define W2ONE 1
#define W1ONE 1
#define SNAPAT 1
#define DMASK 0x0
#define WOKEEP 0x1f
#define VORD2 0x7685943a2b1cd0efull
#define VTRIG 0xba73210
#define WOAT 13
#define PARKS 0x95
#define VSLOT 0x1087654321087654ull
#define OPOLL 2
#define S0EARLY 1
#define NPRE 2
#define ARDELAY 1000
#define QDELAY 0
#define CMAP 0
#define PFW 8u
#define PUBAT 28
#define HW0 30
#define HW1 31
#define FX2LIM 524288.f
#define PROMOW 2
#define PROMO1 0
#define WD1 300
#define WG1 140
#define WPOL POL_NORMAL

constexpr uint32_t G_A = 1u << 28, G_B = 1u << 29, G_C = 1u << 30;
__host__ __device__ constexpr int ring_hs(int j) { return (j + 4) % 5; }
__host__ __device__ constexpr uint32_t load_word(int j) {
    if (j >= 64) return (uint32_t)(j - 64) << 20 | (SM_RING + ring_hs(j) * HALF) | TM_WO << 8 | (CB_WO + j - 64) << 3 | 2 | !(WOKEEP >> (j - 64) & 1);
    const int e = j >> 1, isv = e >= 16, unit = e & 15;
    return (uint32_t)(unit * 256 + (j & 1) * 32) << 20 | (j < 8 ? j * HALF : SM_RING + ring_hs(j) * HALF) | isv << 8 | (j < 8 ? 10 + j : (j - 8) % 10) << 3 | 2
           | (!isv || (DMASK >> unit & 1));
}
__host__ __device__ constexpr int popc(int v) { return v ? (v & 1) + popc(v >> 1) : 0; }
constexpr int NPARK = popc(PARKS);
constexpr int SM_SNAP = SM_RING + ring_hs(12) * HALF, SM_CSP = SM_RING + ring_hs(11) * HALF;
struct Step { int unit, slot, par, next, mma0, nmma; };
struct Sched { uint32_t tile[64][3]; Step st[16]; };
constexpr Sched make_sched() {
    Sched s{};
    for (int j = 0; j < 64; j++) {
        const int e = j >> 1;
        const uint32_t d = load_word(j);
        uint32_t w = (uint32_t)(j < 8 ? 0 : (j - 8) / 10 & 1) << 31 | (e & 15) * 4 << 20 | ((d & 0x3f000) - (j & 1) * HALF) | (d & 0xf8);
        if (e == PUBAT || e == SNAPAT) w |= G_A;
        if (e == HW0 || e == 4) w |= G_B;
        if ((e >= LATEAT && e < LATEAT + 4) || e == HW1) w |= G_C;
        s.tile[j][0] = w;
    }
    for (int j = NI1; j < 69; j++) {
        if (j == 12) continue;
        const int at = j < 12 ? (ETRIG >> (4 * (j - 4)) & 15) : j - 5;
        s.tile[at][1] = load_word(j);
        s.tile[at][2] = j >= PFREE ? 0 : PACE0 + j * PACE / 2 + (j > JP2 ? (j - JP2) * PACE2 : 0);
    }
    int done = 0;
    for (int p = 0; p < 16; p++) {
        Step& c = s.st[p];
        c.unit = (int)(VORD2 >> (4 * p) & 15); c.slot = (int)(VSLOT >> (4 * p) & 15); c.par = p >= 9; c.next = -1;
        c.mma0 = done;
        if (p >= NPARK) { const int avail = p - done + (p >= LAG0); c.nmma = p == 15 ? 16 - done : (avail < NMMA ? avail : NMMA); done += c.nmma; }
    }
    for (int p = 9; p < 16; p++) s.st[VTRIG >> (4 * (p - 9)) & 15].next = p;
    return s;
}
constexpr Sched SCH = make_sched();
__host__ __device__ constexpr int kunit(int o) { return o < 5 ? o + 11 : o == 5 ? 10 : o - 6; }

template <int I> struct IC { static constexpr int value = I; };
template <uint32_t I> struct UC { static constexpr uint32_t value = I; };
template <int A, int B, class F> __device__ __forceinline__ void static_for(F&& f) {
    if constexpr (A < B) { f(IC<A>{}); static_for<A + 1, B>(f); }
}

struct Params {
    CUtensorMap tm[9];
    const __nv_bfloat16 *x, *k, *b1, *b2, *w1;
    __nv_bfloat16* out;
    uint4 tile[66];
};

typedef unsigned long long u64;
constexpr int ACC_PITCH = 256;
constexpr int ACC_BYTES = 80 * ACC_PITCH;
__device__ __align__(1024) unsigned char g_acc[4 * ACC_BYTES];
__device__ __align__(1024) u64 g_l0[NCTA][384];
__device__ __align__(1024) u64 g_ll[2][NCTA][256];
__device__ unsigned g_epoch;
__device__ __align__(128) unsigned g_zflag;
#define TSTAMP(i)
#define TSTAMP2(i)
#define TSTAMPL(i)
#define TDUMP()
#define CSTAMP(i, x)
#define TRACE(i)

__device__ __forceinline__ void mbar_wait(uint32_t bar, uint32_t parity) {
    asm volatile("{\n.reg .pred p, q;\n.reg .u32 n;\nmov.u32 n, 0;\n"
                 "LOOP:\nmbarrier.try_wait.parity.shared::cta.b64 p, [%0], %1;\n"
                 "add.u32 n, n, 1;\nsetp.lt.and.u32 q, n, 0x100000, !p;\n@q bra.uni LOOP;\n}"
                 :: "r"(bar), "r"(parity) : "memory");
}
__device__ __forceinline__ bool mbar_test(uint32_t bar, uint32_t parity) {
    uint32_t r;
    asm volatile("{\n.reg .pred p;\nmbarrier.test_wait.parity.shared::cta.b64 p, [%1], %2;\nselp.u32 %0, 1, 0, p;\n}" : "=r"(r) : "r"(bar), "r"(parity) : "memory");
    return __all_sync(~0u, r);
}
__device__ __forceinline__ bool elect() {
    uint32_t r;
    asm volatile("{\n.reg .pred p;\nelect.sync _|p, 0xffffffff;\nselp.u32 %0, 1, 0, p;\n}" : "=r"(r));
    return r != 0;
}
__device__ __forceinline__ void mbar_expect(uint32_t bar, uint32_t bytes) {
    asm volatile("mbarrier.arrive.expect_tx.shared::cta.b64 _, [%0], %1;" :: "r"(bar), "r"(bytes) : "memory");
}
__device__ __forceinline__ uint4 lds128(uint32_t a) {
    uint4 v; asm volatile("ld.shared.v4.u32 {%0,%1,%2,%3}, [%4];" : "=r"(v.x), "=r"(v.y), "=r"(v.z), "=r"(v.w) : "r"(a) : "memory"); return v;
}
__device__ __forceinline__ uint4 ldsm_t(uint32_t a) {
    uint4 v; asm volatile("ldmatrix.sync.aligned.m8n8.x4.trans.shared.b16 {%0,%1,%2,%3}, [%4];" : "=r"(v.x), "=r"(v.y), "=r"(v.z), "=r"(v.w) : "r"(a) : "memory"); return v;
}
__device__ __forceinline__ uint2 lds64(uint32_t a) {
    uint2 v; asm volatile("ld.shared.v2.u32 {%0,%1}, [%2];" : "=r"(v.x), "=r"(v.y) : "r"(a) : "memory"); return v;
}
__device__ __forceinline__ float2 lds64f(uint32_t a) { const uint2 v = lds64(a); return make_float2(__uint_as_float(v.x), __uint_as_float(v.y)); }
__device__ __forceinline__ uint32_t lds32(uint32_t a) {
    uint32_t v; asm volatile("ld.shared.u32 %0, [%1];" : "=r"(v) : "r"(a) : "memory"); return v;
}
__device__ __forceinline__ float ldsf(uint32_t a) { return __uint_as_float(lds32(a)); }
__device__ __forceinline__ void sts32(uint32_t a, uint32_t v) { asm volatile("st.shared.u32 [%0], %1;" :: "r"(a), "r"(v) : "memory"); }
__device__ __forceinline__ void stsf(uint32_t a, float v) { sts32(a, __float_as_uint(v)); }
__device__ __forceinline__ void sts16(uint32_t a, uint32_t v) { asm volatile("st.shared.u16 [%0], %1;" :: "r"(a), "h"((uint16_t)v) : "memory"); }
__device__ __forceinline__ void sts64(uint32_t a, uint32_t x, uint32_t y) { asm volatile("st.shared.v2.u32 [%0], {%1,%2};" :: "r"(a), "r"(x), "r"(y) : "memory"); }
__device__ __forceinline__ void sts64f(uint32_t a, float x, float y) { sts64(a, __float_as_uint(x), __float_as_uint(y)); }
__device__ __forceinline__ void sts128f(uint32_t a, float x, float y, float z, float w) {
    asm volatile("st.shared.v4.f32 [%0], {%1,%2,%3,%4};" :: "r"(a), "f"(x), "f"(y), "f"(z), "f"(w) : "memory");
}
__device__ __forceinline__ void mma(float (&c)[4], const uint4& a, uint32_t b0, uint32_t b1) {
    asm volatile("mma.sync.aligned.m16n8k16.row.col.f32.bf16.bf16.f32 {%0,%1,%2,%3}, {%4,%5,%6,%7}, {%8,%9}, {%0,%1,%2,%3};"
                 : "+f"(c[0]), "+f"(c[1]), "+f"(c[2]), "+f"(c[3]) : "r"(a.x), "r"(a.y), "r"(a.z), "r"(a.w), "r"(b0), "r"(b1));
}
__device__ __forceinline__ u64 ld_rlx(const void* p) {
    u64 a; asm volatile("ld.relaxed.gpu.global.u64 %0, [%1];" : "=l"(a) : "l"(p) : "memory"); return a;
}
__device__ __forceinline__ void ld_rlx2(const void* p, u64& a, u64& b) {
    asm volatile("ld.relaxed.gpu.global.v2.u64 {%0,%1}, [%2];" : "=l"(a), "=l"(b) : "l"(p) : "memory");
}
__device__ __forceinline__ void st_rlx(void* p, u64 a) { asm volatile("st.relaxed.gpu.global.u64 [%0], %1;" :: "l"(p), "l"(a) : "memory"); }
__device__ __forceinline__ u64 ll_pack(float v, uint32_t tag) { return ((u64)tag << 32) | __float_as_uint(v); }
__device__ __forceinline__ float ll_val(u64 w) { return __uint_as_float((uint32_t)w); }
__device__ __forceinline__ uint32_t ll_tag(u64 w) { return (uint32_t)(w >> 32); }
__device__ __forceinline__ float bf_lo(uint32_t u) { return __uint_as_float(u << 16); }
__device__ __forceinline__ float bf_hi(uint32_t u) { return __uint_as_float(u & 0xffff0000u); }
__device__ __forceinline__ uint32_t pack_bf(float lo, float hi) {
    uint32_t r; asm("cvt.rn.bf16x2.f32 %0, %1, %2;" : "=r"(r) : "f"(hi), "f"(lo)); return r;
}
__device__ __forceinline__ float ex2(float v) { float r; asm("ex2.approx.ftz.f32 %0, %1;" : "=f"(r) : "f"(v)); return r; }
__device__ __forceinline__ float rcp(float v) { float r; asm("rcp.approx.ftz.f32 %0, %1;" : "=f"(r) : "f"(v)); return r; }
__device__ __forceinline__ float rsq(float v) { float r; asm("rsqrt.approx.ftz.f32 %0, %1;" : "=f"(r) : "f"(v)); return r; }
__device__ __forceinline__ void bar_sync(int id, int n) { asm volatile("bar.sync %0, %1;" :: "r"(id), "r"(n) : "memory"); }
__device__ __forceinline__ uint32_t clk() { uint32_t c; asm volatile("mov.u32 %0, %clock;" : "=r"(c)); return c; }
__device__ __forceinline__ uint32_t pin(uint32_t v) { return __shfl_xor_sync(~0u, v, 0); }
__device__ __forceinline__ float shx(float v, int o) { return __shfl_xor_sync(~0u, v, o); }

__device__ __forceinline__ u64 fx_pack(float v, float scale) { return ((u64)__float2ll_rn(v * scale) & ~255ull) | 1ull; }
__device__ __forceinline__ float fx_scale(float meansq) {
    const int e = max(((int)(__float_as_uint(meansq) >> 23) - 127) >> 1, -6);
    return __uint_as_float((uint32_t)(127 + 32 - e) << 23);
}
__device__ __forceinline__ float fx_inv(float scale) { return __uint_as_float((254u << 23) - __float_as_uint(scale)); }
__device__ __forceinline__ uint32_t lo32(u64 w) { uint32_t l; asm("mov.b64 {%0, _}, %1;" : "=r"(l) : "l"(w)); return l; }
__device__ __forceinline__ int hi32(u64 w) { int h; asm("mov.b64 {_, %0}, %1;" : "=r"(h) : "l"(w)); return h; }
__device__ __forceinline__ float fx_val(u64 w) { return (float)hi32(w) * 4294967296.f + (float)lo32(w); }
constexpr float FX2_ONE = 12582912.f;
__device__ __forceinline__ float fx2_scale(float meansq) { return __uint_as_float((uint32_t)(127 + 16 - max(((int)(__float_as_uint(meansq) >> 23) - 127) >> 1, -100)) << 23); }
__device__ __forceinline__ u64 fx2_pack(float a, float b) {
    const uint32_t lo = __float_as_uint(a) * 512u + (1u - 0x4b400000u * 512u);
    return lo | (u64)(__float_as_uint(b) * 16u - 0x4b400000u * 16u + (uint32_t)((int)lo >> 31)) << 32;
}
__device__ __forceinline__ float fx2_lo(u64 w, float inv) { return (float)(int)(__funnelshift_r(lo32(w), hi32(w), 4) & ~31u) * (inv * 0.5f); }
__device__ __forceinline__ float fx2_hi(u64 w, float inv) { return (float)((hi32(w) + 8) & ~15) * inv; }
__device__ __forceinline__ float fx2_inv(float meansq) { return fx_inv(fx2_scale(meansq)) * 0.0625f; }
__device__ __forceinline__ uint32_t fx2_wide(const unsigned char* a, u64 w, float meansq) {
    const float inv = fx_inv(fx_scale(meansq));
    return pack_bf(fx2_lo(w, fx2_inv(meansq)) + fx_val(ld_rlx(a + 64)) * inv, fx2_hi(w, fx2_inv(meansq)) + fx_val(ld_rlx(a + 96)) * inv);
}
template <int N, bool LOOK, class A> __device__ __forceinline__ void fx2_wait(A a, u64 (&w)[N], uint32_t msqa, float inv, uint32_t (&x)[N]) {
    int it = 0;
    uint32_t miss = lds32(msqa + 4);
    do {
        if (__all_sync(~0u, !(miss & 96))) {
            __threadfence();
#pragma unroll
            for (int i = 0; i < N; i++) x[i] = 0;
#pragma unroll 1
            for (int i = 0; i < 2 * N; i++) {
                const u64 v = ld_rlx(a(i >> 1));
                const float y = ((i & 1) ? fx2_hi(v, inv) : fx2_lo(v, inv)) + fx_val(ld_rlx(a(i >> 1) + 64 + (i & 1) * 32)) * fx_inv(fx_scale(ldsf(msqa)));
#pragma unroll
                for (int k = 0; k < N; k++) x[k] = __funnelshift_r(x[k], k + 1 < N ? x[k + 1] : pack_bf(y, y), 16);
            }
            return;
        }
        if (!LOOK || it) {
#pragma unroll
            for (int i = 0; i < N; i++) w[i] = ld_rlx(a(i));
        }
        uint32_t all = lo32(w[0]), any = all;
#pragma unroll
        for (int i = 1; i < N; i++) { all &= lo32(w[i]); any |= lo32(w[i]); }
        miss = (~all & 96) | (any & 256);
    } while (__any_sync(~0u, miss) & (++it < SPIN));
#pragma unroll
    for (int i = 0; i < N; i++) x[i] = pack_bf(fx2_lo(w[i], inv), fx2_hi(w[i], inv));
}
__device__ __forceinline__ void st_rlx_if(bool p, void* a, u64 v) {
    asm volatile("{\n.reg .pred p;\nsetp.ne.u32 p, %2, 0;\n@p st.relaxed.gpu.global.u64 [%0], %1;\n}" :: "l"(a), "l"(v), "r"((uint32_t)p) : "memory");
}
__device__ __forceinline__ void sts128f(uint32_t a, const float (&v)[4]) { sts128f(a, v[0], v[1], v[2], v[3]); }
__device__ __forceinline__ void bar_arrive(int id, int n) { asm volatile("bar.arrive %0, %1;" :: "r"(id), "r"(n) : "memory"); }
template <class T> __device__ __forceinline__ T* pin(T* p) { return reinterpret_cast<T*>(__shfl_xor_sync(~0u, (u64)p, 0)); }

__device__ __forceinline__ void tma3(uint32_t dst, const CUtensorMap* tm, int c1, int c2, uint32_t bar, uint32_t pol) {
    asm volatile("cp.async.bulk.tensor.3d.shared::cluster.global.mbarrier::complete_tx::bytes.L2::cache_hint [%0], [%1, {%2, %3, %4}], [%5], %6;"
                 :: "r"(dst), "l"(tm), "r"(0), "r"(c1), "r"(c2), "r"(bar), "l"((u64)pol << 32) : "memory");
}
__device__ __forceinline__ void tma3_pf(const CUtensorMap* tm, int c1, int c2, uint32_t pol) {
    asm volatile("cp.async.bulk.prefetch.tensor.3d.L2.global.tile.L2::cache_hint [%0, {%1, %2, %3}], %4;"
                 :: "l"(tm), "r"(0), "r"(c1), "r"(c2), "l"((u64)pol << 32) : "memory");
}
__device__ __forceinline__ void issue_half(uint32_t d, uint32_t sb, int rowc, int cta, const CUtensorMap* tm0) {
    const uint32_t bar = sb + SM_CBAR + (d & 0xf8);
    const CUtensorMap* tm = tm0 + ((d >> 8) & 3);
    const int c1 = (d & 0x200) ? (cta & 3) + 4 * (d >> 20) : 0, c2 = (d & 0x200) ? (cta >> 2) * DH : rowc + (d >> 20);
    mbar_expect(bar, HALF);
    tma3(sb + (d & 0x3f000), tm, c1, c2, bar, POL_FIRST);
    if (!(d & 1)) tma3_pf(tm + 2, c1, c2, POL_NORMAL);
}
__device__ __forceinline__ uint32_t cnt_inc(uint32_t a, uint32_t last) {
    uint32_t old; asm volatile("atom.relaxed.cta.shared.inc.u32 %0, [%1], %2;" : "=r"(old) : "r"(a), "r"(last) : "memory"); return old;
}
__device__ __forceinline__ void wait_until(uint32_t due) {
#pragma unroll 1
    for (int it = 0; it < 4096; it++) { uint32_t now; asm volatile("mov.u32 %0, %globaltimer_lo;" : "=r"(now)); if ((int)(now - due) >= 0) break; }
}
__device__ __forceinline__ uint32_t bf2_mul(uint32_t a, uint32_t b) { uint32_t r; asm("mul.rn.bf16x2 %0, %1, %2;" : "=r"(r) : "r"(a), "r"(b)); return r; }
__device__ __forceinline__ uint32_t bf2_fma(uint32_t a, uint32_t b, uint32_t c) { uint32_t r; asm("fma.rn.bf16x2 %0, %1, %2, %3;" : "=r"(r) : "r"(a), "r"(b), "r"(c)); return r; }
__device__ __forceinline__ uint32_t bf2_amax(uint32_t a, uint32_t b) { uint32_t r; asm("max.NaN.xorsign.abs.bf16x2 %0, %1, %2;" : "=r"(r) : "r"(a), "r"(b)); return r; }
__device__ __forceinline__ uint4 k_unpack(uint32_t l0, uint32_t l1, uint32_t h, uint32_t m1) {
    const uint32_t ha = h & 0x87878787u, hc = ha * m1 + h, hb = __funnelshift_l(hc, hc, 4);
    return make_uint4(__byte_perm(l0, ha, 0x5140), __byte_perm(l0, ha, 0x7362), __byte_perm(l1, hb, 0x5140), __byte_perm(l1, hb, 0x7362));
}
#define KR4(u, i) "+r"(kr[u][i].x), "+r"(kr[u][i].y), "+r"(kr[u][i].z), "+r"(kr[u][i].w)
#define KR6(u) KR4(u, 0), KR4(u, 1), KR4(u, 2), KR4(u, 3), KR4(u, 4), KR4(u, 5)
__device__ __forceinline__ void k_keep(uint4 (&kr)[8][6], const uint32_t (&c)[18], int e, uint32_t a) {
    asm volatile("{\nKT: .branchtargets K0, K1, K2, K3, K4, K5, K6, K7, K8, K9, K10, K11, K12, K13, K14, K15;\nbrx.idx.uni %210, KT;\n"
                 "K0: mov.b32 %12, %192; mov.b32 %13, %193; mov.b32 %14, %194; mov.b32 %15, %195; mov.b32 %16, %196; mov.b32 %17, %197; mov.b32 %18, %198; mov.b32 %19, %199; mov.b32 %20, %200; mov.b32 %21, %201; mov.b32 %22, %202; mov.b32 %23, %203; mov.b32 %24, %204; mov.b32 %25, %205; mov.b32 %26, %206; mov.b32 %27, %207; mov.b32 %28, %208; mov.b32 %29, %209; bra.uni KE;\n"
                 "K1: mov.b32 %30, %192; mov.b32 %31, %193; mov.b32 %32, %194; mov.b32 %33, %195; mov.b32 %34, %196; mov.b32 %35, %197; mov.b32 %36, %198; mov.b32 %37, %199; mov.b32 %38, %200; mov.b32 %39, %201; mov.b32 %40, %202; mov.b32 %41, %203; mov.b32 %42, %204; mov.b32 %43, %205; mov.b32 %44, %206; mov.b32 %45, %207; mov.b32 %46, %208; mov.b32 %47, %209; bra.uni KE;\n"
                 "K2: mov.b32 %48, %192; mov.b32 %49, %193; mov.b32 %50, %194; mov.b32 %51, %195; mov.b32 %52, %196; mov.b32 %53, %197; mov.b32 %54, %198; mov.b32 %55, %199; mov.b32 %56, %200; mov.b32 %57, %201; mov.b32 %58, %202; mov.b32 %59, %203; mov.b32 %60, %204; mov.b32 %61, %205; mov.b32 %62, %206; mov.b32 %63, %207; mov.b32 %64, %208; mov.b32 %65, %209; bra.uni KE;\n"
                 "K3: mov.b32 %66, %192; mov.b32 %67, %193; mov.b32 %68, %194; mov.b32 %69, %195; mov.b32 %70, %196; mov.b32 %71, %197; mov.b32 %72, %198; mov.b32 %73, %199; mov.b32 %74, %200; mov.b32 %75, %201; mov.b32 %76, %202; mov.b32 %77, %203; mov.b32 %78, %204; mov.b32 %79, %205; mov.b32 %80, %206; mov.b32 %81, %207; mov.b32 %82, %208; mov.b32 %83, %209; bra.uni KE;\n"
                 "K4: mov.b32 %84, %192; mov.b32 %85, %193; mov.b32 %86, %194; mov.b32 %87, %195; mov.b32 %88, %196; mov.b32 %89, %197; mov.b32 %90, %198; mov.b32 %91, %199; mov.b32 %92, %200; mov.b32 %93, %201; mov.b32 %94, %202; mov.b32 %95, %203; mov.b32 %96, %204; mov.b32 %97, %205; mov.b32 %98, %206; mov.b32 %99, %207; mov.b32 %100, %208; mov.b32 %101, %209; bra.uni KE;\n"
                 "K5: mov.b32 %102, %192; mov.b32 %103, %193; mov.b32 %104, %194; mov.b32 %105, %195; mov.b32 %106, %196; mov.b32 %107, %197; mov.b32 %108, %198; mov.b32 %109, %199; mov.b32 %110, %200; mov.b32 %111, %201; mov.b32 %112, %202; mov.b32 %113, %203; mov.b32 %114, %204; mov.b32 %115, %205; mov.b32 %116, %206; mov.b32 %117, %207; mov.b32 %118, %208; mov.b32 %119, %209; bra.uni KE;\n"
                 "K6: mov.b32 %120, %192; mov.b32 %121, %193; mov.b32 %122, %194; mov.b32 %123, %195; mov.b32 %124, %196; mov.b32 %125, %197; mov.b32 %126, %198; mov.b32 %127, %199; mov.b32 %128, %200; mov.b32 %129, %201; mov.b32 %130, %202; mov.b32 %131, %203; mov.b32 %132, %204; mov.b32 %133, %205; mov.b32 %134, %206; mov.b32 %135, %207; mov.b32 %136, %208; mov.b32 %137, %209; bra.uni KE;\n"
                 "K7: mov.b32 %138, %192; mov.b32 %139, %193; mov.b32 %140, %194; mov.b32 %141, %195; mov.b32 %142, %196; mov.b32 %143, %197; mov.b32 %144, %198; mov.b32 %145, %199; mov.b32 %146, %200; mov.b32 %147, %201; mov.b32 %148, %202; mov.b32 %149, %203; mov.b32 %150, %204; mov.b32 %151, %205; mov.b32 %152, %206; mov.b32 %153, %207; mov.b32 %154, %208; mov.b32 %155, %209; bra.uni KE;\n"
                 "K8: mov.b32 %156, %192; mov.b32 %157, %193; mov.b32 %158, %194; mov.b32 %159, %195; mov.b32 %160, %196; mov.b32 %161, %197; mov.b32 %162, %198; mov.b32 %163, %199; mov.b32 %164, %200; mov.b32 %165, %201; mov.b32 %166, %202; mov.b32 %167, %203; mov.b32 %168, %204; mov.b32 %169, %205; mov.b32 %170, %206; mov.b32 %171, %207; mov.b32 %172, %208; mov.b32 %173, %209; bra.uni KE;\n"
                 "K9: mov.b32 %174, %192; mov.b32 %175, %193; mov.b32 %176, %194; mov.b32 %177, %195; mov.b32 %178, %196; mov.b32 %179, %197; mov.b32 %180, %198; mov.b32 %181, %199; mov.b32 %182, %200; mov.b32 %183, %201; mov.b32 %184, %202; mov.b32 %185, %203; mov.b32 %186, %204; mov.b32 %187, %205; mov.b32 %188, %206; mov.b32 %189, %207; mov.b32 %190, %208; mov.b32 %191, %209; bra.uni KE;\n"
                 "K10: st.shared.v2.b32 [%211+75784], {%192, %193}; st.shared.v2.b32 [%211+76288], {%194, %195}; st.shared.v2.b32 [%211+76296], {%196, %197}; mov.b32 %0, %198; mov.b32 %1, %199; mov.b32 %2, %200; mov.b32 %3, %201; mov.b32 %4, %202; mov.b32 %5, %203; mov.b32 %6, %204; mov.b32 %7, %205; mov.b32 %8, %206; mov.b32 %9, %207; mov.b32 %10, %208; mov.b32 %11, %209; bra.uni KE;\n"
                 "K11: st.shared.v2.b32 [%211+0], {%192, %193}; st.shared.v2.b32 [%211+8], {%194, %195}; st.shared.v2.b32 [%211+512], {%196, %197}; st.shared.v2.b32 [%211+520], {%198, %199}; st.shared.v2.b32 [%211+1024], {%200, %201}; st.shared.v2.b32 [%211+1032], {%202, %203}; st.shared.v2.b32 [%211+1536], {%204, %205}; st.shared.v2.b32 [%211+1544], {%206, %207}; st.shared.v2.b32 [%211+2048], {%208, %209}; bra.uni KE;\n"
                 "K12: st.shared.v2.b32 [%211+2056], {%192, %193}; st.shared.v2.b32 [%211+2560], {%194, %195}; st.shared.v2.b32 [%211+2568], {%196, %197}; st.shared.v2.b32 [%211+24576], {%198, %199}; st.shared.v2.b32 [%211+24584], {%200, %201}; st.shared.v2.b32 [%211+25088], {%202, %203}; st.shared.v2.b32 [%211+25096], {%204, %205}; st.shared.v2.b32 [%211+25600], {%206, %207}; st.shared.v2.b32 [%211+25608], {%208, %209}; bra.uni KE;\n"
                 "K13: st.shared.v2.b32 [%211+26112], {%192, %193}; st.shared.v2.b32 [%211+26120], {%194, %195}; st.shared.v2.b32 [%211+26624], {%196, %197}; st.shared.v2.b32 [%211+26632], {%198, %199}; st.shared.v2.b32 [%211+27136], {%200, %201}; st.shared.v2.b32 [%211+27144], {%202, %203}; st.shared.v2.b32 [%211+49152], {%204, %205}; st.shared.v2.b32 [%211+49160], {%206, %207}; st.shared.v2.b32 [%211+49664], {%208, %209}; bra.uni KE;\n"
                 "K14: st.shared.v2.b32 [%211+49672], {%192, %193}; st.shared.v2.b32 [%211+50176], {%194, %195}; st.shared.v2.b32 [%211+50184], {%196, %197}; st.shared.v2.b32 [%211+50688], {%198, %199}; st.shared.v2.b32 [%211+50696], {%200, %201}; st.shared.v2.b32 [%211+51200], {%202, %203}; st.shared.v2.b32 [%211+51208], {%204, %205}; st.shared.v2.b32 [%211+51712], {%206, %207}; st.shared.v2.b32 [%211+51720], {%208, %209}; bra.uni KE;\n"
                 "K15: st.shared.v2.b32 [%211+73728], {%192, %193}; st.shared.v2.b32 [%211+73736], {%194, %195}; st.shared.v2.b32 [%211+74240], {%196, %197}; st.shared.v2.b32 [%211+74248], {%198, %199}; st.shared.v2.b32 [%211+74752], {%200, %201}; st.shared.v2.b32 [%211+74760], {%202, %203}; st.shared.v2.b32 [%211+75264], {%204, %205}; st.shared.v2.b32 [%211+75272], {%206, %207}; st.shared.v2.b32 [%211+75776], {%208, %209}; \nKE:\n}"
                 : KR6(0), KR6(1), KR6(2), KR6(3), KR6(4), KR6(5), KR6(6), KR6(7)
                 : "r"(c[0]), "r"(c[1]), "r"(c[2]), "r"(c[3]), "r"(c[4]), "r"(c[5]), "r"(c[6]), "r"(c[7]), "r"(c[8]), "r"(c[9]), "r"(c[10]), "r"(c[11]), "r"(c[12]), "r"(c[13]), "r"(c[14]), "r"(c[15]), "r"(c[16]), "r"(c[17]), "r"(e), "r"(a) : "memory");
}
template <int K> __device__ __forceinline__ uint32_t& word(uint4& v) { if constexpr (K == 0) return v.x; else if constexpr (K == 1) return v.y; else if constexpr (K == 2) return v.z; else return v.w; }
__device__ __forceinline__ void add_if(bool p, float& d, float a, float b) {
    asm volatile("{\n.reg .pred p;\nsetp.ne.u32 p, %3, 0;\n@p add.f32 %0, %1, %2;\n}" : "+f"(d) : "f"(a), "f"(b), "r"((uint32_t)p));
}
__device__ __forceinline__ float warp_max(float v) {
#pragma unroll
    for (int o = 16; o; o >>= 1) v = fmaxf(v, shx(v, o));
    return v;
}
__device__ __forceinline__ float warp_sum(float v) {
#pragma unroll
    for (int o = 16; o; o >>= 1) v += shx(v, o);
    return v;
}
template <int PITCH> __device__ __forceinline__ void ll_look(const u64* buf, u64 (&w)[4]) {
#pragma unroll
    for (int i = 0; i < 4; i++) w[i] = ld_rlx(buf + i * PITCH);
}
template <int PITCH> __device__ __forceinline__ float ll_gather(const u64* buf, uint32_t tag, u64 (&w)[4]) {
    auto miss = [&]() { return __any_sync(~0u, ((ll_tag(w[0]) ^ tag) | (ll_tag(w[1]) ^ tag)) | ((ll_tag(w[2]) ^ tag) | (ll_tag(w[3]) ^ tag))); };
    int it = 0;
    goto check;
again:
    ll_look<PITCH>(buf, w);
check:
    if (miss() & (++it < SPIN)) goto again;
    return (ll_val(w[0]) + ll_val(w[1])) + (ll_val(w[2]) + ll_val(w[3]));
}
__device__ __forceinline__ float sum8(uint32_t a, int pitch) {
    float s[8];
#pragma unroll
    for (int w = 0; w < 8; w++) s[w] = ldsf(a + w * pitch);
    return ((s[0] + s[1]) + (s[2] + s[3])) + ((s[4] + s[5]) + (s[6] + s[7]));
}
__device__ __forceinline__ float sum5(float a, float b, float c, float d, float e) { return ((a + b) + (c + d)) + e; }
__device__ __forceinline__ float ln_part(uint2 xp, int lane) {
    const float x0 = bf_lo(xp.x), x1 = bf_hi(xp.x), x2 = bf_lo(xp.y), x3 = bf_hi(xp.y);
    const float s1 = (x0 + x1) + (x2 + x3), s2 = (x0 * x0 + x1 * x1) + (x2 * x2 + x3 * x3);
    return ((lane & 16) ? s2 : s1) + shx((lane & 16) ? s1 : s2, 16);
}
__device__ __forceinline__ float ln_rstd(float mean, float msq) { return rsq(fmaxf(msq - mean * mean, 0.f) + 1e-5f); }
constexpr float CS = 0.07216878364870322f * 1.4426950408889634f;
constexpr uint32_t ONES = 0x3f803f80u;

__global__ void __launch_bounds__(NTHR, 1) fused_kernel(const __grid_constant__ Params P) {
    extern __shared__ __align__(1024) unsigned char smem[];
    const uint32_t sb = (uint32_t)__cvta_generic_to_shared(smem);
    const int bx = blockIdx.x;
    const int cta0 = bx >= NCTA || CMAP == 0 ? bx : CMAP == 4 ? (((bx >> 1) & 7) + (bx >> 5) * 8) * 4 + ((bx >> 4) & 1) * 2 + (bx & 1)
                   : (((bx >> 1) & 15) + (bx >> 6) * 16) * 4 + ((bx >> 5) & 1) * 2 + (bx & 1);
    int id = cta0 * NTHR + threadIdx.x, tid, lane, g, t, key, warp, cta, mlp, rowc, roww, j40;
    uint32_t maskA, maskB, barw, subw, prow;
    auto fresh = [&]() {
        const int cw = __shfl_sync(~0u, id >> 5, 0);
        id = pin(id); tid = id & 255; lane = id & 31; g = lane >> 2; t = lane & 3; key = (g >> 1) + 4 * (g & 1);
        const uint32_t m = (g & 1) ? 0xffff0000u : 0x0000ffffu;
        maskA = (g & 2) ? 0u : m; maskB = (g & 2) ? m : 0u;
        warp = cw & 7; cta = cw >> 3;
        mlp = (cta & 3) == 3 ? 96 : (cta >> 2) * 3 + (cta & 3);
        rowc = (cta >> 2) * SK + (SK - WIN) + (cta & 3) * 64; roww = rowc + warp * 8;
        j40 = (cta & 3) * 40;
        barw = sb + SM_BAR + warp * 96; subw = sb + warp * SUB; prow = sb + SM_PART + warp * 768;
    };
    fresh();

    if (cta == NCTA) {
        const uint32_t ep = *(volatile unsigned*)&g_epoch;
        if (tid == 0) {
#pragma unroll 1
            for (int it = 0; it < SPIN; it++) { if (ll_tag(ld_rlx(&g_ll[0][0][192])) == ep * 4 + 2) break; __nanosleep(200); }
        }
        __syncthreads();
#pragma unroll 1
        for (int i = tid; i < 4 * 80 * 8; i += NTHR)
            *reinterpret_cast<uint4*>(g_acc + (i >> 3) * ACC_PITCH + (i & 7) * 16) = make_uint4(0, 0, 0, 0);
        __threadfence();
        __syncthreads();
        if (tid == 0) asm volatile("st.relaxed.gpu.global.u32 [%0], %1;" :: "l"(&g_zflag), "r"(ep + 1) : "memory");
        return;
    }
    TSTAMP(0);
    if (tid == 64) { uint32_t now; asm volatile("mov.u32 %0, %globaltimer_lo;" : "=r"(now)); sts32(sb + SM_T0, now); }

    const CUtensorMap* tmk = reinterpret_cast<const CUtensorMap*>(__shfl_sync(~0u, (u64)&P.tm[0] + (lane >> 5), 0));
    auto issue_first = [&](int j) {
        mbar_expect(sb + SM_CBAR + 80 + j * 8, HALF);
        tma3(sb + j * HALF, tmk + TM_KH, 0, rowc + (j >> 1) * 256 + (j & 1) * 32, sb + SM_CBAR + 80 + j * 8, POL_FIRST);
    };
    if (elect()) {
        asm volatile("mbarrier.init.shared::cta.b64 [%0], 1;" :: "r"(barw + 72));
        asm volatile("mbarrier.init.shared::cta.b64 [%0], 1;" :: "r"(sb + SM_CBAR + 64 + warp * 8));
        asm volatile("fence.mbarrier_init.release.cluster;" ::: "memory");
        mbar_expect(barw + 72, warp < 4 ? 3 * SUB : 2 * SUB);
        const int r0 = (cta & 3) * 160 + warp * 8;
        tma3(subw + SM_WQ, tmk + TM_WQ, (cta >> 2) * 3, r0, barw + 72, POL_FIRST);
        tma3(subw + SM_WQ + TILE, tmk + TM_WQ, (cta >> 2) * 3, r0 + 64, barw + 72, POL_FIRST);
        if (warp < 4) tma3(subw + SM_WQR, tmk + TM_WQ, (cta >> 2) * 3, r0 + 128, barw + 72, POL_FIRST);
        if (warp >= 2 && warp < NI0 + 2) issue_first(warp - 2);
#pragma unroll
        for (int i = 0; i < 9; i++) asm volatile("mbarrier.init.shared::cta.b64 [%0], 1;" :: "r"(barw + i * 8));
        asm volatile("mbarrier.init.shared::cta.b64 [%0], 1;" :: "r"(sb + SM_CBAR + warp * 8));
        asm volatile("mbarrier.init.shared::cta.b64 [%0], 1;" :: "r"(sb + SM_CBAR + 128 + warp * 8));
        if (warp < 3) asm volatile("mbarrier.init.shared::cta.b64 [%0], %1;" :: "r"(sb + SM_CBAR + 192 + warp * 8), "r"(warp == 2 ? 8 : 1));
        sts64(barw + 80, 0, 0);
        asm volatile("fence.proxy.async.shared::cta;" ::: "memory");
        asm volatile("prefetch.tensormap [%0];" :: "l"(tmk + warp + 1) : "memory");
    }
    __syncwarp();
    auto c4 = [&]() { return 32 * min(warp, 4) + 16 * (t >> 1) + 2 * g + (t & 1); };
    uint2 xp = make_uint2(0, 0);
    if (tid < 160) asm volatile("ld.global.nc.v2.u32 {%0,%1}, [%2];" : "=r"(xp.x), "=r"(xp.y) : "l"(P.x + 4 * c4()) : "memory");
    else if (tid == 255) { sts32(sb + SM_EPOCH, *(volatile unsigned*)&g_epoch); sts32(sb + SM_M1, ~0u); }
    else if (tid < 176) sts32(sb + SM_B1 + (tid - 160) * 4, (uint32_t)reinterpret_cast<const volatile unsigned short*>(P.b1)[min(mlp, 95) * 16 + tid - 160] << 16);
    else if (tid >= 192 && tid < 192 + NCB) sts32(sb + SM_CNT + (tid - 192) * 8, 0);
    unsigned char* accg = reinterpret_cast<unsigned char*>(__shfl_sync(~0u, (u64)g_acc + (lane >> 5), 0));
    auto release = [&](const uint4& tw) {
        uint32_t old;
        __syncwarp();
        asm volatile("{\n.reg .pred p;\nsetp.eq.u32 p, %2, 0;\nmov.u32 %0, 0;\n@p atom.relaxed.cta.shared.inc.u32 %0, [%1], 3;\n}"
                     : "=r"(old) : "r"(sb + SM_CNT + (tw.x & 0xf8)), "r"(lane) : "memory");
        return old;
    };
    auto refill = [&](const uint4& tw, uint32_t old) {
        if (__any_sync(~0u, old == 3 && (tw.y & 2))) {
            wait_until(lds32(sb + SM_T0) + tw.z);
            if (elect()) issue_half(tw.y, sb, rowc, cta, tmk);
            __syncwarp();
        }
    };
    __syncthreads();
    auto issue_paced = [&](int j0, int j1) {
        if (warp >= j0 && warp < j1) {
            wait_until(lds32(sb + SM_T0) + PACES + warp * PACE / 2);
            if (elect()) issue_first(warp);
            __syncwarp();
        }
    };
    issue_paced(NI0, NIM);
    mbar_wait(barw + 72, 0);

    uint32_t offV0, offV2;
    auto calc_offsets = [&]() {
        offV0 = subw + (6 * t) * 128 + ((g ^ ((6 * t) & 7)) << 4);
        offV2 = subw + (6 * t + 2) * 128 + ((g ^ ((6 * t + 2) & 7)) << 4);
    };
    calc_offsets();

    auto load_v = [&](uint4 (&v)[6], uint32_t so) {
        v[0] = lds128(offV0 + so); v[1] = lds128((offV0 ^ 16) + so + 128); v[2] = lds128(offV2 + so);
        v[3] = lds128((offV2 ^ 16) + so + 128); v[4] = lds128((offV0 ^ 64) + so + 512); v[5] = lds128((offV0 ^ 80) + so + 640);
    };
    auto issue_v = [&](auto I, int dw) {
        constexpr Step c = SCH.st[I.value];
        const uint32_t bar = barw + dw * 96 + c.slot * 8;
        mbar_expect(bar, SUB);
        tma3(subw + dw * SUB + c.slot * TILE, tmk + TM_V, 0, roww + dw * 8 + c.unit * 256, bar, POL_FIRST);
    };
    auto refill2 = [&](auto I) { __syncwarp(); if (elect()) issue_v(I, 0); };
    uint4 wq0[6], wqh[3], wq1[6];
    auto load_wq1 = [&](int i) { wq1[i] = lds128((i == 2 ? offV2 : i == 3 ? (offV2 ^ 16) + 128 : (offV0 ^ (i * 16)) + i * 128) + SM_WQ + TILE); };
    auto load_wq = [&]() {
        load_v(wq0, SM_WQ);
        const uint32_t so = SM_WQR - ((warp + 1) >> 1) * SUB;
        wqh[0] = lds128(((warp & 1) ? (offV2 ^ 16) + 128 : offV0) + so);
        wqh[1] = lds128(((warp & 1) ? (offV0 ^ 64) + 512 : (offV0 ^ 16) + 128) + so);
        wqh[2] = lds128(((warp & 1) ? (offV0 ^ 80) + 640 : offV2) + so);
#pragma unroll
        for (int i = 0; i < NWQ1; i++) load_wq1(i);
    };
    auto xcol = [&](int i, int tt) { return (i < 2 ? 64 * i + 8 * warp : 128 + 8 * (warp >> 1)) + 2 * tt; };
    uint4 kr[8][6];
    const unsigned char* rap;
    u64 rw[2];
    auto q_proj = [&](auto L, uint32_t (&p)[3], uint32_t pst) {
        if (L.value == 0 && g >= 4) p[0] = p[1] = p[2] = ONES;
        float a[3][4], b[3][4];
        const uint32_t dH = __byte_perm(p[2], 0, (warp & 1) ? 0x3232 : 0x1010);
        const uint32_t dA = __byte_perm(p[0], 0, 0x1010), dB = __byte_perm(p[0], 0, 0x3232), dC = __byte_perm(p[1], 0, 0x1010), dD = __byte_perm(p[1], 0, 0x3232);
#pragma unroll
        for (int i = NWQ1; i < 3; i++) load_wq1(i);
#pragma unroll
        for (int j = 0; j < 3; j++) { a[j][0] = a[j][1] = a[j][2] = a[j][3] = 0.f; mma(a[j], wq0[j], dA & maskA, dA & maskB); }
#pragma unroll
        for (int j = 0; j < 3; j++) { b[j][0] = b[j][1] = b[j][2] = b[j][3] = 0.f; mma(b[j], wq0[j + 3], dB & maskA, dB & maskB); }
#pragma unroll
        for (int j = 0; j < 3; j++) mma(a[j], wqh[j], dH & maskA, dH & maskB);
#pragma unroll
        for (int i = 3; i < 6; i++) load_wq1(i);
        auto look_rw = [&]() {
            if constexpr (L.value == 1) {
                if (NWQ1) rap = accg + ACC_BYTES + (c4() >> 2) * ACC_PITCH + (c4() & 3) * 8;
                rw[0] = ld_rlx(rap); rw[1] = ld_rlx(rap + 40 * ACC_PITCH);
            }
        };
        if (RWAT == 0) look_rw();
        if (L.value == 1 && P4AT == 2) refill2(IC<4>{});
#pragma unroll
        for (int j = 0; j < 3; j++) mma(b[j], wq1[j], dC & maskA, dC & maskB);
#pragma unroll
        for (int j = 0; j < 3; j++) mma(a[j], wq1[j + 3], dD & maskA, dD & maskB);
#pragma unroll
        for (int j = 0; j < 3; j++) {
#pragma unroll
            for (int k = 0; k < 4; k++) a[j][k] += b[j][k];
            sts128f(pst + j * 256, a[j]);
        }
        const uint32_t tag = lds32(sb + SM_EPOCH) * 4 + 1 + 2 * L.value;
        u64* pub = L.value ? &g_ll[0][cta][tid] : &g_l0[cta][tid];
        if (RWAT == 1) look_rw();
        if (L.value == 0) asm volatile("fence.proxy.async.shared::cta;" ::: "memory");
        TSTAMPL(21);
        __syncthreads();
        st_rlx_if(tid < 192, pub, ll_pack(sum8(sb + SM_PART + tid * 4, 768), tag));
        if constexpr (L.value == 0) st_rlx_if(tid < 192, pub + 192, ll_pack(sum8(sb + SM_CSP + tid * 4, 768), tag));
        TSTAMPL(23);
    };
    auto ln_stats = [&]() {
        float ss = ln_part(xp, lane);
        ss += shx(ss, 8); ss += shx(ss, 4); ss += shx(ss, 2); ss += shx(ss, 1);
        stsf(sb + SM_STAT + min(warp, 4) * 8 + (lane >> 4) * 4, ss);
    };
    auto ln_final = [&](float& mean, float& rstd) {
        float2 v[5];
#pragma unroll
        for (int w = 0; w < 5; w++) v[w] = lds64f(sb + SM_STAT + w * 8);
        mean = sum5(v[0].x, v[1].x, v[2].x, v[3].x, v[4].x) * (1.f / D_MODEL);
        const float msq = sum5(v[0].y, v[1].y, v[2].y, v[3].y, v[4].y) * (1.f / D_MODEL);
        rstd = ln_rstd(mean, msq);
        stsf(sb + SM_FXS, fx_scale(msq));
    };
    auto q_addr = [&](int d) { return sb + SM_VEC + (((d >> 1) & 1) * 4 + ((d >> 3) & 3)) * 48 + (d >> 5) * 8 + ((d >> 2) & 1) * 4 + (d & 1) * 2; };
    {
        uint32_t px[3];
#pragma unroll
        for (int i = 0; i < 3; i++) px[i] = *reinterpret_cast<const uint32_t*>(P.x + 4 * j40 + xcol(i, t));
        if (warp < 5) ln_stats();
        mbar_wait(sb + SM_BAR + (warp >> 1) * 96 + 72, 0);
        load_wq();
        q_proj(IC<0>{}, px, sb + (t < 2 ? SM_PART : SM_CSP) + warp * 768 + (8 * g + 4 * (t & 1)) * 4);
    }
    {
        uint32_t offQ, offL;
        auto calc_ql = [&]() {
            offQ = pin(sb + SM_VEC + (lane & 7) * 48);
            offL = pin(subw + lane * 16);
        };

        auto issue_w = [&](auto L, int which) {
            const uint32_t bar = sb + SM_CBAR + (CB_W1 + which) * 8;
            if (mlp == 96) asm volatile("mbarrier.arrive.shared::cta.b64 _, [%0];" :: "r"(bar) : "memory");
            else {
                mbar_expect(bar, 20480);
                if (which) {
                    tma3(sb + (L.value ? 3 * TILE : SM_W2), tmk + TM_W2, 0, mlp * 16, bar, W2ONE ? POL_FIRST : WPOL);
                    if (W2ONE && !L.value) tma3_pf(tmk + TM_W2, 0, mlp * 16, POL_NORMAL);
                    if (W1ONE && !L.value) asm volatile("cp.async.bulk.prefetch.L2.global.L2::cache_hint [%0], 20480, %1;" :: "l"(P.w1 + mlp * 10240), "l"((u64)POL_NORMAL << 32) : "memory");
                }
                else asm volatile("cp.async.bulk.tensor.3d.shared::cluster.global.mbarrier::complete_tx::bytes.L2::cache_hint [%0], [%1, {%2, %3, %3}], [%4], %5;"
                                  :: "r"(sb + (L.value ? 2 * TILE : SM_W1)), "l"(tmk + TM_W1), "r"(mlp * 16), "r"(0), "r"(bar), "l"((u64)(W1ONE ? POL_FIRST : WPOL) << 32) : "memory");
            }
        };
        float acc[3][4];
        auto load_q = [&](uint4 (&qf)[3]) {
#pragma unroll
            for (int i = 0; i < 3; i++) qf[i] = lds128(offQ + i * 16);
        };
        auto score = [&](const uint4 (&v)[6], const uint4 (&qf)[3]) {
            float d[2][4];
#pragma unroll
            for (int j = 0; j < 2; j++) d[j][0] = d[j][1] = d[j][2] = d[j][3] = 0.f;
#pragma unroll
            for (int i = 0; i < 3; i++) { mma(d[0], v[2 * i], qf[i].x, qf[i].y); mma(d[1], v[2 * i + 1], qf[i].z, qf[i].w); }
            return (d[0][0] + d[0][3]) + (d[1][0] + d[1][3]);
        };
        auto softmax = [&](float S0, float S1, float S2, float S3) {
            int mi = __float_as_int(fmaxf(fmaxf(S0, S1), fmaxf(S2, S3)));
            mi = __reduce_max_sync(~0u, mi ^ ((mi >> 31) & 0x7fffffff));
            const float mrun = __int_as_float(mi ^ ((mi >> 31) & 0x7fffffff));
            const float p0 = ex2((S0 - mrun) * CS), p1 = ex2((S1 - mrun) * CS), p2 = ex2((S2 - mrun) * CS), p3 = ex2((S3 - mrun) * CS);
            const uint32_t pa = pack_bf(p0, p1), pb = pack_bf(p2, p3), pw = prow + 256 + (key >> 1) * 80 + t * 4 + (key & 1) * 2;
            sts16(pw, pa); sts16(pw + 16, pa >> 16); sts16(pw + 32, pb); sts16(pw + 48, pb >> 16);
            __syncwarp();
#pragma unroll
            for (int j = 0; j < 3; j++) acc[j][0] = acc[j][1] = acc[j][2] = acc[j][3] = 0.f;
            return make_float2(mrun, (p0 + p1) + (p2 + p3));
        };
        auto head_weight = [&](u64 pm, u64 pl, auto L) {
            const uint32_t tag = lds32(sb + SM_EPOCH) * 4 + 2 + 2 * L.value;
#pragma unroll 1
            for (int it = 0; it < SPIN; it++) {
                if (__all_sync(~0u, ll_tag(pm) == tag && ll_tag(pl) == tag)) break;
                ld_rlx2(&g_ll[L.value][cta ^ (lane >> 3)][192 + (lane & 7) * 4], pm, pl);
            }
            const float f = ex2((ll_val(pm) - warp_max(ll_val(pm))) * CS);
            const float w = f * rcp(warp_sum(f * ll_val(pl)));
            if (lane < 8) stsf(sb + SM_FAC + lane * 4, w);
        };
        auto pv = [&](const uint4 (&v)[6], uint32_t pp) {
            const uint32_t dA = __byte_perm(pp, 0, 0x1010), dB = __byte_perm(pp, 0, 0x3232);
            mma(acc[0], v[0], dA & maskA, dA & maskB); mma(acc[1], v[1], dA & maskA, dA & maskB); mma(acc[2], v[2], dA & maskA, dA & maskB);
            mma(acc[0], v[3], dB & maskA, dB & maskB); mma(acc[1], v[4], dB & maskA, dB & maskB); mma(acc[2], v[5], dB & maskA, dB & maskB);
        };
        auto sa = [&]() { return prow + 256 + t * 32 + g * 4; };
        auto pass1 = [&]() {
            issue_paced(NIM, NI1);
#pragma unroll
            for (int u = 0; u < 8; u++)
#pragma unroll
                for (int i = 0; i < 6; i++) kr[u][i] = lds128(sb + SM_CS + (u * 6 + i) * 16);
            fresh();
            calc_ql();
            __syncthreads();
            sts64(prow + lane * 8, xp.x, xp.y);
            int e = 0;
            const uint4* tab = P.tile + (warp >> 2);
            uint4 tw = tab[0];
            uint32_t ka[3];
#pragma unroll
            for (int j = 0; j < 3; j++) ka[j] = pin(subw + key * 384 + j * 128 + ((t ^ ((3 * key + j) & 7)) << 4));
            auto load_k = [&](uint4 (&v)[6], uint32_t so) {
#pragma unroll
                for (int i = 0; i < 6; i++) v[i] = lds128(((i & 1) ? ka[i >> 1] ^ 64 : ka[i >> 1]) + so);
            };
            const uint32_t s0 = pin(prow + 256 + g * 4), sca = pin(sb + SM_SC + warp * 128 + g * 16);
#pragma unroll 1
            do {
                const uint4 tn = tab[2 * e + 2];
                uint4 v[6], qf[3];
                if (tw.x & (G_A | G_B | G_C)) {
                    if ((tw.x & G_A) && warp == 7 && elect()) {
                        mbar_expect(sb + SM_CBAR + CB_SNAP * 8, HALF);
                        asm volatile("cp.async.bulk.shared::cluster.global.mbarrier::complete_tx::bytes [%0], [%1], 12288, [%2];"
                                     :: "r"(sb + SM_SNAP), "l"(&g_l0[cta & ~3][0]), "r"(sb + SM_CBAR + CB_SNAP * 8) : "memory");
                    }
                    if (tw.x & G_B) {
                        if (warp < 6) {
                            mbar_wait(sb + SM_CBAR + CB_SNAP * 8, 0);
                            float qc[2] = {0.f, 0.f}, mean, rstd;
#pragma unroll 1
                            for (int k = 0; k < 2; k++) {
                                u64 qw[4];
#pragma unroll
                                for (int i = 0; i < 4; i++) { const uint2 x = lds64(sb + SM_SNAP + i * 3072 + k * 1536 + tid * 8); qw[i] = x.x | (u64)x.y << 32; }
                                qc[0] = qc[1];
                                qc[1] = ll_gather<384>(&g_l0[cta & ~3][k * 192 + tid], lds32(sb + SM_EPOCH) * 4 + 1, qw);
                            }
                            ln_final(mean, rstd);
                            stsf(sb + SM_CS + tid * 4, qc[1]);
                            const float q = (qc[0] - mean * qc[1]) * rstd;
                            sts16(q_addr(tid), pack_bf(q, q));
                        }
                        __syncthreads();
                        if (warp == 7 && elect()) issue_half(UC<load_word(12)>::value, sb, rowc, cta, tmk);
                        TSTAMP(2);
                    }
                    if (tw.x & G_C) {
                        load_k(v, (e - LATEAT) * TILE);
                        load_q(qf);
                        stsf(s0 + (e - LATEAT) * 32, score(v, qf));
                    }
                }
                load_q(qf);
                mbar_wait(sb + SM_CBAR + (tw.x & 0xf8), tw.x >> 31);
                TRACE(e);
                load_k(v, tw.x & 0x3f000);
                const uint32_t old = release(tw);
                const float s = score(v, qf);
                uint32_t m;
                {
                    uint32_t a[6];
#pragma unroll
                    for (int i = 0; i < 6; i++) a[i] = bf2_amax(bf2_amax(v[i].x, v[i].y), bf2_amax(v[i].z, v[i].w));
                    m = bf2_amax(bf2_amax(bf2_amax(a[0], a[1]), bf2_amax(a[2], a[3])), bf2_amax(a[4], a[5]));
                }
                m = bf2_amax(m, m >> 16) & 0x7f80;
                m = max(m, __shfl_xor_sync(~0u, m, 1));
                stsf(s0 + e * 32, s);
                m = max(m, __shfl_xor_sync(~0u, m, 2));
                refill(tw, old);
                const uint32_t b = min(max(m, 15u << 7) - (15u << 7), 126u << 7);
                const uint32_t dn = ((127u << 7) - b) * 0x10001u, up = ((127u << 7 | 0x8000u) + b) * 0x10001u;
                uint32_t c[18], any = m > (141u << 7);
#pragma unroll
                for (int i = 0; i < 6; i++) {
                    const uint32_t y0 = bf2_mul(v[i].x, dn), y1 = bf2_mul(v[i].y, dn), y2 = bf2_mul(v[i].z, dn), y3 = bf2_mul(v[i].w, dn);
                    v[i] = make_uint4(bf2_fma(y0, up, v[i].x), bf2_fma(y1, up, v[i].y), bf2_fma(y2, up, v[i].z), bf2_fma(y3, up, v[i].w));
                    any |= v[i].x | v[i].y;
                    any |= v[i].z | v[i].w;
                    const uint32_t hb = __byte_perm(y2, y3, 0x7531);
                    c[3 * i] = __byte_perm(y0, y1, 0x6420); c[3 * i + 1] = __byte_perm(y2, y3, 0x6420);
                    c[3 * i + 2] = __byte_perm(y0, y1, 0x7531) | __funnelshift_r(hb, hb, 4);
                }
                asm volatile("st.shared.u8 [%0], %1;" :: "r"(sca + (e & 3) * 4 + (e >> 2)), "r"((b >> 7) + 63) : "memory");
                const bool rare = __any_sync(~0u, any);
                k_keep(kr, c, e, offL);
                if (rare) {
                    uint32_t odd = m > (141u << 7) ? 64u : 0u;
#pragma unroll
                    for (int i = 0; i < 6; i++) if (v[i].x | v[i].y | v[i].z | v[i].w) odd |= 1u << i;
                    odd = __reduce_or_sync(~0u, odd);
                    const uint2 st = lds64(barw + 80);
                    uint32_t lt; asm volatile("mov.u32 %0, %lanemask_lt;" : "=r"(lt));
                    uint32_t n = odd >= 64 ? NEXC + 1 : __shfl_sync(~0u, st.x, 0);
#pragma unroll 1
                    for (; odd && n <= NEXC; odd &= odd - 1) {
                        const int i = __ffs(odd) - 1;
                        uint4 r = v[0];
#pragma unroll
                        for (int k = 1; k < 6; k++) if (i == k) r = v[k];
#pragma unroll 1
                        for (int k = 0; k < 4; k++) {
                            const uint32_t who = __ballot_sync(~0u, r.x), at = n + __popc(who & lt);
                            if (r.x && at < NEXC) sts64(sb + SM_EXC + warp * 128 + at * 8, r.x, (e * 32 + g * 4) << 16 | (((k & 1) * 4 + t) * 48 + i * 8 + (k >> 1) * 4));
                            n += __popc(who);
                            r.x = r.y; r.y = r.z; r.z = r.w;
                        }
                    }
                    if (n > NEXC) asm volatile("st.shared.u8 [%0], %1;" :: "r"(sca + (e & 3) * 4 + (e >> 2)), "r"(0) : "memory");
                    sts64(barw + 80, n > NEXC ? st.x : n, n > NEXC ? st.y | 1u << e : st.y);
                    __syncwarp();
                }
                tw = tn;
            } while (++e < 16);
            asm volatile("fence.proxy.async.shared::cta;" ::: "memory");
            __syncwarp();
            TSTAMP(10);
            fresh(); calc_offsets();
            {
                const uint2 st = lds64(barw + 80);
                const uint32_t xa = sb + SM_EXC + warp * 128 + (lane & 15) * 8 + 4;
                uint32_t pos = lds32(xa), lt;
                asm volatile("mov.u32 %0, %lanemask_lt;" : "=r"(lt));
                if (lane >= st.x) pos = 0x80000000u;
                const bool dup = (__match_any_sync(~0u, pos >> 16) & lt) && lane < st.x;
                if (lane < 16) sts32(xa, dup ? pos | 0x40000000u : pos);
                if (__any_sync(~0u, dup)) sts32(barw + 84, st.y | 0x10000u);
                const float2 ml = softmax(ldsf(sa()), ldsf(sa() + 128), ldsf(sa() + 256), ldsf(sa() + 384));
                sts64f(sb + SM_ML + warp * 8, ml.x, warp_sum(ml.y));
            }
            u64 pm = 0, pl = 0;
#pragma unroll 1
            do {
                const uint4 tn = tab[2 * e + 2];
                if (tw.x & (G_A | G_B | G_C)) {
                    if (tw.x & G_A) {
                        if (lane < 24) st_rlx(&g_ll[0][cta][warp * 24 + lane], 0ull);
                        else if (lane < 28) st_rlx(&g_ll[0][cta][168 + warp * 4 + lane], ll_pack(ldsf(sb + SM_ML + warp * 8 + (lane & 1) * 4), lds32(sb + SM_EPOCH) * 4 + 2));
                    }
                    if (warp == 2) {
                        if (tw.x & G_B) ld_rlx2(&g_ll[0][cta ^ (lane >> 3)][192 + (lane & 7) * 4], pm, pl);
                        if (tw.x & G_C) head_weight(pm, pl, IC<0>{});
                    }
                    __syncwarp();
                }
                const uint32_t pp = lds32(prow + 256 + t * 80 + ((tw.x >> 20) & 255));
                mbar_wait(sb + SM_CBAR + (tw.x & 0xf8), tw.x >> 31);
                TRACE(e);
                uint4 v[6];
                load_v(v, tw.x & 0x3f000);
                refill(tw, release(tw));
                pv(v, pp);
                tw = tn;
            } while (++e < 32);
        };
        uint32_t osa, ora, owa, orow, otag;
        u64* olb;
        auto o_setup = [&](auto L) {
            fresh();
            const int lz = lane, d = warp * 24 + min(lz, 23);
            osa = pin(prow + ((lz >> 2) * 8 + (lz & 1) * 4) * 4);
            ora = pin(sb + SM_PART + d * 4);
            olb = pin(&g_ll[L.value][cta & ~3][d]);
            orow = pin((lz & 1) + 2 * (lz & 2) + 2 * (lz >> 4));
            owa = pin(sb + SM_RING + warp * 1536 + orow * 64 + ((((lz >> 2) & 3) ^ (orow >> 1)) << 4));
            otag = lds32(sb + SM_EPOCH) * 4 + 2 + 2 * L.value;
            xp = lds64(prow + lz * 8);
        };
        auto pass2 = [&]() {
            constexpr IC<1> L{};
            if (P4AT == 0) refill2(IC<4>{});
            if (P2LATE == 1 && warp >= 4) refill2(IC<2>{});
            offQ = sb + SM_VEC + (lane & 7) * 48; offL = subw + lane * 16;
            uint4 tb[8][3];
            auto load_tb = [&](auto I) {
#pragma unroll
                for (int i = 0; i < 3; i++) tb[I.value][i] = lds128(offL + (I.value >> 1) * TILE + ((I.value & 1) * 3 + i) * 512);
            };
            const float cs = ldsf(sb + SM_CS + min(tid, 191) * 4), inv = fx2_inv(ldsf(sb + SM_MSQ));
            const uint32_t qtag = lds32(sb + SM_EPOCH) * 4 + 3;
            uint32_t m1 = lds32(sb + SM_M1), m1n = m1;
            static_for<0, NPRE>(load_tb);
            const u64* qb = &g_ll[0][cta & ~3][min(tid, 191)];
            const uint32_t qa = pin(q_addr(min(tid, 191)));
            {
                uint32_t x[2];
                fx2_wait<2, true>([&](int i) { return rap + i * 40 * ACC_PITCH; }, rw, sb + SM_MSQ, inv, x);
                xp = make_uint2(x[0], x[1]);
            }
            u64 qw[4];
            ll_look<256>(qb, qw);
            ln_stats();
            if (P4AT == 1) refill2(IC<4>{});
            if (S0EARLY) refill2(IC<5>{});
            __syncthreads();
            auto vwait = [&](auto I) { mbar_wait(barw + IC<SCH.st[I.value].slot>::value * 8, IC<SCH.st[I.value].par>::value); };
            bool ok;
            {
                float mean, rstd;
                ln_final(mean, rstd);
                sts64(prow + lane * 8, xp.x, xp.y);
                sts128f(prow + 256 + lane * 16, 0.f, 0.f, 0.f, 0.f);
                const float sq = rstd * 0x1p64f, q0 = -mean * cs * sq;
                const float q = ll_gather<256>(qb, qtag, qw) * sq + q0;
                sts16(qa, pack_bf(q, q));
                TSTAMPL(24);
            }
            if (!S0EARLY) refill2(IC<5>{});
            if (P2LATE == 2 && warp >= 4) refill2(IC<2>{});
            if (P4AT == 3) refill2(IC<4>{});
            if (NOWIN & 1) { if (warp < 6) refill2(IC<0>{}); if (warp >= 5) refill2(IC<3>{}); }
            if (NOWIN & 2) { if (warp >= 6) refill2(IC<1>{}); if (warp < 4) refill2(IC<2>{}); }
            if (NOWIN & 4) { if (warp >= 6) refill2(IC<0>{}); if (warp < 6) refill2(IC<1>{}); }
            if (NOWIN & 8) { if (warp < 5) refill2(IC<3>{}); if (warp >= 4) refill2(IC<2>{}); }
            __syncthreads();
            uint4 qf[3];
            load_q(qf);
            float S[4], d[2][4];
            auto vload = [&](auto I) {
                constexpr int p = I.value;
                constexpr Step c = SCH.st[p];
                load_v(kr[p & 7], c.slot * TILE);
                if constexpr (c.next >= 0) refill2(IC<c.next>{});
                if constexpr (p == 11) { __syncwarp(); if (elect()) asm volatile("mbarrier.arrive.shared::cta.b64 _, [%0];" :: "r"(sb + SM_CBAR + CB_REL * 8) : "memory"); }
            };
            auto side = [&](uint2 x) {
                const uint32_t qq = lds32(sb + SM_VEC + (x.y & 0xffff));
                return (bf_lo(x.x) * bf_lo(qq) + bf_hi(x.x) * bf_hi(qq)) * 0x1p-64f;
            };
            static_for<0, 96>([&](auto F) {
                constexpr int f = F.value, i = f % 6, u = kunit(f / 6), w = 3 * f % 12;
                uint4 (&src)[3] = *reinterpret_cast<uint4 (*)[3]>(f < 32 ? &tb[f / 4 & 7][0] : &kr[(f / 8 + 4) & 7][(f / 4 & 1) * 3]);
                const uint4 a = k_unpack(word<w % 4>(src[w / 4]), word<(w + 1) % 4>(src[(w + 1) / 4]), word<(w + 2) % 4>(src[(w + 2) / 4]), m1);
                if constexpr (f < 32 ? f % 4 == M1AT : f % 8 == M1P) m1 = m1n;
                if constexpr (f % 4 == 3 && f / 4 + NPRE < 8) {
                    load_tb(IC<f / 4 + NPRE>{});
                    if constexpr ((f / 4 + NPRE) & 1) { refill2(IC<5 + (f / 4 + NPRE) / 2>{}); m1n = lds32(sb + SM_M1); }
                }
                if constexpr (i < 2) d[i][0] = d[i][1] = d[i][2] = d[i][3] = 0.f;
                mma(d[i & 1], a, (i & 1) ? qf[i / 2].z : qf[i / 2].x, (i & 1) ? qf[i / 2].w : qf[i / 2].y);
                if constexpr (i == 5) {
                    if constexpr (u == 11 || ((u & 3) == 0 && u != 8)) S[u >> 2] = (d[0][0] + d[0][3]) + (d[1][0] + d[1][3]);
                    else add_if(t == (u & 3), S[u >> 2], d[0][0] + d[0][3], d[1][0] + d[1][3]);
                    if constexpr (f < 64) S[u >> 2] = shx(S[u >> 2], 0);
                }
                if constexpr (f == 31) { fresh(); calc_offsets(); ok = mbar_test(barw + IC<SCH.st[0].slot>::value * 8, 0); }
                if constexpr (f == 48) {
                    const uint2 x = lds64(sb + SM_EXC + warp * 128 + (lane & 15) * 8);
                    const float c = side(x);
                    if (x.y < 0x40000000u) stsf(prow + 256 + (x.y >> 16), c);
                }
                if constexpr (f >= 32 && f % 8 == 7) {
                    if constexpr (PARKS >> (f / 8 - 4) & 1) {
                        constexpr int p = popc(PARKS & ((1 << (f / 8 - 4)) - 1));
                        if (!ok) vwait(IC<p>{});
                        vload(IC<p>{});
                        m1n = lds32(sb + SM_M1);
                        ok = mbar_test(barw + IC<SCH.st[p + 1].slot>::value * 8, IC<SCH.st[p + 1].par>::value);
                    }
                }
            });
            uint32_t bad = lds32(barw + 84);
            const uint32_t sc = lds32(sb + SM_SC + tid * 4);
            __syncwarp();
            if (bad) {
                const uint2 x = lds64(sb + SM_EXC + warp * 128 + (lane & 15) * 8);
                if ((int)x.y >= 0x40000000 && lane < 16) asm volatile("red.shared.add.f32 [%0], %1;" :: "r"(prow + 256 + ((x.y >> 16) & 511)), "f"(side(x)) : "memory");
#pragma unroll 1
                for (bad &= 0xffff; bad; bad &= bad - 1) {
                    const int e = __ffs(bad) - 1;
                    const __nv_bfloat16* kp = P.k + (size_t)(roww + e * 256 + key) * DH + t * 8;
                    uint4 v[6];
#pragma unroll
                    for (int i = 0; i < 6; i++) v[i] = *reinterpret_cast<const uint4*>(kp + i * 32);
                    const float s = score(v, qf) * 0x1p-64f;
                    if (t == 0) stsf(sa() + e * 32, s);
                }
                __syncwarp();
            }
            TSTAMP(30);
            const float2 ml = softmax(S[0] * __uint_as_float((sc & 255) << 23) + ldsf(sa()), S[1] * __uint_as_float((sc & 0xff00) << 15) + ldsf(sa() + 128),
                                      S[2] * __uint_as_float((sc & 0xff0000) << 7) + ldsf(sa() + 256), S[3] * __uint_as_float((sc >> 24) << 23) + ldsf(sa() + 384));
            uint4 pq[4];
#pragma unroll
            for (int j = 0; j < 4; j++) pq[j] = lds128(prow + 256 + t * 80 + j * 16);
            TSTAMP(1);
            if (!ok) vwait(IC<NPARK>{});
            float ac2[3][4];
#pragma unroll
            for (int j = 0; j < 3; j++) ac2[j][0] = ac2[j][1] = ac2[j][2] = ac2[j][3] = 0.f;
            const uint32_t sl = (g & 1) ? 0x1044 : 0x4410, sh = (g & 1) ? 0x3244 : 0x4432;
            const uint32_t sA0 = (g & 2) ? 0x4444 : sl, sA1 = (g & 2) ? sl : 0x4444, sB0 = (g & 2) ? 0x4444 : sh, sB1 = (g & 2) ? sh : 0x4444;
            u64 pm = 0, pl = 0;
            static_for<NPARK, 16>([&](auto I) {
                constexpr int p = I.value;
                static_assert(p - SCH.st[p].mma0 < 8, "buffer in use");
                vload(I);
                if constexpr (p < 15) ok = mbar_test(barw + IC<SCH.st[p + 1].slot>::value * 8, IC<SCH.st[p + 1].par>::value);
                static_for<SCH.st[p].mma0, SCH.st[p].mma0 + SCH.st[p].nmma>([&](auto J) {
                    constexpr int u = SCH.st[J.value].unit;
                    const uint32_t pp = word<u & 3>(pq[u >> 2]), a0 = __byte_perm(pp, 0, sA0), a1 = __byte_perm(pp, 0, sA1), b0 = __byte_perm(pp, 0, sB0), b1 = __byte_perm(pp, 0, sB1);
#pragma unroll
                    for (int j = 0; j < 3; j++) mma(acc[j], kr[J.value & 7][j], a0, a1);
#pragma unroll
                    for (int j = 0; j < 3; j++) mma(ac2[j], kr[J.value & 7][j + 3], b0, b1);
                });
                if constexpr (p == NPARK) {
                    const float l = warp_sum(ml.y);
                    if (lane < 28) st_rlx(&g_ll[1][cta][lane < 24 ? warp * 24 + lane : 168 + warp * 4 + lane], lane < 24 ? 0ull : ll_pack((lane & 1) ? l : ml.x, lds32(sb + SM_EPOCH) * 4 + 4));
                }
                if constexpr (p == HWAT) { if (warp == 6) ld_rlx2(&g_ll[1][cta ^ (lane >> 3)][192 + (lane & 7) * 4], pm, pl); }
                if constexpr (p == 13) o_setup(L);
                if constexpr (p == HWAT + 2) { if (warp == 6) head_weight(pm, pl, IC<1>{}); }
                if constexpr (p >= WOAT && p < WOAT + 3) {
                    if (warp == p - WOAT) {
                        mbar_wait(sb + SM_CBAR + CB_REL * 8, 0);
                        if (elect()) {
                            issue_half(UC<load_word(64 + 2 * (p - WOAT)) | 1>::value, sb, rowc, cta, tmk);
                            if constexpr (p < WOAT + 2) issue_half(UC<load_word(65 + 2 * (p - WOAT)) | 1>::value, sb, rowc, cta, tmk);
                        }
                        __syncwarp();
                    }
                }
                if constexpr (p < 15) { if (!ok) mbar_wait(barw + IC<SCH.st[p + 1].slot>::value * 8, IC<SCH.st[p + 1].par>::value); TRACE(33 + p); }
            });
#pragma unroll
            for (int j = 0; j < 3; j++)
#pragma unroll
                for (int k = 0; k < 4; k++) acc[j][k] += ac2[j][k];
        };

        const unsigned char* ap;
        uint32_t hpa, hsa, hst, w2a, la;
        uint2 b2v;
        float b1v, cs1;
        auto mlp_global = [&](auto L) {
            const int cz = c4();
            ap = accg + 2 * L.value * ACC_BYTES + (cz >> 3) * ACC_PITCH + (cz & 7) * 8;
            if (L.value) ap = pin(ap);
            rap = pin(accg + (2 * L.value + 1) * ACC_BYTES + (cz >> 2) * ACC_PITCH + (cz & 3) * 8);
            asm volatile("ld.global.nc.v2.u32 {%0,%1}, [%2];" : "=r"(b2v.x), "=r"(b2v.y) : "l"(P.b2 + 4 * cz));
        };
        auto mlp_shared = [&](auto L) {
            const int lz = lane;
            hpa = pin(sb + SM_PART + warp * 256 + ((lz & 2) * 4 + (lz >> 2)) * 16 + (L.value ? 0 : (lz & 1) * 4));
            hsa = pin(sb + SM_PART + (lz & 15) * 16); hst = pin(sb + SM_PART + (lz & 15) * 16 + warp * 256 + 8 + (lz >> 4) * 4);
            w2a = pin(sb + (L.value ? 3 * TILE : SM_W2) + ((lz & 3) * 10 + 2 * warp) * 128 + (((lz >> 2) ^ ((2 * lz + 2 * warp) & 6)) << 4));
            la = sb + (L.value ? 2 * TILE : SM_W1) + warp * 4096 + (lz & 4) * 512 + (lz & 2) * 64 + (lz & 1) * 32 + (lz >> 4) * 64 + ((((lz >> 3) ^ (lz >> 1)) & 1) << 4);
            b1v = ldsf(sb + SM_B1 + (lz & 15) * 4);
            if (L.value) { la = pin(la); cs1 = ldsf(sb + SM_ML + (lz & 15) * 4); }
            else fresh();
        };
        uint32_t pa;
        unsigned char* rop;
        uint32_t wpa;
        auto sum_setup = [&](auto L) {
            const int lz = lane, word = (lz & 3) * 160 + warp * 32 + (cta & 3) * 8 + (lz >> 2);
            const uint32_t wo = ((lz >> 2) * 8 + (lz & 1) * 4) * 4;
            wpa = pin(sb + SM_RING + warp * 1536 + ((((lz >> 1) ^ (lz >> 4)) & 1) ? HALF + (wo ^ 64) : wo));
            pa = pin(sb + SM_RING + warp * 256 + lz * 4);
            rop = pin(accg + 2 * L.value * ACC_BYTES + (word >> 3) * ACC_PITCH + (word & 7) * 8);
        };
        auto out_proj = [&](auto L) {
            TSTAMP2(3);
            CSTAMP(0, __float_as_uint(acc[2][3]));
            __syncwarp();
#pragma unroll
            for (int j = 0; j < 3; j++) sts128f(osa + 256 * j, acc[j]);
            __syncthreads();
            {
                float s[8];
#pragma unroll
                for (int w = 0; w < 8; w++) s[w] = ldsf(ora + w * 768);
                const uint4 fa = lds128(sb + SM_FAC), fb = lds128(sb + SM_FAC + 16);
            CSTAMP(1, __float_as_uint(s[0]));
                const float own = ((s[0] * __uint_as_float(fa.x) + s[1] * __uint_as_float(fa.y)) + (s[2] * __uint_as_float(fa.z) + s[3] * __uint_as_float(fa.w))) +
                                  ((s[4] * __uint_as_float(fb.x) + s[5] * __uint_as_float(fb.y)) + (s[6] * __uint_as_float(fb.z) + s[7] * __uint_as_float(fb.w)));
                st_rlx_if(lane < 24, olb + (cta & 3) * 256, ll_pack(own, otag));
            CSTAMP(2, __float_as_uint(own));
            }
            TSTAMPL(29);
            if (L.value == 0 && warp == 7) {
#pragma unroll 1
                for (int it = 0; it < SPIN; it++) {
                    uint32_t v; asm volatile("ld.acquire.gpu.global.u32 %0, [%1];" : "=r"(v) : "l"(&g_zflag) : "memory");
                    if (__all_sync(~0u, v == (otag >> 2) + 1)) break;
                }
            }
            constexpr int NW = L.value ? NWO1 : 3;
            uint4 v[5][3];
            u64 ow[4];
            auto read_wo = [&](auto J) {
#pragma unroll
                for (int p = 0; p < 3; p++) v[J.value][p] = lds128(owa + ring_hs(64 + J.value) * HALF + p * 512);
            };
            static_for<0, NW>([&](auto J) {
                if (L.value && J.value == 0) { sum_setup(L); maskA = pin(maskA); maskB = pin(maskB); }
                if ((L.value ? OPOLL1 : OPOLL) == J.value) { ll_look<256>(olb, ow); if (L.value) { mlp_shared(L); mlp_global(L); } }
                mbar_wait(sb + SM_CBAR + (CB_WO + J.value) * 8, L.value);
                read_wo(J);
                if (L.value == 0 && W1AT0 == J.value + 1) {
                    __syncwarp();
                    if (elect() && cnt_inc(sb + SM_CNT + CB_W1 * 8, 7) == 7) issue_w(L, 0);
                    __syncwarp();
                }
                if (L.value == 1 && (W1AT1 == J.value + 1 || W2AT1 == J.value + 1)) {
                    if (warp == 7 && elect()) { if (W1AT1 == J.value + 1) issue_w(L, 0); if (W2AT1 == J.value + 1) issue_w(L, 1); }
                    __syncwarp();
                }
            });
            const float o = ll_gather<256>(olb, otag, ow);
            CSTAMP(3, __float_as_uint(o));
            TSTAMP2(4);
            bool ok = true;
            if constexpr (NW < 5) ok = mbar_test(sb + SM_CBAR + (CB_WO + 4) * 8, L.value);
            if constexpr (NW < 4) ok &= mbar_test(sb + SM_CBAR + (CB_WO + 3) * 8, L.value);
            const uint32_t od = pack_bf(o, o);
            uint32_t oa[3], ob[3];
#pragma unroll
            for (int p = 0; p < 3; p++) { const uint32_t op = __shfl_sync(~0u, od, 8 * p + orow); oa[p] = op & maskA; ob[p] = op & maskB; }
            CSTAMP(4, oa[2]);
            float y[5][4];
#pragma unroll
            for (int j = 0; j < 5; j++) y[j][0] = y[j][1] = y[j][2] = y[j][3] = 0.f;
            auto rest = [&]() {
                if (!ok) static_for<NW, 5>([&](auto J) { mbar_wait(sb + SM_CBAR + (CB_WO + J.value) * 8, L.value); });
                static_for<NW, 5>(read_wo);
            };
            if (L.value) rest();
#pragma unroll
            for (int p = 0; p < 3; p++)
#pragma unroll
                for (int j = 0; j < NW; j++) mma(y[j], v[j][p], oa[p], ob[p]);
            if (!L.value) { rest(); sum_setup(L); }
#pragma unroll
            for (int p = 0; p < 3; p++)
#pragma unroll
                for (int j = NW; j < 5; j++) mma(y[j], v[j][p], oa[p], ob[p]);
            CSTAMP(5, __float_as_uint(y[4][3]));
#pragma unroll
            for (int j = 0; j < 5; j++) sts128f(wpa + j * 256, y[j]);
            TSTAMP2(5);
        };
        u64 yw[2];
        bool wide;
        float msq = 0.f, yf[4];
        auto mlp_part = [&](auto L) {
            const float fxs = ldsf(sb + SM_FXS);
            bar_sync(0, 256);
            CSTAMP(6, __float_as_uint(fxs));
            {
                const float s = sum8(pa, 1536) + sum8(pa + 128, 1536);
            CSTAMP(7, __float_as_uint(s));
                asm volatile("red.relaxed.gpu.global.add.u64 [%0], %1;" :: "l"(rop), "l"(fx_pack(s, fxs)) : "memory");
            }
            const uint32_t c0 = clk();
            TSTAMP2(6);
            if (L.value == 0) bar_arrive(2, 256);
            else if (mlp == 96) { TDUMP(); asm volatile("exit;"); }
            uint4 wf[8], w2r[8];
            u64 w[4];
            auto look = [&]() {
#pragma unroll
                for (int k = 0; k < 4; k++) w[k] = ld_rlx(ap + k * 20 * ACC_PITCH);
            };
            auto read_w1 = [&]() {
#pragma unroll
                for (int j = 0; j < 8; j++) wf[j] = ldsm_t(la + j * 256);
            };
            auto read_w2 = [&]() {
#pragma unroll
                for (int i = 0; i < 8; i++) w2r[i] = lds128(((i & 1) ? (w2a ^ 16) + 128 : w2a) + (i >> 1) * 5120);
            };
            if (L.value == 0) { fresh(); mlp_global(L); }
            mbar_wait(sb + SM_CBAR + CB_W1 * 8, L.value);
            if (L.value == 1) {
                if (W2PRE == 1) mbar_wait(sb + SM_CBAR + CB_W2 * 8, 1);
                read_w1();
                if (W2PRE == 1) read_w2();
            }
            while (clk() - c0 < AR1D);
            look();
            if (L.value == 0) { mlp_shared(L); read_w1(); bar_arrive(3, 256); }
            else if (W2PRE == 2) { mbar_wait(sb + SM_CBAR + CB_W2 * 8, 1); read_w2(); }
            TSTAMPL(28);
            {
                int it = 0;
#pragma unroll 1
                while (__any_sync(~0u, ~(lo32(w[0]) & lo32(w[1]) & lo32(w[2]) & lo32(w[3])) & 32) & (++it < SPIN)) look();
                const float inv = fx_inv(fxs);
            CSTAMP(8, lo32(w[3]));
                xp = make_uint2(pack_bf(bf_lo(xp.x) + fx_val(w[0]) * inv, bf_hi(xp.x) + fx_val(w[1]) * inv),
                                pack_bf(bf_lo(xp.y) + fx_val(w[2]) * inv, bf_hi(xp.y) + fx_val(w[3]) * inv));
            }
            TSTAMP2(7);
            CSTAMP(9, xp.y);
            {
                bool ok = true;
                if (L.value == 0 || !W2PRE) ok = mbar_test(sb + SM_CBAR + CB_W2 * 8, L.value);
                const bool ev = L.value || !(g & 1), od = L.value || (g & 1);
                const uint32_t e0 = ev ? xp.x : ONES, e1 = ev ? xp.y : ONES, o0 = od ? xp.x : ONES, o1 = od ? xp.y : ONES;
                float d[8][4];
#pragma unroll
                for (int j = 0; j < 8; j++) { d[j][0] = d[j][1] = d[j][2] = d[j][3] = 0.f; mma(d[j], wf[j], (j & 1) ? o0 : e0, (j & 1) ? o1 : e1); }
                float ss = ln_part(xp, lane);
                ss += shx(ss, 8); ss += shx(ss, 4);
                float r[4], dd;
#pragma unroll
                for (int k = 0; k < 4; k += 1 + L.value) r[k] = d[0][k] + d[1][k ^ 1];
#pragma unroll
                for (int j = 1; j < 4; j++)
#pragma unroll
                    for (int k = 0; k < 4; k += 1 + L.value) add_if(t == j, r[k], d[2 * j][k], d[2 * j + 1][k ^ 1]);
                CSTAMP(10, __float_as_uint(r[2]));
                if (L.value) {
                    dd = ((t & 2) ? r[2] : r[0]) + shx((t & 2) ? r[0] : r[2], 2);
                    ss += shx(ss, 2);
                    dd += shx(dd, 1);
                } else {
                    const float a = ((t & 1) ? r[1] : r[0]) + shx((t & 1) ? r[0] : r[1], 1), b = ((t & 1) ? r[3] : r[2]) + shx((t & 1) ? r[2] : r[3], 1);
                    ss += shx(ss, 2);
                    dd = ((t & 2) ? b : a) + shx((t & 2) ? a : b, 2);
                }
                ss += shx(ss, 1);
                stsf(hpa, dd);
                stsf(hst, ss);
                CSTAMP(11, __float_as_uint(dd + ss));
                if (!ok) mbar_wait(sb + SM_CBAR + CB_W2 * 8, L.value);
            }
            TSTAMPL(25);
            bar_sync(1, 160);
            uint4 hp[5];
#pragma unroll
            for (int w = 0; w < 5; w++) hp[w] = lds128(hsa + w * 256);
            CSTAMP(12, hp[0].x);
            auto hs = [&](auto K) { return sum5(__uint_as_float(word<K.value>(hp[0])), __uint_as_float(word<K.value>(hp[1])), __uint_as_float(word<K.value>(hp[2])),
                                                __uint_as_float(word<K.value>(hp[3])), __uint_as_float(word<K.value>(hp[4]))); };
            const float mean = hs(IC<2>{}) * (1.f / D_MODEL);
            msq = hs(IC<3>{}) * (1.f / D_MODEL);
            if (L.value == 0) cs1 = hs(IC<1>{});
            float hv = hs(IC<0>{}) - mean * cs1;
            CSTAMP(13, __float_as_uint(hv));
            const float sc2 = fx2_scale(msq), lim = fx_inv(sc2) * FX2LIM;
            if (L.value == 0 || !W2PRE) read_w2();
            if (L.value == 0) bar_arrive(4, 256);
            hv = hv * ln_rstd(mean, msq) + b1v;
            CSTAMP(14, __float_as_uint(hv));
            hv = hv * rcp(1.f + ex2(hv * (-2.302208198f - 0.1029432397f * hv * hv)));
            const uint32_t hd = pack_bf(hv, hv);
            CSTAMP(15, hd);
            TSTAMPL(27);
            float ym[4][4];
#pragma unroll
            for (int i = 0; i < 2; i++) {
                ym[i][0] = ym[i][1] = ym[i][2] = ym[i][3] = 0.f;
                const float f = mlp < 64 ? 1.f / 64 : 0.f;
                ym[i + 2][0] = (bf_lo(xp.x) + bf_lo(b2v.x)) * f; ym[i + 2][1] = (bf_hi(xp.x) + bf_hi(b2v.x)) * f;
                ym[i + 2][2] = (bf_lo(xp.y) + bf_lo(b2v.y)) * f; ym[i + 2][3] = (bf_hi(xp.y) + bf_hi(b2v.y)) * f;
            }
#pragma unroll
            for (int i = 0; i < 4; i++) {
                const uint32_t hh = __shfl_sync(~0u, hd, 4 * i + t);
                mma(ym[(i & 1) * 2], w2r[2 * i], hh & maskA, hh & maskB);
                mma(ym[(i & 1) * 2 + 1], w2r[2 * i + 1], hh & maskA, hh & maskB);
            }
#pragma unroll
            for (int k = 0; k < 4; k++) { yf[k] = ym[0][k] + ym[2][k]; add_if(t & 2, yf[k], ym[1][k], ym[3][k]); }
            CSTAMP(16, __float_as_uint(yf[3]));
            yw[0] = fx2_pack(yf[0] * sc2 + FX2_ONE, yf[1] * sc2 + FX2_ONE); yw[1] = fx2_pack(yf[2] * sc2 + FX2_ONE, yf[3] * sc2 + FX2_ONE);
            wide = !(fmaxf(fmaxf(fabsf(yf[0]), fabsf(yf[1])), fmaxf(fabsf(yf[2]), fabsf(yf[3]))) < lim);
            if (wide) yw[0] = yw[1] = 0;
        };
        auto send_wide = [&]() {
#pragma unroll 1
            for (int k = 0; k < 4; k++, yf[0] = yf[1], yf[1] = yf[2], yf[2] = yf[3])
                asm volatile("red.relaxed.gpu.global.add.u64 [%0], %1;" :: "l"(rap + (k >> 1) * 40 * ACC_PITCH + 64 + (k & 1) * 32), "l"(fx_pack(yf[0], fx_scale(msq))) : "memory");
            __threadfence();
#pragma unroll
            for (int k = 0; k < 2; k++) { asm volatile("red.relaxed.gpu.global.or.b64 [%0], 256;" :: "l"(rap + k * 40 * ACC_PITCH) : "memory"); yw[k] = 1; }
        };

        pass1();
        o_setup(IC<0>{});
        out_proj(IC<0>{});
        uint32_t c0;
        if (warp < 5) {
            mlp_part(IC<0>{});
            if (mlp != 96) {
#pragma unroll
                for (int k = 0; k < 2; k++) asm volatile("red.relaxed.gpu.global.add.u64 [%0], %1;" :: "l"(rap + k * 40 * ACC_PITCH), "l"(yw[k]) : "memory");
            }
            c0 = clk();
            stsf(sb + SM_ML + (lane & 15) * 4, cs1);
            TSTAMP(8);
            if (__any_sync(~0u, wide && mlp != 96)) {
                if (wide) {
                    send_wide();
#pragma unroll
                    for (int k = 0; k < 2; k++) asm volatile("red.relaxed.gpu.global.add.u64 [%0], 1;" :: "l"(rap + k * 40 * ACC_PITCH) : "memory");
                }
                __syncwarp();
            }
            fresh(); calc_offsets();
            load_wq();
        } else {
            bar_sync(0, 256);
            if (warp == 5 && elect()) {
                asm volatile("fence.proxy.async.shared::cta;" ::: "memory");
                if (W1AT0 == 4) issue_w(IC<0>{}, 0);
                issue_w(IC<0>{}, 1);
            }
            __syncwarp();
            fresh(); calc_offsets();
            load_wq();
#pragma unroll 1
            for (int ph = 0; ph < 3; ph++) {
                bar_sync(ph + 2, 256);
                c0 = clk();
                if (ph == 2) {
                    msq = sum5(ldsf(sb + SM_PART + 12), ldsf(sb + SM_PART + 268), ldsf(sb + SM_PART + 524), ldsf(sb + SM_PART + 780), ldsf(sb + SM_PART + 1036)) * (1.f / D_MODEL);
                    bar_arrive(5, 256);
                }
                if (!(NOWIN >> ph & 1) && elect()) {
                    asm volatile("fence.proxy.async.shared::cta;" ::: "memory");
                    const uint32_t gap = ph == 0 ? WG1 : ph == 1 ? WG2 : WG3;
                    uint32_t c1 = c0 + (ph == 0 ? WD1 : ph == 1 ? WD2 : 0) + (warp - 5) * gap;
#pragma unroll 1
                    for (int k = warp + (ph == 0 ? -5 : ph == 1 ? 9 : 1); k < (ph == 0 ? 9 : ph == 1 ? 20 : 14); k += 3, c1 += 3 * gap) {
                        const int i = ph == 0 && k >= 6 ? k + 23 : k;
                        const uint32_t bar = sb + SM_BAR + (i & 7) * 96 + 32 + (i & 24);
                        while ((int)(clk() - c1) < 0);
                        mbar_expect(bar, SUB);
                        tma3(sb + SM_RING + i * SUB, tmk + TM_V, 0,
                             rowc + (i & 7) * 8 + ((UC<SCH.st[0].unit | SCH.st[1].unit << 8 | SCH.st[2].unit << 16 | SCH.st[3].unit << 24>::value >> (i & 24)) & 15) * 256, bar, POL_FIRST);
                    }
                }
                __syncwarp();
            }
            c0 += PCD;
        }
        {
            constexpr IC<1> L{};
            fresh();
            const int lz = lane;
            const unsigned char* xa[2];
#pragma unroll
            for (int i = 0; i < 2; i++) {
                const int col = xcol(2 * i, lz & 3), cw = j40 + (col >> 2);
                xa[i] = pin(accg + ACC_BYTES + ((cw >> 2) + (col & 2) * 20) * ACC_PITCH + (cw & 3) * 8);
            }
            const uint32_t pst = pin(prow + ((lz >> 2) * 8 + (lz & 1) * 4) * 4);
            stsf(sb + SM_MSQ, msq);
            const float inv = shx(fx2_inv(msq), 0);
            if (!NWQ1) rap = pin(accg + ACC_BYTES + (c4() >> 2) * ACC_PITCH + (c4() & 3) * 8);
            fresh();
            if (!NWQ1) { maskA = pin(maskA); maskB = pin(maskB); }
            u64 w[3];
            uint32_t x2[3];
            auto xat = [&](int i) { return ((i & 2) ? xa[1] : xa[0]) + (i & 1) * 4 * ACC_PITCH; };
            if (warp < 5) {
                bar_sync(5, 256);
                if (DPRE) { while ((int)(clk() - c0) < WD4 + warp * WG4); if (warp < DPRE) refill2(IC<3>{}); }
            }
            while ((int)(clk() - c0) < ARDELAY);
#pragma unroll
            for (int i = 0; i < 3; i++) w[i] = ld_rlx(xat(i));
            if (warp < 5 && !(NOWIN & 8) && elect()) {
                if (DPOST) while ((int)(clk() - c0) < ARDELAY + DPOST);
                if (warp >= DPRE) issue_v(IC<3>{}, 0);
                if (warp < 4 && !P2LATE) issue_v(IC<2>{}, 4);
            }
            __syncwarp();
            fx2_wait<3, true>(xat, w, sb + SM_MSQ, inv, x2);
            TSTAMP(9);
            q_proj(L, x2, pst);
            pass2();
            out_proj(L);
            if (warp >= 5) {
                bar_arrive(0, 256);
                if ((W1AT1 == 6 || W2AT1 == 6) && warp == 5 && elect()) { if (W1AT1 == 6) issue_w(L, 0); if (W2AT1 == 6) issue_w(L, 1); }
                TDUMP();
                return;
            }
            mlp_part(L);
            u64 old[2];
            auto add = [&]() {
#pragma unroll
                for (int k = 0; k < 2; k++) asm volatile("atom.relaxed.gpu.global.add.u64 %0, [%1], %2;" : "=l"(old[k]) : "l"(rap + k * 40 * ACC_PITCH), "l"(yw[k]) : "memory");
            };
            add();
            uint32_t* op = reinterpret_cast<uint32_t*>(P.out) + 2 * c4();
            if (wide) { send_wide(); add(); }
            TSTAMP(18);
            CSTAMP(17, hi32(yw[1]));
            const float inv2 = fx2_inv(msq);
            const uint32_t ep1 = lds32(sb + SM_EPOCH) + 1;
            CSTAMP(18, lo32(old[0]) ^ lo32(old[1]));
#pragma unroll
            for (int k = 0; k < 2; k++) {
                yw[k] += old[k];
                asm volatile("{\n.reg .pred p;\nsetp.eq.u32 p, %2, 96;\n@p st.global.u32 [%0], %1;\n}"
                             :: "l"(op + k), "r"(pack_bf(fx2_lo(yw[k], inv2), fx2_hi(yw[k], inv2))), "r"(lo32(yw[k]) & 511) : "memory");
            }
            if ((lo32(yw[0]) & 255) == 96 && tid == 0) g_epoch = ep1;
            if ((lo32(yw[0]) | lo32(yw[1])) & 256) {
                __threadfence();
#pragma unroll 1
                for (int k = 0; k < 2; k++, yw[0] = yw[1]) if ((lo32(yw[0]) & 511) == 256 + 96) op[k] = fx2_wide(rap + k * 40 * ACC_PITCH, yw[0], msq);
            }
            TSTAMP(19);
            CSTAMP(19, lo32(yw[1]));
            TDUMP();
        }
    }
}

typedef CUresult (*EncodeFn)(CUtensorMap*, CUtensorMapDataType, cuuint32_t, void*, const cuuint64_t*, const cuuint64_t*, const cuuint32_t*,
                             const cuuint32_t*, CUtensorMapInterleave, CUtensorMapSwizzle, CUtensorMapL2promotion, CUtensorMapFloatOOBfill);

}

extern "C" void kernel_launch(void* const* d_in, const int* in_sizes, int n_in, void* d_out, int out_size) {
    (void)in_sizes; (void)n_in; (void)out_size;
    static EncodeFn enc = nullptr;
    if (!enc) {
        void* fn = nullptr;
        cudaDriverEntryPointQueryResult qr;
        cudaGetDriverEntryPoint("cuTensorMapEncodeTiled", &fn, cudaEnableDefault, &qr);
        enc = (EncodeFn)fn;
        cudaFuncSetAttribute(fused_kernel, cudaFuncAttributeMaxDynamicSharedMemorySize, SM_TOTAL);
    }
    Params P = {};
    auto map3 = [&](int m, int in, cuuint64_t d0, cuuint64_t d1, cuuint64_t d2, cuuint64_t s1, cuuint64_t s2, cuuint32_t b0, cuuint32_t b1, cuuint32_t b2,
                    CUtensorMapSwizzle sw, int promo) {
        const cuuint64_t dim[3] = {d0, d1, d2}, str[2] = {s1, s2};
        const cuuint32_t box[3] = {b0, b1, b2}, ones[3] = {1, 1, 1};
        enc(&P.tm[m], CU_TENSOR_MAP_DATA_TYPE_BFLOAT16, 3, d_in[in], dim, str, box, ones, CU_TENSOR_MAP_INTERLEAVE_NONE, sw, (CUtensorMapL2promotion)promo,
            CU_TENSOR_MAP_FLOAT_OOB_FILL_NONE);
    };
    map3(TM_KH, 1, 64, 3, NHEAD * SK, 128, DH * 2, 64, 3, 32, CU_TENSOR_MAP_SWIZZLE_128B, 0);
    map3(TM_VH, 2, 64, 3, NHEAD * SK, 128, DH * 2, 64, 3, 32, CU_TENSOR_MAP_SWIZZLE_128B, 0);
    map3(TM_VP, 2, 64, 3, NHEAD * SK, 128, DH * 2, PFW, 3, 32, CU_TENSOR_MAP_SWIZZLE_NONE, 0);
    map3(TM_V, 2, 64, 3, NHEAD * SK, 128, DH * 2, 64, 3, 8, CU_TENSOR_MAP_SWIZZLE_128B, 0);
    map3(TM_WO, 4, 32, 20, NHEAD * DH, 64, D_MODEL * 2, 32, 1, DH, CU_TENSOR_MAP_SWIZZLE_64B, PROMOW);
    map3(TM_WOP, 4, 32, 20, NHEAD * DH, 64, D_MODEL * 2, PFW, 1, DH, CU_TENSOR_MAP_SWIZZLE_NONE, 0);
    map3(TM_WQ, 3, 64, NHEAD * 3, D_MODEL, 128, NHEAD * DH * 2, 64, 3, 8, CU_TENSOR_MAP_SWIZZLE_128B, 0);
    map3(TM_W1, 6, DFF, 128, 5, DFF * 2, DFF * 256, 16, 128, 5, CU_TENSOR_MAP_SWIZZLE_32B, PROMO1);
    map3(TM_W2, 8, 64, 10, DFF, 128, D_MODEL * 2, 64, 10, 16, CU_TENSOR_MAP_SWIZZLE_128B, 0);
    P.x = (const __nv_bfloat16*)d_in[0];
    P.k = (const __nv_bfloat16*)d_in[1];
    P.b1 = (const __nv_bfloat16*)d_in[7];
    P.b2 = (const __nv_bfloat16*)d_in[9];
    P.w1 = (const __nv_bfloat16*)d_in[6];
    P.out = (__nv_bfloat16*)d_out;
    for (int i = 0; i < 64; i++) P.tile[i] = make_uint4(SCH.tile[i][0], SCH.tile[i][1], SCH.tile[i][2], 0);
    fused_kernel<<<NCTA + 1, NTHR, SM_TOTAL, cudaStreamPerThread>>>(P);
}
```

```cpp
#include <cuda_runtime.h>
#include <cuda_bf16.h>
#include <cuda.h>
#include <stdint.h>

namespace {

constexpr int D_MODEL = 640, NHEAD = 32, SK = 32768, DH = 192, WIN = 4096, DFF = 1536;
constexpr int NCTA = 128, NTHR = 256;
constexpr int TILE = 64 * DH * 2;
constexpr int HALF = TILE / 2;
constexpr int SUB = 8 * DH * 2;
constexpr int SM_RING = 4 * TILE;
constexpr int SM_W2 = SM_RING + 20480, SM_W1 = SM_W2 + 20480;
constexpr int SM_WQR = 6 * TILE + HALF, SM_WQ = 7 * TILE;
constexpr int SM_PART = 9 * TILE;
constexpr int SM_EXC = SM_PART + 6144;
constexpr int SM_SC = SM_EXC + 1024;
constexpr int SM_BAR = SM_SC + 1024;
constexpr int SM_VEC = SM_BAR + 768;
constexpr int SM_CS = SM_VEC + 384;
constexpr int SM_FAC = SM_CS + 768;
constexpr int SM_ML = SM_FAC + 32;
constexpr int SM_B1 = SM_ML + 64;
constexpr int SM_STAT = SM_B1 + 64;
constexpr int NCB = 27;
constexpr int CB_WO = 18, CB_W1 = 23, CB_W2 = 24, CB_SNAP = 25, CB_REL = 26;
constexpr int SM_CBAR = SM_STAT + 40;
constexpr int SM_CNT = SM_CBAR + NCB * 8;
constexpr int SM_EPOCH = SM_CNT + NCB * 8;
constexpr int SM_FXS = SM_EPOCH + 4;
constexpr int SM_T0 = SM_FXS + 4;
constexpr int SM_MSQ = SM_T0 + 4;
constexpr int SM_M1 = SM_MSQ + 4;
constexpr int SM_TS = SM_M1 + 4;
constexpr int SM_TOTAL = 232448;
static_assert(SM_TS + 320 <= SM_TOTAL, "smem");
constexpr int NEXC = 16;

constexpr int SPIN = 1 << 20;
enum { TM_KH = 0, TM_VH = 1, TM_WO = 2, TM_VP = 3, TM_WOP = 4, TM_V = 5, TM_WQ = 6, TM_W1 = 7, TM_W2 = 8 };
constexpr uint32_t POL_NORMAL = 0x16F00000u, POL_FIRST = 0x12F00000u;

#define PACE 980
#define PACE0 1600
#define NI0 1
#define NI1 6
#define ETRIG 0x54321000
#define LATEAT 5
#define HWAT 12
#define PFREE 66
#define W1AT0 3
#define W1AT1 3
#define AR1D 300
#define LAG0 12
#define NMMA 2
#define M1AT 1
#define M1P 3
#define NWO1 4
#define WG2 90
#define WG3 120
#define WD4 250
#define WG4 70
#define NWQ1 0
#define P4AT 0
#define P2LATE 0
#define RWAT 1
#define W2AT1 6
#define PCD 150
#define NOWIN 0
#define DPRE 0
#define DPOST 200
#define NIM 4
#define PACES PACE0
#define JP2 54
#define PACE2 0
#define WD2 0
#define W2PRE 2
#define OPOLL1 2
#define W2ONE 1
#define W1ONE 1
#define FX1LIM 524288.f
#define SNAPAT 1
#define DMASK 0x0
#define WOKEEP 0x1f
#define VORD2 0x7685943a2b1cd0efull
#define VTRIG 0xba73210
#define WOAT 13
#define PARKS 0x95
#define VSLOT 0x1087654321087654ull
#define OPOLL 2
#define S0EARLY 1
#define NPRE 2
#define ARDELAY 1000
#define QDELAY 0
#define CMAP 0
#define PFW 8u
#define PUBAT 28
#define HW0 30
#define HW1 31
#define FX2LIM 524288.f
#define PROMOW 2
#define PROMO1 0
#define WD1 300
#define WG1 140
#define WPOL POL_NORMAL

constexpr uint32_t G_A = 1u << 28, G_B = 1u << 29, G_C = 1u << 30;
__host__ __device__ constexpr int ring_hs(int j) { return (j + 4) % 5; }
__host__ __device__ constexpr uint32_t load_word(int j) {
    if (j >= 64) return (uint32_t)(j - 64) << 20 | (SM_RING + ring_hs(j) * HALF) | TM_WO << 8 | (CB_WO + j - 64) << 3 | 2 | !(WOKEEP >> (j - 64) & 1);
    const int e = j >> 1, isv = e >= 16, unit = e & 15;
    return (uint32_t)(unit * 256 + (j & 1) * 32) << 20 | (j < 8 ? j * HALF : SM_RING + ring_hs(j) * HALF) | isv << 8 | (j < 8 ? 10 + j : (j - 8) % 10) << 3 | 2
           | (!isv || (DMASK >> unit & 1));
}
__host__ __device__ constexpr int popc(int v) { return v ? (v & 1) + popc(v >> 1) : 0; }
constexpr int NPARK = popc(PARKS);
constexpr int SM_SNAP = SM_RING + ring_hs(12) * HALF, SM_CSP = SM_RING + ring_hs(11) * HALF;
struct Step { int unit, slot, par, next, mma0, nmma; };
struct Sched { uint32_t tile[64][3]; Step st[16]; };
constexpr Sched make_sched() {
    Sched s{};
    for (int j = 0; j < 64; j++) {
        const int e = j >> 1;
        const uint32_t d = load_word(j);
        uint32_t w = (uint32_t)(j < 8 ? 0 : (j - 8) / 10 & 1) << 31 | (e & 15) * 4 << 20 | ((d & 0x3f000) - (j & 1) * HALF) | (d & 0xf8);
        if (e == PUBAT || e == SNAPAT) w |= G_A;
        if (e == HW0 || e == 4) w |= G_B;
        if ((e >= LATEAT && e < LATEAT + 4) || e == HW1) w |= G_C;
        s.tile[j][0] = w;
    }
    for (int j = NI1; j < 69; j++) {
        if (j == 12) continue;
        const int at = j < 12 ? (ETRIG >> (4 * (j - 4)) & 15) : j - 5;
        s.tile[at][1] = load_word(j);
        s.tile[at][2] = j >= PFREE ? 0 : PACE0 + j * PACE / 2 + (j > JP2 ? (j - JP2) * PACE2 : 0);
    }
    int done = 0;
    for (int p = 0; p < 16; p++) {
        Step& c = s.st[p];
        c.unit = (int)(VORD2 >> (4 * p) & 15); c.slot = (int)(VSLOT >> (4 * p) & 15); c.par = p >= 9; c.next = -1;
        c.mma0 = done;
        if (p >= NPARK) { const int avail = p - done + (p >= LAG0); c.nmma = p == 15 ? 16 - done : (avail < NMMA ? avail : NMMA); done += c.nmma; }
    }
    for (int p = 9; p < 16; p++) s.st[VTRIG >> (4 * (p - 9)) & 15].next = p;
    return s;
}
constexpr Sched SCH = make_sched();
__host__ __device__ constexpr int kunit(int o) { return o < 5 ? o + 11 : o == 5 ? 10 : o - 6; }

template <int I> struct IC { static constexpr int value = I; };
template <uint32_t I> struct UC { static constexpr uint32_t value = I; };
template <int A, int B, class F> __device__ __forceinline__ void static_for(F&& f) {
    if constexpr (A < B) { f(IC<A>{}); static_for<A + 1, B>(f); }
}

struct Params {
    CUtensorMap tm[9];
    const __nv_bfloat16 *x, *k, *b1, *b2, *w1;
    __nv_bfloat16* out;
    uint4 tile[66];
};

typedef unsigned long long u64;
constexpr int ACC_PITCH = 256;
constexpr int ACC_BYTES = 80 * ACC_PITCH;
__device__ __align__(1024) unsigned char g_acc[4 * ACC_BYTES];
__device__ __align__(1024) u64 g_l0[NCTA][384];
__device__ __align__(1024) u64 g_ll[2][NCTA][256];
__device__ unsigned g_epoch;
__device__ __align__(128) unsigned g_zflag;
#define TSTAMP(i)
#define TSTAMP2(i)
#define TSTAMPL(i)
#define TDUMP()
#define CSTAMP(i, x)
#define TRACE(i)

__device__ __forceinline__ void mbar_wait(uint32_t bar, uint32_t parity) {
    asm volatile("{\n.reg .pred p, q;\n.reg .u32 n;\nmov.u32 n, 0;\n"
                 "LOOP:\nmbarrier.try_wait.parity.shared::cta.b64 p, [%0], %1;\n"
                 "add.u32 n, n, 1;\nsetp.lt.and.u32 q, n, 0x100000, !p;\n@q bra.uni LOOP;\n}"
                 :: "r"(bar), "r"(parity) : "memory");
}
__device__ __forceinline__ bool mbar_test(uint32_t bar, uint32_t parity) {
    uint32_t r;
    asm volatile("{\n.reg .pred p;\nmbarrier.test_wait.parity.shared::cta.b64 p, [%1], %2;\nselp.u32 %0, 1, 0, p;\n}" : "=r"(r) : "r"(bar), "r"(parity) : "memory");
    return __all_sync(~0u, r);
}
__device__ __forceinline__ bool elect() {
    uint32_t r;
    asm volatile("{\n.reg .pred p;\nelect.sync _|p, 0xffffffff;\nselp.u32 %0, 1, 0, p;\n}" : "=r"(r));
    return r != 0;
}
__device__ __forceinline__ void mbar_expect(uint32_t bar, uint32_t bytes) {
    asm volatile("mbarrier.arrive.expect_tx.shared::cta.b64 _, [%0], %1;" :: "r"(bar), "r"(bytes) : "memory");
}
__device__ __forceinline__ uint4 lds128(uint32_t a) {
    uint4 v; asm volatile("ld.shared.v4.u32 {%0,%1,%2,%3}, [%4];" : "=r"(v.x), "=r"(v.y), "=r"(v.z), "=r"(v.w) : "r"(a) : "memory"); return v;
}
__device__ __forceinline__ uint4 ldsm_t(uint32_t a) {
    uint4 v; asm volatile("ldmatrix.sync.aligned.m8n8.x4.trans.shared.b16 {%0,%1,%2,%3}, [%4];" : "=r"(v.x), "=r"(v.y), "=r"(v.z), "=r"(v.w) : "r"(a) : "memory"); return v;
}
__device__ __forceinline__ uint2 lds64(uint32_t a) {
    uint2 v; asm volatile("ld.shared.v2.u32 {%0,%1}, [%2];" : "=r"(v.x), "=r"(v.y) : "r"(a) : "memory"); return v;
}
__device__ __forceinline__ float2 lds64f(uint32_t a) { const uint2 v = lds64(a); return make_float2(__uint_as_float(v.x), __uint_as_float(v.y)); }
__device__ __forceinline__ uint32_t lds32(uint32_t a) {
    uint32_t v; asm volatile("ld.shared.u32 %0, [%1];" : "=r"(v) : "r"(a) : "memory"); return v;
}
__device__ __forceinline__ float ldsf(uint32_t a) { return __uint_as_float(lds32(a)); }
__device__ __forceinline__ void sts32(uint32_t a, uint32_t v) { asm volatile("st.shared.u32 [%0], %1;" :: "r"(a), "r"(v) : "memory"); }
__device__ __forceinline__ void stsf(uint32_t a, float v) { sts32(a, __float_as_uint(v)); }
__device__ __forceinline__ void sts16(uint32_t a, uint32_t v) { asm volatile("st.shared.u16 [%0], %1;" :: "r"(a), "h"((uint16_t)v) : "memory"); }
__device__ __forceinline__ void sts64(uint32_t a, uint32_t x, uint32_t y) { asm volatile("st.shared.v2.u32 [%0], {%1,%2};" :: "r"(a), "r"(x), "r"(y) : "memory"); }
__device__ __forceinline__ void sts64f(uint32_t a, float x, float y) { sts64(a, __float_as_uint(x), __float_as_uint(y)); }
__device__ __forceinline__ void sts128f(uint32_t a, float x, float y, float z, float w) {
    asm volatile("st.shared.v4.f32 [%0], {%1,%2,%3,%4};" :: "r"(a), "f"(x), "f"(y), "f"(z), "f"(w) : "memory");
}
__device__ __forceinline__ void mma(float (&c)[4], const uint4& a, uint32_t b0, uint32_t b1) {
    asm volatile("mma.sync.aligned.m16n8k16.row.col.f32.bf16.bf16.f32 {%0,%1,%2,%3}, {%4,%5,%6,%7}, {%8,%9}, {%0,%1,%2,%3};"
                 : "+f"(c[0]), "+f"(c[1]), "+f"(c[2]), "+f"(c[3]) : "r"(a.x), "r"(a.y), "r"(a.z), "r"(a.w), "r"(b0), "r"(b1));
}
__device__ __forceinline__ u64 ld_rlx(const void* p) {
    u64 a; asm volatile("ld.relaxed.gpu.global.u64 %0, [%1];" : "=l"(a) : "l"(p) : "memory"); return a;
}
__device__ __forceinline__ void ld_rlx2(const void* p, u64& a, u64& b) {
    asm volatile("ld.relaxed.gpu.global.v2.u64 {%0,%1}, [%2];" : "=l"(a), "=l"(b) : "l"(p) : "memory");
}
__device__ __forceinline__ void st_rlx(void* p, u64 a) { asm volatile("st.relaxed.gpu.global.u64 [%0], %1;" :: "l"(p), "l"(a) : "memory"); }
__device__ __forceinline__ u64 ll_pack(float v, uint32_t tag) { return ((u64)tag << 32) | __float_as_uint(v); }
__device__ __forceinline__ float ll_val(u64 w) { return __uint_as_float((uint32_t)w); }
__device__ __forceinline__ uint32_t ll_tag(u64 w) { return (uint32_t)(w >> 32); }
__device__ __forceinline__ float bf_lo(uint32_t u) { return __uint_as_float(u << 16); }
__device__ __forceinline__ float bf_hi(uint32_t u) { return __uint_as_float(u & 0xffff0000u); }
__device__ __forceinline__ uint32_t pack_bf(float lo, float hi) {
    uint32_t r; asm("cvt.rn.bf16x2.f32 %0, %1, %2;" : "=r"(r) : "f"(hi), "f"(lo)); return r;
}
__device__ __forceinline__ float ex2(float v) { float r; asm("ex2.approx.ftz.f32 %0, %1;" : "=f"(r) : "f"(v)); return r; }
__device__ __forceinline__ float rcp(float v) { float r; asm("rcp.approx.ftz.f32 %0, %1;" : "=f"(r) : "f"(v)); return r; }
__device__ __forceinline__ float rsq(float v) { float r; asm("rsqrt.approx.ftz.f32 %0, %1;" : "=f"(r) : "f"(v)); return r; }
__device__ __forceinline__ void bar_sync(int id, int n) { asm volatile("bar.sync %0, %1;" :: "r"(id), "r"(n) : "memory"); }
__device__ __forceinline__ uint32_t clk() { uint32_t c; asm volatile("mov.u32 %0, %clock;" : "=r"(c)); return c; }
__device__ __forceinline__ uint32_t pin(uint32_t v) { return __shfl_xor_sync(~0u, v, 0); }
__device__ __forceinline__ float shx(float v, int o) { return __shfl_xor_sync(~0u, v, o); }

__device__ __forceinline__ u64 fx_pack(float v, float scale) { return ((u64)__float2ll_rn(v * scale) & ~255ull) | 1ull; }
__device__ __forceinline__ float fx_scale(float meansq) {
    const int e = max(((int)(__float_as_uint(meansq) >> 23) - 127) >> 1, -6);
    return __uint_as_float((uint32_t)(127 + 32 - e) << 23);
}
__device__ __forceinline__ float fx_inv(float scale) { return __uint_as_float((254u << 23) - __float_as_uint(scale)); }
__device__ __forceinline__ uint32_t lo32(u64 w) { uint32_t l; asm("mov.b64 {%0, _}, %1;" : "=r"(l) : "l"(w)); return l; }
__device__ __forceinline__ int hi32(u64 w) { int h; asm("mov.b64 {_, %0}, %1;" : "=r"(h) : "l"(w)); return h; }
__device__ __forceinline__ float fx_val(u64 w) { return (float)hi32(w) * 4294967296.f + (float)lo32(w); }
constexpr float FX2_ONE = 12582912.f;
__device__ __forceinline__ float fx2_scale(float meansq) { return __uint_as_float((uint32_t)(127 + 16 - max(((int)(__float_as_uint(meansq) >> 23) - 127) >> 1, -100)) << 23); }
__device__ __forceinline__ u64 fx2_pack(float a, float b) {
    const uint32_t lo = __float_as_uint(a) * 512u + (1u - 0x4b400000u * 512u);
    return lo | (u64)(__float_as_uint(b) * 16u - 0x4b400000u * 16u + (uint32_t)((int)lo >> 31)) << 32;
}
__device__ __forceinline__ float fx2_lo(u64 w, float inv) { return (float)(int)(__funnelshift_r(lo32(w), hi32(w), 4) & ~31u) * (inv * 0.5f); }
__device__ __forceinline__ float fx2_hi(u64 w, float inv) { return (float)((hi32(w) + 8) & ~15) * inv; }
__device__ __forceinline__ float fx2_inv(float meansq) { return fx_inv(fx2_scale(meansq)) * 0.0625f; }
__device__ __forceinline__ uint32_t fx2_wide(const unsigned char* a, u64 w, float meansq) {
    const float inv = fx_inv(fx_scale(meansq));
    return pack_bf(fx2_lo(w, fx2_inv(meansq)) + fx_val(ld_rlx(a + 64)) * inv, fx2_hi(w, fx2_inv(meansq)) + fx_val(ld_rlx(a + 96)) * inv);
}
template <int N, bool LOOK, class A> __device__ __forceinline__ void fx2_wait(A a, u64 (&w)[N], uint32_t msqa, float inv, uint32_t (&x)[N]) {
    int it = 0;
    uint32_t miss = lds32(msqa + 4);
    do {
        if (__all_sync(~0u, !(miss & 96))) {
            __threadfence();
#pragma unroll
            for (int i = 0; i < N; i++) x[i] = 0;
#pragma unroll 1
            for (int i = 0; i < 2 * N; i++) {
                const u64 v = ld_rlx(a(i >> 1));
                const float y = ((i & 1) ? fx2_hi(v, inv) : fx2_lo(v, inv)) + fx_val(ld_rlx(a(i >> 1) + 64 + (i & 1) * 32)) * fx_inv(fx_scale(ldsf(msqa)));
#pragma unroll
                for (int k = 0; k < N; k++) x[k] = __funnelshift_r(x[k], k + 1 < N ? x[k + 1] : pack_bf(y, y), 16);
            }
            return;
        }
        if (!LOOK || it) {
#pragma unroll
            for (int i = 0; i < N; i++) w[i] = ld_rlx(a(i));
        }
        uint32_t all = lo32(w[0]), any = all;
#pragma unroll
        for (int i = 1; i < N; i++) { all &= lo32(w[i]); any |= lo32(w[i]); }
        miss = (~all & 96) | (any & 256);
    } while (__any_sync(~0u, miss) & (++it < SPIN));
#pragma unroll
    for (int i = 0; i < N; i++) x[i] = pack_bf(fx2_lo(w[i], inv), fx2_hi(w[i], inv));
}
__device__ __forceinline__ void st_rlx_if(bool p, void* a, u64 v) {
    asm volatile("{\n.reg .pred p;\nsetp.ne.u32 p, %2, 0;\n@p st.relaxed.gpu.global.u64 [%0], %1;\n}" :: "l"(a), "l"(v), "r"((uint32_t)p) : "memory");
}
__device__ __forceinline__ void sts128f(uint32_t a, const float (&v)[4]) { sts128f(a, v[0], v[1], v[2], v[3]); }
__device__ __forceinline__ void bar_arrive(int id, int n) { asm volatile("bar.arrive %0, %1;" :: "r"(id), "r"(n) : "memory"); }
template <class T> __device__ __forceinline__ T* pin(T* p) { return reinterpret_cast<T*>(__shfl_xor_sync(~0u, (u64)p, 0)); }

__device__ __forceinline__ void tma3(uint32_t dst, const CUtensorMap* tm, int c1, int c2, uint32_t bar, uint32_t pol) {
    asm volatile("cp.async.bulk.tensor.3d.shared::cluster.global.mbarrier::complete_tx::bytes.L2::cache_hint [%0], [%1, {%2, %3, %4}], [%5], %6;"
                 :: "r"(dst), "l"(tm), "r"(0), "r"(c1), "r"(c2), "r"(bar), "l"((u64)pol << 32) : "memory");
}
__device__ __forceinline__ void tma3_pf(const CUtensorMap* tm, int c1, int c2, uint32_t pol) {
    asm volatile("cp.async.bulk.prefetch.tensor.3d.L2.global.tile.L2::cache_hint [%0, {%1, %2, %3}], %4;"
                 :: "l"(tm), "r"(0), "r"(c1), "r"(c2), "l"((u64)pol << 32) : "memory");
}
__device__ __forceinline__ void issue_half(uint32_t d, uint32_t sb, int rowc, int cta, const CUtensorMap* tm0) {
    const uint32_t bar = sb + SM_CBAR + (d & 0xf8);
    const CUtensorMap* tm = tm0 + ((d >> 8) & 3);
    const int c1 = (d & 0x200) ? (cta & 3) + 4 * (d >> 20) : 0, c2 = (d & 0x200) ? (cta >> 2) * DH : rowc + (d >> 20);
    mbar_expect(bar, HALF);
    tma3(sb + (d & 0x3f000), tm, c1, c2, bar, POL_FIRST);
    if (!(d & 1)) tma3_pf(tm + 2, c1, c2, POL_NORMAL);
}
__device__ __forceinline__ uint32_t cnt_inc(uint32_t a, uint32_t last) {
    uint32_t old; asm volatile("atom.relaxed.cta.shared.inc.u32 %0, [%1], %2;" : "=r"(old) : "r"(a), "r"(last) : "memory"); return old;
}
__device__ __forceinline__ void wait_until(uint32_t due) {
#pragma unroll 1
    for (int it = 0; it < 4096; it++) { uint32_t now; asm volatile("mov.u32 %0, %globaltimer_lo;" : "=r"(now)); if ((int)(now - due) >= 0) break; }
}
__device__ __forceinline__ uint32_t bf2_mul(uint32_t a, uint32_t b) { uint32_t r; asm("mul.rn.bf16x2 %0, %1, %2;" : "=r"(r) : "r"(a), "r"(b)); return r; }
__device__ __forceinline__ uint32_t bf2_fma(uint32_t a, uint32_t b, uint32_t c) { uint32_t r; asm("fma.rn.bf16x2 %0, %1, %2, %3;" : "=r"(r) : "r"(a), "r"(b), "r"(c)); return r; }
__device__ __forceinline__ uint32_t bf2_amax(uint32_t a, uint32_t b) { uint32_t r; asm("max.NaN.xorsign.abs.bf16x2 %0, %1, %2;" : "=r"(r) : "r"(a), "r"(b)); return r; }
__device__ __forceinline__ uint4 k_unpack(uint32_t l0, uint32_t l1, uint32_t h, uint32_t m1) {
    const uint32_t ha = h & 0x87878787u, hc = ha * m1 + h, hb = __funnelshift_l(hc, hc, 4);
    return make_uint4(__byte_perm(l0, ha, 0x5140), __byte_perm(l0, ha, 0x7362), __byte_perm(l1, hb, 0x5140), __byte_perm(l1, hb, 0x7362));
}
#define KR4(u, i) "+r"(kr[u][i].x), "+r"(kr[u][i].y), "+r"(kr[u][i].z), "+r"(kr[u][i].w)
#define KR6(u) KR4(u, 0), KR4(u, 1), KR4(u, 2), KR4(u, 3), KR4(u, 4), KR4(u, 5)
__device__ __forceinline__ void k_keep(uint4 (&kr)[8][6], const uint32_t (&c)[18], int e, uint32_t a) {
    asm volatile("{\nKT: .branchtargets K0, K1, K2, K3, K4, K5, K6, K7, K8, K9, K10, K11, K12, K13, K14, K15;\nbrx.idx.uni %210, KT;\n"
                 "K0: mov.b32 %12, %192; mov.b32 %13, %193; mov.b32 %14, %194; mov.b32 %15, %195; mov.b32 %16, %196; mov.b32 %17, %197; mov.b32 %18, %198; mov.b32 %19, %199; mov.b32 %20, %200; mov.b32 %21, %201; mov.b32 %22, %202; mov.b32 %23, %203; mov.b32 %24, %204; mov.b32 %25, %205; mov.b32 %26, %206; mov.b32 %27, %207; mov.b32 %28, %208; mov.b32 %29, %209; bra.uni KE;\n"
                 "K1: mov.b32 %30, %192; mov.b32 %31, %193; mov.b32 %32, %194; mov.b32 %33, %195; mov.b32 %34, %196; mov.b32 %35, %197; mov.b32 %36, %198; mov.b32 %37, %199; mov.b32 %38, %200; mov.b32 %39, %201; mov.b32 %40, %202; mov.b32 %41, %203; mov.b32 %42, %204; mov.b32 %43, %205; mov.b32 %44, %206; mov.b32 %45, %207; mov.b32 %46, %208; mov.b32 %47, %209; bra.uni KE;\n"
                 "K2: mov.b32 %48, %192; mov.b32 %49, %193; mov.b32 %50, %194; mov.b32 %51, %195; mov.b32 %52, %196; mov.b32 %53, %197; mov.b32 %54, %198; mov.b32 %55, %199; mov.b32 %56, %200; mov.b32 %57, %201; mov.b32 %58, %202; mov.b32 %59, %203; mov.b32 %60, %204; mov.b32 %61, %205; mov.b32 %62, %206; mov.b32 %63, %207; mov.b32 %64, %208; mov.b32 %65, %209; bra.uni KE;\n"
                 "K3: mov.b32 %66, %192; mov.b32 %67, %193; mov.b32 %68, %194; mov.b32 %69, %195; mov.b32 %70, %196; mov.b32 %71, %197; mov.b32 %72, %198; mov.b32 %73, %199; mov.b32 %74, %200; mov.b32 %75, %201; mov.b32 %76, %202; mov.b32 %77, %203; mov.b32 %78, %204; mov.b32 %79, %205; mov.b32 %80, %206; mov.b32 %81, %207; mov.b32 %82, %208; mov.b32 %83, %209; bra.uni KE;\n"
                 "K4: mov.b32 %84, %192; mov.b32 %85, %193; mov.b32 %86, %194; mov.b32 %87, %195; mov.b32 %88, %196; mov.b32 %89, %197; mov.b32 %90, %198; mov.b32 %91, %199; mov.b32 %92, %200; mov.b32 %93, %201; mov.b32 %94, %202; mov.b32 %95, %203; mov.b32 %96, %204; mov.b32 %97, %205; mov.b32 %98, %206; mov.b32 %99, %207; mov.b32 %100, %208; mov.b32 %101, %209; bra.uni KE;\n"
                 "K5: mov.b32 %102, %192; mov.b32 %103, %193; mov.b32 %104, %194; mov.b32 %105, %195; mov.b32 %106, %196; mov.b32 %107, %197; mov.b32 %108, %198; mov.b32 %109, %199; mov.b32 %110, %200; mov.b32 %111, %201; mov.b32 %112, %202; mov.b32 %113, %203; mov.b32 %114, %204; mov.b32 %115, %205; mov.b32 %116, %206; mov.b32 %117, %207; mov.b32 %118, %208; mov.b32 %119, %209; bra.uni KE;\n"
                 "K6: mov.b32 %120, %192; mov.b32 %121, %193; mov.b32 %122, %194; mov.b32 %123, %195; mov.b32 %124, %196; mov.b32 %125, %197; mov.b32 %126, %198; mov.b32 %127, %199; mov.b32 %128, %200; mov.b32 %129, %201; mov.b32 %130, %202; mov.b32 %131, %203; mov.b32 %132, %204; mov.b32 %133, %205; mov.b32 %134, %206; mov.b32 %135, %207; mov.b32 %136, %208; mov.b32 %137, %209; bra.uni KE;\n"
                 "K7: mov.b32 %138, %192; mov.b32 %139, %193; mov.b32 %140, %194; mov.b32 %141, %195; mov.b32 %142, %196; mov.b32 %143, %197; mov.b32 %144, %198; mov.b32 %145, %199; mov.b32 %146, %200; mov.b32 %147, %201; mov.b32 %148, %202; mov.b32 %149, %203; mov.b32 %150, %204; mov.b32 %151, %205; mov.b32 %152, %206; mov.b32 %153, %207; mov.b32 %154, %208; mov.b32 %155, %209; bra.uni KE;\n"
                 "K8: mov.b32 %156, %192; mov.b32 %157, %193; mov.b32 %158, %194; mov.b32 %159, %195; mov.b32 %160, %196; mov.b32 %161, %197; mov.b32 %162, %198; mov.b32 %163, %199; mov.b32 %164, %200; mov.b32 %165, %201; mov.b32 %166, %202; mov.b32 %167, %203; mov.b32 %168, %204; mov.b32 %169, %205; mov.b32 %170, %206; mov.b32 %171, %207; mov.b32 %172, %208; mov.b32 %173, %209; bra.uni KE;\n"
                 "K9: mov.b32 %174, %192; mov.b32 %175, %193; mov.b32 %176, %194; mov.b32 %177, %195; mov.b32 %178, %196; mov.b32 %179, %197; mov.b32 %180, %198; mov.b32 %181, %199; mov.b32 %182, %200; mov.b32 %183, %201; mov.b32 %184, %202; mov.b32 %185, %203; mov.b32 %186, %204; mov.b32 %187, %205; mov.b32 %188, %206; mov.b32 %189, %207; mov.b32 %190, %208; mov.b32 %191, %209; bra.uni KE;\n"
                 "K10: st.shared.v2.b32 [%211+75784], {%192, %193}; st.shared.v2.b32 [%211+76288], {%194, %195}; st.shared.v2.b32 [%211+76296], {%196, %197}; mov.b32 %0, %198; mov.b32 %1, %199; mov.b32 %2, %200; mov.b32 %3, %201; mov.b32 %4, %202; mov.b32 %5, %203; mov.b32 %6, %204; mov.b32 %7, %205; mov.b32 %8, %206; mov.b32 %9, %207; mov.b32 %10, %208; mov.b32 %11, %209; bra.uni KE;\n"
                 "K11: st.shared.v2.b32 [%211+0], {%192, %193}; st.shared.v2.b32 [%211+8], {%194, %195}; st.shared.v2.b32 [%211+512], {%196, %197}; st.shared.v2.b32 [%211+520], {%198, %199}; st.shared.v2.b32 [%211+1024], {%200, %201}; st.shared.v2.b32 [%211+1032], {%202, %203}; st.shared.v2.b32 [%211+1536], {%204, %205}; st.shared.v2.b32 [%211+1544], {%206, %207}; st.shared.v2.b32 [%211+2048], {%208, %209}; bra.uni KE;\n"
                 "K12: st.shared.v2.b32 [%211+2056], {%192, %193}; st.shared.v2.b32 [%211+2560], {%194, %195}; st.shared.v2.b32 [%211+2568], {%196, %197}; st.shared.v2.b32 [%211+24576], {%198, %199}; st.shared.v2.b32 [%211+24584], {%200, %201}; st.shared.v2.b32 [%211+25088], {%202, %203}; st.shared.v2.b32 [%211+25096], {%204, %205}; st.shared.v2.b32 [%211+25600], {%206, %207}; st.shared.v2.b32 [%211+25608], {%208, %209}; bra.uni KE;\n"
                 "K13: st.shared.v2.b32 [%211+26112], {%192, %193}; st.shared.v2.b32 [%211+26120], {%194, %195}; st.shared.v2.b32 [%211+26624], {%196, %197}; st.shared.v2.b32 [%211+26632], {%198, %199}; st.shared.v2.b32 [%211+27136], {%200, %201}; st.shared.v2.b32 [%211+27144], {%202, %203}; st.shared.v2.b32 [%211+49152], {%204, %205}; st.shared.v2.b32 [%211+49160], {%206, %207}; st.shared.v2.b32 [%211+49664], {%208, %209}; bra.uni KE;\n"
                 "K14: st.shared.v2.b32 [%211+49672], {%192, %193}; st.shared.v2.b32 [%211+50176], {%194, %195}; st.shared.v2.b32 [%211+50184], {%196, %197}; st.shared.v2.b32 [%211+50688], {%198, %199}; st.shared.v2.b32 [%211+50696], {%200, %201}; st.shared.v2.b32 [%211+51200], {%202, %203}; st.shared.v2.b32 [%211+51208], {%204, %205}; st.shared.v2.b32 [%211+51712], {%206, %207}; st.shared.v2.b32 [%211+51720], {%208, %209}; bra.uni KE;\n"
                 "K15: st.shared.v2.b32 [%211+73728], {%192, %193}; st.shared.v2.b32 [%211+73736], {%194, %195}; st.shared.v2.b32 [%211+74240], {%196, %197}; st.shared.v2.b32 [%211+74248], {%198, %199}; st.shared.v2.b32 [%211+74752], {%200, %201}; st.shared.v2.b32 [%211+74760], {%202, %203}; st.shared.v2.b32 [%211+75264], {%204, %205}; st.shared.v2.b32 [%211+75272], {%206, %207}; st.shared.v2.b32 [%211+75776], {%208, %209}; \nKE:\n}"
                 : KR6(0), KR6(1), KR6(2), KR6(3), KR6(4), KR6(5), KR6(6), KR6(7)
                 : "r"(c[0]), "r"(c[1]), "r"(c[2]), "r"(c[3]), "r"(c[4]), "r"(c[5]), "r"(c[6]), "r"(c[7]), "r"(c[8]), "r"(c[9]), "r"(c[10]), "r"(c[11]), "r"(c[12]), "r"(c[13]), "r"(c[14]), "r"(c[15]), "r"(c[16]), "r"(c[17]), "r"(e), "r"(a) : "memory");
}
template <int K> __device__ __forceinline__ uint32_t& word(uint4& v) { if constexpr (K == 0) return v.x; else if constexpr (K == 1) return v.y; else if constexpr (K == 2) return v.z; else return v.w; }
__device__ __forceinline__ void add_if(bool p, float& d, float a, float b) {
    asm volatile("{\n.reg .pred p;\nsetp.ne.u32 p, %3, 0;\n@p add.f32 %0, %1, %2;\n}" : "+f"(d) : "f"(a), "f"(b), "r"((uint32_t)p));
}
__device__ __forceinline__ float warp_max(float v) {
#pragma unroll
    for (int o = 16; o; o >>= 1) v = fmaxf(v, shx(v, o));
    return v;
}
__device__ __forceinline__ float warp_sum(float v) {
#pragma unroll
    for (int o = 16; o; o >>= 1) v += shx(v, o);
    return v;
}
template <int PITCH> __device__ __forceinline__ void ll_look(const u64* buf, u64 (&w)[4]) {
#pragma unroll
    for (int i = 0; i < 4; i++) w[i] = ld_rlx(buf + i * PITCH);
}
template <int PITCH> __device__ __forceinline__ float ll_gather(const u64* buf, uint32_t tag, u64 (&w)[4]) {
    auto miss = [&]() { return __any_sync(~0u, ((ll_tag(w[0]) ^ tag) | (ll_tag(w[1]) ^ tag)) | ((ll_tag(w[2]) ^ tag) | (ll_tag(w[3]) ^ tag))); };
    int it = 0;
    goto check;
again:
    ll_look<PITCH>(buf, w);
check:
    if (miss() & (++it < SPIN)) goto again;
    return (ll_val(w[0]) + ll_val(w[1])) + (ll_val(w[2]) + ll_val(w[3]));
}
__device__ __forceinline__ float sum8(uint32_t a, int pitch) {
    float s[8];
#pragma unroll
    for (int w = 0; w < 8; w++) s[w] = ldsf(a + w * pitch);
    return ((s[0] + s[1]) + (s[2] + s[3])) + ((s[4] + s[5]) + (s[6] + s[7]));
}
__device__ __forceinline__ float sum5(float a, float b, float c, float d, float e) { return ((a + b) + (c + d)) + e; }
__device__ __forceinline__ float ln_part(uint2 xp, int lane) {
    const float x0 = bf_lo(xp.x), x1 = bf_hi(xp.x), x2 = bf_lo(xp.y), x3 = bf_hi(xp.y);
    const float s1 = (x0 + x1) + (x2 + x3), s2 = (x0 * x0 + x1 * x1) + (x2 * x2 + x3 * x3);
    return ((lane & 16) ? s2 : s1) + shx((lane & 16) ? s1 : s2, 16);
}
__device__ __forceinline__ float ln_rstd(float mean, float msq) { return rsq(fmaxf(msq - mean * mean, 0.f) + 1e-5f); }
constexpr float CS = 0.07216878364870322f * 1.4426950408889634f;
constexpr uint32_t ONES = 0x3f803f80u;

__global__ void __launch_bounds__(NTHR, 1) fused_kernel(const __grid_constant__ Params P) {
    extern __shared__ __align__(1024) unsigned char smem[];
    const uint32_t sb = (uint32_t)__cvta_generic_to_shared(smem);
    const int bx = blockIdx.x;
    const int cta0 = bx >= NCTA || CMAP == 0 ? bx : CMAP == 4 ? (((bx >> 1) & 7) + (bx >> 5) * 8) * 4 + ((bx >> 4) & 1) * 2 + (bx & 1)
                   : (((bx >> 1) & 15) + (bx >> 6) * 16) * 4 + ((bx >> 5) & 1) * 2 + (bx & 1);
    int id = cta0 * NTHR + threadIdx.x, tid, lane, g, t, key, warp, cta, mlp, rowc, roww, j40;
    uint32_t maskA, maskB, barw, subw, prow;
    auto fresh = [&]() {
        const int cw = __shfl_sync(~0u, id >> 5, 0);
        id = pin(id); tid = id & 255; lane = id & 31; g = lane >> 2; t = lane & 3; key = (g >> 1) + 4 * (g & 1);
        const uint32_t m = (g & 1) ? 0xffff0000u : 0x0000ffffu;
        maskA = (g & 2) ? 0u : m; maskB = (g & 2) ? m : 0u;
        warp = cw & 7; cta = cw >> 3;
        mlp = (cta & 3) == 3 ? 96 : (cta >> 2) * 3 + (cta & 3);
        rowc = (cta >> 2) * SK + (SK - WIN) + (cta & 3) * 64; roww = rowc + warp * 8;
        j40 = (cta & 3) * 40;
        barw = sb + SM_BAR + warp * 96; subw = sb + warp * SUB; prow = sb + SM_PART + warp * 768;
    };
    fresh();

    if (cta == NCTA) {
        const uint32_t ep = *(volatile unsigned*)&g_epoch;
        if (tid == 0) {
#pragma unroll 1
            for (int it = 0; it < SPIN; it++) { if (ll_tag(ld_rlx(&g_ll[0][0][192])) == ep * 4 + 2) break; __nanosleep(200); }
        }
        __syncthreads();
#pragma unroll 1
        for (int i = tid; i < 4 * 80 * 8; i += NTHR)
            *reinterpret_cast<uint4*>(g_acc + (i >> 3) * ACC_PITCH + (i & 7) * 16) = make_uint4(0, 0, 0, 0);
        __threadfence();
        __syncthreads();
        if (tid == 0) asm volatile("st.relaxed.gpu.global.u32 [%0], %1;" :: "l"(&g_zflag), "r"(ep + 1) : "memory");
        return;
    }
    TSTAMP(0);
    if (tid == 64) { uint32_t now; asm volatile("mov.u32 %0, %globaltimer_lo;" : "=r"(now)); sts32(sb + SM_T0, now); }

    const CUtensorMap* tmk = reinterpret_cast<const CUtensorMap*>(__shfl_sync(~0u, (u64)&P.tm[0] + (lane >> 5), 0));
    auto issue_first = [&](int j) {
        mbar_expect(sb + SM_CBAR + 80 + j * 8, HALF);
        tma3(sb + j * HALF, tmk + TM_KH, 0, rowc + (j >> 1) * 256 + (j & 1) * 32, sb + SM_CBAR + 80 + j * 8, POL_FIRST);
    };
    if (elect()) {
        asm volatile("mbarrier.init.shared::cta.b64 [%0], 1;" :: "r"(barw + 72));
        asm volatile("mbarrier.init.shared::cta.b64 [%0], 1;" :: "r"(sb + SM_CBAR + 64 + warp * 8));
        asm volatile("fence.mbarrier_init.release.cluster;" ::: "memory");
        mbar_expect(barw + 72, warp < 4 ? 3 * SUB : 2 * SUB);
        const int r0 = (cta & 3) * 160 + warp * 8;
        tma3(subw + SM_WQ, tmk + TM_WQ, (cta >> 2) * 3, r0, barw + 72, POL_FIRST);
        tma3(subw + SM_WQ + TILE, tmk + TM_WQ, (cta >> 2) * 3, r0 + 64, barw + 72, POL_FIRST);
        if (warp < 4) tma3(subw + SM_WQR, tmk + TM_WQ, (cta >> 2) * 3, r0 + 128, barw + 72, POL_FIRST);
        if (warp >= 2 && warp < NI0 + 2) issue_first(warp - 2);
#pragma unroll
        for (int i = 0; i < 9; i++) asm volatile("mbarrier.init.shared::cta.b64 [%0], 1;" :: "r"(barw + i * 8));
        asm volatile("mbarrier.init.shared::cta.b64 [%0], 1;" :: "r"(sb + SM_CBAR + warp * 8));
        asm volatile("mbarrier.init.shared::cta.b64 [%0], 1;" :: "r"(sb + SM_CBAR + 128 + warp * 8));
        if (warp < 3) asm volatile("mbarrier.init.shared::cta.b64 [%0], %1;" :: "r"(sb + SM_CBAR + 192 + warp * 8), "r"(warp == 2 ? 8 : 1));
        sts64(barw + 80, 0, 0);
        asm volatile("fence.proxy.async.shared::cta;" ::: "memory");
        asm volatile("prefetch.tensormap [%0];" :: "l"(tmk + warp + 1) : "memory");
    }
    __syncwarp();
    auto c4 = [&]() { return 32 * min(warp, 4) + 16 * (t >> 1) + 2 * g + (t & 1); };
    uint2 xp = make_uint2(0, 0);
    if (tid < 160) asm volatile("ld.global.nc.v2.u32 {%0,%1}, [%2];" : "=r"(xp.x), "=r"(xp.y) : "l"(P.x + 4 * c4()) : "memory");
    else if (tid == 255) { sts32(sb + SM_EPOCH, *(volatile unsigned*)&g_epoch); sts32(sb + SM_M1, ~0u); }
    else if (tid < 176) sts32(sb + SM_B1 + (tid - 160) * 4, (uint32_t)reinterpret_cast<const volatile unsigned short*>(P.b1)[min(mlp, 95) * 16 + tid - 160] << 16);
    else if (tid >= 192 && tid < 192 + NCB) sts32(sb + SM_CNT + (tid - 192) * 8, 0);
    unsigned char* accg = reinterpret_cast<unsigned char*>(__shfl_sync(~0u, (u64)g_acc + (lane >> 5), 0));
    auto release = [&](const uint4& tw) {
        uint32_t old;
        __syncwarp();
        asm volatile("{\n.reg .pred p;\nsetp.eq.u32 p, %2, 0;\nmov.u32 %0, 0;\n@p atom.relaxed.cta.shared.inc.u32 %0, [%1], 3;\n}"
                     : "=r"(old) : "r"(sb + SM_CNT + (tw.x & 0xf8)), "r"(lane) : "memory");
        return old;
    };
    auto refill = [&](const uint4& tw, uint32_t old) {
        if (__any_sync(~0u, old == 3 && (tw.y & 2))) {
            wait_until(lds32(sb + SM_T0) + tw.z);
            if (elect()) issue_half(tw.y, sb, rowc, cta, tmk);
            __syncwarp();
        }
    };
    __syncthreads();
    auto issue_paced = [&](int j0, int j1) {
        if (warp >= j0 && warp < j1) {
            wait_until(lds32(sb + SM_T0) + PACES + warp * PACE / 2);
            if (elect()) issue_first(warp);
            __syncwarp();
        }
    };
    issue_paced(NI0, NIM);
    mbar_wait(barw + 72, 0);

    uint32_t offV0, offV2;
    auto calc_offsets = [&]() {
        offV0 = subw + (6 * t) * 128 + ((g ^ ((6 * t) & 7)) << 4);
        offV2 = subw + (6 * t + 2) * 128 + ((g ^ ((6 * t + 2) & 7)) << 4);
    };
    calc_offsets();

    auto load_v = [&](uint4 (&v)[6], uint32_t so) {
        v[0] = lds128(offV0 + so); v[1] = lds128((offV0 ^ 16) + so + 128); v[2] = lds128(offV2 + so);
        v[3] = lds128((offV2 ^ 16) + so + 128); v[4] = lds128((offV0 ^ 64) + so + 512); v[5] = lds128((offV0 ^ 80) + so + 640);
    };
    auto issue_v = [&](auto I, int dw) {
        constexpr Step c = SCH.st[I.value];
        const uint32_t bar = barw + dw * 96 + c.slot * 8;
        mbar_expect(bar, SUB);
        tma3(subw + dw * SUB + c.slot * TILE, tmk + TM_V, 0, roww + dw * 8 + c.unit * 256, bar, POL_FIRST);
    };
    auto refill2 = [&](auto I) { __syncwarp(); if (elect()) issue_v(I, 0); };
    uint4 wq0[6], wqh[3], wq1[6];
    auto load_wq1 = [&](int i) { wq1[i] = lds128((i == 2 ? offV2 : i == 3 ? (offV2 ^ 16) + 128 : (offV0 ^ (i * 16)) + i * 128) + SM_WQ + TILE); };
    auto load_wq = [&]() {
        load_v(wq0, SM_WQ);
        const uint32_t so = SM_WQR - ((warp + 1) >> 1) * SUB;
        wqh[0] = lds128(((warp & 1) ? (offV2 ^ 16) + 128 : offV0) + so);
        wqh[1] = lds128(((warp & 1) ? (offV0 ^ 64) + 512 : (offV0 ^ 16) + 128) + so);
        wqh[2] = lds128(((warp & 1) ? (offV0 ^ 80) + 640 : offV2) + so);
#pragma unroll
        for (int i = 0; i < NWQ1; i++) load_wq1(i);
    };
    auto xcol = [&](int i, int tt) { return (i < 2 ? 64 * i + 8 * warp : 128 + 8 * (warp >> 1)) + 2 * tt; };
    uint4 kr[8][6];
    const unsigned char* rap;
    u64 rw[2];
    auto q_proj = [&](auto L, uint32_t (&p)[3], uint32_t pst) {
        if (L.value == 0 && g >= 4) p[0] = p[1] = p[2] = ONES;
        float a[3][4], b[3][4];
        const uint32_t dH = __byte_perm(p[2], 0, (warp & 1) ? 0x3232 : 0x1010);
        const uint32_t dA = __byte_perm(p[0], 0, 0x1010), dB = __byte_perm(p[0], 0, 0x3232), dC = __byte_perm(p[1], 0, 0x1010), dD = __byte_perm(p[1], 0, 0x3232);
#pragma unroll
        for (int i = NWQ1; i < 3; i++) load_wq1(i);
#pragma unroll
        for (int j = 0; j < 3; j++) { a[j][0] = a[j][1] = a[j][2] = a[j][3] = 0.f; mma(a[j], wq0[j], dA & maskA, dA & maskB); }
#pragma unroll
        for (int j = 0; j < 3; j++) { b[j][0] = b[j][1] = b[j][2] = b[j][3] = 0.f; mma(b[j], wq0[j + 3], dB & maskA, dB & maskB); }
#pragma unroll
        for (int j = 0; j < 3; j++) mma(a[j], wqh[j], dH & maskA, dH & maskB);
#pragma unroll
        for (int i = 3; i < 6; i++) load_wq1(i);
        auto look_rw = [&]() {
            if constexpr (L.value == 1) {
                if (NWQ1) rap = accg + ACC_BYTES + (c4() >> 2) * ACC_PITCH + (c4() & 3) * 8;
                rw[0] = ld_rlx(rap); rw[1] = ld_rlx(rap + 40 * ACC_PITCH);
            }
        };
        if (RWAT == 0) look_rw();
        if (L.value == 1 && P4AT == 2) refill2(IC<4>{});
#pragma unroll
        for (int j = 0; j < 3; j++) mma(b[j], wq1[j], dC & maskA, dC & maskB);
#pragma unroll
        for (int j = 0; j < 3; j++) mma(a[j], wq1[j + 3], dD & maskA, dD & maskB);
#pragma unroll
        for (int j = 0; j < 3; j++) {
#pragma unroll
            for (int k = 0; k < 4; k++) a[j][k] += b[j][k];
            sts128f(pst + j * 256, a[j]);
        }
        const uint32_t tag = lds32(sb + SM_EPOCH) * 4 + 1 + 2 * L.value;
        u64* pub = L.value ? &g_ll[0][cta][tid] : &g_l0[cta][tid];
        if (RWAT == 1) look_rw();
        if (L.value == 0) asm volatile("fence.proxy.async.shared::cta;" ::: "memory");
        TSTAMPL(21);
        __syncthreads();
        st_rlx_if(tid < 192, pub, ll_pack(sum8(sb + SM_PART + tid * 4, 768), tag));
        if constexpr (L.value == 0) st_rlx_if(tid < 192, pub + 192, ll_pack(sum8(sb + SM_CSP + tid * 4, 768), tag));
        TSTAMPL(23);
    };
    auto ln_stats = [&]() {
        float ss = ln_part(xp, lane);
        ss += shx(ss, 8); ss += shx(ss, 4); ss += shx(ss, 2); ss += shx(ss, 1);
        stsf(sb + SM_STAT + min(warp, 4) * 8 + (lane >> 4) * 4, ss);
    };
    auto ln_final = [&](float& mean, float& rstd) {
        float2 v[5];
#pragma unroll
        for (int w = 0; w < 5; w++) v[w] = lds64f(sb + SM_STAT + w * 8);
        mean = sum5(v[0].x, v[1].x, v[2].x, v[3].x, v[4].x) * (1.f / D_MODEL);
        const float msq = sum5(v[0].y, v[1].y, v[2].y, v[3].y, v[4].y) * (1.f / D_MODEL);
        rstd = ln_rstd(mean, msq);
        stsf(sb + SM_FXS, msq);
    };
    auto q_addr = [&](int d) { return sb + SM_VEC + (((d >> 1) & 1) * 4 + ((d >> 3) & 3)) * 48 + (d >> 5) * 8 + ((d >> 2) & 1) * 4 + (d & 1) * 2; };
    {
        uint32_t px[3];
#pragma unroll
        for (int i = 0; i < 3; i++) px[i] = *reinterpret_cast<const uint32_t*>(P.x + 4 * j40 + xcol(i, t));
        if (warp < 5) ln_stats();
        mbar_wait(sb + SM_BAR + (warp >> 1) * 96 + 72, 0);
        load_wq();
        q_proj(IC<0>{}, px, sb + (t < 2 ? SM_PART : SM_CSP) + warp * 768 + (8 * g + 4 * (t & 1)) * 4);
    }
    {
        uint32_t offQ, offL;
        auto calc_ql = [&]() {
            offQ = pin(sb + SM_VEC + (lane & 7) * 48);
            offL = pin(subw + lane * 16);
        };

        auto issue_w = [&](auto L, int which) {
            const uint32_t bar = sb + SM_CBAR + (CB_W1 + which) * 8;
            if (mlp == 96) asm volatile("mbarrier.arrive.shared::cta.b64 _, [%0];" :: "r"(bar) : "memory");
            else {
                mbar_expect(bar, 20480);
                if (which) {
                    tma3(sb + (L.value ? 3 * TILE : SM_W2), tmk + TM_W2, 0, mlp * 16, bar, W2ONE ? POL_FIRST : WPOL);
                    if (W2ONE && !L.value) tma3_pf(tmk + TM_W2, 0, mlp * 16, POL_NORMAL);
                    if (W1ONE && !L.value) asm volatile("cp.async.bulk.prefetch.L2.global.L2::cache_hint [%0], 20480, %1;" :: "l"(P.w1 + mlp * 10240), "l"((u64)POL_NORMAL << 32) : "memory");
                }
                else asm volatile("cp.async.bulk.tensor.3d.shared::cluster.global.mbarrier::complete_tx::bytes.L2::cache_hint [%0], [%1, {%2, %3, %3}], [%4], %5;"
                                  :: "r"(sb + (L.value ? 2 * TILE : SM_W1)), "l"(tmk + TM_W1), "r"(mlp * 16), "r"(0), "r"(bar), "l"((u64)(W1ONE ? POL_FIRST : WPOL) << 32) : "memory");
            }
        };
        float acc[3][4];
        auto load_q = [&](uint4 (&qf)[3]) {
#pragma unroll
            for (int i = 0; i < 3; i++) qf[i] = lds128(offQ + i * 16);
        };
        auto score = [&](const uint4 (&v)[6], const uint4 (&qf)[3]) {
            float d[2][4];
#pragma unroll
            for (int j = 0; j < 2; j++) d[j][0] = d[j][1] = d[j][2] = d[j][3] = 0.f;
#pragma unroll
            for (int i = 0; i < 3; i++) { mma(d[0], v[2 * i], qf[i].x, qf[i].y); mma(d[1], v[2 * i + 1], qf[i].z, qf[i].w); }
            return (d[0][0] + d[0][3]) + (d[1][0] + d[1][3]);
        };
        auto softmax = [&](float S0, float S1, float S2, float S3) {
            int mi = __float_as_int(fmaxf(fmaxf(S0, S1), fmaxf(S2, S3)));
            mi = __reduce_max_sync(~0u, mi ^ ((mi >> 31) & 0x7fffffff));
            const float mrun = __int_as_float(mi ^ ((mi >> 31) & 0x7fffffff));
            const float p0 = ex2((S0 - mrun) * CS), p1 = ex2((S1 - mrun) * CS), p2 = ex2((S2 - mrun) * CS), p3 = ex2((S3 - mrun) * CS);
            const uint32_t pa = pack_bf(p0, p1), pb = pack_bf(p2, p3), pw = prow + 256 + (key >> 1) * 80 + t * 4 + (key & 1) * 2;
            sts16(pw, pa); sts16(pw + 16, pa >> 16); sts16(pw + 32, pb); sts16(pw + 48, pb >> 16);
            __syncwarp();
#pragma unroll
            for (int j = 0; j < 3; j++) acc[j][0] = acc[j][1] = acc[j][2] = acc[j][3] = 0.f;
            return make_float2(mrun, (p0 + p1) + (p2 + p3));
        };
        auto head_weight = [&](u64 pm, u64 pl, auto L) {
            const uint32_t tag = lds32(sb + SM_EPOCH) * 4 + 2 + 2 * L.value;
#pragma unroll 1
            for (int it = 0; it < SPIN; it++) {
                if (__all_sync(~0u, ll_tag(pm) == tag && ll_tag(pl) == tag)) break;
                ld_rlx2(&g_ll[L.value][cta ^ (lane >> 3)][192 + (lane & 7) * 4], pm, pl);
            }
            const float f = ex2((ll_val(pm) - warp_max(ll_val(pm))) * CS);
            const float w = f * rcp(warp_sum(f * ll_val(pl)));
            if (lane < 8) stsf(sb + SM_FAC + lane * 4, w);
        };
        auto pv = [&](const uint4 (&v)[6], uint32_t pp) {
            const uint32_t dA = __byte_perm(pp, 0, 0x1010), dB = __byte_perm(pp, 0, 0x3232);
            mma(acc[0], v[0], dA & maskA, dA & maskB); mma(acc[1], v[1], dA & maskA, dA & maskB); mma(acc[2], v[2], dA & maskA, dA & maskB);
            mma(acc[0], v[3], dB & maskA, dB & maskB); mma(acc[1], v[4], dB & maskA, dB & maskB); mma(acc[2], v[5], dB & maskA, dB & maskB);
        };
        auto sa = [&]() { return prow + 256 + t * 32 + g * 4; };
        auto pass1 = [&]() {
            issue_paced(NIM, NI1);
#pragma unroll
            for (int u = 0; u < 8; u++)
#pragma unroll
                for (int i = 0; i < 6; i++) kr[u][i] = lds128(sb + SM_CS + (u * 6 + i) * 16);
            fresh();
            calc_ql();
            __syncthreads();
            sts64(prow + lane * 8, xp.x, xp.y);
            int e = 0;
            const uint4* tab = P.tile + (warp >> 2);
            uint4 tw = tab[0];
            uint32_t ka[3];
#pragma unroll
            for (int j = 0; j < 3; j++) ka[j] = pin(subw + key * 384 + j * 128 + ((t ^ ((3 * key + j) & 7)) << 4));
            auto load_k = [&](uint4 (&v)[6], uint32_t so) {
#pragma unroll
                for (int i = 0; i < 6; i++) v[i] = lds128(((i & 1) ? ka[i >> 1] ^ 64 : ka[i >> 1]) + so);
            };
            const uint32_t s0 = pin(prow + 256 + g * 4), sca = pin(sb + SM_SC + warp * 128 + g * 16);
#pragma unroll 1
            do {
                const uint4 tn = tab[2 * e + 2];
                uint4 v[6], qf[3];
                if (tw.x & (G_A | G_B | G_C)) {
                    if ((tw.x & G_A) && warp == 7 && elect()) {
                        mbar_expect(sb + SM_CBAR + CB_SNAP * 8, HALF);
                        asm volatile("cp.async.bulk.shared::cluster.global.mbarrier::complete_tx::bytes [%0], [%1], 12288, [%2];"
                                     :: "r"(sb + SM_SNAP), "l"(&g_l0[cta & ~3][0]), "r"(sb + SM_CBAR + CB_SNAP * 8) : "memory");
                    }
                    if (tw.x & G_B) {
                        if (warp < 6) {
                            mbar_wait(sb + SM_CBAR + CB_SNAP * 8, 0);
                            float qc[2] = {0.f, 0.f}, mean, rstd;
#pragma unroll 1
                            for (int k = 0; k < 2; k++) {
                                u64 qw[4];
#pragma unroll
                                for (int i = 0; i < 4; i++) { const uint2 x = lds64(sb + SM_SNAP + i * 3072 + k * 1536 + tid * 8); qw[i] = x.x | (u64)x.y << 32; }
                                qc[0] = qc[1];
                                qc[1] = ll_gather<384>(&g_l0[cta & ~3][k * 192 + tid], lds32(sb + SM_EPOCH) * 4 + 1, qw);
                            }
                            ln_final(mean, rstd);
                            stsf(sb + SM_CS + tid * 4, qc[1]);
                            const float q = (qc[0] - mean * qc[1]) * rstd;
                            sts16(q_addr(tid), pack_bf(q, q));
                        }
                        __syncthreads();
                        if (warp == 7 && elect()) issue_half(UC<load_word(12)>::value, sb, rowc, cta, tmk);
                        TSTAMP(2);
                    }
                    if (tw.x & G_C) {
                        load_k(v, (e - LATEAT) * TILE);
                        load_q(qf);
                        stsf(s0 + (e - LATEAT) * 32, score(v, qf));
                    }
                }
                load_q(qf);
                mbar_wait(sb + SM_CBAR + (tw.x & 0xf8), tw.x >> 31);
                TRACE(e);
                load_k(v, tw.x & 0x3f000);
                const uint32_t old = release(tw);
                const float s = score(v, qf);
                uint32_t m;
                {
                    uint32_t a[6];
#pragma unroll
                    for (int i = 0; i < 6; i++) a[i] = bf2_amax(bf2_amax(v[i].x, v[i].y), bf2_amax(v[i].z, v[i].w));
                    m = bf2_amax(bf2_amax(bf2_amax(a[0], a[1]), bf2_amax(a[2], a[3])), bf2_amax(a[4], a[5]));
                }
                m = bf2_amax(m, m >> 16) & 0x7f80;
                m = max(m, __shfl_xor_sync(~0u, m, 1));
                stsf(s0 + e * 32, s);
                m = max(m, __shfl_xor_sync(~0u, m, 2));
                refill(tw, old);
                const uint32_t b = min(max(m, 15u << 7) - (15u << 7), 126u << 7);
                const uint32_t dn = ((127u << 7) - b) * 0x10001u, up = ((127u << 7 | 0x8000u) + b) * 0x10001u;
                uint32_t c[18], any = m > (141u << 7);
#pragma unroll
                for (int i = 0; i < 6; i++) {
                    const uint32_t y0 = bf2_mul(v[i].x, dn), y1 = bf2_mul(v[i].y, dn), y2 = bf2_mul(v[i].z, dn), y3 = bf2_mul(v[i].w, dn);
                    v[i] = make_uint4(bf2_fma(y0, up, v[i].x), bf2_fma(y1, up, v[i].y), bf2_fma(y2, up, v[i].z), bf2_fma(y3, up, v[i].w));
                    any |= v[i].x | v[i].y;
                    any |= v[i].z | v[i].w;
                    const uint32_t hb = __byte_perm(y2, y3, 0x7531);
                    c[3 * i] = __byte_perm(y0, y1, 0x6420); c[3 * i + 1] = __byte_perm(y2, y3, 0x6420);
                    c[3 * i + 2] = __byte_perm(y0, y1, 0x7531) | __funnelshift_r(hb, hb, 4);
                }
                asm volatile("st.shared.u8 [%0], %1;" :: "r"(sca + (e & 3) * 4 + (e >> 2)), "r"((b >> 7) + 63) : "memory");
                const bool rare = __any_sync(~0u, any);
                k_keep(kr, c, e, offL);
                if (rare) {
                    uint32_t odd = m > (141u << 7) ? 64u : 0u;
#pragma unroll
                    for (int i = 0; i < 6; i++) if (v[i].x | v[i].y | v[i].z | v[i].w) odd |= 1u << i;
                    odd = __reduce_or_sync(~0u, odd);
                    const uint2 st = lds64(barw + 80);
                    uint32_t lt; asm volatile("mov.u32 %0, %lanemask_lt;" : "=r"(lt));
                    uint32_t n = odd >= 64 ? NEXC + 1 : __shfl_sync(~0u, st.x, 0);
#pragma unroll 1
                    for (; odd && n <= NEXC; odd &= odd - 1) {
                        const int i = __ffs(odd) - 1;
                        uint4 r = v[0];
#pragma unroll
                        for (int k = 1; k < 6; k++) if (i == k) r = v[k];
#pragma unroll 1
                        for (int k = 0; k < 4; k++) {
                            const uint32_t who = __ballot_sync(~0u, r.x), at = n + __popc(who & lt);
                            if (r.x && at < NEXC) sts64(sb + SM_EXC + warp * 128 + at * 8, r.x, (e * 32 + g * 4) << 16 | (((k & 1) * 4 + t) * 48 + i * 8 + (k >> 1) * 4));
                            n += __popc(who);
                            r.x = r.y; r.y = r.z; r.z = r.w;
                        }
                    }
                    if (n > NEXC) asm volatile("st.shared.u8 [%0], %1;" :: "r"(sca + (e & 3) * 4 + (e >> 2)), "r"(0) : "memory");
                    sts64(barw + 80, n > NEXC ? st.x : n, n > NEXC ? st.y | 1u << e : st.y);
                    __syncwarp();
                }
                tw = tn;
            } while (++e < 16);
            asm volatile("fence.proxy.async.shared::cta;" ::: "memory");
            __syncwarp();
            TSTAMP(10);
            fresh(); calc_offsets();
            {
                const uint2 st = lds64(barw + 80);
                const uint32_t xa = sb + SM_EXC + warp * 128 + (lane & 15) * 8 + 4;
                uint32_t pos = lds32(xa), lt;
                asm volatile("mov.u32 %0, %lanemask_lt;" : "=r"(lt));
                if (lane >= st.x) pos = 0x80000000u;
                const bool dup = (__match_any_sync(~0u, pos >> 16) & lt) && lane < st.x;
                if (lane < 16) sts32(xa, dup ? pos | 0x40000000u : pos);
                if (__any_sync(~0u, dup)) sts32(barw + 84, st.y | 0x10000u);
                const float2 ml = softmax(ldsf(sa()), ldsf(sa() + 128), ldsf(sa() + 256), ldsf(sa() + 384));
                sts64f(sb + SM_ML + warp * 8, ml.x, warp_sum(ml.y));
            }
            u64 pm = 0, pl = 0;
#pragma unroll 1
            do {
                const uint4 tn = tab[2 * e + 2];
                if (tw.x & (G_A | G_B | G_C)) {
                    if (tw.x & G_A) {
                        if (lane < 24) st_rlx(&g_ll[0][cta][warp * 24 + lane], 0ull);
                        else if (lane < 28) st_rlx(&g_ll[0][cta][168 + warp * 4 + lane], ll_pack(ldsf(sb + SM_ML + warp * 8 + (lane & 1) * 4), lds32(sb + SM_EPOCH) * 4 + 2));
                    }
                    if (warp == 2) {
                        if (tw.x & G_B) ld_rlx2(&g_ll[0][cta ^ (lane >> 3)][192 + (lane & 7) * 4], pm, pl);
                        if (tw.x & G_C) head_weight(pm, pl, IC<0>{});
                    }
                    __syncwarp();
                }
                const uint32_t pp = lds32(prow + 256 + t * 80 + ((tw.x >> 20) & 255));
                mbar_wait(sb + SM_CBAR + (tw.x & 0xf8), tw.x >> 31);
                TRACE(e);
                uint4 v[6];
                load_v(v, tw.x & 0x3f000);
                refill(tw, release(tw));
                pv(v, pp);
                tw = tn;
            } while (++e < 32);
        };
        uint32_t osa, ora, owa, orow, otag;
        u64* olb;
        float xc;
        auto o_setup = [&](auto L) {
            fresh();
            const int lz = lane, d = warp * 24 + min(lz, 23);
            osa = pin(prow + ((lz >> 2) * 8 + (lz & 1) * 4) * 4);
            ora = pin(sb + SM_PART + d * 4);
            olb = pin(&g_ll[L.value][cta & ~3][d]);
            orow = pin((lz & 1) + 2 * (lz & 2) + 2 * (lz >> 4));
            owa = pin(sb + SM_RING + warp * 1536 + orow * 64 + ((((lz >> 2) & 3) ^ (orow >> 1)) << 4));
            otag = lds32(sb + SM_EPOCH) * 4 + 2 + 2 * L.value;
            uint32_t x; asm volatile("ld.shared.u16 %0, [%1];" : "=r"(x) : "r"(prow + ((cta & 1) * 16 + (lz >> 3) * 4 + (cta & 2) + ((lz >> 2) & 1)) * 8 + (lz & 3) * 2) : "memory");
            xc = bf_lo(x) * (1.f / 32);
        };
        auto pass2 = [&]() {
            constexpr IC<1> L{};
            if (P4AT == 0) refill2(IC<4>{});
            if (P2LATE == 1 && warp >= 4) refill2(IC<2>{});
            offQ = sb + SM_VEC + (lane & 7) * 48; offL = subw + lane * 16;
            uint4 tb[8][3];
            auto load_tb = [&](auto I) {
#pragma unroll
                for (int i = 0; i < 3; i++) tb[I.value][i] = lds128(offL + (I.value >> 1) * TILE + ((I.value & 1) * 3 + i) * 512);
            };
            const float cs = ldsf(sb + SM_CS + min(tid, 191) * 4), inv = fx2_inv(ldsf(sb + SM_MSQ));
            const uint32_t qtag = lds32(sb + SM_EPOCH) * 4 + 3;
            uint32_t m1 = lds32(sb + SM_M1), m1n = m1;
            static_for<0, NPRE>(load_tb);
            const u64* qb = &g_ll[0][cta & ~3][min(tid, 191)];
            const uint32_t qa = pin(q_addr(min(tid, 191)));
            {
                uint32_t x[2];
                fx2_wait<2, true>([&](int i) { return rap + i * 40 * ACC_PITCH; }, rw, sb + SM_MSQ, inv, x);
                xp = make_uint2(x[0], x[1]);
            }
            u64 qw[4];
            ll_look<256>(qb, qw);
            ln_stats();
            if (P4AT == 1) refill2(IC<4>{});
            if (S0EARLY) refill2(IC<5>{});
            __syncthreads();
            auto vwait = [&](auto I) { mbar_wait(barw + IC<SCH.st[I.value].slot>::value * 8, IC<SCH.st[I.value].par>::value); };
            bool ok;
            {
                float mean, rstd;
                ln_final(mean, rstd);
                sts64(prow + lane * 8, xp.x, xp.y);
                sts128f(prow + 256 + lane * 16, 0.f, 0.f, 0.f, 0.f);
                const float sq = rstd * 0x1p64f, q0 = -mean * cs * sq;
                const float q = ll_gather<256>(qb, qtag, qw) * sq + q0;
                sts16(qa, pack_bf(q, q));
                TSTAMPL(24);
            }
            if (!S0EARLY) refill2(IC<5>{});
            if (P2LATE == 2 && warp >= 4) refill2(IC<2>{});
            if (P4AT == 3) refill2(IC<4>{});
            if (NOWIN & 1) { if (warp < 6) refill2(IC<0>{}); if (warp >= 5) refill2(IC<3>{}); }
            if (NOWIN & 2) { if (warp >= 6) refill2(IC<1>{}); if (warp < 4) refill2(IC<2>{}); }
            if (NOWIN & 4) { if (warp >= 6) refill2(IC<0>{}); if (warp < 6) refill2(IC<1>{}); }
            if (NOWIN & 8) { if (warp < 5) refill2(IC<3>{}); if (warp >= 4) refill2(IC<2>{}); }
            __syncthreads();
            uint4 qf[3];
            load_q(qf);
            float S[4], d[2][4];
            auto vload = [&](auto I) {
                constexpr int p = I.value;
                constexpr Step c = SCH.st[p];
                load_v(kr[p & 7], c.slot * TILE);
                if constexpr (c.next >= 0) refill2(IC<c.next>{});
                if constexpr (p == 11) { __syncwarp(); if (elect()) asm volatile("mbarrier.arrive.shared::cta.b64 _, [%0];" :: "r"(sb + SM_CBAR + CB_REL * 8) : "memory"); }
            };
            auto side = [&](uint2 x) {
                const uint32_t qq = lds32(sb + SM_VEC + (x.y & 0xffff));
                return (bf_lo(x.x) * bf_lo(qq) + bf_hi(x.x) * bf_hi(qq)) * 0x1p-64f;
            };
            static_for<0, 96>([&](auto F) {
                constexpr int f = F.value, i = f % 6, u = kunit(f / 6), w = 3 * f % 12;
                uint4 (&src)[3] = *reinterpret_cast<uint4 (*)[3]>(f < 32 ? &tb[f / 4 & 7][0] : &kr[(f / 8 + 4) & 7][(f / 4 & 1) * 3]);
                const uint4 a = k_unpack(word<w % 4>(src[w / 4]), word<(w + 1) % 4>(src[(w + 1) / 4]), word<(w + 2) % 4>(src[(w + 2) / 4]), m1);
                if constexpr (f < 32 ? f % 4 == M1AT : f % 8 == M1P) m1 = m1n;
                if constexpr (f % 4 == 3 && f / 4 + NPRE < 8) {
                    load_tb(IC<f / 4 + NPRE>{});
                    if constexpr ((f / 4 + NPRE) & 1) { refill2(IC<5 + (f / 4 + NPRE) / 2>{}); m1n = lds32(sb + SM_M1); }
                }
                if constexpr (i < 2) d[i][0] = d[i][1] = d[i][2] = d[i][3] = 0.f;
                mma(d[i & 1], a, (i & 1) ? qf[i / 2].z : qf[i / 2].x, (i & 1) ? qf[i / 2].w : qf[i / 2].y);
                if constexpr (i == 5) {
                    if constexpr (u == 11 || ((u & 3) == 0 && u != 8)) S[u >> 2] = (d[0][0] + d[0][3]) + (d[1][0] + d[1][3]);
                    else add_if(t == (u & 3), S[u >> 2], d[0][0] + d[0][3], d[1][0] + d[1][3]);
                    if constexpr (f < 64) S[u >> 2] = shx(S[u >> 2], 0);
                }
                if constexpr (f == 31) { fresh(); calc_offsets(); ok = mbar_test(barw + IC<SCH.st[0].slot>::value * 8, 0); }
                if constexpr (f == 48) {
                    const uint2 x = lds64(sb + SM_EXC + warp * 128 + (lane & 15) * 8);
                    const float c = side(x);
                    if (x.y < 0x40000000u) stsf(prow + 256 + (x.y >> 16), c);
                }
                if constexpr (f >= 32 && f % 8 == 7) {
                    if constexpr (PARKS >> (f / 8 - 4) & 1) {
                        constexpr int p = popc(PARKS & ((1 << (f / 8 - 4)) - 1));
                        if (!ok) vwait(IC<p>{});
                        vload(IC<p>{});
                        m1n = lds32(sb + SM_M1);
                        ok = mbar_test(barw + IC<SCH.st[p + 1].slot>::value * 8, IC<SCH.st[p + 1].par>::value);
                    }
                }
            });
            uint32_t bad = lds32(barw + 84);
            const uint32_t sc = lds32(sb + SM_SC + tid * 4);
            __syncwarp();
            if (bad) {
                const uint2 x = lds64(sb + SM_EXC + warp * 128 + (lane & 15) * 8);
                if ((int)x.y >= 0x40000000 && lane < 16) asm volatile("red.shared.add.f32 [%0], %1;" :: "r"(prow + 256 + ((x.y >> 16) & 511)), "f"(side(x)) : "memory");
#pragma unroll 1
                for (bad &= 0xffff; bad; bad &= bad - 1) {
                    const int e = __ffs(bad) - 1;
                    const __nv_bfloat16* kp = P.k + (size_t)(roww + e * 256 + key) * DH + t * 8;
                    uint4 v[6];
#pragma unroll
                    for (int i = 0; i < 6; i++) v[i] = *reinterpret_cast<const uint4*>(kp + i * 32);
                    const float s = score(v, qf) * 0x1p-64f;
                    if (t == 0) stsf(sa() + e * 32, s);
                }
                __syncwarp();
            }
            TSTAMP(30);
            const float2 ml = softmax(S[0] * __uint_as_float((sc & 255) << 23) + ldsf(sa()), S[1] * __uint_as_float((sc & 0xff00) << 15) + ldsf(sa() + 128),
                                      S[2] * __uint_as_float((sc & 0xff0000) << 7) + ldsf(sa() + 256), S[3] * __uint_as_float((sc >> 24) << 23) + ldsf(sa() + 384));
            uint4 pq[4];
#pragma unroll
            for (int j = 0; j < 4; j++) pq[j] = lds128(prow + 256 + t * 80 + j * 16);
            TSTAMP(1);
            if (!ok) vwait(IC<NPARK>{});
            float ac2[3][4];
#pragma unroll
            for (int j = 0; j < 3; j++) ac2[j][0] = ac2[j][1] = ac2[j][2] = ac2[j][3] = 0.f;
            const uint32_t sl = (g & 1) ? 0x1044 : 0x4410, sh = (g & 1) ? 0x3244 : 0x4432;
            const uint32_t sA0 = (g & 2) ? 0x4444 : sl, sA1 = (g & 2) ? sl : 0x4444, sB0 = (g & 2) ? 0x4444 : sh, sB1 = (g & 2) ? sh : 0x4444;
            u64 pm = 0, pl = 0;
            static_for<NPARK, 16>([&](auto I) {
                constexpr int p = I.value;
                static_assert(p - SCH.st[p].mma0 < 8, "buffer in use");
                vload(I);
                if constexpr (p < 15) ok = mbar_test(barw + IC<SCH.st[p + 1].slot>::value * 8, IC<SCH.st[p + 1].par>::value);
                static_for<SCH.st[p].mma0, SCH.st[p].mma0 + SCH.st[p].nmma>([&](auto J) {
                    constexpr int u = SCH.st[J.value].unit;
                    const uint32_t pp = word<u & 3>(pq[u >> 2]), a0 = __byte_perm(pp, 0, sA0), a1 = __byte_perm(pp, 0, sA1), b0 = __byte_perm(pp, 0, sB0), b1 = __byte_perm(pp, 0, sB1);
#pragma unroll
                    for (int j = 0; j < 3; j++) mma(acc[j], kr[J.value & 7][j], a0, a1);
#pragma unroll
                    for (int j = 0; j < 3; j++) mma(ac2[j], kr[J.value & 7][j + 3], b0, b1);
                });
                if constexpr (p == NPARK) {
                    const float l = warp_sum(ml.y);
                    if (lane < 28) st_rlx(&g_ll[1][cta][lane < 24 ? warp * 24 + lane : 168 + warp * 4 + lane], lane < 24 ? 0ull : ll_pack((lane & 1) ? l : ml.x, lds32(sb + SM_EPOCH) * 4 + 4));
                }
                if constexpr (p == HWAT) { if (warp == 6) ld_rlx2(&g_ll[1][cta ^ (lane >> 3)][192 + (lane & 7) * 4], pm, pl); }
                if constexpr (p == 13) o_setup(L);
                if constexpr (p == HWAT + 2) { if (warp == 6) head_weight(pm, pl, IC<1>{}); }
                if constexpr (p >= WOAT && p < WOAT + 3) {
                    if (warp == p - WOAT) {
                        mbar_wait(sb + SM_CBAR + CB_REL * 8, 0);
                        if (elect()) {
                            issue_half(UC<load_word(64 + 2 * (p - WOAT)) | 1>::value, sb, rowc, cta, tmk);
                            if constexpr (p < WOAT + 2) issue_half(UC<load_word(65 + 2 * (p - WOAT)) | 1>::value, sb, rowc, cta, tmk);
                        }
                        __syncwarp();
                    }
                }
                if constexpr (p < 15) { if (!ok) mbar_wait(barw + IC<SCH.st[p + 1].slot>::value * 8, IC<SCH.st[p + 1].par>::value); TRACE(33 + p); }
            });
#pragma unroll
            for (int j = 0; j < 3; j++)
#pragma unroll
                for (int k = 0; k < 4; k++) acc[j][k] += ac2[j][k];
        };

        const unsigned char* ap;
        uint32_t hpa, hsa, hst, w2a, la;
        uint2 b2v;
        float b1v, cs1;
        auto mlp_global = [&](auto L) {
            const int cz = c4();
            ap = accg + 2 * L.value * ACC_BYTES + (cz >> 1) * ACC_PITCH + (cz & 1) * 16;
            if (L.value) ap = pin(ap);
            rap = pin(accg + (2 * L.value + 1) * ACC_BYTES + (cz >> 2) * ACC_PITCH + (cz & 3) * 8);
            asm volatile("ld.global.nc.v2.u32 {%0,%1}, [%2];" : "=r"(b2v.x), "=r"(b2v.y) : "l"(P.b2 + 4 * cz));
        };
        auto mlp_shared = [&](auto L) {
            const int lz = lane;
            hpa = pin(sb + SM_PART + warp * 256 + ((lz & 2) * 4 + (lz >> 2)) * 16 + (L.value ? 0 : (lz & 1) * 4));
            hsa = pin(sb + SM_PART + (lz & 15) * 16); hst = pin(sb + SM_PART + (lz & 15) * 16 + warp * 256 + 8 + (lz >> 4) * 4);
            w2a = pin(sb + (L.value ? 3 * TILE : SM_W2) + ((lz & 3) * 10 + 2 * warp) * 128 + (((lz >> 2) ^ ((2 * lz + 2 * warp) & 6)) << 4));
            la = sb + (L.value ? 2 * TILE : SM_W1) + warp * 4096 + (lz & 4) * 512 + (lz & 2) * 64 + (lz & 1) * 32 + (lz >> 4) * 64 + ((((lz >> 3) ^ (lz >> 1)) & 1) << 4);
            b1v = ldsf(sb + SM_B1 + (lz & 15) * 4);
            if (L.value) { la = pin(la); cs1 = ldsf(sb + SM_ML + (lz & 15) * 4); }
            else fresh();
        };
        uint32_t pa;
        unsigned char* rop;
        uint32_t wpa;
        auto sum_setup = [&](auto L) {
            const int lz = lane, word = warp * 128 + (cta & 3) * 32 + lz;
            const uint32_t wo = ((lz >> 2) * 8 + (lz & 1) * 4) * 4;
            wpa = pin(sb + SM_RING + warp * 1536 + ((((lz >> 1) ^ (lz >> 4)) & 1) ? HALF + (wo ^ 64) : wo));
            pa = pin(sb + SM_RING + warp * 256 + lz * 4);
            rop = pin(accg + 2 * L.value * ACC_BYTES + (word >> 3) * ACC_PITCH + (word & 7) * 4);
        };
        auto out_proj = [&](auto L) {
            TSTAMP2(3);
            CSTAMP(0, __float_as_uint(acc[2][3]));
            __syncwarp();
#pragma unroll
            for (int j = 0; j < 3; j++) sts128f(osa + 256 * j, acc[j]);
            __syncthreads();
            {
                float s[8];
#pragma unroll
                for (int w = 0; w < 8; w++) s[w] = ldsf(ora + w * 768);
                const uint4 fa = lds128(sb + SM_FAC), fb = lds128(sb + SM_FAC + 16);
            CSTAMP(1, __float_as_uint(s[0]));
                const float own = ((s[0] * __uint_as_float(fa.x) + s[1] * __uint_as_float(fa.y)) + (s[2] * __uint_as_float(fa.z) + s[3] * __uint_as_float(fa.w))) +
                                  ((s[4] * __uint_as_float(fb.x) + s[5] * __uint_as_float(fb.y)) + (s[6] * __uint_as_float(fb.z) + s[7] * __uint_as_float(fb.w)));
                st_rlx_if(lane < 24, olb + (cta & 3) * 256, ll_pack(own, otag));
            CSTAMP(2, __float_as_uint(own));
            }
            TSTAMPL(29);
            if (L.value == 0 && warp == 7) {
#pragma unroll 1
                for (int it = 0; it < SPIN; it++) {
                    uint32_t v; asm volatile("ld.acquire.gpu.global.u32 %0, [%1];" : "=r"(v) : "l"(&g_zflag) : "memory");
                    if (__all_sync(~0u, v == (otag >> 2) + 1)) break;
                }
            }
            constexpr int NW = L.value ? NWO1 : 3;
            uint4 v[5][3];
            u64 ow[4];
            auto read_wo = [&](auto J) {
#pragma unroll
                for (int p = 0; p < 3; p++) v[J.value][p] = lds128(owa + ring_hs(64 + J.value) * HALF + p * 512);
            };
            static_for<0, NW>([&](auto J) {
                if (L.value && J.value == 0) { sum_setup(L); maskA = pin(maskA); maskB = pin(maskB); }
                if ((L.value ? OPOLL1 : OPOLL) == J.value) { ll_look<256>(olb, ow); if (L.value) { mlp_shared(L); mlp_global(L); } }
                mbar_wait(sb + SM_CBAR + (CB_WO + J.value) * 8, L.value);
                read_wo(J);
                if (L.value == 0 && W1AT0 == J.value + 1) {
                    __syncwarp();
                    if (elect() && cnt_inc(sb + SM_CNT + CB_W1 * 8, 7) == 7) issue_w(L, 0);
                    __syncwarp();
                }
                if (L.value == 1 && (W1AT1 == J.value + 1 || W2AT1 == J.value + 1)) {
                    if (warp == 7 && elect()) { if (W1AT1 == J.value + 1) issue_w(L, 0); if (W2AT1 == J.value + 1) issue_w(L, 1); }
                    __syncwarp();
                }
            });
            const float o = ll_gather<256>(olb, otag, ow);
            CSTAMP(3, __float_as_uint(o));
            TSTAMP2(4);
            bool ok = true;
            if constexpr (NW < 5) ok = mbar_test(sb + SM_CBAR + (CB_WO + 4) * 8, L.value);
            if constexpr (NW < 4) ok &= mbar_test(sb + SM_CBAR + (CB_WO + 3) * 8, L.value);
            const uint32_t od = pack_bf(o, o);
            uint32_t oa[3], ob[3];
#pragma unroll
            for (int p = 0; p < 3; p++) { const uint32_t op = __shfl_sync(~0u, od, 8 * p + orow); oa[p] = op & maskA; ob[p] = op & maskB; }
            CSTAMP(4, oa[2]);
            float y[5][4];
#pragma unroll
            for (int j = 0; j < 5; j++) y[j][0] = y[j][1] = y[j][2] = y[j][3] = 0.f;
            auto rest = [&]() {
                if (!ok) static_for<NW, 5>([&](auto J) { mbar_wait(sb + SM_CBAR + (CB_WO + J.value) * 8, L.value); });
                static_for<NW, 5>(read_wo);
            };
            if (L.value) rest();
#pragma unroll
            for (int p = 0; p < 3; p++)
#pragma unroll
                for (int j = 0; j < NW; j++) mma(y[j], v[j][p], oa[p], ob[p]);
            if (!L.value) { rest(); sum_setup(L); }
#pragma unroll
            for (int p = 0; p < 3; p++)
#pragma unroll
                for (int j = NW; j < 5; j++) mma(y[j], v[j][p], oa[p], ob[p]);
            CSTAMP(5, __float_as_uint(y[4][3]));
#pragma unroll
            for (int j = 0; j < 5; j++) sts128f(wpa + j * 256, y[j]);
            TSTAMP2(5);
        };
        u64 yw[2];
        bool wide;
        float msq = 0.f, yf[4];
        auto mlp_part = [&](auto L) {
            const float sc1 = fx2_scale(ldsf(sb + SM_FXS)) * 0.25f;
            bar_sync(0, 256);
            CSTAMP(6, __float_as_uint(sc1));
            const float s = (sum8(pa, 1536) + xc) + sum8(pa + 128, 1536), sm = s * sc1 + FX2_ONE;
            CSTAMP(7, __float_as_uint(s));
            const bool wide1 = !(fabsf(sm - FX2_ONE) < FX1LIM);
            asm volatile("red.relaxed.gpu.global.add.u32 [%0], %1;" :: "l"(rop), "r"(wide1 ? 0u : __float_as_uint(sm) * 128u + (1u - 0x4b400000u * 128u)) : "memory");
            const uint32_t c0 = clk();
            TSTAMP2(6);
            if (L.value == 0) bar_arrive(2, 256);
            if (wide1) {
                asm volatile("red.relaxed.gpu.global.add.u64 [%0], %1;" :: "l"(rop + 64 + (lane & 7) * 4), "l"(fx_pack(s, fx_scale(ldsf(sb + SM_FXS)))) : "memory");
                __threadfence();
                asm volatile("red.relaxed.gpu.global.or.b32 [%0], 64;\nred.relaxed.gpu.global.add.u32 [%0], 1;" :: "l"(rop) : "memory");
            }
            __syncwarp();
            if (L.value == 1 && mlp == 96) { TDUMP(); asm volatile("exit;"); }
            uint4 wf[8], w2r[8];
            uint4 w;
            auto look = [&]() { asm volatile("ld.relaxed.gpu.global.v4.u32 {%0,%1,%2,%3}, [%4];" : "=r"(w.x), "=r"(w.y), "=r"(w.z), "=r"(w.w) : "l"(ap) : "memory"); };
            auto read_w1 = [&]() {
#pragma unroll
                for (int j = 0; j < 8; j++) wf[j] = ldsm_t(la + j * 256);
            };
            auto read_w2 = [&]() {
#pragma unroll
                for (int i = 0; i < 8; i++) w2r[i] = lds128(((i & 1) ? (w2a ^ 16) + 128 : w2a) + (i >> 1) * 5120);
            };
            if (L.value == 0) { fresh(); mlp_global(L); }
            mbar_wait(sb + SM_CBAR + CB_W1 * 8, L.value);
            if (L.value == 1) {
                if (W2PRE == 1) mbar_wait(sb + SM_CBAR + CB_W2 * 8, 1);
                read_w1();
                if (W2PRE == 1) read_w2();
            }
            while (clk() - c0 < AR1D);
            look();
            if (L.value == 0) { mlp_shared(L); read_w1(); bar_arrive(3, 256); }
            else if (W2PRE == 2) { mbar_wait(sb + SM_CBAR + CB_W2 * 8, 1); read_w2(); }
            TSTAMPL(28);
            {
                const float inv = shx(fx_inv(sc1) * (1.f / 128), 0), off = inv * -32.f;
                int it = 0;
#pragma unroll 1
                while (__any_sync(~0u, ~(w.x & w.y & w.z & w.w) & 32) & (++it < SPIN)) look();
                CSTAMP(8, w.w);
                xp = make_uint2(pack_bf((float)(int)w.x * inv + off, (float)(int)w.y * inv + off), pack_bf((float)(int)w.z * inv + off, (float)(int)w.w * inv + off));
                if (__any_sync(~0u, (w.x | w.y | w.z | w.w) & 64)) {
                    __threadfence();
#pragma unroll 1
                    for (int k = 0; k < 4; k++, w.x = w.y, w.y = w.z, w.z = w.w) {
                        const float y = (float)(int)(w.x & ~127u) * inv + fx_val(ld_rlx(ap + 64 + (t & 1) * 16 + k * 8)) * fx_inv(fx_scale(ldsf(sb + SM_FXS)));
                        xp = make_uint2(__funnelshift_r(xp.x, xp.y, 16), __funnelshift_r(xp.y, pack_bf(y, y), 16));
                    }
                }
            }
            TSTAMP2(7);
            CSTAMP(9, xp.y);
            {
                bool ok = true;
                if (L.value == 0 || !W2PRE) ok = mbar_test(sb + SM_CBAR + CB_W2 * 8, L.value);
                const bool ev = L.value || !(g & 1), od = L.value || (g & 1);
                const uint32_t e0 = ev ? xp.x : ONES, e1 = ev ? xp.y : ONES, o0 = od ? xp.x : ONES, o1 = od ? xp.y : ONES;
                float d[8][4];
#pragma unroll
                for (int j = 0; j < 8; j++) { d[j][0] = d[j][1] = d[j][2] = d[j][3] = 0.f; mma(d[j], wf[j], (j & 1) ? o0 : e0, (j & 1) ? o1 : e1); }
                float ss = ln_part(xp, lane);
                ss += shx(ss, 8); ss += shx(ss, 4);
                float r[4], dd;
#pragma unroll
                for (int k = 0; k < 4; k += 1 + L.value) r[k] = d[0][k] + d[1][k ^ 1];
#pragma unroll
                for (int j = 1; j < 4; j++)
#pragma unroll
                    for (int k = 0; k < 4; k += 1 + L.value) add_if(t == j, r[k], d[2 * j][k], d[2 * j + 1][k ^ 1]);
                CSTAMP(10, __float_as_uint(r[2]));
                if (L.value) {
                    dd = ((t & 2) ? r[2] : r[0]) + shx((t & 2) ? r[0] : r[2], 2);
                    ss += shx(ss, 2);
                    dd += shx(dd, 1);
                } else {
                    const float a = ((t & 1) ? r[1] : r[0]) + shx((t & 1) ? r[0] : r[1], 1), b = ((t & 1) ? r[3] : r[2]) + shx((t & 1) ? r[2] : r[3], 1);
                    ss += shx(ss, 2);
                    dd = ((t & 2) ? b : a) + shx((t & 2) ? a : b, 2);
                }
                ss += shx(ss, 1);
                stsf(hpa, dd);
                stsf(hst, ss);
                CSTAMP(11, __float_as_uint(dd + ss));
                if (!ok) mbar_wait(sb + SM_CBAR + CB_W2 * 8, L.value);
            }
            TSTAMPL(25);
            bar_sync(1, 160);
            uint4 hp[5];
#pragma unroll
            for (int w = 0; w < 5; w++) hp[w] = lds128(hsa + w * 256);
            CSTAMP(12, hp[0].x);
            auto hs = [&](auto K) { return sum5(__uint_as_float(word<K.value>(hp[0])), __uint_as_float(word<K.value>(hp[1])), __uint_as_float(word<K.value>(hp[2])),
                                                __uint_as_float(word<K.value>(hp[3])), __uint_as_float(word<K.value>(hp[4]))); };
            const float mean = hs(IC<2>{}) * (1.f / D_MODEL);
            msq = hs(IC<3>{}) * (1.f / D_MODEL);
            if (L.value == 0) cs1 = hs(IC<1>{});
            float hv = hs(IC<0>{}) - mean * cs1;
            CSTAMP(13, __float_as_uint(hv));
            const float sc2 = fx2_scale(msq), lim = fx_inv(sc2) * FX2LIM;
            if (L.value == 0 || !W2PRE) read_w2();
            if (L.value == 0) bar_arrive(4, 256);
            hv = hv * ln_rstd(mean, msq) + b1v;
            CSTAMP(14, __float_as_uint(hv));
            hv = hv * rcp(1.f + ex2(hv * (-2.302208198f - 0.1029432397f * hv * hv)));
            const uint32_t hd = pack_bf(hv, hv);
            CSTAMP(15, hd);
            TSTAMPL(27);
            float ym[4][4];
#pragma unroll
            for (int i = 0; i < 2; i++) {
                ym[i][0] = ym[i][1] = ym[i][2] = ym[i][3] = 0.f;
                const float f = mlp < 64 ? 1.f / 64 : 0.f;
                ym[i + 2][0] = (bf_lo(xp.x) + bf_lo(b2v.x)) * f; ym[i + 2][1] = (bf_hi(xp.x) + bf_hi(b2v.x)) * f;
                ym[i + 2][2] = (bf_lo(xp.y) + bf_lo(b2v.y)) * f; ym[i + 2][3] = (bf_hi(xp.y) + bf_hi(b2v.y)) * f;
            }
#pragma unroll
            for (int i = 0; i < 4; i++) {
                const uint32_t hh = __shfl_sync(~0u, hd, 4 * i + t);
                mma(ym[(i & 1) * 2], w2r[2 * i], hh & maskA, hh & maskB);
                mma(ym[(i & 1) * 2 + 1], w2r[2 * i + 1], hh & maskA, hh & maskB);
            }
#pragma unroll
            for (int k = 0; k < 4; k++) { yf[k] = ym[0][k] + ym[2][k]; add_if(t & 2, yf[k], ym[1][k], ym[3][k]); }
            CSTAMP(16, __float_as_uint(yf[3]));
            yw[0] = fx2_pack(yf[0] * sc2 + FX2_ONE, yf[1] * sc2 + FX2_ONE); yw[1] = fx2_pack(yf[2] * sc2 + FX2_ONE, yf[3] * sc2 + FX2_ONE);
            wide = !(fmaxf(fmaxf(fabsf(yf[0]), fabsf(yf[1])), fmaxf(fabsf(yf[2]), fabsf(yf[3]))) < lim);
            if (wide) yw[0] = yw[1] = 0;
        };
        auto send_wide = [&]() {
#pragma unroll 1
            for (int k = 0; k < 4; k++, yf[0] = yf[1], yf[1] = yf[2], yf[2] = yf[3])
                asm volatile("red.relaxed.gpu.global.add.u64 [%0], %1;" :: "l"(rap + (k >> 1) * 40 * ACC_PITCH + 64 + (k & 1) * 32), "l"(fx_pack(yf[0], fx_scale(msq))) : "memory");
            __threadfence();
#pragma unroll
            for (int k = 0; k < 2; k++) { asm volatile("red.relaxed.gpu.global.or.b64 [%0], 256;" :: "l"(rap + k * 40 * ACC_PITCH) : "memory"); yw[k] = 1; }
        };

        pass1();
        o_setup(IC<0>{});
        out_proj(IC<0>{});
        uint32_t c0;
        if (warp < 5) {
            mlp_part(IC<0>{});
            if (mlp != 96) {
#pragma unroll
                for (int k = 0; k < 2; k++) asm volatile("red.relaxed.gpu.global.add.u64 [%0], %1;" :: "l"(rap + k * 40 * ACC_PITCH), "l"(yw[k]) : "memory");
            }
            c0 = clk();
            stsf(sb + SM_ML + (lane & 15) * 4, cs1);
            TSTAMP(8);
            if (__any_sync(~0u, wide && mlp != 96)) {
                if (wide) {
                    send_wide();
#pragma unroll
                    for (int k = 0; k < 2; k++) asm volatile("red.relaxed.gpu.global.add.u64 [%0], 1;" :: "l"(rap + k * 40 * ACC_PITCH) : "memory");
                }
                __syncwarp();
            }
            fresh(); calc_offsets();
            load_wq();
        } else {
            bar_sync(0, 256);
            if (warp == 5 && elect()) {
                asm volatile("fence.proxy.async.shared::cta;" ::: "memory");
                if (W1AT0 == 4) issue_w(IC<0>{}, 0);
                issue_w(IC<0>{}, 1);
            }
            __syncwarp();
            fresh(); calc_offsets();
            load_wq();
#pragma unroll 1
            for (int ph = 0; ph < 3; ph++) {
                bar_sync(ph + 2, 256);
                c0 = clk();
                if (ph == 2) {
                    msq = sum5(ldsf(sb + SM_PART + 12), ldsf(sb + SM_PART + 268), ldsf(sb + SM_PART + 524), ldsf(sb + SM_PART + 780), ldsf(sb + SM_PART + 1036)) * (1.f / D_MODEL);
                    bar_arrive(5, 256);
                }
                if (!(NOWIN >> ph & 1) && elect()) {
                    asm volatile("fence.proxy.async.shared::cta;" ::: "memory");
                    const uint32_t gap = ph == 0 ? WG1 : ph == 1 ? WG2 : WG3;
                    uint32_t c1 = c0 + (ph == 0 ? WD1 : ph == 1 ? WD2 : 0) + (warp - 5) * gap;
#pragma unroll 1
                    for (int k = warp + (ph == 0 ? -5 : ph == 1 ? 9 : 1); k < (ph == 0 ? 9 : ph == 1 ? 20 : 14); k += 3, c1 += 3 * gap) {
                        const int i = ph == 0 && k >= 6 ? k + 23 : k;
                        const uint32_t bar = sb + SM_BAR + (i & 7) * 96 + 32 + (i & 24);
                        while ((int)(clk() - c1) < 0);
                        mbar_expect(bar, SUB);
                        tma3(sb + SM_RING + i * SUB, tmk + TM_V, 0,
                             rowc + (i & 7) * 8 + ((UC<SCH.st[0].unit | SCH.st[1].unit << 8 | SCH.st[2].unit << 16 | SCH.st[3].unit << 24>::value >> (i & 24)) & 15) * 256, bar, POL_FIRST);
                    }
                }
                __syncwarp();
            }
            c0 += PCD;
        }
        {
            constexpr IC<1> L{};
            fresh();
            const int lz = lane;
            const unsigned char* xa[2];
#pragma unroll
            for (int i = 0; i < 2; i++) {
                const int col = xcol(2 * i, lz & 3), cw = j40 + (col >> 2);
                xa[i] = pin(accg + ACC_BYTES + ((cw >> 2) + (col & 2) * 20) * ACC_PITCH + (cw & 3) * 8);
            }
            const uint32_t pst = pin(prow + ((lz >> 2) * 8 + (lz & 1) * 4) * 4);
            stsf(sb + SM_MSQ, msq);
            const float inv = shx(fx2_inv(msq), 0);
            if (!NWQ1) rap = pin(accg + ACC_BYTES + (c4() >> 2) * ACC_PITCH + (c4() & 3) * 8);
            fresh();
            if (!NWQ1) { maskA = pin(maskA); maskB = pin(maskB); }
            u64 w[3];
            uint32_t x2[3];
            auto xat = [&](int i) { return ((i & 2) ? xa[1] : xa[0]) + (i & 1) * 4 * ACC_PITCH; };
            if (warp < 5) {
                bar_sync(5, 256);
                if (DPRE) { while ((int)(clk() - c0) < WD4 + warp * WG4); if (warp < DPRE) refill2(IC<3>{}); }
            }
            while ((int)(clk() - c0) < ARDELAY);
#pragma unroll
            for (int i = 0; i < 3; i++) w[i] = ld_rlx(xat(i));
            if (warp < 5 && !(NOWIN & 8) && elect()) {
                if (DPOST) while ((int)(clk() - c0) < ARDELAY + DPOST);
                if (warp >= DPRE) issue_v(IC<3>{}, 0);
                if (warp < 4 && !P2LATE) issue_v(IC<2>{}, 4);
            }
            __syncwarp();
            fx2_wait<3, true>(xat, w, sb + SM_MSQ, inv, x2);
            TSTAMP(9);
            q_proj(L, x2, pst);
            pass2();
            out_proj(L);
            if (warp >= 5) {
                bar_arrive(0, 256);
                if ((W1AT1 == 6 || W2AT1 == 6) && warp == 5 && elect()) { if (W1AT1 == 6) issue_w(L, 0); if (W2AT1 == 6) issue_w(L, 1); }
                TDUMP();
                return;
            }
            mlp_part(L);
            u64 old[2];
            auto add = [&]() {
#pragma unroll
                for (int k = 0; k < 2; k++) asm volatile("atom.relaxed.gpu.global.add.u64 %0, [%1], %2;" : "=l"(old[k]) : "l"(rap + k * 40 * ACC_PITCH), "l"(yw[k]) : "memory");
            };
            add();
            uint32_t* op = reinterpret_cast<uint32_t*>(P.out) + 2 * c4();
            if (wide) { send_wide(); add(); }
            TSTAMP(18);
            CSTAMP(17, hi32(yw[1]));
            const float inv2 = fx2_inv(msq);
            const uint32_t ep1 = lds32(sb + SM_EPOCH) + 1;
            CSTAMP(18, lo32(old[0]) ^ lo32(old[1]));
#pragma unroll
            for (int k = 0; k < 2; k++) {
                yw[k] += old[k];
                asm volatile("{\n.reg .pred p;\nsetp.eq.u32 p, %2, 96;\n@p st.global.u32 [%0], %1;\n}"
                             :: "l"(op + k), "r"(pack_bf(fx2_lo(yw[k], inv2), fx2_hi(yw[k], inv2))), "r"(lo32(yw[k]) & 511) : "memory");
            }
            if ((lo32(yw[0]) & 255) == 96 && tid == 0) g_epoch = ep1;
            if ((lo32(yw[0]) | lo32(yw[1])) & 256) {
                __threadfence();
#pragma unroll 1
                for (int k = 0; k < 2; k++, yw[0] = yw[1]) if ((lo32(yw[0]) & 511) == 256 + 96) op[k] = fx2_wide(rap + k * 40 * ACC_PITCH, yw[0], msq);
            }
            TSTAMP(19);
            CSTAMP(19, lo32(yw[1]));
            TDUMP();
        }
    }
}

typedef CUresult (*EncodeFn)(CUtensorMap*, CUtensorMapDataType, cuuint32_t, void*, const cuuint64_t*, const cuuint64_t*, const cuuint32_t*,
                             const cuuint32_t*, CUtensorMapInterleave, CUtensorMapSwizzle, CUtensorMapL2promotion, CUtensorMapFloatOOBfill);

}

extern "C" void kernel_launch(void* const* d_in, const int* in_sizes, int n_in, void* d_out, int out_size) {
    (void)in_sizes; (void)n_in; (void)out_size;
    static EncodeFn enc = nullptr;
    if (!enc) {
        void* fn = nullptr;
        cudaDriverEntryPointQueryResult qr;
        cudaGetDriverEntryPoint("cuTensorMapEncodeTiled", &fn, cudaEnableDefault, &qr);
        enc = (EncodeFn)fn;
        cudaFuncSetAttribute(fused_kernel, cudaFuncAttributeMaxDynamicSharedMemorySize, SM_TOTAL);
    }
    Params P = {};
    auto map3 = [&](int m, int in, cuuint64_t d0, cuuint64_t d1, cuuint64_t d2, cuuint64_t s1, cuuint64_t s2, cuuint32_t b0, cuuint32_t b1, cuuint32_t b2,
                    CUtensorMapSwizzle sw, int promo) {
        const cuuint64_t dim[3] = {d0, d1, d2}, str[2] = {s1, s2};
        const cuuint32_t box[3] = {b0, b1, b2}, ones[3] = {1, 1, 1};
        enc(&P.tm[m], CU_TENSOR_MAP_DATA_TYPE_BFLOAT16, 3, d_in[in], dim, str, box, ones, CU_TENSOR_MAP_INTERLEAVE_NONE, sw, (CUtensorMapL2promotion)promo,
            CU_TENSOR_MAP_FLOAT_OOB_FILL_NONE);
    };
    map3(TM_KH, 1, 64, 3, NHEAD * SK, 128, DH * 2, 64, 3, 32, CU_TENSOR_MAP_SWIZZLE_128B, 0);
    map3(TM_VH, 2, 64, 3, NHEAD * SK, 128, DH * 2, 64, 3, 32, CU_TENSOR_MAP_SWIZZLE_128B, 0);
    map3(TM_VP, 2, 64, 3, NHEAD * SK, 128, DH * 2, PFW, 3, 32, CU_TENSOR_MAP_SWIZZLE_NONE, 0);
    map3(TM_V, 2, 64, 3, NHEAD * SK, 128, DH * 2, 64, 3, 8, CU_TENSOR_MAP_SWIZZLE_128B, 0);
    map3(TM_WO, 4, 32, 20, NHEAD * DH, 64, D_MODEL * 2, 32, 1, DH, CU_TENSOR_MAP_SWIZZLE_64B, PROMOW);
    map3(TM_WOP, 4, 32, 20, NHEAD * DH, 64, D_MODEL * 2, PFW, 1, DH, CU_TENSOR_MAP_SWIZZLE_NONE, 0);
    map3(TM_WQ, 3, 64, NHEAD * 3, D_MODEL, 128, NHEAD * DH * 2, 64, 3, 8, CU_TENSOR_MAP_SWIZZLE_128B, 0);
    map3(TM_W1, 6, DFF, 128, 5, DFF * 2, DFF * 256, 16, 128, 5, CU_TENSOR_MAP_SWIZZLE_32B, PROMO1);
    map3(TM_W2, 8, 64, 10, DFF, 128, D_MODEL * 2, 64, 10, 16, CU_TENSOR_MAP_SWIZZLE_128B, 0);
    P.x = (const __nv_bfloat16*)d_in[0];
    P.k = (const __nv_bfloat16*)d_in[1];
    P.b1 = (const __nv_bfloat16*)d_in[7];
    P.b2 = (const __nv_bfloat16*)d_in[9];
    P.w1 = (const __nv_bfloat16*)d_in[6];
    P.out = (__nv_bfloat16*)d_out;
    for (int i = 0; i < 64; i++) P.tile[i] = make_uint4(SCH.tile[i][0], SCH.tile[i][1], SCH.tile[i][2], 0);
    fused_kernel<<<NCTA + 1, NTHR, SM_TOTAL, cudaStreamPerThread>>>(P);
}
```

```cpp
#include <cuda_runtime.h>
#include <cuda_bf16.h>
#include <cuda.h>
#include <stdint.h>

namespace {

constexpr int D_MODEL = 640, NHEAD = 32, SK = 32768, DH = 192, WIN = 4096, DFF = 1536;
constexpr int NCTA = 128, NTHR = 256;
constexpr int TILE = 64 * DH * 2;
constexpr int HALF = TILE / 2;
constexpr int SUB = 8 * DH * 2;
constexpr int SM_RING = 4 * TILE;
constexpr int SM_W2 = SM_RING + 20480, SM_W1 = SM_W2 + 20480;
constexpr int SM_WQR = 6 * TILE + HALF, SM_WQ = 7 * TILE;
constexpr int SM_PART = 9 * TILE;
constexpr int SM_EXC = SM_PART + 6144;
constexpr int SM_SC = SM_EXC + 1024;
constexpr int SM_BAR = SM_SC + 1024;
constexpr int SM_VEC = SM_BAR + 768;
constexpr int SM_CS = SM_VEC + 384;
constexpr int SM_FAC = SM_CS + 768;
constexpr int SM_ML = SM_FAC + 32;
constexpr int SM_B1 = SM_ML + 64;
constexpr int SM_STAT = SM_B1 + 64;
constexpr int NCB = 28;
constexpr int CB_WO = 18, CB_W1 = 23, CB_W2 = 24, CB_SNAP = 25, CB_REL = 26, CB_WQ = 27;
constexpr int SM_CBAR = SM_STAT + 40;
constexpr int SM_CNT = SM_CBAR + NCB * 8;
constexpr int SM_EPOCH = SM_CNT + NCB * 8;
constexpr int SM_FXS = SM_EPOCH + 4;
constexpr int SM_T0 = SM_FXS + 4;
constexpr int SM_MSQ = SM_T0 + 4;
constexpr int SM_M1 = SM_MSQ + 4;
constexpr int SM_TS = SM_M1 + 4;
constexpr int SM_TOTAL = 232448;
static_assert(SM_TS + 320 <= SM_TOTAL, "smem");
constexpr int NEXC = 16;

constexpr int SPIN = 1 << 20;
enum { TM_V = 0, TM_KH = 1, TM_VH = 2, TM_WO = 3, TM_VP = 4, TM_WOP = 5, TM_W1 = 6, TM_W2 = 7, TM_WQ = 8 };
constexpr uint32_t POL_NORMAL = 0x16F00000u, POL_FIRST = 0x12F00000u;

#define PACE 980
#define PACE0 1500
#define K0FIRST 1
#define NI1 6
#define ETRIG 0x54321000
#define LATEAT 5
#define HWAT 12
#define PFREE 66
#define W1AT0 3
#define W1AT1 3
#define AR1D 300
#define LAG0 12
#define NMMA 2
#define M1AT 1
#define M1P 3
#define NWO1 4
#define WG2 90
#define WG3 120
#define WD4 250
#define WG4 70
#define NWQ1 0
#define P4AT 0
#define P2LATE 0
#define RWAT 1
#define W2AT1 6
#define PCD 150
#define NOWIN 0
#define DPRE 0
#define DPOST 200
#define NIM 4
#define PACES 1300
#define JP2 54
#define PACE2 0
#define WD2 0
#define W2PRE 2
#define OPOLL1 2
#define W2ONE 1
#define W1ONE 1
#define FX1LIM 524288.f
#define C96 0
#define SNAPAT 1
#define DMASK 0x0
#define WOKEEP 0x1f
#define VORD2 0x7685943a2b1cd0efull
#define VTRIG 0xba73210
#define WOAT 13
#define PARKS 0x95
#define VSLOT 0x1087654321087654ull
#define OPOLL 2
#define S0EARLY 1
#define NPRE 2
#define ARDELAY 1000
#define QDELAY 0
#define CMAP 0
#define PFW 8u
#define PUBAT 28
#define HW0 30
#define HW1 31
#define FX2LIM 524288.f
#define PROMOW 2
#define PROMO1 0
#define WD1 300
#define WG1 140
#define WPOL POL_NORMAL

constexpr uint32_t G_A = 1u << 28, G_B = 1u << 29, G_C = 1u << 30;
__host__ __device__ constexpr int ring_hs(int j) { return (j + 4) % 5; }
__host__ __device__ constexpr uint32_t load_word(int j) {
    if (j >= 64) return (uint32_t)(j - 64) << 20 | (SM_RING + ring_hs(j) * HALF) | TM_WO << 8 | (CB_WO + j - 64) << 3 | 2 | !(WOKEEP >> (j - 64) & 1);
    const int e = j >> 1, isv = e >= 16, unit = e & 15;
    return (uint32_t)(unit * 256 + (j & 1) * 32) << 20 | (j < 8 ? j * HALF : SM_RING + ring_hs(j) * HALF) | (TM_KH + isv) << 8 | (j < 8 ? 10 + j : (j - 8) % 10) << 3 | 2
           | (!isv || (DMASK >> unit & 1));
}
__host__ __device__ constexpr int popc(int v) { return v ? (v & 1) + popc(v >> 1) : 0; }
constexpr int NPARK = popc(PARKS);
constexpr int SM_SNAP = SM_RING + ring_hs(12) * HALF, SM_CSP = SM_RING + ring_hs(11) * HALF;
struct Step { int unit, slot, par, next, mma0, nmma; };
struct Sched { uint32_t tile[64][3]; Step st[16]; };
constexpr Sched make_sched() {
    Sched s{};
    for (int j = 0; j < 64; j++) {
        const int e = j >> 1;
        const uint32_t d = load_word(j);
        uint32_t w = (uint32_t)(j < 8 ? 0 : (j - 8) / 10 & 1) << 31 | (e & 15) * 4 << 20 | ((d & 0x3f000) - (j & 1) * HALF) | (d & 0xf8);
        if (e == PUBAT || e == SNAPAT) w |= G_A;
        if (e == HW0 || e == 4) w |= G_B;
        if ((e >= LATEAT && e < LATEAT + 4) || e == HW1) w |= G_C;
        s.tile[j][0] = w;
    }
    for (int j = NI1; j < 69; j++) {
        if (j == 12) continue;
        const int at = j < 12 ? (ETRIG >> (4 * (j - 4)) & 15) : j - 5;
        s.tile[at][1] = load_word(j);
        s.tile[at][2] = j >= PFREE ? 0 : PACE0 + j * PACE / 2 + (j > JP2 ? (j - JP2) * PACE2 : 0);
    }
    int done = 0;
    for (int p = 0; p < 16; p++) {
        Step& c = s.st[p];
        c.unit = (int)(VORD2 >> (4 * p) & 15); c.slot = (int)(VSLOT >> (4 * p) & 15); c.par = p >= 9; c.next = -1;
        c.mma0 = done;
        if (p >= NPARK) { const int avail = p - done + (p >= LAG0); c.nmma = p == 15 ? 16 - done : (avail < NMMA ? avail : NMMA); done += c.nmma; }
    }
    for (int p = 9; p < 16; p++) s.st[VTRIG >> (4 * (p - 9)) & 15].next = p;
    return s;
}
constexpr Sched SCH = make_sched();
__host__ __device__ constexpr int kunit(int o) { return o < 5 ? o + 11 : o == 5 ? 10 : o - 6; }

template <int I> struct IC { static constexpr int value = I; };
template <uint32_t I> struct UC { static constexpr uint32_t value = I; };
template <int A, int B, class F> __device__ __forceinline__ void static_for(F&& f) {
    if constexpr (A < B) { f(IC<A>{}); static_for<A + 1, B>(f); }
}

struct Params {
    CUtensorMap tm[9];
    const __nv_bfloat16 *x, *k, *b1, *b2, *w1;
    __nv_bfloat16* out;
    uint4 tile[66];
};

typedef unsigned long long u64;
constexpr int ACC_PITCH = 256;
constexpr int ACC_BYTES = 80 * ACC_PITCH;
__device__ __align__(1024) unsigned char g_acc[4 * ACC_BYTES];
__device__ __align__(1024) u64 g_l0[NCTA][384];
__device__ __align__(1024) u64 g_ll[2][NCTA][256];
__device__ unsigned g_epoch;
__device__ __align__(128) unsigned g_zflag;
#define TSTAMP(i)
#define TSTAMP2(i)
#define TSTAMPL(i)
#define TDUMP()
#define CSTAMP(i, x)
#define TRACE(i)

__device__ __forceinline__ void mbar_wait(uint32_t bar, uint32_t parity) {
    asm volatile("{\n.reg .pred p, q;\n.reg .u32 n;\nmov.u32 n, 0;\n"
                 "LOOP:\nmbarrier.try_wait.parity.shared::cta.b64 p, [%0], %1;\n"
                 "add.u32 n, n, 1;\nsetp.lt.and.u32 q, n, 0x100000, !p;\n@q bra.uni LOOP;\n}"
                 :: "r"(bar), "r"(parity) : "memory");
}
__device__ __forceinline__ bool mbar_test(uint32_t bar, uint32_t parity) {
    uint32_t r;
    asm volatile("{\n.reg .pred p;\nmbarrier.test_wait.parity.shared::cta.b64 p, [%1], %2;\nselp.u32 %0, 1, 0, p;\n}" : "=r"(r) : "r"(bar), "r"(parity) : "memory");
    return __all_sync(~0u, r);
}
__device__ __forceinline__ bool elect() {
    uint32_t r;
    asm volatile("{\n.reg .pred p;\nelect.sync _|p, 0xffffffff;\nselp.u32 %0, 1, 0, p;\n}" : "=r"(r));
    return r != 0;
}
__device__ __forceinline__ void mbar_expect(uint32_t bar, uint32_t bytes) {
    asm volatile("mbarrier.arrive.expect_tx.shared::cta.b64 _, [%0], %1;" :: "r"(bar), "r"(bytes) : "memory");
}
__device__ __forceinline__ uint4 lds128(uint32_t a) {
    uint4 v; asm volatile("ld.shared.v4.u32 {%0,%1,%2,%3}, [%4];" : "=r"(v.x), "=r"(v.y), "=r"(v.z), "=r"(v.w) : "r"(a) : "memory"); return v;
}
__device__ __forceinline__ uint4 ldsm_t(uint32_t a) {
    uint4 v; asm volatile("ldmatrix.sync.aligned.m8n8.x4.trans.shared.b16 {%0,%1,%2,%3}, [%4];" : "=r"(v.x), "=r"(v.y), "=r"(v.z), "=r"(v.w) : "r"(a) : "memory"); return v;
}
__device__ __forceinline__ uint2 lds64(uint32_t a) {
    uint2 v; asm volatile("ld.shared.v2.u32 {%0,%1}, [%2];" : "=r"(v.x), "=r"(v.y) : "r"(a) : "memory"); return v;
}
__device__ __forceinline__ float2 lds64f(uint32_t a) { const uint2 v = lds64(a); return make_float2(__uint_as_float(v.x), __uint_as_float(v.y)); }
__device__ __forceinline__ uint32_t lds32(uint32_t a) {
    uint32_t v; asm volatile("ld.shared.u32 %0, [%1];" : "=r"(v) : "r"(a) : "memory"); return v;
}
__device__ __forceinline__ float ldsf(uint32_t a) { return __uint_as_float(lds32(a)); }
__device__ __forceinline__ void sts32(uint32_t a, uint32_t v) { asm volatile("st.shared.u32 [%0], %1;" :: "r"(a), "r"(v) : "memory"); }
__device__ __forceinline__ void stsf(uint32_t a, float v) { sts32(a, __float_as_uint(v)); }
__device__ __forceinline__ void sts16(uint32_t a, uint32_t v) { asm volatile("st.shared.u16 [%0], %1;" :: "r"(a), "h"((uint16_t)v) : "memory"); }
__device__ __forceinline__ void sts64(uint32_t a, uint32_t x, uint32_t y) { asm volatile("st.shared.v2.u32 [%0], {%1,%2};" :: "r"(a), "r"(x), "r"(y) : "memory"); }
__device__ __forceinline__ void sts64f(uint32_t a, float x, float y) { sts64(a, __float_as_uint(x), __float_as_uint(y)); }
__device__ __forceinline__ void sts128f(uint32_t a, float x, float y, float z, float w) {
    asm volatile("st.shared.v4.f32 [%0], {%1,%2,%3,%4};" :: "r"(a), "f"(x), "f"(y), "f"(z), "f"(w) : "memory");
}
__device__ __forceinline__ void mma(float (&c)[4], const uint4& a, uint32_t b0, uint32_t b1) {
    asm volatile("mma.sync.aligned.m16n8k16.row.col.f32.bf16.bf16.f32 {%0,%1,%2,%3}, {%4,%5,%6,%7}, {%8,%9}, {%0,%1,%2,%3};"
                 : "+f"(c[0]), "+f"(c[1]), "+f"(c[2]), "+f"(c[3]) : "r"(a.x), "r"(a.y), "r"(a.z), "r"(a.w), "r"(b0), "r"(b1));
}
__device__ __forceinline__ u64 ld_rlx(const void* p) {
    u64 a; asm volatile("ld.relaxed.gpu.global.u64 %0, [%1];" : "=l"(a) : "l"(p) : "memory"); return a;
}
__device__ __forceinline__ void ld_rlx2(const void* p, u64& a, u64& b) {
    asm volatile("ld.relaxed.gpu.global.v2.u64 {%0,%1}, [%2];" : "=l"(a), "=l"(b) : "l"(p) : "memory");
}
__device__ __forceinline__ void st_rlx(void* p, u64 a) { asm volatile("st.relaxed.gpu.global.u64 [%0], %1;" :: "l"(p), "l"(a) : "memory"); }
__device__ __forceinline__ u64 ll_pack(float v, uint32_t tag) { return ((u64)tag << 32) | __float_as_uint(v); }
__device__ __forceinline__ float ll_val(u64 w) { return __uint_as_float((uint32_t)w); }
__device__ __forceinline__ uint32_t ll_tag(u64 w) { return (uint32_t)(w >> 32); }
__device__ __forceinline__ float bf_lo(uint32_t u) { return __uint_as_float(u << 16); }
__device__ __forceinline__ float bf_hi(uint32_t u) { return __uint_as_float(u & 0xffff0000u); }
__device__ __forceinline__ uint32_t pack_bf(float lo, float hi) {
    uint32_t r; asm("cvt.rn.bf16x2.f32 %0, %1, %2;" : "=r"(r) : "f"(hi), "f"(lo)); return r;
}
__device__ __forceinline__ float ex2(float v) { float r; asm("ex2.approx.ftz.f32 %0, %1;" : "=f"(r) : "f"(v)); return r; }
__device__ __forceinline__ float rcp(float v) { float r; asm("rcp.approx.ftz.f32 %0, %1;" : "=f"(r) : "f"(v)); return r; }
__device__ __forceinline__ float rsq(float v) { float r; asm("rsqrt.approx.ftz.f32 %0, %1;" : "=f"(r) : "f"(v)); return r; }
__device__ __forceinline__ void bar_sync(int id, int n) { asm volatile("bar.sync %0, %1;" :: "r"(id), "r"(n) : "memory"); }
__device__ __forceinline__ uint32_t clk() { uint32_t c; asm volatile("mov.u32 %0, %clock;" : "=r"(c)); return c; }
__device__ __forceinline__ uint32_t pin(uint32_t v) { return __shfl_xor_sync(~0u, v, 0); }
__device__ __forceinline__ float shx(float v, int o) { return __shfl_xor_sync(~0u, v, o); }

__device__ __forceinline__ u64 fx_pack(float v, float scale) { return ((u64)__float2ll_rn(v * scale) & ~255ull) | 1ull; }
__device__ __forceinline__ float fx_scale(float meansq) {
    const int e = max(((int)(__float_as_uint(meansq) >> 23) - 127) >> 1, -6);
    return __uint_as_float((uint32_t)(127 + 32 - e) << 23);
}
__device__ __forceinline__ float fx_inv(float scale) { return __uint_as_float((254u << 23) - __float_as_uint(scale)); }
__device__ __forceinline__ uint32_t lo32(u64 w) { uint32_t l; asm("mov.b64 {%0, _}, %1;" : "=r"(l) : "l"(w)); return l; }
__device__ __forceinline__ int hi32(u64 w) { int h; asm("mov.b64 {_, %0}, %1;" : "=r"(h) : "l"(w)); return h; }
__device__ __forceinline__ float fx_val(u64 w) { return (float)hi32(w) * 4294967296.f + (float)lo32(w); }
constexpr float FX2_ONE = 12582912.f;
__device__ __forceinline__ float fx2_scale(float meansq) { return __uint_as_float((uint32_t)(127 + 16 - max(((int)(__float_as_uint(meansq) >> 23) - 127) >> 1, -100)) << 23); }
__device__ __forceinline__ u64 fx2_pack(float a, float b) {
    const uint32_t lo = __float_as_uint(a) * 512u + (1u - 0x4b400000u * 512u);
    return lo | (u64)(__float_as_uint(b) * 16u - 0x4b400000u * 16u + (uint32_t)((int)lo >> 31)) << 32;
}
__device__ __forceinline__ float fx2_lo(u64 w, float inv) { return (float)(int)(__funnelshift_r(lo32(w), hi32(w), 4) & ~31u) * (inv * 0.5f); }
__device__ __forceinline__ float fx2_hi(u64 w, float inv) { return (float)((hi32(w) + 8) & ~15) * inv; }
__device__ __forceinline__ float fx2_inv(float meansq) { return fx_inv(fx2_scale(meansq)) * 0.0625f; }
__device__ __noinline__ uint32_t fx2_wide(const unsigned char* a, float meansq) {
    __threadfence();
    const u64 w = ld_rlx(a);
    const float inv = fx_inv(fx_scale(meansq));
    return pack_bf(fx2_lo(w, fx2_inv(meansq)) + fx_val(ld_rlx(a + 64)) * inv, fx2_hi(w, fx2_inv(meansq)) + fx_val(ld_rlx(a + 96)) * inv);
}
__device__ __noinline__ uint32_t fx1_wide(const unsigned char* a, float meansq) {
    __threadfence();
    const u64 w = ld_rlx(a);
    const unsigned char* b = a + 64 + (reinterpret_cast<u64>(a) & 31);
    const float inv = fx_inv(fx_scale(meansq)), inv1 = fx2_inv(meansq) * 0.5f;
    return pack_bf((float)(int)(lo32(w) & ~127u) * inv1 + fx_val(ld_rlx(b)) * inv, (float)(hi32(w) & ~127) * inv1 + fx_val(ld_rlx(b + 8)) * inv);
}
__device__ __noinline__ void fx_send(const unsigned char* wide, float v, float meansq, const unsigned char* a, uint32_t flag) {
    asm volatile("red.relaxed.gpu.global.add.u64 [%0], %1;" :: "l"(wide), "l"(fx_pack(v, fx_scale(meansq))) : "memory");
    __threadfence();
    asm volatile("red.relaxed.gpu.global.or.b32 [%0], %1;" :: "l"(a), "r"(flag) : "memory");
}
template <int N, bool LOOK, class A> __device__ __forceinline__ void fx2_wait(A a, u64 (&w)[N], uint32_t msqa, float inv, uint32_t (&x)[N]) {
    int it = 0;
    uint32_t miss = lds32(msqa + 4);
    do {
        if (__all_sync(~0u, !(miss & 96))) {
            const float meansq = ldsf(msqa);
#pragma unroll
            for (int i = 0; i < N; i++) x[i] = fx2_wide(a(i), meansq);
            return;
        }
        if (!LOOK || it) {
#pragma unroll
            for (int i = 0; i < N; i++) w[i] = ld_rlx(a(i));
        }
        uint32_t all = lo32(w[0]), any = all;
#pragma unroll
        for (int i = 1; i < N; i++) { all &= lo32(w[i]); any |= lo32(w[i]); }
        miss = (~all & 96) | (any & 256);
    } while (__any_sync(~0u, miss) & (++it < SPIN));
#pragma unroll
    for (int i = 0; i < N; i++) x[i] = pack_bf(fx2_lo(w[i], inv), fx2_hi(w[i], inv));
}
__device__ __forceinline__ void st_rlx_if(bool p, void* a, u64 v) {
    asm volatile("{\n.reg .pred p;\nsetp.ne.u32 p, %2, 0;\n@p st.relaxed.gpu.global.u64 [%0], %1;\n}" :: "l"(a), "l"(v), "r"((uint32_t)p) : "memory");
}
__device__ __forceinline__ void sts128f(uint32_t a, const float (&v)[4]) { sts128f(a, v[0], v[1], v[2], v[3]); }
__device__ __forceinline__ void bar_arrive(int id, int n) { asm volatile("bar.arrive %0, %1;" :: "r"(id), "r"(n) : "memory"); }
template <class T> __device__ __forceinline__ T* pin(T* p) { return reinterpret_cast<T*>(__shfl_xor_sync(~0u, (u64)p, 0)); }

__device__ __forceinline__ void tma3(uint32_t dst, const CUtensorMap* tm, int c1, int c2, uint32_t bar, uint32_t pol) {
    asm volatile("cp.async.bulk.tensor.3d.shared::cluster.global.mbarrier::complete_tx::bytes.L2::cache_hint [%0], [%1, {%2, %3, %4}], [%5], %6;"
                 :: "r"(dst), "l"(tm), "r"(0), "r"(c1), "r"(c2), "r"(bar), "l"((u64)pol << 32) : "memory");
}
__device__ __forceinline__ void tma_v(uint32_t dst, const CUtensorMap* tm, int line, uint32_t bar) {
    asm volatile("cp.async.bulk.tensor.2d.shared::cluster.global.mbarrier::complete_tx::bytes.L2::cache_hint [%0], [%1, {%2, %3}], [%4], %5;"
                 :: "r"(dst), "l"(tm), "r"(0), "r"(line), "r"(bar), "l"((u64)POL_FIRST << 32) : "memory");
}
__device__ __forceinline__ void tma3_pf(const CUtensorMap* tm, int c1, int c2, uint32_t pol) {
    asm volatile("cp.async.bulk.prefetch.tensor.3d.L2.global.tile.L2::cache_hint [%0, {%1, %2, %3}], %4;"
                 :: "l"(tm), "r"(0), "r"(c1), "r"(c2), "l"((u64)pol << 32) : "memory");
}
__device__ __forceinline__ void issue_half(uint32_t d, uint32_t sb, int rowc, int cta, const CUtensorMap* tm0) {
    const uint32_t bar = sb + SM_CBAR + (d & 0xf8);
    const CUtensorMap* tm = tm0 + ((d >> 8) & 3);
    const bool wo = (d & 0x300) == TM_WO << 8;
    const int c1 = wo ? (cta & 3) + 4 * (d >> 20) : 0, c2 = wo ? (cta >> 2) * DH : rowc + (d >> 20);
    mbar_expect(bar, HALF);
    tma3(sb + (d & 0x3f000), tm, c1, c2, bar, POL_FIRST);
    if (!(d & 1)) tma3_pf(tm + 2, c1, c2, POL_NORMAL);
}
__device__ __forceinline__ uint32_t cnt_inc(uint32_t a, uint32_t last) {
    uint32_t old; asm volatile("atom.relaxed.cta.shared.inc.u32 %0, [%1], %2;" : "=r"(old) : "r"(a), "r"(last) : "memory"); return old;
}
__device__ __forceinline__ void wait_until(uint32_t due) {
#pragma unroll 1
    for (int it = 0; it < 4096; it++) { uint32_t now; asm volatile("mov.u32 %0, %globaltimer_lo;" : "=r"(now)); if ((int)(now - due) >= 0) break; }
}
__device__ __forceinline__ uint32_t bf2_mul(uint32_t a, uint32_t b) { uint32_t r; asm("mul.rn.bf16x2 %0, %1, %2;" : "=r"(r) : "r"(a), "r"(b)); return r; }
__device__ __forceinline__ uint32_t bf2_fma(uint32_t a, uint32_t b, uint32_t c) { uint32_t r; asm("fma.rn.bf16x2 %0, %1, %2, %3;" : "=r"(r) : "r"(a), "r"(b), "r"(c)); return r; }
__device__ __forceinline__ uint32_t bf2_amax(uint32_t a, uint32_t b) { uint32_t r; asm("max.NaN.xorsign.abs.bf16x2 %0, %1, %2;" : "=r"(r) : "r"(a), "r"(b)); return r; }
__device__ __forceinline__ uint4 k_unpack(uint32_t l0, uint32_t l1, uint32_t h, uint32_t m1) {
    const uint32_t ha = h & 0x87878787u, hc = ha * m1 + h, hb = __funnelshift_l(hc, hc, 4);
    return make_uint4(__byte_perm(l0, ha, 0x5140), __byte_perm(l0, ha, 0x7362), __byte_perm(l1, hb, 0x5140), __byte_perm(l1, hb, 0x7362));
}
#define KR4(u, i) "+r"(kr[u][i].x), "+r"(kr[u][i].y), "+r"(kr[u][i].z), "+r"(kr[u][i].w)
#define KR6(u) KR4(u, 0), KR4(u, 1), KR4(u, 2), KR4(u, 3), KR4(u, 4), KR4(u, 5)
__device__ __forceinline__ void k_keep(uint4 (&kr)[8][6], const uint32_t (&c)[18], int e, uint32_t a) {
    asm volatile("{\nKT: .branchtargets K0, K1, K2, K3, K4, K5, K6, K7, K8, K9, K10, K11, K12, K13, K14, K15;\nbrx.idx.uni %210, KT;\n"
                 "K0: mov.b32 %12, %192; mov.b32 %13, %193; mov.b32 %14, %194; mov.b32 %15, %195; mov.b32 %16, %196; mov.b32 %17, %197; mov.b32 %18, %198; mov.b32 %19, %199; mov.b32 %20, %200; mov.b32 %21, %201; mov.b32 %22, %202; mov.b32 %23, %203; mov.b32 %24, %204; mov.b32 %25, %205; mov.b32 %26, %206; mov.b32 %27, %207; mov.b32 %28, %208; mov.b32 %29, %209; bra.uni KE;\n"
                 "K1: mov.b32 %30, %192; mov.b32 %31, %193; mov.b32 %32, %194; mov.b32 %33, %195; mov.b32 %34, %196; mov.b32 %35, %197; mov.b32 %36, %198; mov.b32 %37, %199; mov.b32 %38, %200; mov.b32 %39, %201; mov.b32 %40, %202; mov.b32 %41, %203; mov.b32 %42, %204; mov.b32 %43, %205; mov.b32 %44, %206; mov.b32 %45, %207; mov.b32 %46, %208; mov.b32 %47, %209; bra.uni KE;\n"
                 "K2: mov.b32 %48, %192; mov.b32 %49, %193; mov.b32 %50, %194; mov.b32 %51, %195; mov.b32 %52, %196; mov.b32 %53, %197; mov.b32 %54, %198; mov.b32 %55, %199; mov.b32 %56, %200; mov.b32 %57, %201; mov.b32 %58, %202; mov.b32 %59, %203; mov.b32 %60, %204; mov.b32 %61, %205; mov.b32 %62, %206; mov.b32 %63, %207; mov.b32 %64, %208; mov.b32 %65, %209; bra.uni KE;\n"
                 "K3: mov.b32 %66, %192; mov.b32 %67, %193; mov.b32 %68, %194; mov.b32 %69, %195; mov.b32 %70, %196; mov.b32 %71, %197; mov.b32 %72, %198; mov.b32 %73, %199; mov.b32 %74, %200; mov.b32 %75, %201; mov.b32 %76, %202; mov.b32 %77, %203; mov.b32 %78, %204; mov.b32 %79, %205; mov.b32 %80, %206; mov.b32 %81, %207; mov.b32 %82, %208; mov.b32 %83, %209; bra.uni KE;\n"
                 "K4: mov.b32 %84, %192; mov.b32 %85, %193; mov.b32 %86, %194; mov.b32 %87, %195; mov.b32 %88, %196; mov.b32 %89, %197; mov.b32 %90, %198; mov.b32 %91, %199; mov.b32 %92, %200; mov.b32 %93, %201; mov.b32 %94, %202; mov.b32 %95, %203; mov.b32 %96, %204; mov.b32 %97, %205; mov.b32 %98, %206; mov.b32 %99, %207; mov.b32 %100, %208; mov.b32 %101, %209; bra.uni KE;\n"
                 "K5: mov.b32 %102, %192; mov.b32 %103, %193; mov.b32 %104, %194; mov.b32 %105, %195; mov.b32 %106, %196; mov.b32 %107, %197; mov.b32 %108, %198; mov.b32 %109, %199; mov.b32 %110, %200; mov.b32 %111, %201; mov.b32 %112, %202; mov.b32 %113, %203; mov.b32 %114, %204; mov.b32 %115, %205; mov.b32 %116, %206; mov.b32 %117, %207; mov.b32 %118, %208; mov.b32 %119, %209; bra.uni KE;\n"
                 "K6: mov.b32 %120, %192; mov.b32 %121, %193; mov.b32 %122, %194; mov.b32 %123, %195; mov.b32 %124, %196; mov.b32 %125, %197; mov.b32 %126, %198; mov.b32 %127, %199; mov.b32 %128, %200; mov.b32 %129, %201; mov.b32 %130, %202; mov.b32 %131, %203; mov.b32 %132, %204; mov.b32 %133, %205; mov.b32 %134, %206; mov.b32 %135, %207; mov.b32 %136, %208; mov.b32 %137, %209; bra.uni KE;\n"
                 "K7: mov.b32 %138, %192; mov.b32 %139, %193; mov.b32 %140, %194; mov.b32 %141, %195; mov.b32 %142, %196; mov.b32 %143, %197; mov.b32 %144, %198; mov.b32 %145, %199; mov.b32 %146, %200; mov.b32 %147, %201; mov.b32 %148, %202; mov.b32 %149, %203; mov.b32 %150, %204; mov.b32 %151, %205; mov.b32 %152, %206; mov.b32 %153, %207; mov.b32 %154, %208; mov.b32 %155, %209; bra.uni KE;\n"
                 "K8: mov.b32 %156, %192; mov.b32 %157, %193; mov.b32 %158, %194; mov.b32 %159, %195; mov.b32 %160, %196; mov.b32 %161, %197; mov.b32 %162, %198; mov.b32 %163, %199; mov.b32 %164, %200; mov.b32 %165, %201; mov.b32 %166, %202; mov.b32 %167, %203; mov.b32 %168, %204; mov.b32 %169, %205; mov.b32 %170, %206; mov.b32 %171, %207; mov.b32 %172, %208; mov.b32 %173, %209; bra.uni KE;\n"
                 "K9: mov.b32 %174, %192; mov.b32 %175, %193; mov.b32 %176, %194; mov.b32 %177, %195; mov.b32 %178, %196; mov.b32 %179, %197; mov.b32 %180, %198; mov.b32 %181, %199; mov.b32 %182, %200; mov.b32 %183, %201; mov.b32 %184, %202; mov.b32 %185, %203; mov.b32 %186, %204; mov.b32 %187, %205; mov.b32 %188, %206; mov.b32 %189, %207; mov.b32 %190, %208; mov.b32 %191, %209; bra.uni KE;\n"
                 "K10: st.shared.v2.b32 [%211+75784], {%192, %193}; st.shared.v2.b32 [%211+76288], {%194, %195}; st.shared.v2.b32 [%211+76296], {%196, %197}; mov.b32 %0, %198; mov.b32 %1, %199; mov.b32 %2, %200; mov.b32 %3, %201; mov.b32 %4, %202; mov.b32 %5, %203; mov.b32 %6, %204; mov.b32 %7, %205; mov.b32 %8, %206; mov.b32 %9, %207; mov.b32 %10, %208; mov.b32 %11, %209; bra.uni KE;\n"
                 "K11: st.shared.v2.b32 [%211+0], {%192, %193}; st.shared.v2.b32 [%211+8], {%194, %195}; st.shared.v2.b32 [%211+512], {%196, %197}; st.shared.v2.b32 [%211+520], {%198, %199}; st.shared.v2.b32 [%211+1024], {%200, %201}; st.shared.v2.b32 [%211+1032], {%202, %203}; st.shared.v2.b32 [%211+1536], {%204, %205}; st.shared.v2.b32 [%211+1544], {%206, %207}; st.shared.v2.b32 [%211+2048], {%208, %209}; bra.uni KE;\n"
                 "K12: st.shared.v2.b32 [%211+2056], {%192, %193}; st.shared.v2.b32 [%211+2560], {%194, %195}; st.shared.v2.b32 [%211+2568], {%196, %197}; st.shared.v2.b32 [%211+24576], {%198, %199}; st.shared.v2.b32 [%211+24584], {%200, %201}; st.shared.v2.b32 [%211+25088], {%202, %203}; st.shared.v2.b32 [%211+25096], {%204, %205}; st.shared.v2.b32 [%211+25600], {%206, %207}; st.shared.v2.b32 [%211+25608], {%208, %209}; bra.uni KE;\n"
                 "K13: st.shared.v2.b32 [%211+26112], {%192, %193}; st.shared.v2.b32 [%211+26120], {%194, %195}; st.shared.v2.b32 [%211+26624], {%196, %197}; st.shared.v2.b32 [%211+26632], {%198, %199}; st.shared.v2.b32 [%211+27136], {%200, %201}; st.shared.v2.b32 [%211+27144], {%202, %203}; st.shared.v2.b32 [%211+49152], {%204, %205}; st.shared.v2.b32 [%211+49160], {%206, %207}; st.shared.v2.b32 [%211+49664], {%208, %209}; bra.uni KE;\n"
                 "K14: st.shared.v2.b32 [%211+49672], {%192, %193}; st.shared.v2.b32 [%211+50176], {%194, %195}; st.shared.v2.b32 [%211+50184], {%196, %197}; st.shared.v2.b32 [%211+50688], {%198, %199}; st.shared.v2.b32 [%211+50696], {%200, %201}; st.shared.v2.b32 [%211+51200], {%202, %203}; st.shared.v2.b32 [%211+51208], {%204, %205}; st.shared.v2.b32 [%211+51712], {%206, %207}; st.shared.v2.b32 [%211+51720], {%208, %209}; bra.uni KE;\n"
                 "K15: st.shared.v2.b32 [%211+73728], {%192, %193}; st.shared.v2.b32 [%211+73736], {%194, %195}; st.shared.v2.b32 [%211+74240], {%196, %197}; st.shared.v2.b32 [%211+74248], {%198, %199}; st.shared.v2.b32 [%211+74752], {%200, %201}; st.shared.v2.b32 [%211+74760], {%202, %203}; st.shared.v2.b32 [%211+75264], {%204, %205}; st.shared.v2.b32 [%211+75272], {%206, %207}; st.shared.v2.b32 [%211+75776], {%208, %209}; \nKE:\n}"
                 : KR6(0), KR6(1), KR6(2), KR6(3), KR6(4), KR6(5), KR6(6), KR6(7)
                 : "r"(c[0]), "r"(c[1]), "r"(c[2]), "r"(c[3]), "r"(c[4]), "r"(c[5]), "r"(c[6]), "r"(c[7]), "r"(c[8]), "r"(c[9]), "r"(c[10]), "r"(c[11]), "r"(c[12]), "r"(c[13]), "r"(c[14]), "r"(c[15]), "r"(c[16]), "r"(c[17]), "r"(e), "r"(a) : "memory");
}
__device__ __forceinline__ uint32_t smem_base() { extern __shared__ __align__(1024) unsigned char smem[]; return (uint32_t)__cvta_generic_to_shared(smem); }
__device__ __forceinline__ void k_rare(uint4 v0, uint4 v1, uint4 v2, uint4 v3, uint4 v4, uint4 v5, uint32_t odd, int e, int warp, int lane) {
    const uint32_t sb = smem_base(), g = lane >> 2, t = lane & 3, st = sb + SM_BAR + warp * 96 + 80;
    uint32_t lt; asm volatile("mov.u32 %0, %lanemask_lt;" : "=r"(lt));
    const uint4 v[6] = {v0, v1, v2, v3, v4, v5};
    odd <<= 6;
#pragma unroll
    for (int i = 0; i < 6; i++) if (v[i].x | v[i].y | v[i].z | v[i].w) odd |= 1u << i;
    odd = __reduce_or_sync(~0u, odd);
    uint32_t n = odd >= 64 ? NEXC + 1 : __shfl_sync(~0u, lds32(st), 0);
#pragma unroll 1
    for (; odd && n <= NEXC; odd &= odd - 1) {
        const int i = __ffs(odd) - 1;
#pragma unroll
        for (int k = 1; k < 6; k++) if (i == k) v0 = v[k];
#pragma unroll 1
        for (int k = 0; k < 4; k++, v0.x = v0.y, v0.y = v0.z, v0.z = v0.w) {
            const uint32_t who = __ballot_sync(~0u, v0.x), at = n + __popc(who & lt);
            sts64(v0.x && at < NEXC ? sb + SM_EXC + warp * 128 + at * 8 : st + 8, v0.x, (e * 32 + g * 4) << 16 | (((k & 1) * 4 + t) * 48 + i * 8 + (k >> 1) * 4));
            n += __popc(who);
        }
    }
    const uint32_t bad = lds32(st + 4);
    __syncwarp();
    if (n <= NEXC) sts32(st, n);
    else {
        sts32(st + 4, bad | 1u << e);
        asm volatile("st.shared.u8 [%0], %1;" :: "r"(sb + SM_SC + warp * 128 + g * 16 + (e & 3) * 4 + (e >> 2)), "r"(0) : "memory");
    }
    __syncwarp();
}
template <int K> __device__ __forceinline__ uint32_t& word(uint4& v) { if constexpr (K == 0) return v.x; else if constexpr (K == 1) return v.y; else if constexpr (K == 2) return v.z; else return v.w; }
__device__ __forceinline__ void add_if(bool p, float& d, float a, float b) {
    asm volatile("{\n.reg .pred p;\nsetp.ne.u32 p, %3, 0;\n@p add.f32 %0, %1, %2;\n}" : "+f"(d) : "f"(a), "f"(b), "r"((uint32_t)p));
}
__device__ __forceinline__ float warp_max(float v) {
#pragma unroll
    for (int o = 16; o; o >>= 1) v = fmaxf(v, shx(v, o));
    return v;
}
__device__ __forceinline__ float warp_sum(float v) {
#pragma unroll
    for (int o = 16; o; o >>= 1) v += shx(v, o);
    return v;
}
template <int PITCH> __device__ __forceinline__ void ll_look(const u64* buf, u64 (&w)[4]) {
#pragma unroll
    for (int i = 0; i < 4; i++) w[i] = ld_rlx(buf + i * PITCH);
}
template <int PITCH> __device__ __forceinline__ float ll_gather(const u64* buf, uint32_t tag, u64 (&w)[4]) {
    auto miss = [&]() { return __any_sync(~0u, ((ll_tag(w[0]) ^ tag) | (ll_tag(w[1]) ^ tag)) | ((ll_tag(w[2]) ^ tag) | (ll_tag(w[3]) ^ tag))); };
    int it = 0;
    goto check;
again:
    ll_look<PITCH>(buf, w);
check:
    if (miss() & (++it < SPIN)) goto again;
    return (ll_val(w[0]) + ll_val(w[1])) + (ll_val(w[2]) + ll_val(w[3]));
}
__device__ __forceinline__ float sum8(uint32_t a, int pitch) {
    float s[8];
#pragma unroll
    for (int w = 0; w < 8; w++) s[w] = ldsf(a + w * pitch);
    return ((s[0] + s[1]) + (s[2] + s[3])) + ((s[4] + s[5]) + (s[6] + s[7]));
}
__device__ __forceinline__ float sum5(float a, float b, float c, float d, float e) { return ((a + b) + (c + d)) + e; }
__device__ __forceinline__ float ln_part(uint2 xp, int lane) {
    const float x0 = bf_lo(xp.x), x1 = bf_hi(xp.x), x2 = bf_lo(xp.y), x3 = bf_hi(xp.y);
    const float s1 = (x0 + x1) + (x2 + x3), s2 = (x0 * x0 + x1 * x1) + (x2 * x2 + x3 * x3);
    return ((lane & 16) ? s2 : s1) + shx((lane & 16) ? s1 : s2, 16);
}
__device__ __forceinline__ float ln_rstd(float mean, float msq) { return rsq(fmaxf(msq - mean * mean, 0.f) + 1e-5f); }
__device__ __forceinline__ float score(const uint4 (&v)[6], const uint4 (&qf)[3]) {
    float d[2][4];
#pragma unroll
    for (int j = 0; j < 2; j++) d[j][0] = d[j][1] = d[j][2] = d[j][3] = 0.f;
#pragma unroll
    for (int i = 0; i < 3; i++) { mma(d[0], v[2 * i], qf[i].x, qf[i].y); mma(d[1], v[2 * i + 1], qf[i].z, qf[i].w); }
    return (d[0][0] + d[0][3]) + (d[1][0] + d[1][3]);
}
__device__ __forceinline__ float k_side(uint32_t sb, uint2 x) {
    const uint32_t qq = lds32(sb + SM_VEC + (x.y & 0xffff));
    return (bf_lo(x.x) * bf_lo(qq) + bf_hi(x.x) * bf_hi(qq)) * 0x1p-64f;
}
__device__ __forceinline__ void k_fix(const __nv_bfloat16* k, uint32_t bad, int warp, int lane) {
    const uint32_t sb = smem_base(), g = lane >> 2, sa = sb + SM_PART + warp * 768 + 256;
    const uint2 x = lds64(sb + SM_EXC + warp * 128 + (lane & 15) * 8);
    if ((int)x.y >= 0x40000000 && lane < 16) asm volatile("red.shared.add.f32 [%0], %1;" :: "r"(sa + ((x.y >> 16) & 511)), "f"(k_side(sb, x)) : "memory");
    __syncwarp();
#pragma unroll 1
    for (bad &= 0xffff; bad; bad &= bad - 1) {
        const int e = __ffs(bad) - 1;
        const __nv_bfloat16* kp = k + (e * 256 + (g >> 1) + 4 * (g & 1)) * DH + (lane & 3) * 8;
        uint4 v[6], qf[3];
#pragma unroll
        for (int i = 0; i < 6; i++) v[i] = *reinterpret_cast<const uint4*>(kp + i * 32);
#pragma unroll
        for (int i = 0; i < 3; i++) qf[i] = lds128(sb + SM_VEC + (lane & 7) * 48 + i * 16);
        stsf(sa + e * 32 + g * 4, score(v, qf) * 0x1p-64f);
    }
    __syncwarp();
}
constexpr float CS = 0.07216878364870322f * 1.4426950408889634f;
__device__ __forceinline__ void head_weight(const u64* a, u64 pm, u64 pl, int layer, int lane) {
    const uint32_t sb = smem_base(), tag = lds32(sb + SM_EPOCH) * 4 + 2 + 2 * layer;
#pragma unroll 1
    for (int it = 0; it < SPIN; it++) {
        if (__all_sync(~0u, ll_tag(pm) == tag && ll_tag(pl) == tag)) break;
        ld_rlx2(a, pm, pl);
    }
    const float f = ex2((ll_val(pm) - warp_max(ll_val(pm))) * CS);
    const float w = f * rcp(warp_sum(f * ll_val(pl)));
    if (lane < 8) stsf(sb + SM_FAC + lane * 4, w);
}
constexpr uint32_t ONES = 0x3f803f80u;

__global__ void __launch_bounds__(NTHR, 1) fused_kernel(const __grid_constant__ Params P) {
    const uint32_t sb = smem_base();
    const int bx = blockIdx.x;
    const int cta0 = bx >= NCTA || CMAP == 0 ? bx : CMAP == 4 ? (((bx >> 1) & 7) + (bx >> 5) * 8) * 4 + ((bx >> 4) & 1) * 2 + (bx & 1)
                   : (((bx >> 1) & 15) + (bx >> 6) * 16) * 4 + ((bx >> 5) & 1) * 2 + (bx & 1);
    if (__all_sync(~0u, threadIdx.x >= NTHR - 32 && bx < NCTA) && elect()) {
        asm volatile("mbarrier.init.shared::cta.b64 [%0], 1;" :: "r"(sb + SM_CBAR + CB_WQ * 8));
        asm volatile("mbarrier.init.shared::cta.b64 [%0], 1;" :: "r"(sb + SM_CBAR + 80));
        asm volatile("fence.mbarrier_init.release.cluster;" ::: "memory");
        mbar_expect(sb + SM_CBAR + CB_WQ * 8, 5 * HALF);
        auto k0 = [&]() {
            mbar_expect(sb + SM_CBAR + 80, HALF);
            tma3(sb, &P.tm[TM_KH], 0, (cta0 >> 2) * SK + (SK - WIN) + (cta0 & 3) * 64, sb + SM_CBAR + 80, POL_FIRST);
        };
        if (K0FIRST) k0();
#pragma unroll 1
        for (int i = 0; i < 5; i++) tma3(sb + SM_WQR + (i == 4 ? 0 : i + 1) * HALF, &P.tm[TM_WQ], (cta0 >> 2) * 3, (cta0 & 3) * 160 + i * 32, sb + SM_CBAR + CB_WQ * 8, POL_FIRST);
        if (!K0FIRST) k0();
    }
    __syncwarp();
    int id = cta0 * NTHR + threadIdx.x, tid, lane, g, t, key, warp, cta, mlp, rowc, roww, j40;
    uint32_t maskA, maskB, barw, subw, prow;
    auto fresh = [&]() {
        const int cw = __shfl_sync(~0u, id >> 5, 0);
        id = pin(id); tid = id & 255; lane = id & 31; g = lane >> 2; t = lane & 3; key = (g >> 1) + 4 * (g & 1);
        const uint32_t m = (g & 1) ? 0xffff0000u : 0x0000ffffu;
        maskA = (g & 2) ? 0u : m; maskB = (g & 2) ? m : 0u;
        warp = cw & 7; cta = cw >> 3;
        mlp = (cta & 3) == 3 ? 96 : (cta >> 2) * 3 + (cta & 3);
        rowc = (cta >> 2) * SK + (SK - WIN) + (cta & 3) * 64; roww = rowc + warp * 8;
        j40 = (cta & 3) * 40;
        barw = sb + SM_BAR + warp * 96; subw = sb + warp * SUB; prow = sb + SM_PART + warp * 768;
    };
    fresh();

    if (cta == NCTA) {
        const uint32_t ep = *(volatile unsigned*)&g_epoch;
        if (tid == 0) {
#pragma unroll 1
            for (int it = 0; it < SPIN; it++) { if (ll_tag(ld_rlx(&g_ll[0][0][192])) == ep * 4 + 2) break; __nanosleep(200); }
        }
        __syncthreads();
#pragma unroll 1
        for (int i = tid; i < 4 * 80 * 8; i += NTHR)
            *reinterpret_cast<uint4*>(g_acc + (i >> 3) * ACC_PITCH + (i & 7) * 16) = make_uint4(0, 0, 0, 0);
        __threadfence();
        __syncthreads();
        if (tid == 0) asm volatile("st.relaxed.gpu.global.u32 [%0], %1;" :: "l"(&g_zflag), "r"(ep + 1) : "memory");
        return;
    }
    TSTAMP(0);
    if (tid == 64) { uint32_t now; asm volatile("mov.u32 %0, %globaltimer_lo;" : "=r"(now)); sts32(sb + SM_T0, now); }

    const CUtensorMap* tmk = reinterpret_cast<const CUtensorMap*>(__shfl_sync(~0u, (u64)&P.tm[0] + (lane >> 5), 0));
    auto c4 = [&]() { return 32 * min(warp, 4) + 16 * (t >> 1) + 2 * g + (t & 1); };
    auto xcol = [&](int i, int tt) { return (i < 2 ? 64 * i + 8 * warp : 128 + 8 * (warp >> 1)) + 2 * tt; };
    uint2 xp;
    uint32_t px[3], small;
    auto issue_first = [&](int j) {
        mbar_expect(sb + SM_CBAR + 80 + j * 8, HALF);
        tma3(sb + j * HALF, tmk + TM_KH, 0, rowc + (j >> 1) * 256 + (j & 1) * 32, sb + SM_CBAR + 80 + j * 8, POL_FIRST);
    };
    if (elect()) {
        if (warp != 2) asm volatile("mbarrier.init.shared::cta.b64 [%0], 1;" :: "r"(sb + SM_CBAR + 64 + warp * 8));
#pragma unroll
        for (int i = 0; i < 9; i++) asm volatile("mbarrier.init.shared::cta.b64 [%0], 1;" :: "r"(barw + i * 8));
        asm volatile("mbarrier.init.shared::cta.b64 [%0], 1;" :: "r"(sb + SM_CBAR + warp * 8));
        asm volatile("mbarrier.init.shared::cta.b64 [%0], 1;" :: "r"(sb + SM_CBAR + 128 + warp * 8));
        if (warp < 3) asm volatile("mbarrier.init.shared::cta.b64 [%0], %1;" :: "r"(sb + SM_CBAR + 192 + warp * 8), "r"(warp == 2 ? 8 : 1));
        sts64(barw + 80, 0, 0);
        asm volatile("fence.mbarrier_init.release.cluster;" ::: "memory");
        asm volatile("prefetch.tensormap [%0];" :: "l"(tmk + warp) : "memory");
    }
    __syncwarp();
    asm volatile("ld.global.nc.v2.u32 {%0,%1}, [%2];" : "=r"(xp.x), "=r"(xp.y) : "l"(P.x + 4 * c4()) : "memory");
#pragma unroll
    for (int i = 0; i < 3; i++) asm volatile("ld.global.nc.u32 %0, [%1];" : "=r"(px[i]) : "l"(P.x + 4 * j40 + xcol(i, t)) : "memory");
    asm volatile("ld.relaxed.gpu.global.u32 %0, [%1];" : "=r"(small) : "l"(lane < 16 ? (const void*)(P.b1 + min(mlp, 95) * 16 + (lane & 14)) : (const void*)&g_epoch) : "memory");
    if (tid >= 192 && tid < 192 + NCB) sts32(sb + SM_CNT + (tid - 192) * 8, 0);
    unsigned char* accg = reinterpret_cast<unsigned char*>(__shfl_sync(~0u, (u64)g_acc + (lane >> 5), 0));
    auto release = [&](const uint4& tw) {
        uint32_t old;
        __syncwarp();
        asm volatile("atom.relaxed.cta.shared.add.u32 %0, [%1], 1;" : "=r"(old) : "r"(sb + SM_CNT + (tw.x & 0xf8)) : "memory");
        return old;
    };
    auto refill = [&](const uint4& tw, uint32_t old) {
        if (__any_sync(~0u, (old & 127) == 127 && (tw.y & 2))) {
            wait_until(lds32(sb + SM_T0) + tw.z);
            if (elect()) issue_half(tw.y, sb, rowc, cta, tmk);
            __syncwarp();
        }
    };
    __syncthreads();
    auto issue_paced = [&](int j0, int j1) {
        if (warp >= j0 && warp < j1) {
            wait_until(lds32(sb + SM_T0) + PACES + warp * PACE / 2);
            if (elect()) issue_first(warp);
            __syncwarp();
        }
    };

    uint32_t offV0, offV2;
    auto calc_offsets = [&]() {
        offV0 = subw + (6 * t) * 128 + ((g ^ ((6 * t) & 7)) << 4);
        offV2 = subw + (6 * t + 2) * 128 + ((g ^ ((6 * t + 2) & 7)) << 4);
    };
    calc_offsets();

    auto load_v = [&](uint4 (&v)[6], uint32_t so) {
        v[0] = lds128(offV0 + so); v[1] = lds128((offV0 ^ 16) + so + 128); v[2] = lds128(offV2 + so);
        v[3] = lds128((offV2 ^ 16) + so + 128); v[4] = lds128((offV0 ^ 64) + so + 512); v[5] = lds128((offV0 ^ 80) + so + 640);
    };
    auto issue_v = [&](auto I, int dw) {
        constexpr Step c = SCH.st[I.value];
        const uint32_t bar = barw + dw * 96 + c.slot * 8;
        mbar_expect(bar, SUB);
        tma_v(subw + dw * SUB + c.slot * TILE, tmk, roww * 3 + dw * 24 + c.unit * 768, bar);
    };
    auto refill2 = [&](auto I) { __syncwarp(); if (elect()) issue_v(I, 0); };
    uint4 wq0[6], wqh[3], wq1[6];
    auto load_wq1 = [&](int i) { wq1[i] = lds128((i == 2 ? offV2 : i == 3 ? (offV2 ^ 16) + 128 : (offV0 ^ (i * 16)) + i * 128) + SM_WQ + TILE); };
    auto load_wq = [&]() {
        load_v(wq0, SM_WQ);
        const uint32_t so = SM_WQR - ((warp + 1) >> 1) * SUB;
        wqh[0] = lds128(((warp & 1) ? (offV2 ^ 16) + 128 : offV0) + so);
        wqh[1] = lds128(((warp & 1) ? (offV0 ^ 64) + 512 : (offV0 ^ 16) + 128) + so);
        wqh[2] = lds128(((warp & 1) ? (offV0 ^ 80) + 640 : offV2) + so);
#pragma unroll
        for (int i = 0; i < NWQ1; i++) load_wq1(i);
    };
    uint4 kr[8][6];
    const unsigned char* rap;
    u64 rw[2];
    auto q_proj = [&](auto L, uint32_t (&p)[3], uint32_t pst) {
        if (L.value == 0 && g >= 4) p[0] = p[1] = p[2] = ONES;
        float a[3][4], b[3][4];
        const uint32_t dH = __byte_perm(p[2], 0, (warp & 1) ? 0x3232 : 0x1010);
        const uint32_t dA = __byte_perm(p[0], 0, 0x1010), dB = __byte_perm(p[0], 0, 0x3232), dC = __byte_perm(p[1], 0, 0x1010), dD = __byte_perm(p[1], 0, 0x3232);
#pragma unroll
        for (int i = NWQ1; i < 3; i++) load_wq1(i);
#pragma unroll
        for (int j = 0; j < 3; j++) { a[j][0] = a[j][1] = a[j][2] = a[j][3] = 0.f; mma(a[j], wq0[j], dA & maskA, dA & maskB); }
#pragma unroll
        for (int j = 0; j < 3; j++) { b[j][0] = b[j][1] = b[j][2] = b[j][3] = 0.f; mma(b[j], wq0[j + 3], dB & maskA, dB & maskB); }
#pragma unroll
        for (int j = 0; j < 3; j++) mma(a[j], wqh[j], dH & maskA, dH & maskB);
#pragma unroll
        for (int i = 3; i < 6; i++) load_wq1(i);
        auto look_rw = [&]() {
            if constexpr (L.value == 1) {
                if (NWQ1) rap = accg + ACC_BYTES + (c4() >> 2) * ACC_PITCH + (c4() & 3) * 8;
                rw[0] = ld_rlx(rap); rw[1] = ld_rlx(rap + 40 * ACC_PITCH);
            }
        };
        if (RWAT == 0) look_rw();
        if (L.value == 1 && P4AT == 2) refill2(IC<4>{});
#pragma unroll
        for (int j = 0; j < 3; j++) mma(b[j], wq1[j], dC & maskA, dC & maskB);
#pragma unroll
        for (int j = 0; j < 3; j++) mma(a[j], wq1[j + 3], dD & maskA, dD & maskB);
#pragma unroll
        for (int j = 0; j < 3; j++) {
#pragma unroll
            for (int k = 0; k < 4; k++) a[j][k] += b[j][k];
            sts128f(pst + j * 256, a[j]);
        }
        uint32_t tag;
        if (L.value) tag = lds32(sb + SM_EPOCH) * 4 + 3;
        u64* pub = L.value ? &g_ll[0][cta][tid] : &g_l0[cta][tid];
        if (RWAT == 1) look_rw();
        if (L.value == 0) asm volatile("fence.proxy.async.shared::cta;" ::: "memory");
        TSTAMPL(21);
        __syncthreads();
        if (!L.value) tag = lds32(sb + SM_EPOCH) * 4 + 1;
#pragma unroll 1
        for (int k = 0; k < 2 - L.value; k++) st_rlx_if(tid < 192, pub + k * 192, ll_pack(sum8(sb + (k ? SM_CSP : SM_PART) + tid * 4, 768), tag));
        TSTAMPL(23);
    };
    auto ln_stats = [&]() {
        float ss = ln_part(xp, lane);
        ss += shx(ss, 8); ss += shx(ss, 4); ss += shx(ss, 2); ss += shx(ss, 1);
        stsf(sb + SM_STAT + min(warp, 4) * 8 + (lane >> 4) * 4, ss);
    };
    auto ln_final = [&](float& mean, float& rstd) {
        float2 v[5];
#pragma unroll
        for (int w = 0; w < 5; w++) v[w] = lds64f(sb + SM_STAT + w * 8);
        mean = sum5(v[0].x, v[1].x, v[2].x, v[3].x, v[4].x) * (1.f / D_MODEL);
        const float msq = sum5(v[0].y, v[1].y, v[2].y, v[3].y, v[4].y) * (1.f / D_MODEL);
        rstd = ln_rstd(mean, msq);
        stsf(sb + SM_FXS, msq);
    };
    auto q_addr = [&](int d) { return sb + SM_VEC + (((d >> 1) & 1) * 4 + ((d >> 3) & 3)) * 48 + (d >> 5) * 8 + ((d >> 2) & 1) * 4 + (d & 1) * 2; };
    {
#pragma unroll
        for (int u = 0; u < 8; u++)
#pragma unroll
            for (int i = 0; i < 6; i++) kr[u][i] = lds128(sb + SM_CS + (u * 6 + i) * 16);
        issue_paced(1, NIM);
        ln_stats();
        if (tid == 16) { sts32(sb + SM_EPOCH, small); sts32(sb + SM_M1, ~0u); }
        else if (tid < 16) sts32(sb + SM_B1 + tid * 4, (tid & 1) ? small & 0xffff0000u : small << 16);
        mbar_wait(sb + SM_CBAR + CB_WQ * 8, 0);
        load_wq();
        q_proj(IC<0>{}, px, sb + (t < 2 ? SM_PART : SM_CSP) + warp * 768 + (8 * g + 4 * (t & 1)) * 4);
    }
    {
        uint32_t offQ, offL;
        auto calc_ql = [&]() {
            offQ = pin(sb + SM_VEC + (lane & 7) * 48);
            offL = pin(subw + lane * 16);
        };

        auto issue_w = [&](auto L, int which) {
            const uint32_t bar = sb + SM_CBAR + (CB_W1 + which) * 8;
            if (mlp == 96) asm volatile("mbarrier.arrive.shared::cta.b64 _, [%0];" :: "r"(bar) : "memory");
            else {
                mbar_expect(bar, 20480);
                if (which) {
                    tma3(sb + (L.value ? 3 * TILE : SM_W2), tmk + TM_W2, 0, mlp * 16, bar, W2ONE ? POL_FIRST : WPOL);
                    if (W2ONE && !L.value) tma3_pf(tmk + TM_W2, 0, mlp * 16, POL_NORMAL);
                    if (W1ONE && !L.value) asm volatile("cp.async.bulk.prefetch.L2.global.L2::cache_hint [%0], 20480, %1;" :: "l"(P.w1 + mlp * 10240), "l"((u64)POL_NORMAL << 32) : "memory");
                }
                else asm volatile("cp.async.bulk.tensor.3d.shared::cluster.global.mbarrier::complete_tx::bytes.L2::cache_hint [%0], [%1, {%2, %3, %3}], [%4], %5;"
                                  :: "r"(sb + (L.value ? 2 * TILE : SM_W1)), "l"(tmk + TM_W1), "r"(mlp * 16), "r"(0), "r"(bar), "l"((u64)(W1ONE ? POL_FIRST : WPOL) << 32) : "memory");
            }
        };
        float acc[3][4];
        auto load_q = [&](uint4 (&qf)[3]) {
#pragma unroll
            for (int i = 0; i < 3; i++) qf[i] = lds128(offQ + i * 16);
        };
        auto softmax = [&](float S0, float S1, float S2, float S3) {
            int mi = __float_as_int(fmaxf(fmaxf(S0, S1), fmaxf(S2, S3)));
            mi = __reduce_max_sync(~0u, mi ^ ((mi >> 31) & 0x7fffffff));
            const float mrun = __int_as_float(mi ^ ((mi >> 31) & 0x7fffffff));
            const float p0 = ex2((S0 - mrun) * CS), p1 = ex2((S1 - mrun) * CS), p2 = ex2((S2 - mrun) * CS), p3 = ex2((S3 - mrun) * CS);
            const uint32_t pa = pack_bf(p0, p1), pb = pack_bf(p2, p3), pw = prow + 256 + (key >> 1) * 80 + t * 4 + (key & 1) * 2;
            sts16(pw, pa); sts16(pw + 16, pa >> 16); sts16(pw + 32, pb); sts16(pw + 48, pb >> 16);
            __syncwarp();
#pragma unroll
            for (int j = 0; j < 3; j++) acc[j][0] = acc[j][1] = acc[j][2] = acc[j][3] = 0.f;
            return make_float2(mrun, (p0 + p1) + (p2 + p3));
        };
        auto pv = [&](const uint4 (&v)[6], uint32_t pp) {
            const uint32_t dA = __byte_perm(pp, 0, 0x1010), dB = __byte_perm(pp, 0, 0x3232);
            mma(acc[0], v[0], dA & maskA, dA & maskB); mma(acc[1], v[1], dA & maskA, dA & maskB); mma(acc[2], v[2], dA & maskA, dA & maskB);
            mma(acc[0], v[3], dB & maskA, dB & maskB); mma(acc[1], v[4], dB & maskA, dB & maskB); mma(acc[2], v[5], dB & maskA, dB & maskB);
        };
        auto sa = [&]() { return prow + 256 + t * 32 + g * 4; };
        auto pass1 = [&]() {
            if (NIM < NI1) issue_paced(NIM, NI1);
            fresh();
            calc_ql();
            __syncthreads();
            sts64(prow + lane * 8, xp.x, xp.y);
            int e = 0;
            const uint4* tab = P.tile + (warp >> 2);
            uint4 tw = tab[0];
            uint32_t ka[3];
#pragma unroll
            for (int j = 0; j < 3; j++) ka[j] = pin(subw + key * 384 + j * 128 + ((t ^ ((3 * key + j) & 7)) << 4));
            auto load_k = [&](uint4 (&v)[6], uint32_t so) {
#pragma unroll
                for (int i = 0; i < 6; i++) v[i] = lds128(((i & 1) ? ka[i >> 1] ^ 64 : ka[i >> 1]) + so);
            };
            const uint32_t s0 = pin(prow + 256 + g * 4), sca = pin(sb + SM_SC + warp * 128 + g * 16);
#pragma unroll 1
            do {
                const uint4 tn = tab[2 * e + 2];
                uint4 v[6], qf[3];
                if (tw.x & (G_A | G_B | G_C)) {
                    if ((tw.x & G_A) && warp == 7 && elect()) {
                        mbar_expect(sb + SM_CBAR + CB_SNAP * 8, HALF);
                        asm volatile("cp.async.bulk.shared::cluster.global.mbarrier::complete_tx::bytes [%0], [%1], 12288, [%2];"
                                     :: "r"(sb + SM_SNAP), "l"(&g_l0[cta & ~3][0]), "r"(sb + SM_CBAR + CB_SNAP * 8) : "memory");
                    }
                    if (tw.x & G_B) {
                        if (warp < 6) {
                            mbar_wait(sb + SM_CBAR + CB_SNAP * 8, 0);
                            float qc[2] = {0.f, 0.f}, mean, rstd;
#pragma unroll 1
                            for (int k = 0; k < 2; k++) {
                                u64 qw[4];
#pragma unroll
                                for (int i = 0; i < 4; i++) { const uint2 x = lds64(sb + SM_SNAP + i * 3072 + k * 1536 + tid * 8); qw[i] = x.x | (u64)x.y << 32; }
                                qc[0] = qc[1];
                                qc[1] = ll_gather<384>(&g_l0[cta & ~3][k * 192 + tid], lds32(sb + SM_EPOCH) * 4 + 1, qw);
                            }
                            ln_final(mean, rstd);
                            stsf(sb + SM_CS + tid * 4, qc[1]);
                            const float q = (qc[0] - mean * qc[1]) * rstd;
                            sts16(q_addr(tid), pack_bf(q, q));
                        }
                        __syncthreads();
                        if (warp == 7 && elect()) issue_half(UC<load_word(12)>::value, sb, rowc, cta, tmk);
                        TSTAMP(2);
                    }
                    if (tw.x & G_C) {
                        load_k(v, (e - LATEAT) * TILE);
                        load_q(qf);
                        stsf(s0 + (e - LATEAT) * 32, score(v, qf));
                    }
                }
                load_q(qf);
                mbar_wait(sb + SM_CBAR + (tw.x & 0xf8), tw.x >> 31);
                TRACE(e);
                load_k(v, tw.x & 0x3f000);
                const uint32_t old = release(tw);
                const float s = score(v, qf);
                uint32_t m;
                {
                    uint32_t a[6];
#pragma unroll
                    for (int i = 0; i < 6; i++) a[i] = bf2_amax(bf2_amax(v[i].x, v[i].y), bf2_amax(v[i].z, v[i].w));
                    m = bf2_amax(bf2_amax(bf2_amax(a[0], a[1]), bf2_amax(a[2], a[3])), bf2_amax(a[4], a[5]));
                }
                m = bf2_amax(m, m >> 16) & 0x7f80;
                m = max(m, __shfl_xor_sync(~0u, m, 1));
                stsf(s0 + e * 32, s);
                m = max(m, __shfl_xor_sync(~0u, m, 2));
                refill(tw, old);
                const uint32_t b = min(max(m, 15u << 7) - (15u << 7), 126u << 7);
                const uint32_t dn = ((127u << 7) - b) * 0x10001u, up = ((127u << 7 | 0x8000u) + b) * 0x10001u;
                uint32_t c[18], any = m > (141u << 7);
#pragma unroll
                for (int i = 0; i < 6; i++) {
                    const uint32_t y0 = bf2_mul(v[i].x, dn), y1 = bf2_mul(v[i].y, dn), y2 = bf2_mul(v[i].z, dn), y3 = bf2_mul(v[i].w, dn);
                    v[i] = make_uint4(bf2_fma(y0, up, v[i].x), bf2_fma(y1, up, v[i].y), bf2_fma(y2, up, v[i].z), bf2_fma(y3, up, v[i].w));
                    any |= v[i].x | v[i].y;
                    any |= v[i].z | v[i].w;
                    const uint32_t hb = __byte_perm(y2, y3, 0x7531);
                    c[3 * i] = __byte_perm(y0, y1, 0x6420); c[3 * i + 1] = __byte_perm(y2, y3, 0x6420);
                    c[3 * i + 2] = __byte_perm(y0, y1, 0x7531) | __funnelshift_r(hb, hb, 4);
                }
                asm volatile("st.shared.u8 [%0], %1;" :: "r"(sca + (e & 3) * 4 + (e >> 2)), "r"((b >> 7) + 63) : "memory");
                const bool rare = __any_sync(~0u, any);
                k_keep(kr, c, e, offL);
                if (rare) k_rare(v[0], v[1], v[2], v[3], v[4], v[5], m > (141u << 7), e, warp, lane);
                tw = tn;
            } while (++e < 16);
            asm volatile("fence.proxy.async.shared::cta;" ::: "memory");
            __syncwarp();
            TSTAMP(10);
            fresh(); calc_offsets();
            {
                const uint2 st = lds64(barw + 80);
                const uint32_t xa = sb + SM_EXC + warp * 128 + (lane & 15) * 8 + 4;
                uint32_t pos = lds32(xa), lt;
                asm volatile("mov.u32 %0, %lanemask_lt;" : "=r"(lt));
                if (lane >= st.x) pos = 0x80000000u;
                const bool dup = (__match_any_sync(~0u, pos >> 16) & lt) && lane < st.x;
                if (lane < 16) sts32(xa, dup ? pos | 0x40000000u : pos);
                if (__any_sync(~0u, dup)) sts32(barw + 84, st.y | 0x10000u);
                const float2 ml = softmax(ldsf(sa()), ldsf(sa() + 128), ldsf(sa() + 256), ldsf(sa() + 384));
                sts64f(sb + SM_ML + warp * 8, ml.x, warp_sum(ml.y));
            }
            u64 pm = 0, pl = 0;
#pragma unroll 1
            do {
                const uint4 tn = tab[2 * e + 2];
                if (tw.x & (G_A | G_B | G_C)) {
                    if (tw.x & G_A) {
                        if (lane < 24) st_rlx(&g_ll[0][cta][warp * 24 + lane], 0ull);
                        else if (lane < 28) st_rlx(&g_ll[0][cta][168 + warp * 4 + lane], ll_pack(ldsf(sb + SM_ML + warp * 8 + (lane & 1) * 4), lds32(sb + SM_EPOCH) * 4 + 2));
                    }
                    if (warp == 2) {
                        if (tw.x & G_B) ld_rlx2(&g_ll[0][cta ^ (lane >> 3)][192 + (lane & 7) * 4], pm, pl);
                        if (tw.x & G_C) head_weight(&g_ll[0][cta ^ (lane >> 3)][192 + (lane & 7) * 4], pm, pl, 0, lane);
                    }
                    __syncwarp();
                }
                const uint32_t pp = lds32(prow + 256 + t * 80 + ((tw.x >> 20) & 255));
                mbar_wait(sb + SM_CBAR + (tw.x & 0xf8), tw.x >> 31);
                TRACE(e);
                uint4 v[6];
                load_v(v, tw.x & 0x3f000);
                refill(tw, release(tw));
                pv(v, pp);
                tw = tn;
            } while (++e < 32);
        };
        uint32_t osa, ora, owa, orow, otag;
        u64* olb;
        float xc;
        auto o_setup = [&](auto L) {
            fresh();
            const int lz = lane, d = warp * 24 + min(lz, 23);
            osa = pin(prow + ((lz >> 2) * 8 + (lz & 1) * 4) * 4);
            ora = pin(sb + SM_PART + d * 4);
            olb = pin(&g_ll[L.value][cta & ~3][d]);
            orow = pin((lz & 1) + 2 * (lz & 2) + 2 * (lz >> 4));
            owa = pin(sb + SM_RING + warp * 1536 + orow * 64 + ((((lz >> 2) & 3) ^ (orow >> 1)) << 4));
            otag = lds32(sb + SM_EPOCH) * 4 + 2 + 2 * L.value;
            uint32_t x; asm volatile("ld.shared.u16 %0, [%1];" : "=r"(x) : "r"(prow + ((cta & 1) * 16 + (lz >> 3) * 4 + (cta & 2) + ((lz >> 2) & 1)) * 8 + (lz & 3) * 2) : "memory");
            xc = bf_lo(x) * (1.f / 32);
        };
        auto pass2 = [&]() {
            constexpr IC<1> L{};
            if (P4AT == 0) refill2(IC<4>{});
            if (P2LATE == 1 && warp >= 4) refill2(IC<2>{});
            offQ = sb + SM_VEC + (lane & 7) * 48; offL = subw + lane * 16;
            uint4 tb[8][3];
            auto load_tb = [&](auto I) {
#pragma unroll
                for (int i = 0; i < 3; i++) tb[I.value][i] = lds128(offL + (I.value >> 1) * TILE + ((I.value & 1) * 3 + i) * 512);
            };
            const float cs = ldsf(sb + SM_CS + min(tid, 191) * 4), inv = fx2_inv(ldsf(sb + SM_MSQ));
            const uint32_t qtag = lds32(sb + SM_EPOCH) * 4 + 3;
            uint32_t m1 = lds32(sb + SM_M1), m1n = m1;
            static_for<0, NPRE>(load_tb);
            const u64* qb = &g_ll[0][cta & ~3][min(tid, 191)];
            const uint32_t qa = pin(q_addr(min(tid, 191)));
            {
                uint32_t x[2];
                fx2_wait<2, true>([&](int i) { return rap + i * 40 * ACC_PITCH; }, rw, sb + SM_MSQ, inv, x);
                xp = make_uint2(x[0], x[1]);
            }
            u64 qw[4];
            ll_look<256>(qb, qw);
            ln_stats();
            if (P4AT == 1) refill2(IC<4>{});
            if (S0EARLY) refill2(IC<5>{});
            __syncthreads();
            auto vwait = [&](auto I) { mbar_wait(barw + IC<SCH.st[I.value].slot>::value * 8, IC<SCH.st[I.value].par>::value); };
            bool ok;
            {
                float mean, rstd;
                ln_final(mean, rstd);
                sts64(prow + lane * 8, xp.x, xp.y);
                sts128f(prow + 256 + lane * 16, 0.f, 0.f, 0.f, 0.f);
                const float sq = rstd * 0x1p64f, q0 = -mean * cs * sq;
                const float q = ll_gather<256>(qb, qtag, qw) * sq + q0;
                sts16(qa, pack_bf(q, q));
                TSTAMPL(24);
            }
            if (!S0EARLY) refill2(IC<5>{});
            if (P2LATE == 2 && warp >= 4) refill2(IC<2>{});
            if (P4AT == 3) refill2(IC<4>{});
            if (NOWIN & 1) { if (warp < 6) refill2(IC<0>{}); if (warp >= 5) refill2(IC<3>{}); }
            if (NOWIN & 2) { if (warp >= 6) refill2(IC<1>{}); if (warp < 4) refill2(IC<2>{}); }
            if (NOWIN & 4) { if (warp >= 6) refill2(IC<0>{}); if (warp < 6) refill2(IC<1>{}); }
            if (NOWIN & 8) { if (warp < 5) refill2(IC<3>{}); if (warp >= 4) refill2(IC<2>{}); }
            __syncthreads();
            uint4 qf[3];
            load_q(qf);
            float S[4], d[2][4];
            auto vload = [&](auto I) {
                constexpr int p = I.value;
                constexpr Step c = SCH.st[p];
                load_v(kr[p & 7], c.slot * TILE);
                if constexpr (c.next >= 0) refill2(IC<c.next>{});
                if constexpr (p == 11) { __syncwarp(); if (elect()) asm volatile("mbarrier.arrive.shared::cta.b64 _, [%0];" :: "r"(sb + SM_CBAR + CB_REL * 8) : "memory"); }
            };
            static_for<0, 96>([&](auto F) {
                constexpr int f = F.value, i = f % 6, u = kunit(f / 6), w = 3 * f % 12;
                uint4 (&src)[3] = *reinterpret_cast<uint4 (*)[3]>(f < 32 ? &tb[f / 4 & 7][0] : &kr[(f / 8 + 4) & 7][(f / 4 & 1) * 3]);
                const uint4 a = k_unpack(word<w % 4>(src[w / 4]), word<(w + 1) % 4>(src[(w + 1) / 4]), word<(w + 2) % 4>(src[(w + 2) / 4]), m1);
                if constexpr (f < 32 ? f % 4 == M1AT : f % 8 == M1P) m1 = m1n;
                if constexpr (f % 4 == 3 && f / 4 + NPRE < 8) {
                    load_tb(IC<f / 4 + NPRE>{});
                    if constexpr ((f / 4 + NPRE) & 1) { refill2(IC<5 + (f / 4 + NPRE) / 2>{}); m1n = lds32(sb + SM_M1); }
                }
                if constexpr (i < 2) d[i][0] = d[i][1] = d[i][2] = d[i][3] = 0.f;
                mma(d[i & 1], a, (i & 1) ? qf[i / 2].z : qf[i / 2].x, (i & 1) ? qf[i / 2].w : qf[i / 2].y);
                if constexpr (i == 5) {
                    if constexpr (u == 11 || ((u & 3) == 0 && u != 8)) S[u >> 2] = (d[0][0] + d[0][3]) + (d[1][0] + d[1][3]);
                    else add_if(t == (u & 3), S[u >> 2], d[0][0] + d[0][3], d[1][0] + d[1][3]);
                    if constexpr (f < 64) S[u >> 2] = shx(S[u >> 2], 0);
                }
                if constexpr (f == 31) { fresh(); calc_offsets(); ok = mbar_test(barw + IC<SCH.st[0].slot>::value * 8, 0); }
                if constexpr (f == 48) {
                    const uint2 x = lds64(sb + SM_EXC + warp * 128 + (lane & 15) * 8);
                    const float c = k_side(sb, x);
                    if (x.y < 0x40000000u) stsf(prow + 256 + (x.y >> 16), c);
                }
                if constexpr (f >= 32 && f % 8 == 7) {
                    if constexpr (PARKS >> (f / 8 - 4) & 1) {
                        constexpr int p = popc(PARKS & ((1 << (f / 8 - 4)) - 1));
                        if (!ok) vwait(IC<p>{});
                        vload(IC<p>{});
                        m1n = lds32(sb + SM_M1);
                        ok = mbar_test(barw + IC<SCH.st[p + 1].slot>::value * 8, IC<SCH.st[p + 1].par>::value);
                    }
                }
            });
            uint32_t bad = lds32(barw + 84);
            const uint32_t sc = lds32(sb + SM_SC + tid * 4);
            __syncwarp();
            if (bad) k_fix(P.k + (size_t)roww * DH, bad, warp, lane);
            TSTAMP(30);
            const float2 ml = softmax(S[0] * __uint_as_float((sc & 255) << 23) + ldsf(sa()), S[1] * __uint_as_float((sc & 0xff00) << 15) + ldsf(sa() + 128),
                                      S[2] * __uint_as_float((sc & 0xff0000) << 7) + ldsf(sa() + 256), S[3] * __uint_as_float((sc >> 24) << 23) + ldsf(sa() + 384));
            uint4 pq[4];
#pragma unroll
            for (int j = 0; j < 4; j++) pq[j] = lds128(prow + 256 + t * 80 + j * 16);
            TSTAMP(1);
            if (!ok) vwait(IC<NPARK>{});
            float ac2[3][4];
#pragma unroll
            for (int j = 0; j < 3; j++) ac2[j][0] = ac2[j][1] = ac2[j][2] = ac2[j][3] = 0.f;
            const uint32_t sl = (g & 1) ? 0x1044 : 0x4410, sh = (g & 1) ? 0x3244 : 0x4432;
            const uint32_t sA0 = (g & 2) ? 0x4444 : sl, sA1 = (g & 2) ? sl : 0x4444, sB0 = (g & 2) ? 0x4444 : sh, sB1 = (g & 2) ? sh : 0x4444;
            u64 pm = 0, pl = 0;
            static_for<NPARK, 16>([&](auto I) {
                constexpr int p = I.value;
                static_assert(p - SCH.st[p].mma0 < 8, "buffer in use");
                vload(I);
                if constexpr (p < 15) ok = mbar_test(barw + IC<SCH.st[p + 1].slot>::value * 8, IC<SCH.st[p + 1].par>::value);
                static_for<SCH.st[p].mma0, SCH.st[p].mma0 + SCH.st[p].nmma>([&](auto J) {
                    constexpr int u = SCH.st[J.value].unit;
                    const uint32_t pp = word<u & 3>(pq[u >> 2]), a0 = __byte_perm(pp, 0, sA0), a1 = __byte_perm(pp, 0, sA1), b0 = __byte_perm(pp, 0, sB0), b1 = __byte_perm(pp, 0, sB1);
#pragma unroll
                    for (int j = 0; j < 3; j++) mma(acc[j], kr[J.value & 7][j], a0, a1);
#pragma unroll
                    for (int j = 0; j < 3; j++) mma(ac2[j], kr[J.value & 7][j + 3], b0, b1);
                });
                if constexpr (p == NPARK) {
                    const float l = warp_sum(ml.y);
                    if (lane < 28) st_rlx(&g_ll[1][cta][lane < 24 ? warp * 24 + lane : 168 + warp * 4 + lane], lane < 24 ? 0ull : ll_pack((lane & 1) ? l : ml.x, lds32(sb + SM_EPOCH) * 4 + 4));
                }
                if constexpr (p == HWAT) { if (warp == 6) ld_rlx2(&g_ll[1][cta ^ (lane >> 3)][192 + (lane & 7) * 4], pm, pl); }
                if constexpr (p == 13) o_setup(L);
                if constexpr (p == HWAT + 2) { if (warp == 6) head_weight(&g_ll[1][cta ^ (lane >> 3)][192 + (lane & 7) * 4], pm, pl, 1, lane); }
                if constexpr (p >= WOAT && p < WOAT + 3) {
                    if (warp == p - WOAT) {
                        mbar_wait(sb + SM_CBAR + CB_REL * 8, 0);
                        if (elect()) {
                            issue_half(UC<load_word(64 + 2 * (p - WOAT)) | 1>::value, sb, rowc, cta, tmk);
                            if constexpr (p < WOAT + 2) issue_half(UC<load_word(65 + 2 * (p - WOAT)) | 1>::value, sb, rowc, cta, tmk);
                        }
                        __syncwarp();
                    }
                }
                if constexpr (p < 15) { if (!ok) mbar_wait(barw + IC<SCH.st[p + 1].slot>::value * 8, IC<SCH.st[p + 1].par>::value); TRACE(33 + p); }
            });
#pragma unroll
            for (int j = 0; j < 3; j++)
#pragma unroll
                for (int k = 0; k < 4; k++) acc[j][k] += ac2[j][k];
        };

        const unsigned char* ap;
        uint32_t hpa, hsa, hst, w2a, la;
        uint2 b2v;
        float b1v, cs1;
        auto mlp_global = [&](auto L) {
            const int cz = c4();
            ap = accg + 2 * L.value * ACC_BYTES + (cz >> 1) * ACC_PITCH + (cz & 1) * 16;
            if (L.value) ap = pin(ap);
            rap = pin(accg + (2 * L.value + 1) * ACC_BYTES + (cz >> 2) * ACC_PITCH + (cz & 3) * 8);
            asm volatile("ld.global.nc.v2.u32 {%0,%1}, [%2];" : "=r"(b2v.x), "=r"(b2v.y) : "l"(P.b2 + 4 * cz));
        };
        auto mlp_shared = [&](auto L) {
            const int lz = lane;
            hpa = pin(sb + SM_PART + warp * 256 + ((lz & 2) * 4 + (lz >> 2)) * 16 + (L.value ? 0 : (lz & 1) * 4));
            hsa = pin(sb + SM_PART + (lz & 15) * 16); hst = pin(sb + SM_PART + (lz & 15) * 16 + warp * 256 + 8 + (lz >> 4) * 4);
            w2a = pin(sb + (L.value ? 3 * TILE : SM_W2) + ((lz & 3) * 10 + 2 * warp) * 128 + (((lz >> 2) ^ ((2 * lz + 2 * warp) & 6)) << 4));
            la = sb + (L.value ? 2 * TILE : SM_W1) + warp * 4096 + (lz & 4) * 512 + (lz & 2) * 64 + (lz & 1) * 32 + (lz >> 4) * 64 + ((((lz >> 3) ^ (lz >> 1)) & 1) << 4);
            b1v = ldsf(sb + SM_B1 + (lz & 15) * 4);
            if (L.value) { la = pin(la); cs1 = ldsf(sb + SM_ML + (lz & 15) * 4); }
            else fresh();
        };
        uint32_t pa;
        unsigned char* rop;
        uint32_t wpa;
        auto sum_setup = [&](auto L) {
            const int lz = lane, word = warp * 128 + (cta & 3) * 32 + lz;
            const uint32_t wo = ((lz >> 2) * 8 + (lz & 1) * 4) * 4;
            wpa = pin(sb + SM_RING + warp * 1536 + ((((lz >> 1) ^ (lz >> 4)) & 1) ? HALF + (wo ^ 64) : wo));
            pa = pin(sb + SM_RING + warp * 256 + lz * 4);
            rop = pin(accg + 2 * L.value * ACC_BYTES + (word >> 3) * ACC_PITCH + (word & 7) * 4);
        };
        auto out_proj = [&](auto L) {
            TSTAMP2(3);
            CSTAMP(0, __float_as_uint(acc[2][3]));
            __syncwarp();
#pragma unroll
            for (int j = 0; j < 3; j++) sts128f(osa + 256 * j, acc[j]);
            __syncthreads();
            {
                float s[8];
#pragma unroll
                for (int w = 0; w < 8; w++) s[w] = ldsf(ora + w * 768);
                const uint4 fa = lds128(sb + SM_FAC), fb = lds128(sb + SM_FAC + 16);
            CSTAMP(1, __float_as_uint(s[0]));
                const float own = ((s[0] * __uint_as_float(fa.x) + s[1] * __uint_as_float(fa.y)) + (s[2] * __uint_as_float(fa.z) + s[3] * __uint_as_float(fa.w))) +
                                  ((s[4] * __uint_as_float(fb.x) + s[5] * __uint_as_float(fb.y)) + (s[6] * __uint_as_float(fb.z) + s[7] * __uint_as_float(fb.w)));
                st_rlx_if(lane < 24, olb + (cta & 3) * 256, ll_pack(own, otag));
            CSTAMP(2, __float_as_uint(own));
            }
            TSTAMPL(29);
            if (L.value == 0 && warp == 7) {
#pragma unroll 1
                for (int it = 0; it < SPIN; it++) {
                    uint32_t v; asm volatile("ld.acquire.gpu.global.u32 %0, [%1];" : "=r"(v) : "l"(&g_zflag) : "memory");
                    if (__all_sync(~0u, v == (otag >> 2) + 1)) break;
                }
            }
            constexpr int NW = L.value ? NWO1 : 3;
            uint4 v[5][3];
            u64 ow[4];
            auto read_wo = [&](auto J) {
#pragma unroll
                for (int p = 0; p < 3; p++) v[J.value][p] = lds128(owa + ring_hs(64 + J.value) * HALF + p * 512);
            };
            static_for<0, NW>([&](auto J) {
                if (L.value && J.value == 0) { sum_setup(L); maskA = pin(maskA); maskB = pin(maskB); }
                if ((L.value ? OPOLL1 : OPOLL) == J.value) { ll_look<256>(olb, ow); if (L.value) { mlp_shared(L); mlp_global(L); } }
                mbar_wait(sb + SM_CBAR + (CB_WO + J.value) * 8, L.value);
                read_wo(J);
                if (L.value == 0 && W1AT0 == J.value + 1) {
                    __syncwarp();
                    if (elect() && cnt_inc(sb + SM_CNT + CB_W1 * 8, 7) == 7) issue_w(L, 0);
                    __syncwarp();
                }
                if (L.value == 1 && (W1AT1 == J.value + 1 || W2AT1 == J.value + 1)) {
                    if (warp == 7 && elect()) { if (W1AT1 == J.value + 1) issue_w(L, 0); if (W2AT1 == J.value + 1) issue_w(L, 1); }
                    __syncwarp();
                }
            });
            const float o = ll_gather<256>(olb, otag, ow);
            CSTAMP(3, __float_as_uint(o));
            TSTAMP2(4);
            bool ok = true;
            if constexpr (NW < 5) ok = mbar_test(sb + SM_CBAR + (CB_WO + 4) * 8, L.value);
            if constexpr (NW < 4) ok &= mbar_test(sb + SM_CBAR + (CB_WO + 3) * 8, L.value);
            const uint32_t od = pack_bf(o, o);
            uint32_t oa[3], ob[3];
#pragma unroll
            for (int p = 0; p < 3; p++) { const uint32_t op = __shfl_sync(~0u, od, 8 * p + orow); oa[p] = op & maskA; ob[p] = op & maskB; }
            CSTAMP(4, oa[2]);
            float y[5][4];
#pragma unroll
            for (int j = 0; j < 5; j++) y[j][0] = y[j][1] = y[j][2] = y[j][3] = 0.f;
            auto rest = [&]() {
                if (!ok) static_for<NW, 5>([&](auto J) { mbar_wait(sb + SM_CBAR + (CB_WO + J.value) * 8, L.value); });
                static_for<NW, 5>(read_wo);
            };
            if (L.value) rest();
#pragma unroll
            for (int p = 0; p < 3; p++)
#pragma unroll
                for (int j = 0; j < NW; j++) mma(y[j], v[j][p], oa[p], ob[p]);
            if (!L.value) { rest(); sum_setup(L); }
#pragma unroll
            for (int p = 0; p < 3; p++)
#pragma unroll
                for (int j = NW; j < 5; j++) mma(y[j], v[j][p], oa[p], ob[p]);
            CSTAMP(5, __float_as_uint(y[4][3]));
#pragma unroll
            for (int j = 0; j < 5; j++) sts128f(wpa + j * 256, y[j]);
            TSTAMP2(5);
        };
        u64 yw[2];
        bool wide;
        float msq = 0.f, yf[4];
        auto mlp_part = [&](auto L) {
            const float sc1 = fx2_scale(ldsf(sb + SM_FXS)) * 0.25f;
            bar_sync(0, 256);
            CSTAMP(6, __float_as_uint(sc1));
            const float s = (sum8(pa, 1536) + xc) + sum8(pa + 128, 1536), sm = s * sc1 + FX2_ONE;
            CSTAMP(7, __float_as_uint(s));
            const bool wide1 = !(fabsf(sm - FX2_ONE) < FX1LIM);
            asm volatile("red.relaxed.gpu.global.add.u32 [%0], %1;" :: "l"(rop), "r"(wide1 ? 0u : __float_as_uint(sm) * 128u + (1u - 0x4b400000u * 128u)) : "memory");
            const uint32_t c0 = clk();
            TSTAMP2(6);
            if (L.value == 0) bar_arrive(2, 256);
            if (wide1) {
                fx_send(rop + 64 + (lane & 7) * 4, s, ldsf(sb + SM_FXS), rop, 64);
                asm volatile("red.relaxed.gpu.global.add.u32 [%0], 1;" :: "l"(rop) : "memory");
            }
            __syncwarp();
            if (L.value == 1 && mlp == 96) { TDUMP(); asm volatile("exit;"); }
            uint4 wf[8], w2r[8];
            uint4 w;
            auto look = [&]() { asm volatile("ld.relaxed.gpu.global.v4.u32 {%0,%1,%2,%3}, [%4];" : "=r"(w.x), "=r"(w.y), "=r"(w.z), "=r"(w.w) : "l"(ap) : "memory"); };
            auto read_w1 = [&]() {
#pragma unroll
                for (int j = 0; j < 8; j++) wf[j] = ldsm_t(la + j * 256);
            };
            auto read_w2 = [&]() {
#pragma unroll
                for (int i = 0; i < 8; i++) w2r[i] = lds128(((i & 1) ? (w2a ^ 16) + 128 : w2a) + (i >> 1) * 5120);
            };
            if (L.value == 0) { fresh(); mlp_global(L); }
            mbar_wait(sb + SM_CBAR + CB_W1 * 8, L.value);
            if (L.value == 1) {
                if (W2PRE == 1) mbar_wait(sb + SM_CBAR + CB_W2 * 8, 1);
                read_w1();
                if (W2PRE == 1) read_w2();
            }
            while (clk() - c0 < AR1D);
            look();
            if (L.value == 0) { mlp_shared(L); read_w1(); bar_arrive(3, 256); }
            else if (W2PRE == 2) { mbar_wait(sb + SM_CBAR + CB_W2 * 8, 1); read_w2(); }
            TSTAMPL(28);
            {
                const float inv = shx(fx_inv(sc1) * (1.f / 128), 0), off = inv * -32.f;
                int it = 0;
#pragma unroll 1
                while (__any_sync(~0u, ~(w.x & w.y & w.z & w.w) & 32) & (++it < SPIN)) look();
                CSTAMP(8, w.w);
                xp = make_uint2(pack_bf((float)(int)w.x * inv + off, (float)(int)w.y * inv + off), pack_bf((float)(int)w.z * inv + off, (float)(int)w.w * inv + off));
                if (__any_sync(~0u, (w.x | w.y | w.z | w.w) & 64)) { xp.x = fx1_wide(ap, ldsf(sb + SM_FXS)); xp.y = fx1_wide(ap + 8, ldsf(sb + SM_FXS)); }
            }
            TSTAMP2(7);
            CSTAMP(9, xp.y);
            {
                bool ok = true;
                if (L.value == 0 || !W2PRE) ok = mbar_test(sb + SM_CBAR + CB_W2 * 8, L.value);
                const bool ev = L.value || !(g & 1), od = L.value || (g & 1);
                const uint32_t e0 = ev ? xp.x : ONES, e1 = ev ? xp.y : ONES, o0 = od ? xp.x : ONES, o1 = od ? xp.y : ONES;
                float d[8][4];
#pragma unroll
                for (int j = 0; j < 8; j++) { d[j][0] = d[j][1] = d[j][2] = d[j][3] = 0.f; mma(d[j], wf[j], (j & 1) ? o0 : e0, (j & 1) ? o1 : e1); }
                float ss = ln_part(xp, lane);
                ss += shx(ss, 8); ss += shx(ss, 4);
                float r[4], dd;
#pragma unroll
                for (int k = 0; k < 4; k += 1 + L.value) r[k] = d[0][k] + d[1][k ^ 1];
#pragma unroll
                for (int j = 1; j < 4; j++)
#pragma unroll
                    for (int k = 0; k < 4; k += 1 + L.value) add_if(t == j, r[k], d[2 * j][k], d[2 * j + 1][k ^ 1]);
                CSTAMP(10, __float_as_uint(r[2]));
                if (L.value) {
                    dd = ((t & 2) ? r[2] : r[0]) + shx((t & 2) ? r[0] : r[2], 2);
                    ss += shx(ss, 2);
                    dd += shx(dd, 1);
                } else {
                    const float a = ((t & 1) ? r[1] : r[0]) + shx((t & 1) ? r[0] : r[1], 1), b = ((t & 1) ? r[3] : r[2]) + shx((t & 1) ? r[2] : r[3], 1);
                    ss += shx(ss, 2);
                    dd = ((t & 2) ? b : a) + shx((t & 2) ? a : b, 2);
                }
                ss += shx(ss, 1);
                stsf(hpa, dd);
                stsf(hst, ss);
                CSTAMP(11, __float_as_uint(dd + ss));
                if (!ok) mbar_wait(sb + SM_CBAR + CB_W2 * 8, L.value);
            }
            TSTAMPL(25);
            bar_sync(1, 160);
            uint4 hp[5];
#pragma unroll
            for (int w = 0; w < 5; w++) hp[w] = lds128(hsa + w * 256);
            CSTAMP(12, hp[0].x);
            auto hs = [&](auto K) { return sum5(__uint_as_float(word<K.value>(hp[0])), __uint_as_float(word<K.value>(hp[1])), __uint_as_float(word<K.value>(hp[2])),
                                                __uint_as_float(word<K.value>(hp[3])), __uint_as_float(word<K.value>(hp[4]))); };
            const float mean = hs(IC<2>{}) * (1.f / D_MODEL);
            msq = hs(IC<3>{}) * (1.f / D_MODEL);
            if (L.value == 0) cs1 = hs(IC<1>{});
            float hv = hs(IC<0>{}) - mean * cs1;
            CSTAMP(13, __float_as_uint(hv));
            const float sc2 = fx2_scale(msq), lim = fx_inv(sc2) * FX2LIM;
            if (L.value == 0 || !W2PRE) read_w2();
            if (L.value == 0) bar_arrive(4, 256);
            hv = hv * ln_rstd(mean, msq) + b1v;
            CSTAMP(14, __float_as_uint(hv));
            hv = hv * rcp(1.f + ex2(hv * (-2.302208198f - 0.1029432397f * hv * hv)));
            const uint32_t hd = pack_bf(hv, hv);
            CSTAMP(15, hd);
            TSTAMPL(27);
            float ym[4][4];
#pragma unroll
            for (int i = 0; i < 2; i++) {
                ym[i][0] = ym[i][1] = ym[i][2] = ym[i][3] = 0.f;
                const float f = mlp < 64 ? 1.f / 64 : 0.f;
                ym[i + 2][0] = (bf_lo(xp.x) + bf_lo(b2v.x)) * f; ym[i + 2][1] = (bf_hi(xp.x) + bf_hi(b2v.x)) * f;
                ym[i + 2][2] = (bf_lo(xp.y) + bf_lo(b2v.y)) * f; ym[i + 2][3] = (bf_hi(xp.y) + bf_hi(b2v.y)) * f;
            }
#pragma unroll
            for (int i = 0; i < 4; i++) {
                const uint32_t hh = __shfl_sync(~0u, hd, 4 * i + t);
                mma(ym[(i & 1) * 2], w2r[2 * i], hh & maskA, hh & maskB);
                mma(ym[(i & 1) * 2 + 1], w2r[2 * i + 1], hh & maskA, hh & maskB);
            }
#pragma unroll
            for (int k = 0; k < 4; k++) { yf[k] = ym[0][k] + ym[2][k]; add_if(t & 2, yf[k], ym[1][k], ym[3][k]); }
            CSTAMP(16, __float_as_uint(yf[3]));
            yw[0] = fx2_pack(yf[0] * sc2 + FX2_ONE, yf[1] * sc2 + FX2_ONE); yw[1] = fx2_pack(yf[2] * sc2 + FX2_ONE, yf[3] * sc2 + FX2_ONE);
            wide = !(fmaxf(fmaxf(fabsf(yf[0]), fabsf(yf[1])), fmaxf(fabsf(yf[2]), fabsf(yf[3]))) < lim);
            if (wide) yw[0] = yw[1] = 0;
        };
        auto send_wide = [&]() {
#pragma unroll 1
            for (int k = 0; k < 4; k++, yf[0] = yf[1], yf[1] = yf[2], yf[2] = yf[3]) {
                const unsigned char* a = rap + (k >> 1) * 40 * ACC_PITCH;
                fx_send(a + 64 + (k & 1) * 32, yf[0], msq, a, 256);
            }
            yw[0] = yw[1] = 1;
        };

        pass1();
        o_setup(IC<0>{});
        out_proj(IC<0>{});
        uint32_t c0;
        if (warp < 5) {
            mlp_part(IC<0>{});
            if (mlp != 96) {
#pragma unroll
                for (int k = 0; k < 2; k++) asm volatile("red.relaxed.gpu.global.add.u64 [%0], %1;" :: "l"(rap + k * 40 * ACC_PITCH), "l"(yw[k]) : "memory");
            }
            c0 = clk();
            stsf(sb + SM_ML + (lane & 15) * 4, cs1);
            TSTAMP(8);
            if (__any_sync(~0u, wide && mlp != 96)) {
                if (wide) {
                    send_wide();
#pragma unroll
                    for (int k = 0; k < 2; k++) asm volatile("red.relaxed.gpu.global.add.u64 [%0], 1;" :: "l"(rap + k * 40 * ACC_PITCH) : "memory");
                }
                __syncwarp();
            }
            fresh(); calc_offsets();
            load_wq();
        } else {
            bar_sync(0, 256);
            if (warp == 5 && elect()) {
                asm volatile("fence.proxy.async.shared::cta;" ::: "memory");
                if (W1AT0 == 4) issue_w(IC<0>{}, 0);
                issue_w(IC<0>{}, 1);
            }
            __syncwarp();
            fresh(); calc_offsets();
            load_wq();
#pragma unroll 1
            for (int ph = 0; ph < 3; ph++) {
                bar_sync(ph + 2, 256);
                c0 = clk();
                if (ph == 2) {
                    msq = sum5(ldsf(sb + SM_PART + 12), ldsf(sb + SM_PART + 268), ldsf(sb + SM_PART + 524), ldsf(sb + SM_PART + 780), ldsf(sb + SM_PART + 1036)) * (1.f / D_MODEL);
                    bar_arrive(5, 256);
                }
                if (!(NOWIN >> ph & 1) && elect()) {
                    asm volatile("fence.proxy.async.shared::cta;" ::: "memory");
                    const uint32_t gap = ph == 0 ? WG1 : ph == 1 ? WG2 : WG3;
                    uint32_t c1 = c0 + (ph == 0 ? WD1 : ph == 1 ? WD2 : 0) + (warp - 5) * gap;
#pragma unroll 1
                    for (int k = warp + (ph == 0 ? -5 : ph == 1 && !(C96 && mlp == 96) ? 9 : 1); k < (ph == 0 ? 9 : ph == 1 ? 20 : C96 && mlp == 96 ? 0 : 14); k += 3, c1 += 3 * gap) {
                        const int i = ph == 0 && k >= 6 ? k + 23 : k;
                        const uint32_t bar = sb + SM_BAR + (i & 7) * 96 + 32 + (i & 24);
                        while ((int)(clk() - c1) < 0);
                        mbar_expect(bar, SUB);
                        tma_v(sb + SM_RING + i * SUB, tmk,
                              rowc * 3 + (i & 7) * 24 + ((UC<SCH.st[0].unit | SCH.st[1].unit << 8 | SCH.st[2].unit << 16 | SCH.st[3].unit << 24>::value >> (i & 24)) & 15) * 768, bar);
                    }
                }
                __syncwarp();
            }
            c0 += PCD;
        }
        {
            constexpr IC<1> L{};
            fresh();
            const int lz = lane;
            const unsigned char* xa[2];
#pragma unroll
            for (int i = 0; i < 2; i++) {
                const int col = xcol(2 * i, lz & 3), cw = j40 + (col >> 2);
                xa[i] = pin(accg + ACC_BYTES + ((cw >> 2) + (col & 2) * 20) * ACC_PITCH + (cw & 3) * 8);
            }
            const uint32_t pst = pin(prow + ((lz >> 2) * 8 + (lz & 1) * 4) * 4);
            stsf(sb + SM_MSQ, msq);
            const float inv = shx(fx2_inv(msq), 0);
            if (!NWQ1) rap = pin(accg + ACC_BYTES + (c4() >> 2) * ACC_PITCH + (c4() & 3) * 8);
            fresh();
            if (!NWQ1) { maskA = pin(maskA); maskB = pin(maskB); }
            u64 w[3];
            uint32_t x2[3];
            auto xat = [&](int i) { return ((i & 2) ? xa[1] : xa[0]) + (i & 1) * 4 * ACC_PITCH; };
            if (warp < 5) {
                bar_sync(5, 256);
                if (DPRE) { while ((int)(clk() - c0) < WD4 + warp * WG4); if (warp < DPRE) refill2(IC<3>{}); }
            }
            while ((int)(clk() - c0) < ARDELAY);
#pragma unroll
            for (int i = 0; i < 3; i++) w[i] = ld_rlx(xat(i));
            if (warp < 5 && !(NOWIN & 8) && elect()) {
                if (DPOST) while ((int)(clk() - c0) < ARDELAY + DPOST);
                if (warp >= DPRE) issue_v(IC<3>{}, 0);
                if (warp < 4 && !P2LATE) issue_v(IC<2>{}, 4);
            }
            __syncwarp();
            fx2_wait<3, true>(xat, w, sb + SM_MSQ, inv, x2);
            TSTAMP(9);
            q_proj(L, x2, pst);
            pass2();
            out_proj(L);
            if (warp >= 5) {
                bar_arrive(0, 256);
                if ((W1AT1 == 6 || W2AT1 == 6) && warp == 5 && elect()) { if (W1AT1 == 6) issue_w(L, 0); if (W2AT1 == 6) issue_w(L, 1); }
                TDUMP();
                return;
            }
            mlp_part(L);
            u64 old[2];
            auto add = [&]() {
#pragma unroll
                for (int k = 0; k < 2; k++) asm volatile("atom.relaxed.gpu.global.add.u64 %0, [%1], %2;" : "=l"(old[k]) : "l"(rap + k * 40 * ACC_PITCH), "l"(yw[k]) : "memory");
            };
            add();
            uint32_t* op = reinterpret_cast<uint32_t*>(P.out) + 2 * c4();
            if (wide) { send_wide(); add(); }
            TSTAMP(18);
            CSTAMP(17, hi32(yw[1]));
            const float inv2 = fx2_inv(msq);
            const uint32_t ep1 = lds32(sb + SM_EPOCH) + 1;
            CSTAMP(18, lo32(old[0]) ^ lo32(old[1]));
#pragma unroll
            for (int k = 0; k < 2; k++) {
                yw[k] += old[k];
                asm volatile("{\n.reg .pred p;\nsetp.eq.u32 p, %2, 96;\n@p st.global.u32 [%0], %1;\n}"
                             :: "l"(op + k), "r"(pack_bf(fx2_lo(yw[k], inv2), fx2_hi(yw[k], inv2))), "r"(lo32(yw[k]) & 511) : "memory");
            }
            if ((lo32(yw[0]) & 255) == 96 && tid == 0) g_epoch = ep1;
#pragma unroll
            for (int k = 0; k < 2; k++) if ((lo32(yw[k]) & 511) == 256 + 96) op[k] = fx2_wide(rap + k * 40 * ACC_PITCH, msq);
            TSTAMP(19);
            CSTAMP(19, lo32(yw[1]));
            TDUMP();
        }
    }
}

typedef CUresult (*EncodeFn)(CUtensorMap*, CUtensorMapDataType, cuuint32_t, void*, const cuuint64_t*, const cuuint64_t*, const cuuint32_t*,
                             const cuuint32_t*, CUtensorMapInterleave, CUtensorMapSwizzle, CUtensorMapL2promotion, CUtensorMapFloatOOBfill);

}

extern "C" void kernel_launch(void* const* d_in, const int* in_sizes, int n_in, void* d_out, int out_size) {
    (void)in_sizes; (void)n_in; (void)out_size;
    static EncodeFn enc = nullptr;
    if (!enc) {
        void* fn = nullptr;
        cudaDriverEntryPointQueryResult qr;
        cudaGetDriverEntryPoint("cuTensorMapEncodeTiled", &fn, cudaEnableDefault, &qr);
        enc = (EncodeFn)fn;
        cudaFuncSetAttribute(fused_kernel, cudaFuncAttributeMaxDynamicSharedMemorySize, SM_TOTAL);
    }
    Params P = {};
    auto map3 = [&](int m, int in, cuuint64_t d0, cuuint64_t d1, cuuint64_t d2, cuuint64_t s1, cuuint64_t s2, cuuint32_t b0, cuuint32_t b1, cuuint32_t b2,
                    CUtensorMapSwizzle sw, int promo) {
        const cuuint64_t dim[3] = {d0, d1, d2}, str[2] = {s1, s2};
        const cuuint32_t box[3] = {b0, b1, b2}, ones[3] = {1, 1, 1};
        enc(&P.tm[m], CU_TENSOR_MAP_DATA_TYPE_BFLOAT16, d2 ? 3 : 2, d_in[in], dim, str, box, ones, CU_TENSOR_MAP_INTERLEAVE_NONE, sw, (CUtensorMapL2promotion)promo,
            CU_TENSOR_MAP_FLOAT_OOB_FILL_NONE);
    };
    map3(TM_KH, 1, 64, 3, NHEAD * SK, 128, DH * 2, 64, 3, 32, CU_TENSOR_MAP_SWIZZLE_128B, 0);
    map3(TM_VH, 2, 64, 3, NHEAD * SK, 128, DH * 2, 64, 3, 32, CU_TENSOR_MAP_SWIZZLE_128B, 0);
    map3(TM_VP, 2, 64, 3, NHEAD * SK, 128, DH * 2, PFW, 3, 32, CU_TENSOR_MAP_SWIZZLE_NONE, 0);
    map3(TM_V, 2, 64, NHEAD * SK * 3, 0, 128, 0, 64, 24, 0, CU_TENSOR_MAP_SWIZZLE_128B, 0);
    map3(TM_WO, 4, 32, 20, NHEAD * DH, 64, D_MODEL * 2, 32, 1, DH, CU_TENSOR_MAP_SWIZZLE_64B, PROMOW);
    map3(TM_WOP, 4, 32, 20, NHEAD * DH, 64, D_MODEL * 2, PFW, 1, DH, CU_TENSOR_MAP_SWIZZLE_NONE, 0);
    map3(TM_WQ, 3, 64, NHEAD * 3, D_MODEL, 128, NHEAD * DH * 2, 64, 3, 32, CU_TENSOR_MAP_SWIZZLE_128B, 0);
    map3(TM_W1, 6, DFF, 128, 5, DFF * 2, DFF * 256, 16, 128, 5, CU_TENSOR_MAP_SWIZZLE_32B, PROMO1);
    map3(TM_W2, 8, 64, 10, DFF, 128, D_MODEL * 2, 64, 10, 16, CU_TENSOR_MAP_SWIZZLE_128B, 0);
    P.x = (const __nv_bfloat16*)d_in[0];
    P.k = (const __nv_bfloat16*)d_in[1];
    P.b1 = (const __nv_bfloat16*)d_in[7];
    P.b2 = (const __nv_bfloat16*)d_in[9];
    P.w1 = (const __nv_bfloat16*)d_in[6];
    P.out = (__nv_bfloat16*)d_out;
    for (int i = 0; i < 64; i++) P.tile[i] = make_uint4(SCH.tile[i][0], SCH.tile[i][1], SCH.tile[i][2], 0);
    fused_kernel<<<NCTA + 1, NTHR, SM_TOTAL, cudaStreamPerThread>>>(P);
}
```

```cpp
#include <cuda_runtime.h>
#include <cuda_bf16.h>
#include <cuda.h>
#include <stdint.h>

namespace {

constexpr int D_MODEL = 640, NHEAD = 32, SK = 32768, DH = 192, WIN = 4096, DFF = 1536;
constexpr int NCTA = 128, NTHR = 256;
constexpr int TILE = 64 * DH * 2;
constexpr int HALF = TILE / 2;
constexpr int SUB = 8 * DH * 2;
constexpr int SM_RING = 4 * TILE;
constexpr int SM_W2 = SM_RING + 20480, SM_W1 = SM_W2 + 20480;
constexpr int SM_WQR = 6 * TILE + HALF, SM_WQ = 7 * TILE;
constexpr int SM_PART = 9 * TILE;
constexpr int SM_EXC = SM_PART + 6144;
constexpr int SM_SC = SM_EXC + 1024;
constexpr int SM_BAR = SM_SC + 1024;
constexpr int SM_VEC = SM_BAR + 768;
constexpr int SM_CS = SM_VEC + 384;
constexpr int SM_FAC = SM_CS + 768;
constexpr int SM_ML = SM_FAC + 32;
constexpr int SM_B1 = SM_ML + 64;
constexpr int SM_STAT = SM_B1 + 64;
constexpr int NCB = 28;
constexpr int CB_WO = 18, CB_W1 = 23, CB_W2 = 24, CB_SNAP = 25, CB_REL = 26, CB_WQ = 27;
constexpr int SM_CBAR = SM_STAT + 40;
constexpr int SM_CNT = SM_CBAR + NCB * 8;
constexpr int SM_EPOCH = SM_CNT + NCB * 8;
constexpr int SM_FXS = SM_EPOCH + 4;
constexpr int SM_T0 = SM_FXS + 4;
constexpr int SM_MSQ = SM_T0 + 4;
constexpr int SM_M1 = SM_MSQ + 4;
constexpr int SM_TS = SM_M1 + 4;
constexpr int SM_TOTAL = 232448;
static_assert(SM_TS + 320 <= SM_TOTAL, "smem");
constexpr int NEXC = 16;

constexpr int SPIN = 1 << 20;
enum { TM_V = 0, TM_KH = 1, TM_VH = 2, TM_WO = 3, TM_VP = 4, TM_WOP = 5, TM_W1 = 6, TM_W2 = 7, TM_WQ = 8 };
constexpr uint32_t POL_NORMAL = 0x16F00000u, POL_FIRST = 0x12F00000u;

#define PACE 980
#define PACE0 1500
#define K0FIRST 1
#define NI1 6
#define ETRIG 0x54321000
#define LATEAT 5
#define HWAT 12
#define PFREE 66
#define W1AT0 3
#define W1AT1 3
#define AR1D 300
#define LAG0 12
#define NMMA 2
#define M1AT 1
#define M1P 3
#define NWO1 4
#define WG2 90
#define WG3 120
#define WD4 250
#define WG4 70
#define NWQ1 0
#define P4AT 0
#define P2LATE 0
#define RWAT 1
#define W2AT1 6
#define PCD 150
#define NOWIN 0
#define DPRE 0
#define DPOST 200
#define NIM 4
#define PACES 1300
#define JP2 54
#define PACE2 0
#define WD2 0
#define W2PRE 2
#define OPOLL1 2
#define W2ONE 1
#define W1ONE 1
#define FX1LIM 524288.f
#define C96 0
#define SNAPAT 1
#define DMASK 0x0
#define WOKEEP 0x1f
#define VORD2 0x7685943a2b1cd0efull
#define VTRIG 0xba73210
#define WOAT 13
#define PARKS 0x95
#define VSLOT 0x1087654321087654ull
#define OPOLL 2
#define S0EARLY 1
#define NPRE 2
#define ARDELAY 1000
#define QDELAY 0
#define CMAP 0
#define PFW 8u
#define PUBAT 28
#define HW0 30
#define HW1 31
#define FX2LIM 524288.f
#define PROMOW 2
#define PROMO1 0
#define WD1 300
#define WG1 140
#define WPOL POL_NORMAL

constexpr uint32_t G_A = 1u << 28, G_B = 1u << 29, G_C = 1u << 30;
__host__ __device__ constexpr int ring_hs(int j) { return (j + 4) % 5; }
__host__ __device__ constexpr uint32_t load_word(int j) {
    if (j >= 64) return (uint32_t)(j - 64) << 20 | (SM_RING + ring_hs(j) * HALF) | TM_WO << 8 | (CB_WO + j - 64) << 3 | 2 | !(WOKEEP >> (j - 64) & 1);
    const int e = j >> 1, isv = e >= 16, unit = e & 15;
    return (uint32_t)(unit * 256 + (j & 1) * 32) << 20 | (j < 8 ? j * HALF : SM_RING + ring_hs(j) * HALF) | (TM_KH + isv) << 8 | (j < 8 ? 10 + j : (j - 8) % 10) << 3 | 2
           | (!isv || (DMASK >> unit & 1));
}
__host__ __device__ constexpr int popc(int v) { return v ? (v & 1) + popc(v >> 1) : 0; }
constexpr int NPARK = popc(PARKS);
constexpr int SM_SNAP = SM_RING + ring_hs(12) * HALF, SM_CSP = SM_RING + ring_hs(11) * HALF;
struct Step { int unit, slot, par, next, mma0, nmma; };
struct Sched { uint32_t tile[64][3]; Step st[16]; };
constexpr Sched make_sched() {
    Sched s{};
    for (int j = 0; j < 64; j++) {
        const int e = j >> 1;
        const uint32_t d = load_word(j);
        uint32_t w = (uint32_t)(j < 8 ? 0 : (j - 8) / 10 & 1) << 31 | (e & 15) * 4 << 20 | ((d & 0x3f000) - (j & 1) * HALF) | (d & 0xf8);
        if (e == PUBAT || e == SNAPAT) w |= G_A;
        if (e == HW0 || e == 4) w |= G_B;
        if ((e >= LATEAT && e < LATEAT + 4) || e == HW1) w |= G_C;
        s.tile[j][0] = w;
    }
    for (int j = NI1; j < 69; j++) {
        if (j == 12) continue;
        const int at = j < 12 ? (ETRIG >> (4 * (j - 4)) & 15) : j - 5;
        s.tile[at][1] = load_word(j);
        s.tile[at][2] = j >= PFREE ? 0 : PACE0 + j * PACE / 2 + (j > JP2 ? (j - JP2) * PACE2 : 0);
    }
    int done = 0;
    for (int p = 0; p < 16; p++) {
        Step& c = s.st[p];
        c.unit = (int)(VORD2 >> (4 * p) & 15); c.slot = (int)(VSLOT >> (4 * p) & 15); c.par = p >= 9; c.next = -1;
        c.mma0 = done;
        if (p >= NPARK) { const int avail = p - done + (p >= LAG0); c.nmma = p == 15 ? 16 - done : (avail < NMMA ? avail : NMMA); done += c.nmma; }
    }
    for (int p = 9; p < 16; p++) s.st[VTRIG >> (4 * (p - 9)) & 15].next = p;
    return s;
}
constexpr Sched SCH = make_sched();
__host__ __device__ constexpr int kunit(int o) { return o < 5 ? o + 11 : o == 5 ? 10 : o - 6; }

template <int I> struct IC { static constexpr int value = I; };
template <uint32_t I> struct UC { static constexpr uint32_t value = I; };
template <int A, int B, class F> __device__ __forceinline__ void static_for(F&& f) {
    if constexpr (A < B) { f(IC<A>{}); static_for<A + 1, B>(f); }
}

struct Params {
    CUtensorMap tm[9];
    const __nv_bfloat16 *x, *k, *b1, *b2, *w1;
    __nv_bfloat16* out;
    uint4 tile[66];
};

typedef unsigned long long u64;
constexpr int ACC_PITCH = 256;
constexpr int ACC_BYTES = 80 * ACC_PITCH;
__device__ __align__(1024) unsigned char g_acc[4 * ACC_BYTES];
__device__ __align__(1024) u64 g_l0[NCTA][384];
__device__ __align__(1024) u64 g_ll[2][NCTA][256];
__device__ unsigned g_epoch;
__device__ __align__(128) unsigned g_zflag;
#define TSTAMP(i)
#define TSTAMP2(i)
#define TSTAMPL(i)
#define TDUMP()
#define CSTAMP(i, x)
#define TRACE(i)

__device__ __forceinline__ void mbar_wait(uint32_t bar, uint32_t parity) {
    asm volatile("{\n.reg .pred p, q;\n.reg .u32 n;\nmov.u32 n, 0;\n"
                 "LOOP:\nmbarrier.try_wait.parity.shared::cta.b64 p, [%0], %1;\n"
                 "add.u32 n, n, 1;\nsetp.lt.and.u32 q, n, 0x100000, !p;\n@q bra.uni LOOP;\n}"
                 :: "r"(bar), "r"(parity) : "memory");
}
__device__ __forceinline__ bool mbar_test(uint32_t bar, uint32_t parity) {
    uint32_t r;
    asm volatile("{\n.reg .pred p;\nmbarrier.test_wait.parity.shared::cta.b64 p, [%1], %2;\nselp.u32 %0, 1, 0, p;\n}" : "=r"(r) : "r"(bar), "r"(parity) : "memory");
    return __all_sync(~0u, r);
}
__device__ __forceinline__ bool elect() {
    uint32_t r;
    asm volatile("{\n.reg .pred p;\nelect.sync _|p, 0xffffffff;\nselp.u32 %0, 1, 0, p;\n}" : "=r"(r));
    return r != 0;
}
__device__ __forceinline__ void mbar_expect(uint32_t bar, uint32_t bytes) {
    asm volatile("mbarrier.arrive.expect_tx.shared::cta.b64 _, [%0], %1;" :: "r"(bar), "r"(bytes) : "memory");
}
__device__ __forceinline__ uint4 lds128(uint32_t a) {
    uint4 v; asm volatile("ld.shared.v4.u32 {%0,%1,%2,%3}, [%4];" : "=r"(v.x), "=r"(v.y), "=r"(v.z), "=r"(v.w) : "r"(a) : "memory"); return v;
}
__device__ __forceinline__ uint4 ldsm_t(uint32_t a) {
    uint4 v; asm volatile("ldmatrix.sync.aligned.m8n8.x4.trans.shared.b16 {%0,%1,%2,%3}, [%4];" : "=r"(v.x), "=r"(v.y), "=r"(v.z), "=r"(v.w) : "r"(a) : "memory"); return v;
}
__device__ __forceinline__ uint2 lds64(uint32_t a) {
    uint2 v; asm volatile("ld.shared.v2.u32 {%0,%1}, [%2];" : "=r"(v.x), "=r"(v.y) : "r"(a) : "memory"); return v;
}
__device__ __forceinline__ float2 lds64f(uint32_t a) { const uint2 v = lds64(a); return make_float2(__uint_as_float(v.x), __uint_as_float(v.y)); }
__device__ __forceinline__ uint32_t lds32(uint32_t a) {
    uint32_t v; asm volatile("ld.shared.u32 %0, [%1];" : "=r"(v) : "r"(a) : "memory"); return v;
}
__device__ __forceinline__ float ldsf(uint32_t a) { return __uint_as_float(lds32(a)); }
__device__ __forceinline__ void sts32(uint32_t a, uint32_t v) { asm volatile("st.shared.u32 [%0], %1;" :: "r"(a), "r"(v) : "memory"); }
__device__ __forceinline__ void stsf(uint32_t a, float v) { sts32(a, __float_as_uint(v)); }
__device__ __forceinline__ void sts16(uint32_t a, uint32_t v) { asm volatile("st.shared.u16 [%0], %1;" :: "r"(a), "h"((uint16_t)v) : "memory"); }
__device__ __forceinline__ void sts64(uint32_t a, uint32_t x, uint32_t y) { asm volatile("st.shared.v2.u32 [%0], {%1,%2};" :: "r"(a), "r"(x), "r"(y) : "memory"); }
__device__ __forceinline__ void sts64f(uint32_t a, float x, float y) { sts64(a, __float_as_uint(x), __float_as_uint(y)); }
__device__ __forceinline__ void sts128f(uint32_t a, float x, float y, float z, float w) {
    asm volatile("st.shared.v4.f32 [%0], {%1,%2,%3,%4};" :: "r"(a), "f"(x), "f"(y), "f"(z), "f"(w) : "memory");
}
__device__ __forceinline__ void mma(float (&c)[4], const uint4& a, uint32_t b0, uint32_t b1) {
    asm volatile("mma.sync.aligned.m16n8k16.row.col.f32.bf16.bf16.f32 {%0,%1,%2,%3}, {%4,%5,%6,%7}, {%8,%9}, {%0,%1,%2,%3};"
                 : "+f"(c[0]), "+f"(c[1]), "+f"(c[2]), "+f"(c[3]) : "r"(a.x), "r"(a.y), "r"(a.z), "r"(a.w), "r"(b0), "r"(b1));
}
__device__ __forceinline__ u64 ld_rlx(const void* p) {
    u64 a; asm volatile("ld.relaxed.gpu.global.u64 %0, [%1];" : "=l"(a) : "l"(p) : "memory"); return a;
}
__device__ __forceinline__ void ld_rlx2(const void* p, u64& a, u64& b) {
    asm volatile("ld.relaxed.gpu.global.v2.u64 {%0,%1}, [%2];" : "=l"(a), "=l"(b) : "l"(p) : "memory");
}
__device__ __forceinline__ void st_rlx(void* p, u64 a) { asm volatile("st.relaxed.gpu.global.u64 [%0], %1;" :: "l"(p), "l"(a) : "memory"); }
__device__ __forceinline__ u64 ll_pack(float v, uint32_t tag) { return ((u64)tag << 32) | __float_as_uint(v); }
__device__ __forceinline__ float ll_val(u64 w) { return __uint_as_float((uint32_t)w); }
__device__ __forceinline__ uint32_t ll_tag(u64 w) { return (uint32_t)(w >> 32); }
__device__ __forceinline__ float bf_lo(uint32_t u) { return __uint_as_float(u << 16); }
__device__ __forceinline__ float bf_hi(uint32_t u) { return __uint_as_float(u & 0xffff0000u); }
__device__ __forceinline__ uint32_t pack_bf(float lo, float hi) {
    uint32_t r; asm("cvt.rn.bf16x2.f32 %0, %1, %2;" : "=r"(r) : "f"(hi), "f"(lo)); return r;
}
__device__ __forceinline__ float ex2(float v) { float r; asm("ex2.approx.ftz.f32 %0, %1;" : "=f"(r) : "f"(v)); return r; }
__device__ __forceinline__ float rcp(float v) { float r; asm("rcp.approx.ftz.f32 %0, %1;" : "=f"(r) : "f"(v)); return r; }
__device__ __forceinline__ float rsq(float v) { float r; asm("rsqrt.approx.ftz.f32 %0, %1;" : "=f"(r) : "f"(v)); return r; }
__device__ __forceinline__ void bar_sync(int id, int n) { asm volatile("bar.sync %0, %1;" :: "r"(id), "r"(n) : "memory"); }
__device__ __forceinline__ uint32_t clk() { uint32_t c; asm volatile("mov.u32 %0, %clock;" : "=r"(c)); return c; }
__device__ __forceinline__ uint32_t pin(uint32_t v) { return __shfl_xor_sync(~0u, v, 0); }
__device__ __forceinline__ float shx(float v, int o) { return __shfl_xor_sync(~0u, v, o); }

__device__ __forceinline__ u64 fx_pack(float v, float scale) { return ((u64)__float2ll_rn(v * scale) & ~255ull) | 1ull; }
__device__ __forceinline__ float fx_scale(float meansq) {
    const int e = max(((int)(__float_as_uint(meansq) >> 23) - 127) >> 1, -6);
    return __uint_as_float((uint32_t)(127 + 32 - e) << 23);
}
__device__ __forceinline__ float fx_inv(float scale) { return __uint_as_float((254u << 23) - __float_as_uint(scale)); }
__device__ __forceinline__ uint32_t lo32(u64 w) { uint32_t l; asm("mov.b64 {%0, _}, %1;" : "=r"(l) : "l"(w)); return l; }
__device__ __forceinline__ int hi32(u64 w) { int h; asm("mov.b64 {_, %0}, %1;" : "=r"(h) : "l"(w)); return h; }
__device__ __forceinline__ float fx_val(u64 w) { return (float)hi32(w) * 4294967296.f + (float)lo32(w); }
constexpr float FX2_ONE = 12582912.f;
__device__ __forceinline__ float fx2_scale(float meansq) { return __uint_as_float((uint32_t)(127 + 16 - max(((int)(__float_as_uint(meansq) >> 23) - 127) >> 1, -100)) << 23); }
__device__ __forceinline__ u64 fx2_pack(float a, float b) {
    const uint32_t lo = __float_as_uint(a) * 512u + (1u - 0x4b400000u * 512u);
    return lo | (u64)(__float_as_uint(b) * 16u - 0x4b400000u * 16u + (uint32_t)((int)lo >> 31)) << 32;
}
__device__ __forceinline__ float fx2_lo(u64 w, float inv) { return (float)(int)(__funnelshift_r(lo32(w), hi32(w), 4) & ~31u) * (inv * 0.5f); }
__device__ __forceinline__ float fx2_hi(u64 w, float inv) { return (float)((hi32(w) + 8) & ~15) * inv; }
__device__ __forceinline__ float fx2_inv(float meansq) { return fx_inv(fx2_scale(meansq)) * 0.0625f; }
__device__ __noinline__ uint32_t fx2_wide(const unsigned char* a, float meansq) {
    __threadfence();
    const u64 w = ld_rlx(a);
    const float inv = fx_inv(fx_scale(meansq));
    return pack_bf(fx2_lo(w, fx2_inv(meansq)) + fx_val(ld_rlx(a + 64)) * inv, fx2_hi(w, fx2_inv(meansq)) + fx_val(ld_rlx(a + 96)) * inv);
}
__device__ __noinline__ uint32_t fx1_wide(const unsigned char* a, float meansq) {
    __threadfence();
    const u64 w = ld_rlx(a);
    const unsigned char* b = a + 64 + (reinterpret_cast<u64>(a) & 31);
    const float inv = fx_inv(fx_scale(meansq)), inv1 = fx2_inv(meansq) * 0.5f;
    return pack_bf((float)(int)(lo32(w) & ~127u) * inv1 + fx_val(ld_rlx(b)) * inv, (float)(hi32(w) & ~127) * inv1 + fx_val(ld_rlx(b + 8)) * inv);
}
__device__ __noinline__ void fx_send(const unsigned char* wide, float v, float meansq, const unsigned char* a, uint32_t flag) {
    asm volatile("red.relaxed.gpu.global.add.u64 [%0], %1;" :: "l"(wide), "l"(fx_pack(v, fx_scale(meansq))) : "memory");
    __threadfence();
    asm volatile("red.relaxed.gpu.global.or.b32 [%0], %1;" :: "l"(a), "r"(flag) : "memory");
}
template <int N, bool LOOK, class A> __device__ __forceinline__ void fx2_wait(A a, u64 (&w)[N], uint32_t msqa, float inv, uint32_t (&x)[N]) {
    int it = 0;
    uint32_t miss = lds32(msqa + 4);
    do {
        if (__all_sync(~0u, !(miss & 96))) {
            const float meansq = ldsf(msqa);
#pragma unroll
            for (int i = 0; i < N; i++) x[i] = fx2_wide(a(i), meansq);
            return;
        }
        if (!LOOK || it) {
#pragma unroll
            for (int i = 0; i < N; i++) w[i] = ld_rlx(a(i));
        }
        uint32_t all = lo32(w[0]), any = all;
#pragma unroll
        for (int i = 1; i < N; i++) { all &= lo32(w[i]); any |= lo32(w[i]); }
        miss = (~all & 96) | (any & 256);
    } while (__any_sync(~0u, miss) & (++it < SPIN));
#pragma unroll
    for (int i = 0; i < N; i++) x[i] = pack_bf(fx2_lo(w[i], inv), fx2_hi(w[i], inv));
}
__device__ __forceinline__ void st_rlx_if(bool p, void* a, u64 v) {
    asm volatile("{\n.reg .pred p;\nsetp.ne.u32 p, %2, 0;\n@p st.relaxed.gpu.global.u64 [%0], %1;\n}" :: "l"(a), "l"(v), "r"((uint32_t)p) : "memory");
}
__device__ __forceinline__ void sts128f(uint32_t a, const float (&v)[4]) { sts128f(a, v[0], v[1], v[2], v[3]); }
__device__ __forceinline__ void bar_arrive(int id, int n) { asm volatile("bar.arrive %0, %1;" :: "r"(id), "r"(n) : "memory"); }
template <class T> __device__ __forceinline__ T* pin(T* p) { return reinterpret_cast<T*>(__shfl_xor_sync(~0u, (u64)p, 0)); }

__device__ __forceinline__ void tma3(uint32_t dst, const CUtensorMap* tm, int c1, int c2, uint32_t bar, uint32_t pol) {
    asm volatile("cp.async.bulk.tensor.3d.shared::cluster.global.mbarrier::complete_tx::bytes.L2::cache_hint [%0], [%1, {%2, %3, %4}], [%5], %6;"
                 :: "r"(dst), "l"(tm), "r"(0), "r"(c1), "r"(c2), "r"(bar), "l"((u64)pol << 32) : "memory");
}
__device__ __forceinline__ void tma_v(uint32_t dst, const CUtensorMap* tm, int line, uint32_t bar) {
    asm volatile("cp.async.bulk.tensor.2d.shared::cluster.global.mbarrier::complete_tx::bytes.L2::cache_hint [%0], [%1, {%2, %3}], [%4], %5;"
                 :: "r"(dst), "l"(tm), "r"(0), "r"(line), "r"(bar), "l"((u64)POL_FIRST << 32) : "memory");
}
__device__ __forceinline__ void tma3_pf(const CUtensorMap* tm, int c1, int c2, uint32_t pol) {
    asm volatile("cp.async.bulk.prefetch.tensor.3d.L2.global.tile.L2::cache_hint [%0, {%1, %2, %3}], %4;"
                 :: "l"(tm), "r"(0), "r"(c1), "r"(c2), "l"((u64)pol << 32) : "memory");
}
__device__ __forceinline__ void issue_half(uint32_t d, uint32_t sb, int rowc, int cta, const CUtensorMap* tm0) {
    const uint32_t bar = sb + SM_CBAR + (d & 0xf8);
    const CUtensorMap* tm = tm0 + ((d >> 8) & 3);
    const bool wo = (d & 0x300) == TM_WO << 8;
    const int c1 = wo ? (cta & 3) + 4 * (d >> 20) : 0, c2 = wo ? (cta >> 2) * DH : rowc + (d >> 20);
    mbar_expect(bar, HALF);
    tma3(sb + (d & 0x3f000), tm, c1, c2, bar, POL_FIRST);
    if (!(d & 1)) tma3_pf(tm + 2, c1, c2, POL_NORMAL);
}
__device__ __forceinline__ uint32_t cnt_inc(uint32_t a, uint32_t last) {
    uint32_t old; asm volatile("atom.relaxed.cta.shared.inc.u32 %0, [%1], %2;" : "=r"(old) : "r"(a), "r"(last) : "memory"); return old;
}
__device__ __forceinline__ void wait_until(uint32_t due) {
#pragma unroll 1
    for (int it = 0; it < 4096; it++) { uint32_t now; asm volatile("mov.u32 %0, %globaltimer_lo;" : "=r"(now)); if ((int)(now - due) >= 0) break; }
}
__device__ __forceinline__ uint32_t bf2_mul(uint32_t a, uint32_t b) { uint32_t r; asm("mul.rn.bf16x2 %0, %1, %2;" : "=r"(r) : "r"(a), "r"(b)); return r; }
__device__ __forceinline__ uint32_t bf2_fma(uint32_t a, uint32_t b, uint32_t c) { uint32_t r; asm("fma.rn.bf16x2 %0, %1, %2, %3;" : "=r"(r) : "r"(a), "r"(b), "r"(c)); return r; }
__device__ __forceinline__ uint32_t bf2_amax(uint32_t a, uint32_t b) { uint32_t r; asm("max.NaN.xorsign.abs.bf16x2 %0, %1, %2;" : "=r"(r) : "r"(a), "r"(b)); return r; }
__device__ __forceinline__ uint4 k_unpack(uint32_t l0, uint32_t l1, uint32_t h, uint32_t m1) {
    const uint32_t ha = h & 0x87878787u, hc = ha * m1 + h, hb = __funnelshift_l(hc, hc, 4);
    return make_uint4(__byte_perm(l0, ha, 0x5140), __byte_perm(l0, ha, 0x7362), __byte_perm(l1, hb, 0x5140), __byte_perm(l1, hb, 0x7362));
}
#define KR4(u, i) "+r"(kr[u][i].x), "+r"(kr[u][i].y), "+r"(kr[u][i].z), "+r"(kr[u][i].w)
#define KR6(u) KR4(u, 0), KR4(u, 1), KR4(u, 2), KR4(u, 3), KR4(u, 4), KR4(u, 5)
__device__ __forceinline__ void k_keep(uint4 (&kr)[8][6], const uint32_t (&c)[18], int e, uint32_t a) {
    asm volatile("{\nKT: .branchtargets K0, K1, K2, K3, K4, K5, K6, K7, K8, K9, K10, K11, K12, K13, K14, K15;\nbrx.idx.uni %210, KT;\n"
                 "K0: mov.b32 %12, %192; mov.b32 %13, %193; mov.b32 %14, %194; mov.b32 %15, %195; mov.b32 %16, %196; mov.b32 %17, %197; mov.b32 %18, %198; mov.b32 %19, %199; mov.b32 %20, %200; mov.b32 %21, %201; mov.b32 %22, %202; mov.b32 %23, %203; mov.b32 %24, %204; mov.b32 %25, %205; mov.b32 %26, %206; mov.b32 %27, %207; mov.b32 %28, %208; mov.b32 %29, %209; bra.uni KE;\n"
                 "K1: mov.b32 %30, %192; mov.b32 %31, %193; mov.b32 %32, %194; mov.b32 %33, %195; mov.b32 %34, %196; mov.b32 %35, %197; mov.b32 %36, %198; mov.b32 %37, %199; mov.b32 %38, %200; mov.b32 %39, %201; mov.b32 %40, %202; mov.b32 %41, %203; mov.b32 %42, %204; mov.b32 %43, %205; mov.b32 %44, %206; mov.b32 %45, %207; mov.b32 %46, %208; mov.b32 %47, %209; bra.uni KE;\n"
                 "K2: mov.b32 %48, %192; mov.b32 %49, %193; mov.b32 %50, %194; mov.b32 %51, %195; mov.b32 %52, %196; mov.b32 %53, %197; mov.b32 %54, %198; mov.b32 %55, %199; mov.b32 %56, %200; mov.b32 %57, %201; mov.b32 %58, %202; mov.b32 %59, %203; mov.b32 %60, %204; mov.b32 %61, %205; mov.b32 %62, %206; mov.b32 %63, %207; mov.b32 %64, %208; mov.b32 %65, %209; bra.uni KE;\n"
                 "K3: mov.b32 %66, %192; mov.b32 %67, %193; mov.b32 %68, %194; mov.b32 %69, %195; mov.b32 %70, %196; mov.b32 %71, %197; mov.b32 %72, %198; mov.b32 %73, %199; mov.b32 %74, %200; mov.b32 %75, %201; mov.b32 %76, %202; mov.b32 %77, %203; mov.b32 %78, %204; mov.b32 %79, %205; mov.b32 %80, %206; mov.b32 %81, %207; mov.b32 %82, %208; mov.b32 %83, %209; bra.uni KE;\n"
                 "K4: mov.b32 %84, %192; mov.b32 %85, %193; mov.b32 %86, %194; mov.b32 %87, %195; mov.b32 %88, %196; mov.b32 %89, %197; mov.b32 %90, %198; mov.b32 %91, %199; mov.b32 %92, %200; mov.b32 %93, %201; mov.b32 %94, %202; mov.b32 %95, %203; mov.b32 %96, %204; mov.b32 %97, %205; mov.b32 %98, %206; mov.b32 %99, %207; mov.b32 %100, %208; mov.b32 %101, %209; bra.uni KE;\n"
                 "K5: mov.b32 %102, %192; mov.b32 %103, %193; mov.b32 %104, %194; mov.b32 %105, %195; mov.b32 %106, %196; mov.b32 %107, %197; mov.b32 %108, %198; mov.b32 %109, %199; mov.b32 %110, %200; mov.b32 %111, %201; mov.b32 %112, %202; mov.b32 %113, %203; mov.b32 %114, %204; mov.b32 %115, %205; mov.b32 %116, %206; mov.b32 %117, %207; mov.b32 %118, %208; mov.b32 %119, %209; bra.uni KE;\n"
                 "K6: mov.b32 %120, %192; mov.b32 %121, %193; mov.b32 %122, %194; mov.b32 %123, %195; mov.b32 %124, %196; mov.b32 %125, %197; mov.b32 %126, %198; mov.b32 %127, %199; mov.b32 %128, %200; mov.b32 %129, %201; mov.b32 %130, %202; mov.b32 %131, %203; mov.b32 %132, %204; mov.b32 %133, %205; mov.b32 %134, %206; mov.b32 %135, %207; mov.b32 %136, %208; mov.b32 %137, %209; bra.uni KE;\n"
                 "K7: mov.b32 %138, %192; mov.b32 %139, %193; mov.b32 %140, %194; mov.b32 %141, %195; mov.b32 %142, %196; mov.b32 %143, %197; mov.b32 %144, %198; mov.b32 %145, %199; mov.b32 %146, %200; mov.b32 %147, %201; mov.b32 %148, %202; mov.b32 %149, %203; mov.b32 %150, %204; mov.b32 %151, %205; mov.b32 %152, %206; mov.b32 %153, %207; mov.b32 %154, %208; mov.b32 %155, %209; bra.uni KE;\n"
                 "K8: mov.b32 %156, %192; mov.b32 %157, %193; mov.b32 %158, %194; mov.b32 %159, %195; mov.b32 %160, %196; mov.b32 %161, %197; mov.b32 %162, %198; mov.b32 %163, %199; mov.b32 %164, %200; mov.b32 %165, %201; mov.b32 %166, %202; mov.b32 %167, %203; mov.b32 %168, %204; mov.b32 %169, %205; mov.b32 %170, %206; mov.b32 %171, %207; mov.b32 %172, %208; mov.b32 %173, %209; bra.uni KE;\n"
                 "K9: mov.b32 %174, %192; mov.b32 %175, %193; mov.b32 %176, %194; mov.b32 %177, %195; mov.b32 %178, %196; mov.b32 %179, %197; mov.b32 %180, %198; mov.b32 %181, %199; mov.b32 %182, %200; mov.b32 %183, %201; mov.b32 %184, %202; mov.b32 %185, %203; mov.b32 %186, %204; mov.b32 %187, %205; mov.b32 %188, %206; mov.b32 %189, %207; mov.b32 %190, %208; mov.b32 %191, %209; bra.uni KE;\n"
                 "K10: st.shared.v2.b32 [%211+75784], {%192, %193}; st.shared.v2.b32 [%211+76288], {%194, %195}; st.shared.v2.b32 [%211+76296], {%196, %197}; mov.b32 %0, %198; mov.b32 %1, %199; mov.b32 %2, %200; mov.b32 %3, %201; mov.b32 %4, %202; mov.b32 %5, %203; mov.b32 %6, %204; mov.b32 %7, %205; mov.b32 %8, %206; mov.b32 %9, %207; mov.b32 %10, %208; mov.b32 %11, %209; bra.uni KE;\n"
                 "K11: st.shared.v2.b32 [%211+0], {%192, %193}; st.shared.v2.b32 [%211+8], {%194, %195}; st.shared.v2.b32 [%211+512], {%196, %197}; st.shared.v2.b32 [%211+520], {%198, %199}; st.shared.v2.b32 [%211+1024], {%200, %201}; st.shared.v2.b32 [%211+1032], {%202, %203}; st.shared.v2.b32 [%211+1536], {%204, %205}; st.shared.v2.b32 [%211+1544], {%206, %207}; st.shared.v2.b32 [%211+2048], {%208, %209}; bra.uni KE;\n"
                 "K12: st.shared.v2.b32 [%211+2056], {%192, %193}; st.shared.v2.b32 [%211+2560], {%194, %195}; st.shared.v2.b32 [%211+2568], {%196, %197}; st.shared.v2.b32 [%211+24576], {%198, %199}; st.shared.v2.b32 [%211+24584], {%200, %201}; st.shared.v2.b32 [%211+25088], {%202, %203}; st.shared.v2.b32 [%211+25096], {%204, %205}; st.shared.v2.b32 [%211+25600], {%206, %207}; st.shared.v2.b32 [%211+25608], {%208, %209}; bra.uni KE;\n"
                 "K13: st.shared.v2.b32 [%211+26112], {%192, %193}; st.shared.v2.b32 [%211+26120], {%194, %195}; st.shared.v2.b32 [%211+26624], {%196, %197}; st.shared.v2.b32 [%211+26632], {%198, %199}; st.shared.v2.b32 [%211+27136], {%200, %201}; st.shared.v2.b32 [%211+27144], {%202, %203}; st.shared.v2.b32 [%211+49152], {%204, %205}; st.shared.v2.b32 [%211+49160], {%206, %207}; st.shared.v2.b32 [%211+49664], {%208, %209}; bra.uni KE;\n"
                 "K14: st.shared.v2.b32 [%211+49672], {%192, %193}; st.shared.v2.b32 [%211+50176], {%194, %195}; st.shared.v2.b32 [%211+50184], {%196, %197}; st.shared.v2.b32 [%211+50688], {%198, %199}; st.shared.v2.b32 [%211+50696], {%200, %201}; st.shared.v2.b32 [%211+51200], {%202, %203}; st.shared.v2.b32 [%211+51208], {%204, %205}; st.shared.v2.b32 [%211+51712], {%206, %207}; st.shared.v2.b32 [%211+51720], {%208, %209}; bra.uni KE;\n"
                 "K15: st.shared.v2.b32 [%211+73728], {%192, %193}; st.shared.v2.b32 [%211+73736], {%194, %195}; st.shared.v2.b32 [%211+74240], {%196, %197}; st.shared.v2.b32 [%211+74248], {%198, %199}; st.shared.v2.b32 [%211+74752], {%200, %201}; st.shared.v2.b32 [%211+74760], {%202, %203}; st.shared.v2.b32 [%211+75264], {%204, %205}; st.shared.v2.b32 [%211+75272], {%206, %207}; st.shared.v2.b32 [%211+75776], {%208, %209}; \nKE:\n}"
                 : KR6(0), KR6(1), KR6(2), KR6(3), KR6(4), KR6(5), KR6(6), KR6(7)
                 : "r"(c[0]), "r"(c[1]), "r"(c[2]), "r"(c[3]), "r"(c[4]), "r"(c[5]), "r"(c[6]), "r"(c[7]), "r"(c[8]), "r"(c[9]), "r"(c[10]), "r"(c[11]), "r"(c[12]), "r"(c[13]), "r"(c[14]), "r"(c[15]), "r"(c[16]), "r"(c[17]), "r"(e), "r"(a) : "memory");
}
__device__ __forceinline__ uint32_t smem_base() { extern __shared__ __align__(1024) unsigned char smem[]; return (uint32_t)__cvta_generic_to_shared(smem); }
__device__ __forceinline__ void k_rare(uint4 v0, uint4 v1, uint4 v2, uint4 v3, uint4 v4, uint4 v5, uint32_t odd, int e, int warp, int lane) {
    const uint32_t sb = smem_base(), g = lane >> 2, t = lane & 3, st = sb + SM_BAR + warp * 96 + 80;
    uint32_t lt; asm volatile("mov.u32 %0, %lanemask_lt;" : "=r"(lt));
    const uint4 v[6] = {v0, v1, v2, v3, v4, v5};
    odd <<= 6;
#pragma unroll
    for (int i = 0; i < 6; i++) if (v[i].x | v[i].y | v[i].z | v[i].w) odd |= 1u << i;
    odd = __reduce_or_sync(~0u, odd);
    uint32_t n = odd >= 64 ? NEXC + 1 : __shfl_sync(~0u, lds32(st), 0);
#pragma unroll 1
    for (; odd && n <= NEXC; odd &= odd - 1) {
        const int i = __ffs(odd) - 1;
#pragma unroll
        for (int k = 1; k < 6; k++) if (i == k) v0 = v[k];
#pragma unroll 1
        for (int k = 0; k < 4; k++, v0.x = v0.y, v0.y = v0.z, v0.z = v0.w) {
            const uint32_t who = __ballot_sync(~0u, v0.x), at = n + __popc(who & lt);
            sts64(v0.x && at < NEXC ? sb + SM_EXC + warp * 128 + at * 8 : st + 8, v0.x, (e * 32 + g * 4) << 16 | (((k & 1) * 4 + t) * 48 + i * 8 + (k >> 1) * 4));
            n += __popc(who);
        }
    }
    const uint32_t bad = lds32(st + 4);
    __syncwarp();
    if (n <= NEXC) sts32(st, n);
    else {
        sts32(st + 4, bad | 1u << e);
        asm volatile("st.shared.u8 [%0], %1;" :: "r"(sb + SM_SC + warp * 128 + g * 16 + (e & 3) * 4 + (e >> 2)), "r"(0) : "memory");
    }
    __syncwarp();
}
template <int K> __device__ __forceinline__ uint32_t& word(uint4& v) { if constexpr (K == 0) return v.x; else if constexpr (K == 1) return v.y; else if constexpr (K == 2) return v.z; else return v.w; }
__device__ __forceinline__ void add_if(bool p, float& d, float a, float b) {
    asm volatile("{\n.reg .pred p;\nsetp.ne.u32 p, %3, 0;\n@p add.f32 %0, %1, %2;\n}" : "+f"(d) : "f"(a), "f"(b), "r"((uint32_t)p));
}
__device__ __forceinline__ float warp_max(float v) {
#pragma unroll
    for (int o = 16; o; o >>= 1) v = fmaxf(v, shx(v, o));
    return v;
}
__device__ __forceinline__ float warp_sum(float v) {
#pragma unroll
    for (int o = 16; o; o >>= 1) v += shx(v, o);
    return v;
}
template <int PITCH> __device__ __forceinline__ void ll_look(const u64* buf, u64 (&w)[4]) {
#pragma unroll
    for (int i = 0; i < 4; i++) w[i] = ld_rlx(buf + i * PITCH);
}
template <int PITCH> __device__ __forceinline__ float ll_gather(const u64* buf, uint32_t tag, u64 (&w)[4]) {
    auto miss = [&]() { return __any_sync(~0u, ((ll_tag(w[0]) ^ tag) | (ll_tag(w[1]) ^ tag)) | ((ll_tag(w[2]) ^ tag) | (ll_tag(w[3]) ^ tag))); };
    int it = 0;
    goto check;
again:
    ll_look<PITCH>(buf, w);
check:
    if (miss() & (++it < SPIN)) goto again;
    return (ll_val(w[0]) + ll_val(w[1])) + (ll_val(w[2]) + ll_val(w[3]));
}
__device__ __forceinline__ float sum8(uint32_t a, int pitch) {
    float s[8];
#pragma unroll
    for (int w = 0; w < 8; w++) s[w] = ldsf(a + w * pitch);
    return ((s[0] + s[1]) + (s[2] + s[3])) + ((s[4] + s[5]) + (s[6] + s[7]));
}
__device__ __forceinline__ float sum5(float a, float b, float c, float d, float e) { return ((a + b) + (c + d)) + e; }
__device__ __forceinline__ float ln_part(uint2 xp, int lane) {
    const float x0 = bf_lo(xp.x), x1 = bf_hi(xp.x), x2 = bf_lo(xp.y), x3 = bf_hi(xp.y);
    const float s1 = (x0 + x1) + (x2 + x3), s2 = (x0 * x0 + x1 * x1) + (x2 * x2 + x3 * x3);
    return ((lane & 16) ? s2 : s1) + shx((lane & 16) ? s1 : s2, 16);
}
__device__ __forceinline__ float ln_rstd(float mean, float msq) { return rsq(fmaxf(msq - mean * mean, 0.f) + 1e-5f); }
__device__ __forceinline__ float score(const uint4 (&v)[6], const uint4 (&qf)[3]) {
    float d[2][4];
#pragma unroll
    for (int j = 0; j < 2; j++) d[j][0] = d[j][1] = d[j][2] = d[j][3] = 0.f;
#pragma unroll
    for (int i = 0; i < 3; i++) { mma(d[0], v[2 * i], qf[i].x, qf[i].y); mma(d[1], v[2 * i + 1], qf[i].z, qf[i].w); }
    return (d[0][0] + d[0][3]) + (d[1][0] + d[1][3]);
}
__device__ __forceinline__ float k_side(uint32_t sb, uint2 x) {
    const uint32_t qq = lds32(sb + SM_VEC + (x.y & 0xffff));
    return (bf_lo(x.x) * bf_lo(qq) + bf_hi(x.x) * bf_hi(qq)) * 0x1p-64f;
}
__device__ __forceinline__ void k_fix(const __nv_bfloat16* k, uint32_t bad, int warp, int lane) {
    const uint32_t sb = smem_base(), g = lane >> 2, sa = sb + SM_PART + warp * 768 + 256;
    const uint2 x = lds64(sb + SM_EXC + warp * 128 + (lane & 15) * 8);
    if ((int)x.y >= 0x40000000 && lane < 16) asm volatile("red.shared.add.f32 [%0], %1;" :: "r"(sa + ((x.y >> 16) & 511)), "f"(k_side(sb, x)) : "memory");
    __syncwarp();
#pragma unroll 1
    for (bad &= 0xffff; bad; bad &= bad - 1) {
        const int e = __ffs(bad) - 1;
        const __nv_bfloat16* kp = k + (e * 256 + (g >> 1) + 4 * (g & 1)) * DH + (lane & 3) * 8;
        uint4 v[6], qf[3];
#pragma unroll
        for (int i = 0; i < 6; i++) v[i] = *reinterpret_cast<const uint4*>(kp + i * 32);
#pragma unroll
        for (int i = 0; i < 3; i++) qf[i] = lds128(sb + SM_VEC + (lane & 7) * 48 + i * 16);
        stsf(sa + e * 32 + g * 4, score(v, qf) * 0x1p-64f);
    }
    __syncwarp();
}
constexpr float CS = 0.07216878364870322f * 1.4426950408889634f;
__device__ __forceinline__ void head_weight(const u64* a, u64 pm, u64 pl, int layer, int lane) {
    const uint32_t sb = smem_base(), tag = lds32(sb + SM_EPOCH) * 4 + 2 + 2 * layer;
#pragma unroll 1
    for (int it = 0; it < SPIN; it++) {
        if (__all_sync(~0u, ll_tag(pm) == tag && ll_tag(pl) == tag)) break;
        ld_rlx2(a, pm, pl);
    }
    const float f = ex2((ll_val(pm) - warp_max(ll_val(pm))) * CS);
    const float w = f * rcp(warp_sum(f * ll_val(pl)));
    if (lane < 8) stsf(sb + SM_FAC + lane * 4, w);
}
constexpr uint32_t ONES = 0x3f803f80u;

__global__ void __launch_bounds__(NTHR, 1) fused_kernel(const __grid_constant__ Params P) {
    const uint32_t sb = smem_base();
    const int bx = blockIdx.x;
    const int cta0 = bx >= NCTA || CMAP == 0 ? bx : CMAP == 4 ? (((bx >> 1) & 7) + (bx >> 5) * 8) * 4 + ((bx >> 4) & 1) * 2 + (bx & 1)
                   : (((bx >> 1) & 15) + (bx >> 6) * 16) * 4 + ((bx >> 5) & 1) * 2 + (bx & 1);
    if (__all_sync(~0u, threadIdx.x >= NTHR - 32 && bx < NCTA) && elect()) {
        asm volatile("mbarrier.init.shared::cta.b64 [%0], 1;" :: "r"(sb + SM_CBAR + CB_WQ * 8));
        asm volatile("mbarrier.init.shared::cta.b64 [%0], 1;" :: "r"(sb + SM_CBAR + 80));
        asm volatile("fence.mbarrier_init.release.cluster;" ::: "memory");
        mbar_expect(sb + SM_CBAR + CB_WQ * 8, 5 * HALF);
        auto k0 = [&]() {
            mbar_expect(sb + SM_CBAR + 80, HALF);
            tma3(sb, &P.tm[TM_KH], 0, (cta0 >> 2) * SK + (SK - WIN) + (cta0 & 3) * 64, sb + SM_CBAR + 80, POL_FIRST);
        };
        if (K0FIRST) k0();
#pragma unroll 1
        for (int i = 0; i < 5; i++) tma3(sb + SM_WQR + (i == 4 ? 0 : i + 1) * HALF, &P.tm[TM_WQ], (cta0 >> 2) * 3, (cta0 & 3) * 160 + i * 32, sb + SM_CBAR + CB_WQ * 8, POL_FIRST);
        if (!K0FIRST) k0();
    }
    __syncwarp();
    int id = cta0 * NTHR + threadIdx.x, tid, lane, g, t, key, warp, cta, mlp, rowc, roww, j40;
    uint32_t maskA, maskB, barw, subw, prow;
    auto fresh = [&]() {
        const int cw = __shfl_sync(~0u, id >> 5, 0);
        id = pin(id); tid = id & 255; lane = id & 31; g = lane >> 2; t = lane & 3; key = (g >> 1) + 4 * (g & 1);
        const uint32_t m = (g & 1) ? 0xffff0000u : 0x0000ffffu;
        maskA = (g & 2) ? 0u : m; maskB = (g & 2) ? m : 0u;
        warp = cw & 7; cta = cw >> 3;
        mlp = (cta & 3) == 3 ? 96 : (cta >> 2) * 3 + (cta & 3);
        rowc = (cta >> 2) * SK + (SK - WIN) + (cta & 3) * 64; roww = rowc + warp * 8;
        j40 = (cta & 3) * 40;
        barw = sb + SM_BAR + warp * 96; subw = sb + warp * SUB; prow = sb + SM_PART + warp * 768;
    };
    fresh();

    if (cta == NCTA) {
        const uint32_t ep = *(volatile unsigned*)&g_epoch;
        if (tid == 0) {
#pragma unroll 1
            for (int it = 0; it < SPIN; it++) { if (ll_tag(ld_rlx(&g_ll[0][0][192])) == ep * 4 + 2) break; __nanosleep(200); }
        }
        __syncthreads();
#pragma unroll 1
        for (int i = tid; i < 4 * 80 * 8; i += NTHR)
            *reinterpret_cast<uint4*>(g_acc + (i >> 3) * ACC_PITCH + (i & 7) * 16) = make_uint4(0, 0, 0, 0);
        __threadfence();
        __syncthreads();
        if (tid == 0) asm volatile("st.relaxed.gpu.global.u32 [%0], %1;" :: "l"(&g_zflag), "r"(ep + 1) : "memory");
        return;
    }
    TSTAMP(0);
    if (tid == 64) { uint32_t now; asm volatile("mov.u32 %0, %globaltimer_lo;" : "=r"(now)); sts32(sb + SM_T0, now); }

    const CUtensorMap* tmk = reinterpret_cast<const CUtensorMap*>(__shfl_sync(~0u, (u64)&P.tm[0] + (lane >> 5), 0));
    auto c4 = [&]() { return 32 * min(warp, 4) + 16 * (t >> 1) + 2 * g + (t & 1); };
    auto xcol = [&](int i, int tt) { return (i < 2 ? 64 * i + 8 * warp : 128 + 8 * (warp >> 1)) + 2 * tt; };
    uint2 xp;
    uint32_t px[3], small;
    auto issue_first = [&](int j) {
        mbar_expect(sb + SM_CBAR + 80 + j * 8, HALF);
        tma3(sb + j * HALF, tmk + TM_KH, 0, rowc + (j >> 1) * 256 + (j & 1) * 32, sb + SM_CBAR + 80 + j * 8, POL_FIRST);
    };
    if (elect()) {
        if (warp != 2) asm volatile("mbarrier.init.shared::cta.b64 [%0], 1;" :: "r"(sb + SM_CBAR + 64 + warp * 8));
#pragma unroll
        for (int i = 0; i < 9; i++) asm volatile("mbarrier.init.shared::cta.b64 [%0], 1;" :: "r"(barw + i * 8));
        asm volatile("mbarrier.init.shared::cta.b64 [%0], 1;" :: "r"(sb + SM_CBAR + warp * 8));
        asm volatile("mbarrier.init.shared::cta.b64 [%0], 1;" :: "r"(sb + SM_CBAR + 128 + warp * 8));
        if (warp < 3) asm volatile("mbarrier.init.shared::cta.b64 [%0], %1;" :: "r"(sb + SM_CBAR + 192 + warp * 8), "r"(warp == 2 ? 8 : 1));
        sts64(barw + 80, 0, 0);
        asm volatile("fence.mbarrier_init.release.cluster;" ::: "memory");
        asm volatile("prefetch.tensormap [%0];" :: "l"(tmk + warp) : "memory");
    }
    __syncwarp();
    asm volatile("ld.global.nc.v2.u32 {%0,%1}, [%2];" : "=r"(xp.x), "=r"(xp.y) : "l"(P.x + 4 * c4()) : "memory");
#pragma unroll
    for (int i = 0; i < 3; i++) asm volatile("ld.global.nc.u32 %0, [%1];" : "=r"(px[i]) : "l"(P.x + 4 * j40 + xcol(i, t)) : "memory");
    asm volatile("ld.relaxed.gpu.global.u32 %0, [%1];" : "=r"(small) : "l"(lane < 16 ? (const void*)(P.b1 + min(mlp, 95) * 16 + (lane & 14)) : (const void*)&g_epoch) : "memory");
    if (tid >= 192 && tid < 192 + NCB) sts32(sb + SM_CNT + (tid - 192) * 8, 0);
    unsigned char* accg = reinterpret_cast<unsigned char*>(__shfl_sync(~0u, (u64)g_acc + (lane >> 5), 0));
    auto release = [&](const uint4& tw) {
        uint32_t old;
        __syncwarp();
        asm volatile("atom.relaxed.cta.shared.add.u32 %0, [%1], 1;" : "=r"(old) : "r"(sb + SM_CNT + (tw.x & 0xf8)) : "memory");
        return old;
    };
    auto refill = [&](const uint4& tw, uint32_t old) {
        if (__any_sync(~0u, (old & 127) == 127 && (tw.y & 2))) {
            wait_until(lds32(sb + SM_T0) + tw.z);
            if (elect()) issue_half(tw.y, sb, rowc, cta, tmk);
            __syncwarp();
        }
    };
    __syncthreads();
    auto issue_paced = [&](int j0, int j1) {
        if (warp >= j0 && warp < j1) {
            wait_until(lds32(sb + SM_T0) + PACES + warp * PACE / 2);
            if (elect()) issue_first(warp);
            __syncwarp();
        }
    };

    uint32_t offV0, offV2;
    auto calc_offsets = [&]() {
        offV0 = subw + (6 * t) * 128 + ((g ^ ((6 * t) & 7)) << 4);
        offV2 = subw + (6 * t + 2) * 128 + ((g ^ ((6 * t + 2) & 7)) << 4);
    };
    calc_offsets();

    auto load_v = [&](uint4 (&v)[6], uint32_t so) {
        v[0] = lds128(offV0 + so); v[1] = lds128((offV0 ^ 16) + so + 128); v[2] = lds128(offV2 + so);
        v[3] = lds128((offV2 ^ 16) + so + 128); v[4] = lds128((offV0 ^ 64) + so + 512); v[5] = lds128((offV0 ^ 80) + so + 640);
    };
    auto issue_v = [&](auto I, int dw) {
        constexpr Step c = SCH.st[I.value];
        const uint32_t bar = barw + dw * 96 + c.slot * 8;
        mbar_expect(bar, SUB);
        tma_v(subw + dw * SUB + c.slot * TILE, tmk, roww * 3 + dw * 24 + c.unit * 768, bar);
    };
    auto refill2 = [&](auto I) { __syncwarp(); if (elect()) issue_v(I, 0); };
    uint4 wq0[6], wqh[3], wq1[6];
    auto load_wq1 = [&](int i) { wq1[i] = lds128((i == 2 ? offV2 : i == 3 ? (offV2 ^ 16) + 128 : (offV0 ^ (i * 16)) + i * 128) + SM_WQ + TILE); };
    auto load_wq = [&]() {
        load_v(wq0, SM_WQ);
        const uint32_t so = SM_WQR - ((warp + 1) >> 1) * SUB;
        wqh[0] = lds128(((warp & 1) ? (offV2 ^ 16) + 128 : offV0) + so);
        wqh[1] = lds128(((warp & 1) ? (offV0 ^ 64) + 512 : (offV0 ^ 16) + 128) + so);
        wqh[2] = lds128(((warp & 1) ? (offV0 ^ 80) + 640 : offV2) + so);
#pragma unroll
        for (int i = 0; i < NWQ1; i++) load_wq1(i);
    };
    uint4 kr[8][6];
    const unsigned char* rap;
    u64 rw[2];
    auto q_proj = [&](auto L, uint32_t (&p)[3], uint32_t pst) {
        if (L.value == 0 && g >= 4) p[0] = p[1] = p[2] = ONES;
        float a[3][4], b[3][4];
        const uint32_t dH = __byte_perm(p[2], 0, (warp & 1) ? 0x3232 : 0x1010);
        const uint32_t dA = __byte_perm(p[0], 0, 0x1010), dB = __byte_perm(p[0], 0, 0x3232), dC = __byte_perm(p[1], 0, 0x1010), dD = __byte_perm(p[1], 0, 0x3232);
#pragma unroll
        for (int i = NWQ1; i < 3; i++) load_wq1(i);
#pragma unroll
        for (int j = 0; j < 3; j++) { a[j][0] = a[j][1] = a[j][2] = a[j][3] = 0.f; mma(a[j], wq0[j], dA & maskA, dA & maskB); }
#pragma unroll
        for (int j = 0; j < 3; j++) { b[j][0] = b[j][1] = b[j][2] = b[j][3] = 0.f; mma(b[j], wq0[j + 3], dB & maskA, dB & maskB); }
#pragma unroll
        for (int j = 0; j < 3; j++) mma(a[j], wqh[j], dH & maskA, dH & maskB);
#pragma unroll
        for (int i = 3; i < 6; i++) load_wq1(i);
        auto look_rw = [&]() {
            if constexpr (L.value == 1) {
                if (NWQ1) rap = accg + ACC_BYTES + (c4() >> 2) * ACC_PITCH + (c4() & 3) * 8;
                rw[0] = ld_rlx(rap); rw[1] = ld_rlx(rap + 40 * ACC_PITCH);
            }
        };
        if (RWAT == 0) look_rw();
        if (L.value == 1 && P4AT == 2) refill2(IC<4>{});
#pragma unroll
        for (int j = 0; j < 3; j++) mma(b[j], wq1[j], dC & maskA, dC & maskB);
#pragma unroll
        for (int j = 0; j < 3; j++) mma(a[j], wq1[j + 3], dD & maskA, dD & maskB);
#pragma unroll
        for (int j = 0; j < 3; j++) {
            if (L.value) {
#pragma unroll
                for (int k = 0; k < 2; k++) { a[j][k] += b[j][k]; add_if(t & 2, a[j][k], a[j][k + 2], b[j][k + 2]); }
                sts64f(pst + j * 256, a[j][0], a[j][1]);
            } else sts128f(pst + j * 256, a[j][0] + b[j][0], a[j][1] + b[j][1], a[j][2] + b[j][2], a[j][3] + b[j][3]);
        }
        CSTAMP(23, __float_as_uint(a[2][1]));
        uint32_t tag;
        if (L.value) tag = lds32(sb + SM_EPOCH) * 4 + 3;
        u64* pub = L.value ? &g_ll[0][cta][tid] : &g_l0[cta][tid];
        if (RWAT == 1) look_rw();
        if (L.value == 0) asm volatile("fence.proxy.async.shared::cta;" ::: "memory");
        TSTAMPL(21);
        __syncthreads();
        if (!L.value) tag = lds32(sb + SM_EPOCH) * 4 + 1;
#pragma unroll 1
        for (int k = 0; k < 2 - L.value; k++) st_rlx_if(tid < 192, pub + k * 192, ll_pack(sum8(sb + (k ? SM_CSP : SM_PART) + tid * 4, 768), tag));
        TSTAMPL(23);
            CSTAMP(24, tag);
    };
    auto ln_stats = [&]() {
        float ss = ln_part(xp, lane);
        ss += shx(ss, 8); ss += shx(ss, 4); ss += shx(ss, 2); ss += shx(ss, 1);
        stsf(sb + SM_STAT + min(warp, 4) * 8 + (lane >> 4) * 4, ss);
    };
    auto ln_final = [&](float& mean, float& rstd) {
        float2 v[5];
#pragma unroll
        for (int w = 0; w < 5; w++) v[w] = lds64f(sb + SM_STAT + w * 8);
        mean = sum5(v[0].x, v[1].x, v[2].x, v[3].x, v[4].x) * (1.f / D_MODEL);
        const float msq = sum5(v[0].y, v[1].y, v[2].y, v[3].y, v[4].y) * (1.f / D_MODEL);
        rstd = ln_rstd(mean, msq);
        stsf(sb + SM_FXS, msq);
    };
    auto q_addr = [&](int d) { return sb + SM_VEC + (((d >> 1) & 1) * 4 + ((d >> 3) & 3)) * 48 + (d >> 5) * 8 + ((d >> 2) & 1) * 4 + (d & 1) * 2; };
    {
#pragma unroll
        for (int u = 0; u < 8; u++)
#pragma unroll
            for (int i = 0; i < 6; i++) kr[u][i] = lds128(sb + SM_CS + (u * 6 + i) * 16);
        issue_paced(1, NIM);
        ln_stats();
        if (tid == 16) { sts32(sb + SM_EPOCH, small); sts32(sb + SM_M1, ~0u); }
        else if (tid < 16) sts32(sb + SM_B1 + tid * 4, (tid & 1) ? small & 0xffff0000u : small << 16);
        mbar_wait(sb + SM_CBAR + CB_WQ * 8, 0);
        load_wq();
        q_proj(IC<0>{}, px, sb + (t < 2 ? SM_PART : SM_CSP) + warp * 768 + (8 * g + 4 * (t & 1)) * 4);
    }
    {
        uint32_t offQ, offL;
        auto calc_ql = [&]() {
            offQ = pin(sb + SM_VEC + (lane & 7) * 48);
            offL = pin(subw + lane * 16);
        };

        auto issue_w = [&](auto L, int which) {
            const uint32_t bar = sb + SM_CBAR + (CB_W1 + which) * 8;
            if (mlp == 96) asm volatile("mbarrier.arrive.shared::cta.b64 _, [%0];" :: "r"(bar) : "memory");
            else {
                mbar_expect(bar, 20480);
                if (which) {
                    tma3(sb + (L.value ? 3 * TILE : SM_W2), tmk + TM_W2, 0, mlp * 16, bar, W2ONE ? POL_FIRST : WPOL);
                    if (W2ONE && !L.value) tma3_pf(tmk + TM_W2, 0, mlp * 16, POL_NORMAL);
                    if (W1ONE && !L.value) asm volatile("cp.async.bulk.prefetch.L2.global.L2::cache_hint [%0], 20480, %1;" :: "l"(P.w1 + mlp * 10240), "l"((u64)POL_NORMAL << 32) : "memory");
                }
                else asm volatile("cp.async.bulk.tensor.3d.shared::cluster.global.mbarrier::complete_tx::bytes.L2::cache_hint [%0], [%1, {%2, %3, %3}], [%4], %5;"
                                  :: "r"(sb + (L.value ? 2 * TILE : SM_W1)), "l"(tmk + TM_W1), "r"(mlp * 16), "r"(0), "r"(bar), "l"((u64)(W1ONE ? POL_FIRST : WPOL) << 32) : "memory");
            }
        };
        float acc[3][4];
        auto load_q = [&](uint4 (&qf)[3]) {
#pragma unroll
            for (int i = 0; i < 3; i++) qf[i] = lds128(offQ + i * 16);
        };
        auto softmax = [&](float S0, float S1, float S2, float S3) {
            int mi = __float_as_int(fmaxf(fmaxf(S0, S1), fmaxf(S2, S3)));
            mi = __reduce_max_sync(~0u, mi ^ ((mi >> 31) & 0x7fffffff));
            const float mrun = __int_as_float(mi ^ ((mi >> 31) & 0x7fffffff));
            const float p0 = ex2((S0 - mrun) * CS), p1 = ex2((S1 - mrun) * CS), p2 = ex2((S2 - mrun) * CS), p3 = ex2((S3 - mrun) * CS);
            const uint32_t pa = pack_bf(p0, p1), pb = pack_bf(p2, p3), pw = prow + 256 + (key >> 1) * 80 + t * 4 + (key & 1) * 2;
            sts16(pw, pa); sts16(pw + 16, pa >> 16); sts16(pw + 32, pb); sts16(pw + 48, pb >> 16);
            __syncwarp();
#pragma unroll
            for (int j = 0; j < 3; j++) acc[j][0] = acc[j][1] = acc[j][2] = acc[j][3] = 0.f;
            return make_float2(mrun, (p0 + p1) + (p2 + p3));
        };
        auto pv = [&](const uint4 (&v)[6], uint32_t pp) {
            const uint32_t dA = __byte_perm(pp, 0, 0x1010), dB = __byte_perm(pp, 0, 0x3232);
            mma(acc[0], v[0], dA & maskA, dA & maskB); mma(acc[1], v[1], dA & maskA, dA & maskB); mma(acc[2], v[2], dA & maskA, dA & maskB);
            mma(acc[0], v[3], dB & maskA, dB & maskB); mma(acc[1], v[4], dB & maskA, dB & maskB); mma(acc[2], v[5], dB & maskA, dB & maskB);
        };
        auto sa = [&]() { return prow + 256 + t * 32 + g * 4; };
        auto pass1 = [&]() {
            if (NIM < NI1) issue_paced(NIM, NI1);
            fresh();
            calc_ql();
            __syncthreads();
            sts64(prow + lane * 8, xp.x, xp.y);
            int e = 0;
            const uint4* tab = P.tile + (warp >> 2);
            uint4 tw = tab[0];
            uint32_t ka[3];
#pragma unroll
            for (int j = 0; j < 3; j++) ka[j] = pin(subw + key * 384 + j * 128 + ((t ^ ((3 * key + j) & 7)) << 4));
            auto load_k = [&](uint4 (&v)[6], uint32_t so) {
#pragma unroll
                for (int i = 0; i < 6; i++) v[i] = lds128(((i & 1) ? ka[i >> 1] ^ 64 : ka[i >> 1]) + so);
            };
            const uint32_t s0 = pin(prow + 256 + g * 4), sca = pin(sb + SM_SC + warp * 128 + g * 16);
#pragma unroll 1
            do {
                const uint4 tn = tab[2 * e + 2];
                uint4 v[6], qf[3];
                if (tw.x & (G_A | G_B | G_C)) {
                    if ((tw.x & G_A) && warp == 7 && elect()) {
                        mbar_expect(sb + SM_CBAR + CB_SNAP * 8, HALF);
                        asm volatile("cp.async.bulk.shared::cluster.global.mbarrier::complete_tx::bytes [%0], [%1], 12288, [%2];"
                                     :: "r"(sb + SM_SNAP), "l"(&g_l0[cta & ~3][0]), "r"(sb + SM_CBAR + CB_SNAP * 8) : "memory");
                    }
                    if (tw.x & G_B) {
                        if (warp < 6) {
                            mbar_wait(sb + SM_CBAR + CB_SNAP * 8, 0);
                            float qc[2] = {0.f, 0.f}, mean, rstd;
#pragma unroll 1
                            for (int k = 0; k < 2; k++) {
                                u64 qw[4];
#pragma unroll
                                for (int i = 0; i < 4; i++) { const uint2 x = lds64(sb + SM_SNAP + i * 3072 + k * 1536 + tid * 8); qw[i] = x.x | (u64)x.y << 32; }
                                qc[0] = qc[1];
                                qc[1] = ll_gather<384>(&g_l0[cta & ~3][k * 192 + tid], lds32(sb + SM_EPOCH) * 4 + 1, qw);
                            }
                            ln_final(mean, rstd);
                            stsf(sb + SM_CS + tid * 4, qc[1]);
                            const float q = (qc[0] - mean * qc[1]) * rstd;
                            sts16(q_addr(tid), pack_bf(q, q));
                        }
                        __syncthreads();
                        if (warp == 7 && elect()) issue_half(UC<load_word(12)>::value, sb, rowc, cta, tmk);
                        TSTAMP(2);
                    }
                    if (tw.x & G_C) {
                        load_k(v, (e - LATEAT) * TILE);
                        load_q(qf);
                        stsf(s0 + (e - LATEAT) * 32, score(v, qf));
                    }
                }
                load_q(qf);
                mbar_wait(sb + SM_CBAR + (tw.x & 0xf8), tw.x >> 31);
                TRACE(e);
                load_k(v, tw.x & 0x3f000);
                const uint32_t old = release(tw);
                const float s = score(v, qf);
                uint32_t m;
                {
                    uint32_t a[6];
#pragma unroll
                    for (int i = 0; i < 6; i++) a[i] = bf2_amax(bf2_amax(v[i].x, v[i].y), bf2_amax(v[i].z, v[i].w));
                    m = bf2_amax(bf2_amax(bf2_amax(a[0], a[1]), bf2_amax(a[2], a[3])), bf2_amax(a[4], a[5]));
                }
                m = bf2_amax(m, m >> 16) & 0x7f80;
                m = max(m, __shfl_xor_sync(~0u, m, 1));
                stsf(s0 + e * 32, s);
                m = max(m, __shfl_xor_sync(~0u, m, 2));
                refill(tw, old);
                const uint32_t b = min(max(m, 15u << 7) - (15u << 7), 126u << 7);
                const uint32_t dn = ((127u << 7) - b) * 0x10001u, up = ((127u << 7 | 0x8000u) + b) * 0x10001u;
                uint32_t c[18], any = m > (141u << 7);
#pragma unroll
                for (int i = 0; i < 6; i++) {
                    const uint32_t y0 = bf2_mul(v[i].x, dn), y1 = bf2_mul(v[i].y, dn), y2 = bf2_mul(v[i].z, dn), y3 = bf2_mul(v[i].w, dn);
                    v[i] = make_uint4(bf2_fma(y0, up, v[i].x), bf2_fma(y1, up, v[i].y), bf2_fma(y2, up, v[i].z), bf2_fma(y3, up, v[i].w));
                    any |= v[i].x | v[i].y;
                    any |= v[i].z | v[i].w;
                    const uint32_t hb = __byte_perm(y2, y3, 0x7531);
                    c[3 * i] = __byte_perm(y0, y1, 0x6420); c[3 * i + 1] = __byte_perm(y2, y3, 0x6420);
                    c[3 * i + 2] = __byte_perm(y0, y1, 0x7531) | __funnelshift_r(hb, hb, 4);
                }
                asm volatile("st.shared.u8 [%0], %1;" :: "r"(sca + (e & 3) * 4 + (e >> 2)), "r"((b >> 7) + 63) : "memory");
                const bool rare = __any_sync(~0u, any);
                k_keep(kr, c, e, offL);
                if (rare) k_rare(v[0], v[1], v[2], v[3], v[4], v[5], m > (141u << 7), e, warp, lane);
                tw = tn;
            } while (++e < 16);
            asm volatile("fence.proxy.async.shared::cta;" ::: "memory");
            __syncwarp();
            TSTAMP(10);
            fresh(); calc_offsets();
            {
                const uint2 st = lds64(barw + 80);
                const uint32_t xa = sb + SM_EXC + warp * 128 + (lane & 15) * 8 + 4;
                uint32_t pos = lds32(xa), lt;
                asm volatile("mov.u32 %0, %lanemask_lt;" : "=r"(lt));
                if (lane >= st.x) pos = 0x80000000u;
                const bool dup = (__match_any_sync(~0u, pos >> 16) & lt) && lane < st.x;
                if (lane < 16) sts32(xa, dup ? pos | 0x40000000u : pos);
                if (__any_sync(~0u, dup)) sts32(barw + 84, st.y | 0x10000u);
                const float2 ml = softmax(ldsf(sa()), ldsf(sa() + 128), ldsf(sa() + 256), ldsf(sa() + 384));
                sts64f(sb + SM_ML + warp * 8, ml.x, warp_sum(ml.y));
            }
            u64 pm = 0, pl = 0;
#pragma unroll 1
            do {
                const uint4 tn = tab[2 * e + 2];
                if (tw.x & (G_A | G_B | G_C)) {
                    if (tw.x & G_A) {
                        if (lane < 24) st_rlx(&g_ll[0][cta][warp * 24 + lane], 0ull);
                        else if (lane < 28) st_rlx(&g_ll[0][cta][168 + warp * 4 + lane], ll_pack(ldsf(sb + SM_ML + warp * 8 + (lane & 1) * 4), lds32(sb + SM_EPOCH) * 4 + 2));
                    }
                    if (warp == 2) {
                        if (tw.x & G_B) ld_rlx2(&g_ll[0][cta ^ (lane >> 3)][192 + (lane & 7) * 4], pm, pl);
                        if (tw.x & G_C) head_weight(&g_ll[0][cta ^ (lane >> 3)][192 + (lane & 7) * 4], pm, pl, 0, lane);
                    }
                    __syncwarp();
                }
                const uint32_t pp = lds32(prow + 256 + t * 80 + ((tw.x >> 20) & 255));
                mbar_wait(sb + SM_CBAR + (tw.x & 0xf8), tw.x >> 31);
                TRACE(e);
                uint4 v[6];
                load_v(v, tw.x & 0x3f000);
                refill(tw, release(tw));
                pv(v, pp);
                tw = tn;
            } while (++e < 32);
        };
        uint32_t osa, ora, owa, orow, otag;
        u64* olb;
        float xc;
        auto o_setup = [&](auto L) {
            fresh();
            const int lz = lane, d = warp * 24 + min(lz, 23);
            osa = pin(prow + ((lz >> 2) * 8 + (lz & 1) * 4 + (lz & 2)) * 4);
            ora = pin(sb + SM_PART + d * 4);
            olb = pin(&g_ll[L.value][cta & ~3][d]);
            orow = pin((lz & 1) + 2 * (lz & 2) + 2 * (lz >> 4));
            owa = pin(sb + SM_RING + warp * 1536 + orow * 64 + ((((lz >> 2) & 3) ^ (orow >> 1)) << 4));
            otag = lds32(sb + SM_EPOCH) * 4 + 2 + 2 * L.value;
            uint32_t x; asm volatile("ld.shared.u16 %0, [%1];" : "=r"(x) : "r"(prow + ((cta & 1) * 16 + (lz >> 3) * 4 + (cta & 2) + ((lz >> 2) & 1)) * 8 + (lz & 3) * 2) : "memory");
            xc = bf_lo(x) * (1.f / 32);
        };
        auto pass2 = [&]() {
            constexpr IC<1> L{};
            if (P4AT == 0) refill2(IC<4>{});
            if (P2LATE == 1 && warp >= 4) refill2(IC<2>{});
            offQ = sb + SM_VEC + (lane & 7) * 48; offL = subw + lane * 16;
            uint4 tb[8][3];
            auto load_tb = [&](auto I) {
#pragma unroll
                for (int i = 0; i < 3; i++) tb[I.value][i] = lds128(offL + (I.value >> 1) * TILE + ((I.value & 1) * 3 + i) * 512);
            };
            const float cs = ldsf(sb + SM_CS + min(tid, 191) * 4), inv = fx2_inv(ldsf(sb + SM_MSQ));
            const uint32_t qtag = lds32(sb + SM_EPOCH) * 4 + 3;
            uint32_t m1 = lds32(sb + SM_M1), m1n = m1;
            static_for<0, NPRE>(load_tb);
            const u64* qb = &g_ll[0][cta & ~3][min(tid, 191)];
            const uint32_t qa = pin(q_addr(min(tid, 191)));
            {
                uint32_t x[2];
                fx2_wait<2, true>([&](int i) { return rap + i * 40 * ACC_PITCH; }, rw, sb + SM_MSQ, inv, x);
                xp = make_uint2(x[0], x[1]);
            CSTAMP(25, xp.y);
            }
            u64 qw[4];
            ll_look<256>(qb, qw);
            ln_stats();
            if (P4AT == 1) refill2(IC<4>{});
            if (S0EARLY) refill2(IC<5>{});
            __syncthreads();
            auto vwait = [&](auto I) { mbar_wait(barw + IC<SCH.st[I.value].slot>::value * 8, IC<SCH.st[I.value].par>::value); };
            bool ok;
            {
                float mean, rstd;
                ln_final(mean, rstd);
                sts64(prow + lane * 8, xp.x, xp.y);
            CSTAMP(26, __float_as_uint(rstd));
                sts128f(prow + 256 + lane * 16, 0.f, 0.f, 0.f, 0.f);
                const float sq = rstd * 0x1p64f, q0 = -mean * cs * sq;
                const float q = ll_gather<256>(qb, qtag, qw) * sq + q0;
                sts16(qa, pack_bf(q, q));
                TSTAMPL(24);
            CSTAMP(27, __float_as_uint(q));
            }
            if (!S0EARLY) refill2(IC<5>{});
            if (P2LATE == 2 && warp >= 4) refill2(IC<2>{});
            if (P4AT == 3) refill2(IC<4>{});
            if (NOWIN & 1) { if (warp < 6) refill2(IC<0>{}); if (warp >= 5) refill2(IC<3>{}); }
            if (NOWIN & 2) { if (warp >= 6) refill2(IC<1>{}); if (warp < 4) refill2(IC<2>{}); }
            if (NOWIN & 4) { if (warp >= 6) refill2(IC<0>{}); if (warp < 6) refill2(IC<1>{}); }
            if (NOWIN & 8) { if (warp < 5) refill2(IC<3>{}); if (warp >= 4) refill2(IC<2>{}); }
            __syncthreads();
            uint4 qf[3];
            load_q(qf);
            CSTAMP(28, qf[0].x);
            float S[4], d[2][4];
            auto vload = [&](auto I) {
                constexpr int p = I.value;
                constexpr Step c = SCH.st[p];
                load_v(kr[p & 7], c.slot * TILE);
                if constexpr (c.next >= 0) refill2(IC<c.next>{});
                if constexpr (p == 11) { __syncwarp(); if (elect()) asm volatile("mbarrier.arrive.shared::cta.b64 _, [%0];" :: "r"(sb + SM_CBAR + CB_REL * 8) : "memory"); }
            };
            static_for<0, 96>([&](auto F) {
                constexpr int f = F.value, i = f % 6, u = kunit(f / 6), w = 3 * f % 12;
                uint4 (&src)[3] = *reinterpret_cast<uint4 (*)[3]>(f < 32 ? &tb[f / 4 & 7][0] : &kr[(f / 8 + 4) & 7][(f / 4 & 1) * 3]);
                const uint4 a = k_unpack(word<w % 4>(src[w / 4]), word<(w + 1) % 4>(src[(w + 1) / 4]), word<(w + 2) % 4>(src[(w + 2) / 4]), m1);
                if constexpr (f < 32 ? f % 4 == M1AT : f % 8 == M1P) m1 = m1n;
                if constexpr (f % 4 == 3 && f / 4 + NPRE < 8) {
                    load_tb(IC<f / 4 + NPRE>{});
                    if constexpr ((f / 4 + NPRE) & 1) { refill2(IC<5 + (f / 4 + NPRE) / 2>{}); m1n = lds32(sb + SM_M1); }
                }
                if constexpr (i < 2) d[i][0] = d[i][1] = d[i][2] = d[i][3] = 0.f;
                mma(d[i & 1], a, (i & 1) ? qf[i / 2].z : qf[i / 2].x, (i & 1) ? qf[i / 2].w : qf[i / 2].y);
                if constexpr (i == 5) {
                    if constexpr (u == 11 || ((u & 3) == 0 && u != 8)) S[u >> 2] = (d[0][0] + d[0][3]) + (d[1][0] + d[1][3]);
                    else add_if(t == (u & 3), S[u >> 2], d[0][0] + d[0][3], d[1][0] + d[1][3]);
                    if constexpr (f < 64) S[u >> 2] = shx(S[u >> 2], 0);
                }
                if constexpr (f == 31) { fresh(); calc_offsets(); ok = mbar_test(barw + IC<SCH.st[0].slot>::value * 8, 0); }
                if constexpr (f == 48) {
                    const uint2 x = lds64(sb + SM_EXC + warp * 128 + (lane & 15) * 8);
                    const float c = k_side(sb, x);
                    if (x.y < 0x40000000u) stsf(prow + 256 + (x.y >> 16), c);
                }
                if constexpr (f >= 32 && f % 8 == 7) {
                    if constexpr (PARKS >> (f / 8 - 4) & 1) {
                        constexpr int p = popc(PARKS & ((1 << (f / 8 - 4)) - 1));
                        if (!ok) vwait(IC<p>{});
                        vload(IC<p>{});
                        m1n = lds32(sb + SM_M1);
                        ok = mbar_test(barw + IC<SCH.st[p + 1].slot>::value * 8, IC<SCH.st[p + 1].par>::value);
                    }
                }
            });
            uint32_t bad = lds32(barw + 84);
            const uint32_t sc = lds32(sb + SM_SC + tid * 4);
            __syncwarp();
            if (bad) k_fix(P.k + (size_t)roww * DH, bad, warp, lane);
            TSTAMP(30);
            CSTAMP(29, __float_as_uint(S[2]));
            const float2 ml = softmax(S[0] * __uint_as_float((sc & 255) << 23) + ldsf(sa()), S[1] * __uint_as_float((sc & 0xff00) << 15) + ldsf(sa() + 128),
                                      S[2] * __uint_as_float((sc & 0xff0000) << 7) + ldsf(sa() + 256), S[3] * __uint_as_float((sc >> 24) << 23) + ldsf(sa() + 384));
            uint4 pq[4];
#pragma unroll
            for (int j = 0; j < 4; j++) pq[j] = lds128(prow + 256 + t * 80 + j * 16);
            TSTAMP(1);
            CSTAMP(30, pq[3].w);
            if (!ok) vwait(IC<NPARK>{});
            float ac2[3][4];
#pragma unroll
            for (int j = 0; j < 3; j++) ac2[j][0] = ac2[j][1] = ac2[j][2] = ac2[j][3] = 0.f;
            const uint32_t sl = (g & 1) ? 0x1044 : 0x4410, sh = (g & 1) ? 0x3244 : 0x4432;
            const uint32_t sA0 = (g & 2) ? 0x4444 : sl, sA1 = (g & 2) ? sl : 0x4444, sB0 = (g & 2) ? 0x4444 : sh, sB1 = (g & 2) ? sh : 0x4444;
            u64 pm = 0, pl = 0;
            static_for<NPARK, 16>([&](auto I) {
                constexpr int p = I.value;
                static_assert(p - SCH.st[p].mma0 < 8, "buffer in use");
                vload(I);
                if constexpr (p < 15) ok = mbar_test(barw + IC<SCH.st[p + 1].slot>::value * 8, IC<SCH.st[p + 1].par>::value);
                static_for<SCH.st[p].mma0, SCH.st[p].mma0 + SCH.st[p].nmma>([&](auto J) {
                    constexpr int u = SCH.st[J.value].unit;
                    const uint32_t pp = word<u & 3>(pq[u >> 2]), a0 = __byte_perm(pp, 0, sA0), a1 = __byte_perm(pp, 0, sA1), b0 = __byte_perm(pp, 0, sB0), b1 = __byte_perm(pp, 0, sB1);
#pragma unroll
                    for (int j = 0; j < 3; j++) mma(acc[j], kr[J.value & 7][j], a0, a1);
#pragma unroll
                    for (int j = 0; j < 3; j++) mma(ac2[j], kr[J.value & 7][j + 3], b0, b1);
                });
                if constexpr (p == NPARK) {
                    const float l = warp_sum(ml.y);
                    if (lane < 28) st_rlx(&g_ll[1][cta][lane < 24 ? warp * 24 + lane : 168 + warp * 4 + lane], lane < 24 ? 0ull : ll_pack((lane & 1) ? l : ml.x, lds32(sb + SM_EPOCH) * 4 + 4));
                }
                if constexpr (p == HWAT) { if (warp == 6) ld_rlx2(&g_ll[1][cta ^ (lane >> 3)][192 + (lane & 7) * 4], pm, pl); }
                if constexpr (p == 13) o_setup(L);
                if constexpr (p == HWAT + 2) { if (warp == 6) head_weight(&g_ll[1][cta ^ (lane >> 3)][192 + (lane & 7) * 4], pm, pl, 1, lane); }
                if constexpr (p >= WOAT && p < WOAT + 3) {
                    if (warp == p - WOAT) {
                        mbar_wait(sb + SM_CBAR + CB_REL * 8, 0);
                        if (elect()) {
                            issue_half(UC<load_word(64 + 2 * (p - WOAT)) | 1>::value, sb, rowc, cta, tmk);
                            if constexpr (p < WOAT + 2) issue_half(UC<load_word(65 + 2 * (p - WOAT)) | 1>::value, sb, rowc, cta, tmk);
                        }
                        __syncwarp();
                    }
                }
                if constexpr (p < 15) { if (!ok) mbar_wait(barw + IC<SCH.st[p + 1].slot>::value * 8, IC<SCH.st[p + 1].par>::value); TRACE(33 + p); }
            });
#pragma unroll
            for (int j = 0; j < 3; j++)
#pragma unroll
                for (int k = 0; k < 2; k++) { acc[j][k] += ac2[j][k]; add_if(t & 2, acc[j][k], acc[j][k + 2], ac2[j][k + 2]); }
        };

        const unsigned char* ap;
        uint32_t hpa, hsa, hst, w2a, la;
        uint2 b2v;
        float b1v, cs1;
        auto mlp_global = [&](auto L) {
            const int cz = c4();
            ap = accg + 2 * L.value * ACC_BYTES + (cz >> 1) * ACC_PITCH + (cz & 1) * 16;
            if (L.value) ap = pin(ap);
            rap = pin(accg + (2 * L.value + 1) * ACC_BYTES + (cz >> 2) * ACC_PITCH + (cz & 3) * 8);
            asm volatile("ld.global.nc.v2.u32 {%0,%1}, [%2];" : "=r"(b2v.x), "=r"(b2v.y) : "l"(P.b2 + 4 * cz));
        };
        auto mlp_shared = [&](auto L) {
            const int lz = lane;
            hpa = pin(sb + SM_PART + warp * 256 + ((lz & 2) * 4 + (lz >> 2)) * 16 + (L.value ? 0 : (lz & 1) * 4));
            hsa = pin(sb + SM_PART + (lz & 15) * 16); hst = pin(sb + SM_PART + (lz & 15) * 16 + warp * 256 + 8 + (lz >> 4) * 4);
            w2a = pin(sb + (L.value ? 3 * TILE : SM_W2) + ((lz & 3) * 10 + 2 * warp) * 128 + (((lz >> 2) ^ ((2 * lz + 2 * warp) & 6)) << 4));
            la = sb + (L.value ? 2 * TILE : SM_W1) + warp * 4096 + (lz & 4) * 512 + (lz & 2) * 64 + (lz & 1) * 32 + (lz >> 4) * 64 + ((((lz >> 3) ^ (lz >> 1)) & 1) << 4);
            b1v = ldsf(sb + SM_B1 + (lz & 15) * 4);
            if (L.value) { la = pin(la); cs1 = ldsf(sb + SM_ML + (lz & 15) * 4); }
            else fresh();
        };
        uint32_t pa;
        unsigned char* rop;
        uint32_t wpa;
        auto sum_setup = [&](auto L) {
            const int lz = lane, word = warp * 128 + (cta & 3) * 32 + lz;
            wpa = pin(sb + SM_RING + warp * 1536 + ((((lz >> 2) * 8 + (lz & 1) * 4) * 4) ^ ((((lz >> 1) ^ (lz >> 4)) & 1) ? 256 + 64 : 0)));
            pa = pin(sb + SM_RING + warp * 256 + ((lz * 4) ^ ((warp & 1) * 64)));
            rop = pin(accg + 2 * L.value * ACC_BYTES + (word >> 3) * ACC_PITCH + (word & 7) * 4);
        };
        auto out_proj = [&](auto L) {
            TSTAMP2(3);
            CSTAMP(0, __float_as_uint(acc[2][1]));
            __syncwarp();
#pragma unroll
            for (int j = 0; j < 3; j++) {
                if (L.value == 0 && (t & 2)) { acc[j][0] = acc[j][2]; acc[j][1] = acc[j][3]; }
                sts64f(osa + 256 * j, acc[j][0], acc[j][1]);
            }
            __syncthreads();
            {
                float s[8];
#pragma unroll
                for (int w = 0; w < 8; w++) s[w] = ldsf(ora + w * 768);
                const uint4 fa = lds128(sb + SM_FAC), fb = lds128(sb + SM_FAC + 16);
            CSTAMP(1, __float_as_uint(s[0]));
                const float own = ((s[0] * __uint_as_float(fa.x) + s[1] * __uint_as_float(fa.y)) + (s[2] * __uint_as_float(fa.z) + s[3] * __uint_as_float(fa.w))) +
                                  ((s[4] * __uint_as_float(fb.x) + s[5] * __uint_as_float(fb.y)) + (s[6] * __uint_as_float(fb.z) + s[7] * __uint_as_float(fb.w)));
                st_rlx_if(lane < 24, olb + (cta & 3) * 256, ll_pack(own, otag));
            CSTAMP(2, __float_as_uint(own));
            }
            TSTAMPL(29);
            if (L.value == 0 && warp == 7) {
#pragma unroll 1
                for (int it = 0; it < SPIN; it++) {
                    uint32_t v; asm volatile("ld.acquire.gpu.global.u32 %0, [%1];" : "=r"(v) : "l"(&g_zflag) : "memory");
                    if (__all_sync(~0u, v == (otag >> 2) + 1)) break;
                }
            }
            constexpr int NW = L.value ? NWO1 : 3;
            uint4 v[5][3];
            u64 ow[4];
            auto read_wo = [&](auto J) {
#pragma unroll
                for (int p = 0; p < 3; p++) v[J.value][p] = lds128(((J.value & 1) ? owa ^ 144 : owa) + ring_hs(64 + J.value) * HALF + p * 512);
            };
            static_for<0, NW>([&](auto J) {
                if (L.value && J.value == 0) { sum_setup(L); maskA = pin(maskA); maskB = pin(maskB); }
                if ((L.value ? OPOLL1 : OPOLL) == J.value) { ll_look<256>(olb, ow); if (L.value) { mlp_shared(L); mlp_global(L); } }
                mbar_wait(sb + SM_CBAR + (CB_WO + J.value) * 8, L.value);
                read_wo(J);
                if (L.value == 0 && W1AT0 == J.value + 1) {
                    __syncwarp();
                    if (elect() && cnt_inc(sb + SM_CNT + CB_W1 * 8, 7) == 7) issue_w(L, 0);
                    __syncwarp();
                }
                if (L.value == 1 && (W1AT1 == J.value + 1 || W2AT1 == J.value + 1)) {
                    if (warp == 7 && elect()) { if (W1AT1 == J.value + 1) issue_w(L, 0); if (W2AT1 == J.value + 1) issue_w(L, 1); }
                    __syncwarp();
                }
            });
            const float o = ll_gather<256>(olb, otag, ow);
            CSTAMP(3, __float_as_uint(o));
            TSTAMP2(4);
            bool ok = true;
            if constexpr (NW < 5) ok = mbar_test(sb + SM_CBAR + (CB_WO + 4) * 8, L.value);
            if constexpr (NW < 4) ok &= mbar_test(sb + SM_CBAR + (CB_WO + 3) * 8, L.value);
            const uint32_t od = pack_bf(o, o);
            uint32_t oa[3], ob[3];
#pragma unroll
            for (int p = 0; p < 3; p++) { const uint32_t op = __shfl_sync(~0u, od, 8 * p + orow); oa[p] = op & maskA; ob[p] = op & maskB; }
            CSTAMP(4, oa[2]);
            float y[5][4];
#pragma unroll
            for (int j = 0; j < 5; j++) y[j][0] = y[j][1] = y[j][2] = y[j][3] = 0.f;
            auto rest = [&]() {
                if (!ok) static_for<NW, 5>([&](auto J) { mbar_wait(sb + SM_CBAR + (CB_WO + J.value) * 8, L.value); });
                static_for<NW, 5>(read_wo);
            };
            if (L.value) rest();
#pragma unroll
            for (int p = 0; p < 3; p++)
#pragma unroll
                for (int j = 0; j < NW; j++) mma(y[j], v[j][p], oa[p], ob[p]);
            if (!L.value) { rest(); sum_setup(L); }
#pragma unroll
            for (int p = 0; p < 3; p++)
#pragma unroll
                for (int j = NW; j < 5; j++) mma(y[j], v[j][p], oa[p], ob[p]);
            CSTAMP(5, __float_as_uint(y[4][3]));
#pragma unroll
            for (int j = 0; j < 5; j += 2) {
                if (j < 4 && (t >> 1) != (g >> 2)) { y[j][0] = y[j + 1][0]; y[j][1] = y[j + 1][1]; y[j][2] = y[j + 1][2]; y[j][3] = y[j + 1][3]; }
                sts128f(wpa + j * 256, y[j]);
            }
            TSTAMP2(5);
        };
        u64 yw[2];
        bool wide;
        float msq = 0.f, yf[4];
        auto mlp_part = [&](auto L) {
            const float sc1 = fx2_scale(ldsf(sb + SM_FXS)) * 0.25f;
            bar_sync(0, 256);
            CSTAMP(6, __float_as_uint(sc1));
            const float s = (sum8(pa, 1536) + xc) + sum8(pa + 128, 1536), sm = s * sc1 + FX2_ONE;
            CSTAMP(7, __float_as_uint(s));
            const bool wide1 = !(fabsf(sm - FX2_ONE) < FX1LIM);
            asm volatile("red.relaxed.gpu.global.add.u32 [%0], %1;" :: "l"(rop), "r"(wide1 ? 0u : __float_as_uint(sm) * 128u + (1u - 0x4b400000u * 128u)) : "memory");
            const uint32_t c0 = clk();
            TSTAMP2(6);
            if (L.value == 0) bar_arrive(2, 256);
            if (wide1) {
                fx_send(rop + 64 + (lane & 7) * 4, s, ldsf(sb + SM_FXS), rop, 64);
                asm volatile("red.relaxed.gpu.global.add.u32 [%0], 1;" :: "l"(rop) : "memory");
            }
            __syncwarp();
            if (L.value == 1 && mlp == 96) { TDUMP(); asm volatile("exit;"); }
            uint4 wf[8], w2r[8];
            uint4 w;
            auto look = [&]() { asm volatile("ld.relaxed.gpu.global.v4.u32 {%0,%1,%2,%3}, [%4];" : "=r"(w.x), "=r"(w.y), "=r"(w.z), "=r"(w.w) : "l"(ap) : "memory"); };
            auto read_w1 = [&]() {
#pragma unroll
                for (int j = 0; j < 8; j++) wf[j] = ldsm_t(la + j * 256);
            };
            auto read_w2 = [&]() {
#pragma unroll
                for (int i = 0; i < 8; i++) w2r[i] = lds128(((i & 1) ? (w2a ^ 16) + 128 : w2a) + (i >> 1) * 5120);
            };
            if (L.value == 0) { fresh(); mlp_global(L); }
            mbar_wait(sb + SM_CBAR + CB_W1 * 8, L.value);
            if (L.value == 1) {
                if (W2PRE == 1) mbar_wait(sb + SM_CBAR + CB_W2 * 8, 1);
                read_w1();
                if (W2PRE == 1) read_w2();
            }
            while (clk() - c0 < AR1D);
            look();
            if (L.value == 0) { mlp_shared(L); read_w1(); bar_arrive(3, 256); }
            else if (W2PRE == 2) { mbar_wait(sb + SM_CBAR + CB_W2 * 8, 1); read_w2(); }
            TSTAMPL(28);
            {
                const float inv = shx(fx_inv(sc1) * (1.f / 128), 0), off = inv * -32.f;
                int it = 0;
#pragma unroll 1
                while (__any_sync(~0u, ~(w.x & w.y & w.z & w.w) & 32) & (++it < SPIN)) look();
                CSTAMP(8, w.w);
                xp = make_uint2(pack_bf((float)(int)w.x * inv + off, (float)(int)w.y * inv + off), pack_bf((float)(int)w.z * inv + off, (float)(int)w.w * inv + off));
                if (__any_sync(~0u, (w.x | w.y | w.z | w.w) & 64)) { xp.x = fx1_wide(ap, ldsf(sb + SM_FXS)); xp.y = fx1_wide(ap + 8, ldsf(sb + SM_FXS)); }
            }
            TSTAMP2(7);
            CSTAMP(9, xp.y);
            {
                bool ok = true;
                if (L.value == 0 || !W2PRE) ok = mbar_test(sb + SM_CBAR + CB_W2 * 8, L.value);
                const bool ev = L.value || !(g & 1), od = L.value || (g & 1);
                const uint32_t e0 = ev ? xp.x : ONES, e1 = ev ? xp.y : ONES, o0 = od ? xp.x : ONES, o1 = od ? xp.y : ONES;
                float d[8][4];
#pragma unroll
                for (int j = 0; j < 8; j++) { d[j][0] = d[j][1] = d[j][2] = d[j][3] = 0.f; mma(d[j], wf[j], (j & 1) ? o0 : e0, (j & 1) ? o1 : e1); }
                float ss = ln_part(xp, lane);
                ss += shx(ss, 8); ss += shx(ss, 4);
                float r[4], dd;
#pragma unroll
                for (int k = 0; k < 4; k += 1 + L.value) r[k] = d[0][k] + d[1][k ^ 1];
#pragma unroll
                for (int j = 1; j < 4; j++)
#pragma unroll
                    for (int k = 0; k < 4; k += 1 + L.value) add_if(t == j, r[k], d[2 * j][k], d[2 * j + 1][k ^ 1]);
                CSTAMP(10, __float_as_uint(r[2]));
                if (L.value) {
                    dd = ((t & 2) ? r[2] : r[0]) + shx((t & 2) ? r[0] : r[2], 2);
                    ss += shx(ss, 2);
                    dd += shx(dd, 1);
                } else {
                    const float a = ((t & 1) ? r[1] : r[0]) + shx((t & 1) ? r[0] : r[1], 1), b = ((t & 1) ? r[3] : r[2]) + shx((t & 1) ? r[2] : r[3], 1);
                    ss += shx(ss, 2);
                    dd = ((t & 2) ? b : a) + shx((t & 2) ? a : b, 2);
                }
                ss += shx(ss, 1);
                stsf(hpa, dd);
                stsf(hst, ss);
                CSTAMP(11, __float_as_uint(dd + ss));
                if (!ok) mbar_wait(sb + SM_CBAR + CB_W2 * 8, L.value);
            }
            TSTAMPL(25);
            bar_sync(1, 160);
            uint4 hp[5];
#pragma unroll
            for (int w = 0; w < 5; w++) hp[w] = lds128(hsa + w * 256);
            CSTAMP(12, hp[0].x);
            auto hs = [&](auto K) { return sum5(__uint_as_float(word<K.value>(hp[0])), __uint_as_float(word<K.value>(hp[1])), __uint_as_float(word<K.value>(hp[2])),
                                                __uint_as_float(word<K.value>(hp[3])), __uint_as_float(word<K.value>(hp[4]))); };
            const float mean = hs(IC<2>{}) * (1.f / D_MODEL);
            msq = hs(IC<3>{}) * (1.f / D_MODEL);
            if (L.value == 0) cs1 = hs(IC<1>{});
            float hv = hs(IC<0>{}) - mean * cs1;
            CSTAMP(13, __float_as_uint(hv));
            const float sc2 = fx2_scale(msq), lim = fx_inv(sc2) * FX2LIM;
            if (L.value == 0 || !W2PRE) read_w2();
            if (L.value == 0) bar_arrive(4, 256);
            hv = hv * ln_rstd(mean, msq) + b1v;
            CSTAMP(14, __float_as_uint(hv));
            hv = hv * rcp(1.f + ex2(hv * (-2.302208198f - 0.1029432397f * hv * hv)));
            const uint32_t hd = pack_bf(hv, hv);
            CSTAMP(15, hd);
            TSTAMPL(27);
            float ym[4][4];
#pragma unroll
            for (int i = 0; i < 2; i++) {
                ym[i][0] = ym[i][1] = ym[i][2] = ym[i][3] = 0.f;
                const float f = mlp < 64 ? 1.f / 64 : 0.f;
                ym[i + 2][0] = (bf_lo(xp.x) + bf_lo(b2v.x)) * f; ym[i + 2][1] = (bf_hi(xp.x) + bf_hi(b2v.x)) * f;
                ym[i + 2][2] = (bf_lo(xp.y) + bf_lo(b2v.y)) * f; ym[i + 2][3] = (bf_hi(xp.y) + bf_hi(b2v.y)) * f;
            }
#pragma unroll
            for (int i = 0; i < 4; i++) {
                const uint32_t hh = __shfl_sync(~0u, hd, 4 * i + t);
                mma(ym[(i & 1) * 2], w2r[2 * i], hh & maskA, hh & maskB);
                mma(ym[(i & 1) * 2 + 1], w2r[2 * i + 1], hh & maskA, hh & maskB);
            }
#pragma unroll
            for (int k = 0; k < 4; k++) { yf[k] = ym[0][k] + ym[2][k]; add_if(t & 2, yf[k], ym[1][k], ym[3][k]); }
            CSTAMP(16, __float_as_uint(yf[3]));
            yw[0] = fx2_pack(yf[0] * sc2 + FX2_ONE, yf[1] * sc2 + FX2_ONE); yw[1] = fx2_pack(yf[2] * sc2 + FX2_ONE, yf[3] * sc2 + FX2_ONE);
            wide = !(fmaxf(fmaxf(fabsf(yf[0]), fabsf(yf[1])), fmaxf(fabsf(yf[2]), fabsf(yf[3]))) < lim);
            if (wide) yw[0] = yw[1] = 0;
        };
        auto send_wide = [&]() {
#pragma unroll 1
            for (int k = 0; k < 4; k++, yf[0] = yf[1], yf[1] = yf[2], yf[2] = yf[3]) {
                const unsigned char* a = rap + (k >> 1) * 40 * ACC_PITCH;
                fx_send(a + 64 + (k & 1) * 32, yf[0], msq, a, 256);
            }
            yw[0] = yw[1] = 1;
        };

        pass1();
        o_setup(IC<0>{});
        out_proj(IC<0>{});
        uint32_t c0;
        if (warp < 5) {
            mlp_part(IC<0>{});
            if (mlp != 96) {
#pragma unroll
                for (int k = 0; k < 2; k++) asm volatile("red.relaxed.gpu.global.add.u64 [%0], %1;" :: "l"(rap + k * 40 * ACC_PITCH), "l"(yw[k]) : "memory");
            }
            c0 = clk();
            stsf(sb + SM_ML + (lane & 15) * 4, cs1);
            TSTAMP(8);
            if (__any_sync(~0u, wide && mlp != 96)) {
                if (wide) {
                    send_wide();
#pragma unroll
                    for (int k = 0; k < 2; k++) asm volatile("red.relaxed.gpu.global.add.u64 [%0], 1;" :: "l"(rap + k * 40 * ACC_PITCH) : "memory");
                }
                __syncwarp();
            }
            fresh(); calc_offsets();
            load_wq();
        } else {
            bar_sync(0, 256);
            if (warp == 5 && elect()) {
                asm volatile("fence.proxy.async.shared::cta;" ::: "memory");
                if (W1AT0 == 4) issue_w(IC<0>{}, 0);
                issue_w(IC<0>{}, 1);
            }
            __syncwarp();
            fresh(); calc_offsets();
            load_wq();
#pragma unroll 1
            for (int ph = 0; ph < 3; ph++) {
                bar_sync(ph + 2, 256);
                c0 = clk();
                if (ph == 2) {
                    msq = sum5(ldsf(sb + SM_PART + 12), ldsf(sb + SM_PART + 268), ldsf(sb + SM_PART + 524), ldsf(sb + SM_PART + 780), ldsf(sb + SM_PART + 1036)) * (1.f / D_MODEL);
                    bar_arrive(5, 256);
                }
                if (!(NOWIN >> ph & 1) && elect()) {
                    asm volatile("fence.proxy.async.shared::cta;" ::: "memory");
                    const uint32_t gap = ph == 0 ? WG1 : ph == 1 ? WG2 : WG3;
                    uint32_t c1 = c0 + (ph == 0 ? WD1 : ph == 1 ? WD2 : 0) + (warp - 5) * gap;
#pragma unroll 1
                    for (int k = warp + (ph == 0 ? -5 : ph == 1 && !(C96 && mlp == 96) ? 9 : 1); k < (ph == 0 ? 9 : ph == 1 ? 20 : C96 && mlp == 96 ? 0 : 14); k += 3, c1 += 3 * gap) {
                        const int i = ph == 0 && k >= 6 ? k + 23 : k;
                        const uint32_t bar = sb + SM_BAR + (i & 7) * 96 + 32 + (i & 24);
                        while ((int)(clk() - c1) < 0);
                        mbar_expect(bar, SUB);
                        tma_v(sb + SM_RING + i * SUB, tmk,
                              rowc * 3 + (i & 7) * 24 + ((UC<SCH.st[0].unit | SCH.st[1].unit << 8 | SCH.st[2].unit << 16 | SCH.st[3].unit << 24>::value >> (i & 24)) & 15) * 768, bar);
                    }
                }
                __syncwarp();
            }
            c0 += PCD;
        }
        {
            constexpr IC<1> L{};
            fresh();
            const int lz = lane;
            const unsigned char* xa[2];
#pragma unroll
            for (int i = 0; i < 2; i++) {
                const int col = xcol(2 * i, lz & 3), cw = j40 + (col >> 2);
                xa[i] = pin(accg + ACC_BYTES + ((cw >> 2) + (col & 2) * 20) * ACC_PITCH + (cw & 3) * 8);
            }
            const uint32_t pst = pin(prow + ((lz >> 2) * 8 + (lz & 1) * 4 + (lz & 2)) * 4);
            stsf(sb + SM_MSQ, msq);
            const float inv = shx(fx2_inv(msq), 0);
            if (!NWQ1) rap = pin(accg + ACC_BYTES + (c4() >> 2) * ACC_PITCH + (c4() & 3) * 8);
            fresh();
            if (!NWQ1) { maskA = pin(maskA); maskB = pin(maskB); }
            u64 w[3];
            uint32_t x2[3];
            auto xat = [&](int i) { return ((i & 2) ? xa[1] : xa[0]) + (i & 1) * 4 * ACC_PITCH; };
            if (warp < 5) {
                bar_sync(5, 256);
                if (DPRE) { while ((int)(clk() - c0) < WD4 + warp * WG4); if (warp < DPRE) refill2(IC<3>{}); }
            }
            while ((int)(clk() - c0) < ARDELAY);
#pragma unroll
            for (int i = 0; i < 3; i++) w[i] = ld_rlx(xat(i));
            if (warp < 5 && !(NOWIN & 8) && elect()) {
                if (DPOST) while ((int)(clk() - c0) < ARDELAY + DPOST);
                if (warp >= DPRE) issue_v(IC<3>{}, 0);
                if (warp < 4 && !P2LATE) issue_v(IC<2>{}, 4);
            }
            __syncwarp();
            fx2_wait<3, true>(xat, w, sb + SM_MSQ, inv, x2);
            TSTAMP(9);
            CSTAMP(22, x2[2]);
            q_proj(L, x2, pst);
            pass2();
            out_proj(L);
            if (warp >= 5) {
                bar_arrive(0, 256);
                if ((W1AT1 == 6 || W2AT1 == 6) && warp == 5 && elect()) { if (W1AT1 == 6) issue_w(L, 0); if (W2AT1 == 6) issue_w(L, 1); }
                TDUMP();
                return;
            }
            mlp_part(L);
            u64 old[2];
            auto add = [&]() {
#pragma unroll
                for (int k = 0; k < 2; k++) asm volatile("atom.relaxed.gpu.global.add.u64 %0, [%1], %2;" : "=l"(old[k]) : "l"(rap + k * 40 * ACC_PITCH), "l"(yw[k]) : "memory");
            };
            add();
            uint32_t* op = reinterpret_cast<uint32_t*>(P.out) + 2 * c4();
            if (wide) { send_wide(); add(); }
            TSTAMP(18);
            CSTAMP(17, hi32(yw[1]));
            const float inv2 = fx2_inv(msq);
            const uint32_t ep1 = lds32(sb + SM_EPOCH) + 1;
            CSTAMP(18, lo32(old[0]) ^ lo32(old[1]));
#pragma unroll
            for (int k = 0; k < 2; k++) {
                yw[k] += old[k];
                asm volatile("{\n.reg .pred p;\nsetp.eq.u32 p, %2, 96;\n@p st.global.u32 [%0], %1;\n}"
                             :: "l"(op + k), "r"(pack_bf(fx2_lo(yw[k], inv2), fx2_hi(yw[k], inv2))), "r"(lo32(yw[k]) & 511) : "memory");
            }
            if ((lo32(yw[0]) & 255) == 96 && tid == 0) g_epoch = ep1;
#pragma unroll
            for (int k = 0; k < 2; k++) if ((lo32(yw[k]) & 511) == 256 + 96) op[k] = fx2_wide(rap + k * 40 * ACC_PITCH, msq);
            TSTAMP(19);
            CSTAMP(19, lo32(yw[1]));
            TDUMP();
        }
    }
}

typedef CUresult (*EncodeFn)(CUtensorMap*, CUtensorMapDataType, cuuint32_t, void*, const cuuint64_t*, const cuuint64_t*, const cuuint32_t*,
                             const cuuint32_t*, CUtensorMapInterleave, CUtensorMapSwizzle, CUtensorMapL2promotion, CUtensorMapFloatOOBfill);

}

extern "C" void kernel_launch(void* const* d_in, const int* in_sizes, int n_in, void* d_out, int out_size) {
    (void)in_sizes; (void)n_in; (void)out_size;
    static EncodeFn enc = nullptr;
    if (!enc) {
        void* fn = nullptr;
        cudaDriverEntryPointQueryResult qr;
        cudaGetDriverEntryPoint("cuTensorMapEncodeTiled", &fn, cudaEnableDefault, &qr);
        enc = (EncodeFn)fn;
        cudaFuncSetAttribute(fused_kernel, cudaFuncAttributeMaxDynamicSharedMemorySize, SM_TOTAL);
    }
    Params P = {};
    auto map3 = [&](int m, int in, cuuint64_t d0, cuuint64_t d1, cuuint64_t d2, cuuint64_t s1, cuuint64_t s2, cuuint32_t b0, cuuint32_t b1, cuuint32_t b2,
                    CUtensorMapSwizzle sw, int promo) {
        const cuuint64_t dim[3] = {d0, d1, d2}, str[2] = {s1, s2};
        const cuuint32_t box[3] = {b0, b1, b2}, ones[3] = {1, 1, 1};
        enc(&P.tm[m], CU_TENSOR_MAP_DATA_TYPE_BFLOAT16, d2 ? 3 : 2, d_in[in], dim, str, box, ones, CU_TENSOR_MAP_INTERLEAVE_NONE, sw, (CUtensorMapL2promotion)promo,
            CU_TENSOR_MAP_FLOAT_OOB_FILL_NONE);
    };
    map3(TM_KH, 1, 64, 3, NHEAD * SK, 128, DH * 2, 64, 3, 32, CU_TENSOR_MAP_SWIZZLE_128B, 0);
    map3(TM_VH, 2, 64, 3, NHEAD * SK, 128, DH * 2, 64, 3, 32, CU_TENSOR_MAP_SWIZZLE_128B, 0);
    map3(TM_VP, 2, 64, 3, NHEAD * SK, 128, DH * 2, PFW, 3, 32, CU_TENSOR_MAP_SWIZZLE_NONE, 0);
    map3(TM_V, 2, 64, NHEAD * SK * 3, 0, 128, 0, 64, 24, 0, CU_TENSOR_MAP_SWIZZLE_128B, 0);
    map3(TM_WO, 4, 32, 20, NHEAD * DH, 64, D_MODEL * 2, 32, 1, DH, CU_TENSOR_MAP_SWIZZLE_64B, PROMOW);
    map3(TM_WOP, 4, 32, 20, NHEAD * DH, 64, D_MODEL * 2, PFW, 1, DH, CU_TENSOR_MAP_SWIZZLE_NONE, 0);
    map3(TM_WQ, 3, 64, NHEAD * 3, D_MODEL, 128, NHEAD * DH * 2, 64, 3, 32, CU_TENSOR_MAP_SWIZZLE_128B, 0);
    map3(TM_W1, 6, DFF, 128, 5, DFF * 2, DFF * 256, 16, 128, 5, CU_TENSOR_MAP_SWIZZLE_32B, PROMO1);
    map3(TM_W2, 8, 64, 10, DFF, 128, D_MODEL * 2, 64, 10, 16, CU_TENSOR_MAP_SWIZZLE_128B, 0);
    P.x = (const __nv_bfloat16*)d_in[0];
    P.k = (const __nv_bfloat16*)d_in[1];
    P.b1 = (const __nv_bfloat16*)d_in[7];
    P.b2 = (const __nv_bfloat16*)d_in[9];
    P.w1 = (const __nv_bfloat16*)d_in[6];
    P.out = (__nv_bfloat16*)d_out;
    for (int i = 0; i < 64; i++) P.tile[i] = make_uint4(SCH.tile[i][0], SCH.tile[i][1], SCH.tile[i][2], 0);
    fused_kernel<<<NCTA + 1, NTHR, SM_TOTAL, cudaStreamPerThread>>>(P);
}
```

```cpp
#include <cuda_runtime.h>
#include <cuda_bf16.h>
#include <cuda.h>
#include <stdint.h>

namespace {

constexpr int D_MODEL = 640, NHEAD = 32, SK = 32768, DH = 192, WIN = 4096, DFF = 1536;
constexpr int NCTA = 128, NTHR = 256;
constexpr int TILE = 64 * DH * 2;
constexpr int HALF = TILE / 2;
constexpr int SUB = 8 * DH * 2;
constexpr int SM_RING = 4 * TILE;
constexpr int SM_W2 = SM_RING + 20480, SM_W1 = SM_W2 + 20480;
constexpr int SM_WQR = 6 * TILE + HALF, SM_WQ = 7 * TILE;
constexpr int SM_PART = 9 * TILE;
constexpr int SM_EXC = SM_PART + 6144;
constexpr int SM_SC = SM_EXC + 1024;
constexpr int SM_BAR = SM_SC + 1024;
constexpr int SM_VEC = SM_BAR + 768;
constexpr int SM_CS = SM_VEC + 384;
constexpr int SM_FAC = SM_CS + 768;
constexpr int SM_ML = SM_FAC + 32;
constexpr int SM_B1 = SM_ML + 64;
constexpr int SM_STAT = SM_B1 + 64;
constexpr int NCB = 28;
constexpr int CB_WO = 18, CB_W1 = 23, CB_W2 = 24, CB_SNAP = 25, CB_REL = 26, CB_WQ = 27;
constexpr int SM_CBAR = SM_STAT + 48;
constexpr int SM_CNT = SM_CBAR + NCB * 8;
constexpr int SM_EPOCH = SM_CNT + NCB * 8;
constexpr int SM_FXS = SM_EPOCH + 4;
constexpr int SM_T0 = SM_FXS + 4;
constexpr int SM_MSQ = SM_T0 + 4;
constexpr int SM_M1 = SM_MSQ + 4;
constexpr int SM_TS = SM_M1 + 4;
constexpr int SM_TOTAL = 232448;
static_assert(SM_TS + 320 <= SM_TOTAL, "smem");
constexpr int NEXC = 16;

constexpr int SPIN = 1 << 20;
enum { TM_V = 0, TM_KH = 1, TM_VH = 2, TM_WO = 3, TM_VP = 4, TM_WOP = 5, TM_W1 = 6, TM_W2 = 7, TM_WQ = 8 };
constexpr uint32_t POL_NORMAL = 0x16F00000u, POL_FIRST = 0x12F00000u;

#define PACE 980
#define PACE0 1500
#define K0FIRST 1
#define NI1 6
#define ETRIG 0x54321000
#define LATEAT 5
#define HWAT 12
#define PFREE 66
#define W1AT0 3
#define W1AT1 3
#define AR1D 300
#define LAG0 12
#define NMMA 2
#define M1AT 1
#define M1P 3
#define NWO1 4
#define WG2 90
#define WG3 120
#define WD4 250
#define WG4 70
#define NWQ1 0
#define P4AT 0
#define P2LATE 0
#define W2AT1 6
#define PCD 150
#define NOWIN 0
#define DPRE 0
#define DPOST 200
#define NIM 4
#define PACES 1300
#define JP2 54
#define PACE2 0
#define WD2 0
#define W2PRE 2
#define OPOLL1 2
#define W2ONE 1
#define W1ONE 1
#define FX1LIM 524288.f
#define C96 0
#define SNAPAT 1
#define DMASK 0x0
#define WOKEEP 0x1f
#define VORD2 0x7685943a2b1cd0efull
#define VTRIG 0xba73210
#define WOAT 13
#define PARKS 0x95
#define VSLOT 0x1087654321087654ull
#define OPOLL 2
#define S0EARLY 1
#define NPRE 2
#define ARDELAY 1000
#define QDELAY 0
#define CMAP 0
#define PFW 8u
#define PUBAT 28
#define HW0 30
#define HW1 31
#define FX2LIM 524288.f
#define PROMOW 2
#define PROMO1 0
#define WD1 300
#define WG1 140
#define WPOL POL_NORMAL

constexpr uint32_t G_A = 1u << 28, G_B = 1u << 29, G_C = 1u << 30;
__host__ __device__ constexpr int ring_hs(int j) { return (j + 4) % 5; }
__host__ __device__ constexpr uint32_t load_word(int j) {
    if (j >= 64) return (uint32_t)(j - 64) << 20 | (SM_RING + ring_hs(j) * HALF) | TM_WO << 8 | (CB_WO + j - 64) << 3 | 2 | !(WOKEEP >> (j - 64) & 1);
    const int e = j >> 1, isv = e >= 16, unit = e & 15;
    return (uint32_t)(unit * 256 + (j & 1) * 32) << 20 | (j < 8 ? j * HALF : SM_RING + ring_hs(j) * HALF) | (TM_KH + isv) << 8 | (j < 8 ? 10 + j : (j - 8) % 10) << 3 | 2
           | (!isv || (DMASK >> unit & 1));
}
__host__ __device__ constexpr int popc(int v) { return v ? (v & 1) + popc(v >> 1) : 0; }
constexpr int NPARK = popc(PARKS);
constexpr int SM_SNAP = SM_RING + ring_hs(12) * HALF, SM_CSP = SM_RING + ring_hs(11) * HALF;
struct Step { int unit, slot, par, next, mma0, nmma; };
struct Sched { uint32_t tile[64][3]; Step st[16]; };
constexpr Sched make_sched() {
    Sched s{};
    for (int j = 0; j < 64; j++) {
        const int e = j >> 1;
        const uint32_t d = load_word(j);
        uint32_t w = (uint32_t)(j < 8 ? 0 : (j - 8) / 10 & 1) << 31 | (e & 15) * 4 << 20 | ((d & 0x3f000) - (j & 1) * HALF) | (d & 0xf8);
        if (e == PUBAT || e == SNAPAT) w |= G_A;
        if (e == HW0 || e == 4) w |= G_B;
        if ((e >= LATEAT && e < LATEAT + 4) || e == HW1) w |= G_C;
        s.tile[j][0] = w;
    }
    for (int j = NI1; j < 69; j++) {
        if (j == 12) continue;
        const int at = j < 12 ? (ETRIG >> (4 * (j - 4)) & 15) : j - 5;
        s.tile[at][1] = load_word(j);
        s.tile[at][2] = j >= PFREE ? 0 : PACE0 + j * PACE / 2 + (j > JP2 ? (j - JP2) * PACE2 : 0);
    }
    int done = 0;
    for (int p = 0; p < 16; p++) {
        Step& c = s.st[p];
        c.unit = (int)(VORD2 >> (4 * p) & 15); c.slot = (int)(VSLOT >> (4 * p) & 15); c.par = p >= 9; c.next = -1;
        c.mma0 = done;
        if (p >= NPARK) { const int avail = p - done + (p >= LAG0); c.nmma = p == 15 ? 16 - done : (avail < NMMA ? avail : NMMA); done += c.nmma; }
    }
    for (int p = 9; p < 16; p++) s.st[VTRIG >> (4 * (p - 9)) & 15].next = p;
    return s;
}
constexpr Sched SCH = make_sched();
__host__ __device__ constexpr int kunit(int o) { return o < 5 ? o + 11 : o == 5 ? 10 : o - 6; }

template <int I> struct IC { static constexpr int value = I; };
template <uint32_t I> struct UC { static constexpr uint32_t value = I; };
template <int A, int B, class F> __device__ __forceinline__ void static_for(F&& f) {
    if constexpr (A < B) { f(IC<A>{}); static_for<A + 1, B>(f); }
}

struct Params {
    CUtensorMap tm[9];
    const __nv_bfloat16 *x, *k, *b1, *b2, *w1;
    __nv_bfloat16* out;
    uint4 tile[66];
};

typedef unsigned long long u64;
constexpr int ACC_PITCH = 256;
constexpr int ACC_BYTES = 80 * ACC_PITCH;
__device__ __align__(1024) unsigned char g_acc[4 * ACC_BYTES];
__device__ __align__(1024) u64 g_l0[NCTA][384];
__device__ __align__(1024) u64 g_ll[2][NCTA][256];
__device__ unsigned g_epoch;
__device__ __align__(128) unsigned g_zflag;
#define TSTAMP(i)
#define TSTAMP2(i)
#define TSTAMPL(i)
#define TDUMP()
#define CSTAMP(i, x)
#define TRACE(i)

__device__ __forceinline__ void mbar_wait(uint32_t bar, uint32_t parity) {
    asm volatile("{\n.reg .pred p, q;\n.reg .u32 n;\nmov.u32 n, 0;\n"
                 "LOOP:\nmbarrier.try_wait.parity.shared::cta.b64 p, [%0], %1;\n"
                 "add.u32 n, n, 1;\nsetp.lt.and.u32 q, n, 0x100000, !p;\n@q bra.uni LOOP;\n}"
                 :: "r"(bar), "r"(parity) : "memory");
}
__device__ __forceinline__ bool mbar_test(uint32_t bar, uint32_t parity) {
    uint32_t r;
    asm volatile("{\n.reg .pred p;\nmbarrier.test_wait.parity.shared::cta.b64 p, [%1], %2;\nselp.u32 %0, 1, 0, p;\n}" : "=r"(r) : "r"(bar), "r"(parity) : "memory");
    return __all_sync(~0u, r);
}
__device__ __forceinline__ bool elect() {
    uint32_t r;
    asm volatile("{\n.reg .pred p;\nelect.sync _|p, 0xffffffff;\nselp.u32 %0, 1, 0, p;\n}" : "=r"(r));
    return r != 0;
}
__device__ __forceinline__ void mbar_expect(uint32_t bar, uint32_t bytes) {
    asm volatile("mbarrier.arrive.expect_tx.shared::cta.b64 _, [%0], %1;" :: "r"(bar), "r"(bytes) : "memory");
}
__device__ __forceinline__ uint4 lds128(uint32_t a) {
    uint4 v; asm volatile("ld.shared.v4.u32 {%0,%1,%2,%3}, [%4];" : "=r"(v.x), "=r"(v.y), "=r"(v.z), "=r"(v.w) : "r"(a) : "memory"); return v;
}
__device__ __forceinline__ uint4 ldsm_t(uint32_t a) {
    uint4 v; asm volatile("ldmatrix.sync.aligned.m8n8.x4.trans.shared.b16 {%0,%1,%2,%3}, [%4];" : "=r"(v.x), "=r"(v.y), "=r"(v.z), "=r"(v.w) : "r"(a) : "memory"); return v;
}
__device__ __forceinline__ uint2 lds64(uint32_t a) {
    uint2 v; asm volatile("ld.shared.v2.u32 {%0,%1}, [%2];" : "=r"(v.x), "=r"(v.y) : "r"(a) : "memory"); return v;
}
__device__ __forceinline__ float2 lds64f(uint32_t a) { const uint2 v = lds64(a); return make_float2(__uint_as_float(v.x), __uint_as_float(v.y)); }
__device__ __forceinline__ uint32_t lds32(uint32_t a) {
    uint32_t v; asm volatile("ld.shared.u32 %0, [%1];" : "=r"(v) : "r"(a) : "memory"); return v;
}
__device__ __forceinline__ float ldsf(uint32_t a) { return __uint_as_float(lds32(a)); }
__device__ __forceinline__ void sts32(uint32_t a, uint32_t v) { asm volatile("st.shared.u32 [%0], %1;" :: "r"(a), "r"(v) : "memory"); }
__device__ __forceinline__ void stsf(uint32_t a, float v) { sts32(a, __float_as_uint(v)); }
__device__ __forceinline__ void sts16(uint32_t a, uint32_t v) { asm volatile("st.shared.u16 [%0], %1;" :: "r"(a), "h"((uint16_t)v) : "memory"); }
__device__ __forceinline__ void sts64(uint32_t a, uint32_t x, uint32_t y) { asm volatile("st.shared.v2.u32 [%0], {%1,%2};" :: "r"(a), "r"(x), "r"(y) : "memory"); }
__device__ __forceinline__ void sts64f(uint32_t a, float x, float y) { sts64(a, __float_as_uint(x), __float_as_uint(y)); }
__device__ __forceinline__ void sts128f(uint32_t a, float x, float y, float z, float w) {
    asm volatile("st.shared.v4.f32 [%0], {%1,%2,%3,%4};" :: "r"(a), "f"(x), "f"(y), "f"(z), "f"(w) : "memory");
}
__device__ __forceinline__ void mma(float (&c)[4], const uint4& a, uint32_t b0, uint32_t b1) {
    asm volatile("mma.sync.aligned.m16n8k16.row.col.f32.bf16.bf16.f32 {%0,%1,%2,%3}, {%4,%5,%6,%7}, {%8,%9}, {%0,%1,%2,%3};"
                 : "+f"(c[0]), "+f"(c[1]), "+f"(c[2]), "+f"(c[3]) : "r"(a.x), "r"(a.y), "r"(a.z), "r"(a.w), "r"(b0), "r"(b1));
}
__device__ __forceinline__ u64 ld_rlx(const void* p) {
    u64 a; asm volatile("ld.relaxed.gpu.global.u64 %0, [%1];" : "=l"(a) : "l"(p) : "memory"); return a;
}
__device__ __forceinline__ void ld_rlx2(const void* p, u64& a, u64& b) {
    asm volatile("ld.relaxed.gpu.global.v2.u64 {%0,%1}, [%2];" : "=l"(a), "=l"(b) : "l"(p) : "memory");
}
__device__ __forceinline__ void st_rlx(void* p, u64 a) { asm volatile("st.relaxed.gpu.global.u64 [%0], %1;" :: "l"(p), "l"(a) : "memory"); }
__device__ __forceinline__ u64 ll_pack(float v, uint32_t tag) { return ((u64)tag << 32) | __float_as_uint(v); }
__device__ __forceinline__ float ll_val(u64 w) { return __uint_as_float((uint32_t)w); }
__device__ __forceinline__ uint32_t ll_tag(u64 w) { return (uint32_t)(w >> 32); }
__device__ __forceinline__ float bf_lo(uint32_t u) { return __uint_as_float(u << 16); }
__device__ __forceinline__ float bf_hi(uint32_t u) { return __uint_as_float(u & 0xffff0000u); }
__device__ __forceinline__ uint32_t pack_bf(float lo, float hi) {
    uint32_t r; asm("cvt.rn.bf16x2.f32 %0, %1, %2;" : "=r"(r) : "f"(hi), "f"(lo)); return r;
}
__device__ __forceinline__ float ex2(float v) { float r; asm("ex2.approx.ftz.f32 %0, %1;" : "=f"(r) : "f"(v)); return r; }
__device__ __forceinline__ float rcp(float v) { float r; asm("rcp.approx.ftz.f32 %0, %1;" : "=f"(r) : "f"(v)); return r; }
__device__ __forceinline__ float rsq(float v) { float r; asm("rsqrt.approx.ftz.f32 %0, %1;" : "=f"(r) : "f"(v)); return r; }
__device__ __forceinline__ void bar_sync(int id, int n) { asm volatile("bar.sync %0, %1;" :: "r"(id), "r"(n) : "memory"); }
__device__ __forceinline__ uint32_t clk() { uint32_t c; asm volatile("mov.u32 %0, %clock;" : "=r"(c)); return c; }
__device__ __forceinline__ uint32_t pin(uint32_t v) { return __shfl_xor_sync(~0u, v, 0); }
__device__ __forceinline__ float shx(float v, int o) { return __shfl_xor_sync(~0u, v, o); }

__device__ __forceinline__ u64 fx_pack(float v, float scale) { return ((u64)__float2ll_rn(v * scale) & ~255ull) | 1ull; }
__device__ __forceinline__ float fx_scale(float meansq) {
    const int e = max(((int)(__float_as_uint(meansq) >> 23) - 127) >> 1, -6);
    return __uint_as_float((uint32_t)(127 + 32 - e) << 23);
}
__device__ __forceinline__ float fx_inv(float scale) { return __uint_as_float((254u << 23) - __float_as_uint(scale)); }
__device__ __forceinline__ uint32_t lo32(u64 w) { uint32_t l; asm("mov.b64 {%0, _}, %1;" : "=r"(l) : "l"(w)); return l; }
__device__ __forceinline__ int hi32(u64 w) { int h; asm("mov.b64 {_, %0}, %1;" : "=r"(h) : "l"(w)); return h; }
__device__ __forceinline__ float fx_val(u64 w) { return (float)hi32(w) * 4294967296.f + (float)lo32(w); }
constexpr float FX2_ONE = 12582912.f;
__device__ __forceinline__ float fx2_scale(float meansq) { return __uint_as_float((uint32_t)(127 + 16 - max(((int)(__float_as_uint(meansq) >> 23) - 127) >> 1, -100)) << 23); }
__device__ __forceinline__ u64 fx2_pack(float a, float b) {
    const uint32_t lo = __float_as_uint(a) * 512u + (1u - 0x4b400000u * 512u);
    return lo | (u64)(__float_as_uint(b) * 16u - 0x4b400000u * 16u + (uint32_t)((int)lo >> 31)) << 32;
}
__device__ __forceinline__ float fx2_lo(u64 w, float inv) { return (float)(int)(__funnelshift_r(lo32(w), hi32(w), 4) & ~31u) * (inv * 0.5f); }
__device__ __forceinline__ float fx2_hi(u64 w, float inv) { return (float)((hi32(w) + 8) & ~15) * inv; }
__device__ __forceinline__ float fx2_inv(float meansq) { return fx_inv(fx2_scale(meansq)) * 0.0625f; }
__device__ __noinline__ uint32_t fx2_wide(const unsigned char* a, float meansq) {
    __threadfence();
    const u64 w = ld_rlx(a);
    const float inv = fx_inv(fx_scale(meansq));
    return pack_bf(fx2_lo(w, fx2_inv(meansq)) + fx_val(ld_rlx(a + 64)) * inv, fx2_hi(w, fx2_inv(meansq)) + fx_val(ld_rlx(a + 96)) * inv);
}
__device__ __noinline__ uint32_t fx1_wide(const unsigned char* a, float meansq) {
    __threadfence();
    const u64 w = ld_rlx(a);
    const unsigned char* b = a + 64 + (reinterpret_cast<u64>(a) & 31);
    const float inv = fx_inv(fx_scale(meansq)), inv1 = fx2_inv(meansq) * 0.5f;
    return pack_bf((float)(int)(lo32(w) & ~127u) * inv1 + fx_val(ld_rlx(b)) * inv, (float)(hi32(w) & ~127) * inv1 + fx_val(ld_rlx(b + 8)) * inv);
}
__device__ __noinline__ void fx_send(const unsigned char* wide, float v, float meansq, const unsigned char* a, uint32_t flag) {
    asm volatile("red.relaxed.gpu.global.add.u64 [%0], %1;" :: "l"(wide), "l"(fx_pack(v, fx_scale(meansq))) : "memory");
    __threadfence();
    asm volatile("red.relaxed.gpu.global.or.b32 [%0], %1;" :: "l"(a), "r"(flag) : "memory");
}
template <int N, class A, class F> __device__ __forceinline__ void fx2_wait(A a, F look, u64 (&w)[N], uint32_t msqa, float inv, uint32_t (&x)[N]) {
    auto get = [&]() {
#pragma unroll
        for (int i = 0; i < N; i++) x[i] = pack_bf(fx2_lo(w[i], inv), fx2_hi(w[i], inv));
    };
    get();
    if (__any_sync(~0u, ((lo32(w[0]) ^ 96) | (lo32(w[N - 1]) ^ 96)) & 0x160)) {
        int it = 0;
#pragma unroll 1
        while (__any_sync(~0u, ~(lo32(w[0]) & lo32(w[N - 1])) & 96) & (++it < SPIN)) look();
        get();
        if (__any_sync(~0u, (lo32(w[0]) | lo32(w[N - 1])) & 256)) {
#pragma unroll
            for (int i = 0; i < N; i++) x[i] = fx2_wide(a(i), ldsf(msqa));
        }
    }
}
__device__ __forceinline__ void st_rlx_if(bool p, void* a, u64 v) {
    asm volatile("{\n.reg .pred p;\nsetp.ne.u32 p, %2, 0;\n@p st.relaxed.gpu.global.u64 [%0], %1;\n}" :: "l"(a), "l"(v), "r"((uint32_t)p) : "memory");
}
__device__ __forceinline__ void sts128f(uint32_t a, const float (&v)[4]) { sts128f(a, v[0], v[1], v[2], v[3]); }
__device__ __forceinline__ void bar_arrive(int id, int n) { asm volatile("bar.arrive %0, %1;" :: "r"(id), "r"(n) : "memory"); }
template <class T> __device__ __forceinline__ T* pin(T* p) { return reinterpret_cast<T*>(__shfl_xor_sync(~0u, (u64)p, 0)); }

__device__ __forceinline__ void tma3(uint32_t dst, const CUtensorMap* tm, int c1, int c2, uint32_t bar, uint32_t pol) {
    asm volatile("cp.async.bulk.tensor.3d.shared::cluster.global.mbarrier::complete_tx::bytes.L2::cache_hint [%0], [%1, {%2, %3, %4}], [%5], %6;"
                 :: "r"(dst), "l"(tm), "r"(0), "r"(c1), "r"(c2), "r"(bar), "l"((u64)pol << 32) : "memory");
}
__device__ __forceinline__ void tma_v(uint32_t dst, const CUtensorMap* tm, int line, uint32_t bar) {
    asm volatile("cp.async.bulk.tensor.2d.shared::cluster.global.mbarrier::complete_tx::bytes.L2::cache_hint [%0], [%1, {%2, %3}], [%4], %5;"
                 :: "r"(dst), "l"(tm), "r"(0), "r"(line), "r"(bar), "l"((u64)POL_FIRST << 32) : "memory");
}
__device__ __forceinline__ void tma3_pf(const CUtensorMap* tm, int c1, int c2, uint32_t pol) {
    asm volatile("cp.async.bulk.prefetch.tensor.3d.L2.global.tile.L2::cache_hint [%0, {%1, %2, %3}], %4;"
                 :: "l"(tm), "r"(0), "r"(c1), "r"(c2), "l"((u64)pol << 32) : "memory");
}
__device__ __forceinline__ void issue_half(uint32_t d, uint32_t sb, int rowc, int cta, const CUtensorMap* tm0) {
    const uint32_t bar = sb + SM_CBAR + (d & 0xf8);
    const CUtensorMap* tm = tm0 + ((d >> 8) & 3);
    const bool wo = (d & 0x300) == TM_WO << 8;
    const int c1 = wo ? (cta & 3) + 4 * (d >> 20) : 0, c2 = wo ? (cta >> 2) * DH : rowc + (d >> 20);
    mbar_expect(bar, HALF);
    tma3(sb + (d & 0x3f000), tm, c1, c2, bar, POL_FIRST);
    if (!(d & 1)) tma3_pf(tm + 2, c1, c2, POL_NORMAL);
}
__device__ __forceinline__ uint32_t cnt_inc(uint32_t a, uint32_t last) {
    uint32_t old; asm volatile("atom.relaxed.cta.shared.inc.u32 %0, [%1], %2;" : "=r"(old) : "r"(a), "r"(last) : "memory"); return old;
}
__device__ __forceinline__ void wait_until(uint32_t due) {
#pragma unroll 1
    for (int it = 0; it < 4096; it++) { uint32_t now; asm volatile("mov.u32 %0, %globaltimer_lo;" : "=r"(now)); if ((int)(now - due) >= 0) break; }
}
__device__ __forceinline__ uint32_t bf2_mul(uint32_t a, uint32_t b) { uint32_t r; asm("mul.rn.bf16x2 %0, %1, %2;" : "=r"(r) : "r"(a), "r"(b)); return r; }
__device__ __forceinline__ uint32_t bf2_fma(uint32_t a, uint32_t b, uint32_t c) { uint32_t r; asm("fma.rn.bf16x2 %0, %1, %2, %3;" : "=r"(r) : "r"(a), "r"(b), "r"(c)); return r; }
__device__ __forceinline__ uint32_t bf2_amax(uint32_t a, uint32_t b) { uint32_t r; asm("max.NaN.xorsign.abs.bf16x2 %0, %1, %2;" : "=r"(r) : "r"(a), "r"(b)); return r; }
__device__ __forceinline__ uint4 k_unpack(uint32_t l0, uint32_t l1, uint32_t h, uint32_t m1) {
    const uint32_t ha = h & 0x87878787u, hc = ha * m1 + h, hb = __funnelshift_l(hc, hc, 4);
    return make_uint4(__byte_perm(l0, ha, 0x5140), __byte_perm(l0, ha, 0x7362), __byte_perm(l1, hb, 0x5140), __byte_perm(l1, hb, 0x7362));
}
#define KR4(u, i) "+r"(kr[u][i].x), "+r"(kr[u][i].y), "+r"(kr[u][i].z), "+r"(kr[u][i].w)
#define KR6(u) KR4(u, 0), KR4(u, 1), KR4(u, 2), KR4(u, 3), KR4(u, 4), KR4(u, 5)
__device__ __forceinline__ void k_keep(uint4 (&kr)[8][6], const uint32_t (&c)[18], int e, uint32_t a) {
    asm volatile("{\nKT: .branchtargets K0, K1, K2, K3, K4, K5, K6, K7, K8, K9, K10, K11, K12, K13, K14, K15;\nbrx.idx.uni %210, KT;\n"
                 "K0: mov.b32 %12, %192; mov.b32 %13, %193; mov.b32 %14, %194; mov.b32 %15, %195; mov.b32 %16, %196; mov.b32 %17, %197; mov.b32 %18, %198; mov.b32 %19, %199; mov.b32 %20, %200; mov.b32 %21, %201; mov.b32 %22, %202; mov.b32 %23, %203; mov.b32 %24, %204; mov.b32 %25, %205; mov.b32 %26, %206; mov.b32 %27, %207; mov.b32 %28, %208; mov.b32 %29, %209; bra.uni KE;\n"
                 "K1: mov.b32 %30, %192; mov.b32 %31, %193; mov.b32 %32, %194; mov.b32 %33, %195; mov.b32 %34, %196; mov.b32 %35, %197; mov.b32 %36, %198; mov.b32 %37, %199; mov.b32 %38, %200; mov.b32 %39, %201; mov.b32 %40, %202; mov.b32 %41, %203; mov.b32 %42, %204; mov.b32 %43, %205; mov.b32 %44, %206; mov.b32 %45, %207; mov.b32 %46, %208; mov.b32 %47, %209; bra.uni KE;\n"
                 "K2: mov.b32 %48, %192; mov.b32 %49, %193; mov.b32 %50, %194; mov.b32 %51, %195; mov.b32 %52, %196; mov.b32 %53, %197; mov.b32 %54, %198; mov.b32 %55, %199; mov.b32 %56, %200; mov.b32 %57, %201; mov.b32 %58, %202; mov.b32 %59, %203; mov.b32 %60, %204; mov.b32 %61, %205; mov.b32 %62, %206; mov.b32 %63, %207; mov.b32 %64, %208; mov.b32 %65, %209; bra.uni KE;\n"
                 "K3: mov.b32 %66, %192; mov.b32 %67, %193; mov.b32 %68, %194; mov.b32 %69, %195; mov.b32 %70, %196; mov.b32 %71, %197; mov.b32 %72, %198; mov.b32 %73, %199; mov.b32 %74, %200; mov.b32 %75, %201; mov.b32 %76, %202; mov.b32 %77, %203; mov.b32 %78, %204; mov.b32 %79, %205; mov.b32 %80, %206; mov.b32 %81, %207; mov.b32 %82, %208; mov.b32 %83, %209; bra.uni KE;\n"
                 "K4: mov.b32 %84, %192; mov.b32 %85, %193; mov.b32 %86, %194; mov.b32 %87, %195; mov.b32 %88, %196; mov.b32 %89, %197; mov.b32 %90, %198; mov.b32 %91, %199; mov.b32 %92, %200; mov.b32 %93, %201; mov.b32 %94, %202; mov.b32 %95, %203; mov.b32 %96, %204; mov.b32 %97, %205; mov.b32 %98, %206; mov.b32 %99, %207; mov.b32 %100, %208; mov.b32 %101, %209; bra.uni KE;\n"
                 "K5: mov.b32 %102, %192; mov.b32 %103, %193; mov.b32 %104, %194; mov.b32 %105, %195; mov.b32 %106, %196; mov.b32 %107, %197; mov.b32 %108, %198; mov.b32 %109, %199; mov.b32 %110, %200; mov.b32 %111, %201; mov.b32 %112, %202; mov.b32 %113, %203; mov.b32 %114, %204; mov.b32 %115, %205; mov.b32 %116, %206; mov.b32 %117, %207; mov.b32 %118, %208; mov.b32 %119, %209; bra.uni KE;\n"
                 "K6: mov.b32 %120, %192; mov.b32 %121, %193; mov.b32 %122, %194; mov.b32 %123, %195; mov.b32 %124, %196; mov.b32 %125, %197; mov.b32 %126, %198; mov.b32 %127, %199; mov.b32 %128, %200; mov.b32 %129, %201; mov.b32 %130, %202; mov.b32 %131, %203; mov.b32 %132, %204; mov.b32 %133, %205; mov.b32 %134, %206; mov.b32 %135, %207; mov.b32 %136, %208; mov.b32 %137, %209; bra.uni KE;\n"
                 "K7: mov.b32 %138, %192; mov.b32 %139, %193; mov.b32 %140, %194; mov.b32 %141, %195; mov.b32 %142, %196; mov.b32 %143, %197; mov.b32 %144, %198; mov.b32 %145, %199; mov.b32 %146, %200; mov.b32 %147, %201; mov.b32 %148, %202; mov.b32 %149, %203; mov.b32 %150, %204; mov.b32 %151, %205; mov.b32 %152, %206; mov.b32 %153, %207; mov.b32 %154, %208; mov.b32 %155, %209; bra.uni KE;\n"
                 "K8: mov.b32 %156, %192; mov.b32 %157, %193; mov.b32 %158, %194; mov.b32 %159, %195; mov.b32 %160, %196; mov.b32 %161, %197; mov.b32 %162, %198; mov.b32 %163, %199; mov.b32 %164, %200; mov.b32 %165, %201; mov.b32 %166, %202; mov.b32 %167, %203; mov.b32 %168, %204; mov.b32 %169, %205; mov.b32 %170, %206; mov.b32 %171, %207; mov.b32 %172, %208; mov.b32 %173, %209; bra.uni KE;\n"
                 "K9: mov.b32 %174, %192; mov.b32 %175, %193; mov.b32 %176, %194; mov.b32 %177, %195; mov.b32 %178, %196; mov.b32 %179, %197; mov.b32 %180, %198; mov.b32 %181, %199; mov.b32 %182, %200; mov.b32 %183, %201; mov.b32 %184, %202; mov.b32 %185, %203; mov.b32 %186, %204; mov.b32 %187, %205; mov.b32 %188, %206; mov.b32 %189, %207; mov.b32 %190, %208; mov.b32 %191, %209; bra.uni KE;\n"
                 "K10: st.shared.v2.b32 [%211+75784], {%192, %193}; st.shared.v2.b32 [%211+76288], {%194, %195}; st.shared.v2.b32 [%211+76296], {%196, %197}; mov.b32 %0, %198; mov.b32 %1, %199; mov.b32 %2, %200; mov.b32 %3, %201; mov.b32 %4, %202; mov.b32 %5, %203; mov.b32 %6, %204; mov.b32 %7, %205; mov.b32 %8, %206; mov.b32 %9, %207; mov.b32 %10, %208; mov.b32 %11, %209; bra.uni KE;\n"
                 "K11: st.shared.v2.b32 [%211+0], {%192, %193}; st.shared.v2.b32 [%211+8], {%194, %195}; st.shared.v2.b32 [%211+512], {%196, %197}; st.shared.v2.b32 [%211+520], {%198, %199}; st.shared.v2.b32 [%211+1024], {%200, %201}; st.shared.v2.b32 [%211+1032], {%202, %203}; st.shared.v2.b32 [%211+1536], {%204, %205}; st.shared.v2.b32 [%211+1544], {%206, %207}; st.shared.v2.b32 [%211+2048], {%208, %209}; bra.uni KE;\n"
                 "K12: st.shared.v2.b32 [%211+2056], {%192, %193}; st.shared.v2.b32 [%211+2560], {%194, %195}; st.shared.v2.b32 [%211+2568], {%196, %197}; st.shared.v2.b32 [%211+24576], {%198, %199}; st.shared.v2.b32 [%211+24584], {%200, %201}; st.shared.v2.b32 [%211+25088], {%202, %203}; st.shared.v2.b32 [%211+25096], {%204, %205}; st.shared.v2.b32 [%211+25600], {%206, %207}; st.shared.v2.b32 [%211+25608], {%208, %209}; bra.uni KE;\n"
                 "K13: st.shared.v2.b32 [%211+26112], {%192, %193}; st.shared.v2.b32 [%211+26120], {%194, %195}; st.shared.v2.b32 [%211+26624], {%196, %197}; st.shared.v2.b32 [%211+26632], {%198, %199}; st.shared.v2.b32 [%211+27136], {%200, %201}; st.shared.v2.b32 [%211+27144], {%202, %203}; st.shared.v2.b32 [%211+49152], {%204, %205}; st.shared.v2.b32 [%211+49160], {%206, %207}; st.shared.v2.b32 [%211+49664], {%208, %209}; bra.uni KE;\n"
                 "K14: st.shared.v2.b32 [%211+49672], {%192, %193}; st.shared.v2.b32 [%211+50176], {%194, %195}; st.shared.v2.b32 [%211+50184], {%196, %197}; st.shared.v2.b32 [%211+50688], {%198, %199}; st.shared.v2.b32 [%211+50696], {%200, %201}; st.shared.v2.b32 [%211+51200], {%202, %203}; st.shared.v2.b32 [%211+51208], {%204, %205}; st.shared.v2.b32 [%211+51712], {%206, %207}; st.shared.v2.b32 [%211+51720], {%208, %209}; bra.uni KE;\n"
                 "K15: st.shared.v2.b32 [%211+73728], {%192, %193}; st.shared.v2.b32 [%211+73736], {%194, %195}; st.shared.v2.b32 [%211+74240], {%196, %197}; st.shared.v2.b32 [%211+74248], {%198, %199}; st.shared.v2.b32 [%211+74752], {%200, %201}; st.shared.v2.b32 [%211+74760], {%202, %203}; st.shared.v2.b32 [%211+75264], {%204, %205}; st.shared.v2.b32 [%211+75272], {%206, %207}; st.shared.v2.b32 [%211+75776], {%208, %209}; \nKE:\n}"
                 : KR6(0), KR6(1), KR6(2), KR6(3), KR6(4), KR6(5), KR6(6), KR6(7)
                 : "r"(c[0]), "r"(c[1]), "r"(c[2]), "r"(c[3]), "r"(c[4]), "r"(c[5]), "r"(c[6]), "r"(c[7]), "r"(c[8]), "r"(c[9]), "r"(c[10]), "r"(c[11]), "r"(c[12]), "r"(c[13]), "r"(c[14]), "r"(c[15]), "r"(c[16]), "r"(c[17]), "r"(e), "r"(a) : "memory");
}
__device__ __forceinline__ uint32_t smem_base() { extern __shared__ __align__(1024) unsigned char smem[]; return (uint32_t)__cvta_generic_to_shared(smem); }
__device__ __forceinline__ void k_rare(uint4 v0, uint4 v1, uint4 v2, uint4 v3, uint4 v4, uint4 v5, uint32_t odd, int e, int warp, int lane) {
    const uint32_t sb = smem_base(), g = lane >> 2, t = lane & 3, st = sb + SM_BAR + warp * 96 + 80;
    uint32_t lt; asm volatile("mov.u32 %0, %lanemask_lt;" : "=r"(lt));
    const uint4 v[6] = {v0, v1, v2, v3, v4, v5};
    odd <<= 6;
#pragma unroll
    for (int i = 0; i < 6; i++) if (v[i].x | v[i].y | v[i].z | v[i].w) odd |= 1u << i;
    odd = __reduce_or_sync(~0u, odd);
    uint32_t n = odd >= 64 ? NEXC + 1 : __shfl_sync(~0u, lds32(st), 0);
#pragma unroll 1
    for (; odd && n <= NEXC; odd &= odd - 1) {
        const int i = __ffs(odd) - 1;
#pragma unroll
        for (int k = 1; k < 6; k++) if (i == k) v0 = v[k];
#pragma unroll 1
        for (int k = 0; k < 4; k++, v0.x = v0.y, v0.y = v0.z, v0.z = v0.w) {
            const uint32_t who = __ballot_sync(~0u, v0.x), at = n + __popc(who & lt);
            sts64(v0.x && at < NEXC ? sb + SM_EXC + warp * 128 + at * 8 : st + 8, v0.x, (e * 32 + g * 4) << 16 | (((k & 1) * 4 + t) * 48 + i * 8 + (k >> 1) * 4));
            n += __popc(who);
        }
    }
    const uint32_t bad = lds32(st + 4);
    __syncwarp();
    if (n <= NEXC) sts32(st, n);
    else {
        sts32(st + 4, bad | 1u << e);
        asm volatile("st.shared.u8 [%0], %1;" :: "r"(sb + SM_SC + warp * 128 + g * 16 + (e & 3) * 4 + (e >> 2)), "r"(0) : "memory");
    }
    __syncwarp();
}
template <int K> __device__ __forceinline__ uint32_t& word(uint4& v) { if constexpr (K == 0) return v.x; else if constexpr (K == 1) return v.y; else if constexpr (K == 2) return v.z; else return v.w; }
__device__ __forceinline__ void add_if(bool p, float& d, float a, float b) {
    asm volatile("{\n.reg .pred p;\nsetp.ne.u32 p, %3, 0;\n@p add.f32 %0, %1, %2;\n}" : "+f"(d) : "f"(a), "f"(b), "r"((uint32_t)p));
}
__device__ __forceinline__ float warp_max(float v) {
#pragma unroll
    for (int o = 16; o; o >>= 1) v = fmaxf(v, shx(v, o));
    return v;
}
__device__ __forceinline__ float warp_sum(float v) {
#pragma unroll
    for (int o = 16; o; o >>= 1) v += shx(v, o);
    return v;
}
template <int PITCH> __device__ __forceinline__ void ll_look(const u64* buf, u64 (&w)[4]) {
#pragma unroll
    for (int i = 0; i < 4; i++) w[i] = ld_rlx(buf + i * PITCH);
}
template <int PITCH> __device__ __forceinline__ float ll_gather(const u64* buf, uint32_t tag, u64 (&w)[4]) {
    auto miss = [&]() { return __any_sync(~0u, ((ll_tag(w[0]) ^ tag) | (ll_tag(w[1]) ^ tag)) | ((ll_tag(w[2]) ^ tag) | (ll_tag(w[3]) ^ tag))); };
    int it = 0;
    goto check;
again:
    ll_look<PITCH>(buf, w);
check:
    if (miss() & (++it < SPIN)) goto again;
    return (ll_val(w[0]) + ll_val(w[1])) + (ll_val(w[2]) + ll_val(w[3]));
}
__device__ __forceinline__ float sum8(uint32_t a, int pitch) {
    float s[8];
#pragma unroll
    for (int w = 0; w < 8; w++) s[w] = ldsf(a + w * pitch);
    return ((s[0] + s[1]) + (s[2] + s[3])) + ((s[4] + s[5]) + (s[6] + s[7]));
}
__device__ __forceinline__ float sum5(float a, float b, float c, float d, float e) { return ((a + b) + (c + d)) + e; }
__device__ __forceinline__ float ln_part(uint2 xp, int lane) {
    const float x0 = bf_lo(xp.x), x1 = bf_hi(xp.x), x2 = bf_lo(xp.y), x3 = bf_hi(xp.y);
    const float s1 = (x0 + x1) + (x2 + x3), s2 = (x0 * x0 + x1 * x1) + (x2 * x2 + x3 * x3);
    return ((lane & 16) ? s2 : s1) + shx((lane & 16) ? s1 : s2, 16);
}
__device__ __forceinline__ float ln_rstd(float mean, float msq) { return rsq(fmaxf(msq - mean * mean, 0.f) + 1e-5f); }
__device__ __forceinline__ float score(const uint4 (&v)[6], const uint4 (&qf)[3]) {
    float d[2][4];
#pragma unroll
    for (int j = 0; j < 2; j++) d[j][0] = d[j][1] = d[j][2] = d[j][3] = 0.f;
#pragma unroll
    for (int i = 0; i < 3; i++) { mma(d[0], v[2 * i], qf[i].x, qf[i].y); mma(d[1], v[2 * i + 1], qf[i].z, qf[i].w); }
    return (d[0][0] + d[0][3]) + (d[1][0] + d[1][3]);
}
__device__ __forceinline__ float k_side(uint32_t sb, uint2 x) {
    const uint32_t qq = lds32(sb + SM_VEC + (x.y & 0xffff));
    return (bf_lo(x.x) * bf_lo(qq) + bf_hi(x.x) * bf_hi(qq)) * 0x1p-64f;
}
__device__ __forceinline__ void k_fix(const __nv_bfloat16* k, uint32_t bad, int warp, int lane) {
    const uint32_t sb = smem_base(), g = lane >> 2, sa = sb + SM_PART + warp * 768 + 256;
    const uint2 x = lds64(sb + SM_EXC + warp * 128 + (lane & 15) * 8);
    if ((int)x.y >= 0x40000000 && lane < 16) asm volatile("red.shared.add.f32 [%0], %1;" :: "r"(sa + ((x.y >> 16) & 511)), "f"(k_side(sb, x)) : "memory");
    __syncwarp();
#pragma unroll 1
    for (bad &= 0xffff; bad; bad &= bad - 1) {
        const int e = __ffs(bad) - 1;
        const __nv_bfloat16* kp = k + (e * 256 + (g >> 1) + 4 * (g & 1)) * DH + (lane & 3) * 8;
        uint4 v[6], qf[3];
#pragma unroll
        for (int i = 0; i < 6; i++) v[i] = *reinterpret_cast<const uint4*>(kp + i * 32);
#pragma unroll
        for (int i = 0; i < 3; i++) qf[i] = lds128(sb + SM_VEC + (lane & 7) * 48 + i * 16);
        stsf(sa + e * 32 + g * 4, score(v, qf) * 0x1p-64f);
    }
    __syncwarp();
}
constexpr float CS = 0.07216878364870322f * 1.4426950408889634f;
__device__ __forceinline__ void head_weight(const u64* a, u64 pm, u64 pl, int layer, int lane) {
    const uint32_t sb = smem_base(), tag = lds32(sb + SM_EPOCH) * 4 + 2 + 2 * layer;
#pragma unroll 1
    for (int it = 0; it < SPIN; it++) {
        if (__all_sync(~0u, ll_tag(pm) == tag && ll_tag(pl) == tag)) break;
        ld_rlx2(a, pm, pl);
    }
    const float f = ex2((ll_val(pm) - warp_max(ll_val(pm))) * CS);
    const float w = f * rcp(warp_sum(f * ll_val(pl)));
    if (lane < 8) stsf(sb + SM_FAC + lane * 4, w);
}
constexpr uint32_t ONES = 0x3f803f80u;

__global__ void __launch_bounds__(NTHR, 1) fused_kernel(const __grid_constant__ Params P) {
    const uint32_t sb = smem_base();
    const int bx = blockIdx.x;
    const int cta0 = bx >= NCTA || CMAP == 0 ? bx : CMAP == 4 ? (((bx >> 1) & 7) + (bx >> 5) * 8) * 4 + ((bx >> 4) & 1) * 2 + (bx & 1)
                   : (((bx >> 1) & 15) + (bx >> 6) * 16) * 4 + ((bx >> 5) & 1) * 2 + (bx & 1);
    if (__all_sync(~0u, threadIdx.x >= NTHR - 32 && bx < NCTA) && elect()) {
        asm volatile("mbarrier.init.shared::cta.b64 [%0], 1;" :: "r"(sb + SM_CBAR + CB_WQ * 8));
        asm volatile("mbarrier.init.shared::cta.b64 [%0], 1;" :: "r"(sb + SM_CBAR + 80));
        asm volatile("fence.mbarrier_init.release.cluster;" ::: "memory");
        mbar_expect(sb + SM_CBAR + CB_WQ * 8, 5 * HALF);
        auto k0 = [&]() {
            mbar_expect(sb + SM_CBAR + 80, HALF);
            tma3(sb, &P.tm[TM_KH], 0, (cta0 >> 2) * SK + (SK - WIN) + (cta0 & 3) * 64, sb + SM_CBAR + 80, POL_FIRST);
        };
        if (K0FIRST) k0();
#pragma unroll 1
        for (int i = 0; i < 5; i++) tma3(sb + SM_WQR + (i == 4 ? 0 : i + 1) * HALF, &P.tm[TM_WQ], (cta0 >> 2) * 3, (cta0 & 3) * 160 + i * 32, sb + SM_CBAR + CB_WQ * 8, POL_FIRST);
        if (!K0FIRST) k0();
    }
    __syncwarp();
    int id = cta0 * NTHR + threadIdx.x, tid, lane, g, t, key, warp, cta, mlp, rowc, roww, j40;
    uint32_t maskA, maskB, barw, subw, prow;
    auto fresh = [&]() {
        const int cw = __shfl_sync(~0u, id >> 5, 0);
        id = pin(id); tid = id & 255; lane = id & 31; g = lane >> 2; t = lane & 3; key = (g >> 1) + 4 * (g & 1);
        const uint32_t m = (g & 1) ? 0xffff0000u : 0x0000ffffu;
        maskA = (g & 2) ? 0u : m; maskB = (g & 2) ? m : 0u;
        warp = cw & 7; cta = cw >> 3;
        mlp = (cta & 3) == 3 ? 96 : (cta >> 2) * 3 + (cta & 3);
        rowc = (cta >> 2) * SK + (SK - WIN) + (cta & 3) * 64; roww = rowc + warp * 8;
        j40 = (cta & 3) * 40;
        barw = sb + SM_BAR + warp * 96; subw = sb + warp * SUB; prow = sb + SM_PART + warp * 768;
    };
    fresh();

    if (cta == NCTA) {
        const uint32_t ep = *(volatile unsigned*)&g_epoch;
        if (tid == 0) {
#pragma unroll 1
            for (int it = 0; it < SPIN; it++) { if (ll_tag(ld_rlx(&g_ll[0][0][192])) == ep * 4 + 2) break; __nanosleep(200); }
        }
        __syncthreads();
#pragma unroll 1
        for (int i = tid; i < 4 * 80 * 8; i += NTHR)
            *reinterpret_cast<uint4*>(g_acc + (i >> 3) * ACC_PITCH + (i & 7) * 16) = make_uint4(0, 0, 0, 0);
        __threadfence();
        __syncthreads();
        if (tid == 0) asm volatile("st.relaxed.gpu.global.u32 [%0], %1;" :: "l"(&g_zflag), "r"(ep + 1) : "memory");
        return;
    }
    TSTAMP(0);
    if (tid == 64) { uint32_t now; asm volatile("mov.u32 %0, %globaltimer_lo;" : "=r"(now)); sts32(sb + SM_T0, now); }

    const CUtensorMap* tmk = reinterpret_cast<const CUtensorMap*>(__shfl_sync(~0u, (u64)&P.tm[0] + (lane >> 5), 0));
    auto c4 = [&]() { return 32 * min(warp, 4) + 16 * (t >> 1) + 2 * g + (t & 1); };
    auto xcol = [&](int i, int tt) { return (i < 2 ? 64 * i + 8 * warp : 128 + 8 * (warp >> 1)) + 2 * tt; };
    uint2 xp;
    uint32_t px[3], small;
    auto issue_first = [&](int j) {
        mbar_expect(sb + SM_CBAR + 80 + j * 8, HALF);
        tma3(sb + j * HALF, tmk + TM_KH, 0, rowc + (j >> 1) * 256 + (j & 1) * 32, sb + SM_CBAR + 80 + j * 8, POL_FIRST);
    };
    if (elect()) {
        if (warp != 2) asm volatile("mbarrier.init.shared::cta.b64 [%0], 1;" :: "r"(sb + SM_CBAR + 64 + warp * 8));
#pragma unroll
        for (int i = 0; i < 9; i++) asm volatile("mbarrier.init.shared::cta.b64 [%0], 1;" :: "r"(barw + i * 8));
        asm volatile("mbarrier.init.shared::cta.b64 [%0], 1;" :: "r"(sb + SM_CBAR + warp * 8));
        asm volatile("mbarrier.init.shared::cta.b64 [%0], 1;" :: "r"(sb + SM_CBAR + 128 + warp * 8));
        if (warp < 3) asm volatile("mbarrier.init.shared::cta.b64 [%0], %1;" :: "r"(sb + SM_CBAR + 192 + warp * 8), "r"(warp == 2 ? 8 : 1));
        sts64(barw + 80, 0, 0);
        asm volatile("fence.mbarrier_init.release.cluster;" ::: "memory");
        asm volatile("prefetch.tensormap [%0];" :: "l"(tmk + warp) : "memory");
    }
    __syncwarp();
    asm volatile("ld.global.nc.v2.u32 {%0,%1}, [%2];" : "=r"(xp.x), "=r"(xp.y) : "l"(P.x + 4 * c4()) : "memory");
#pragma unroll
    for (int i = 0; i < 3; i++) asm volatile("ld.global.nc.u32 %0, [%1];" : "=r"(px[i]) : "l"(P.x + 4 * j40 + xcol(i, t)) : "memory");
    asm volatile("ld.relaxed.gpu.global.u32 %0, [%1];" : "=r"(small) : "l"(lane < 16 ? (const void*)(P.b1 + min(mlp, 95) * 16 + (lane & 14)) : (const void*)&g_epoch) : "memory");
    if (tid >= 192 && tid < 192 + NCB) sts32(sb + SM_CNT + (tid - 192) * 8, 0);
    unsigned char* accg = reinterpret_cast<unsigned char*>(__shfl_sync(~0u, (u64)g_acc + (lane >> 5), 0));
    auto release = [&](const uint4& tw) {
        uint32_t old;
        __syncwarp();
        asm volatile("atom.relaxed.cta.shared.add.u32 %0, [%1], 1;" : "=r"(old) : "r"(sb + SM_CNT + (tw.x & 0xf8)) : "memory");
        return old;
    };
    auto refill = [&](const uint4& tw, uint32_t old) {
        if (__any_sync(~0u, (old & 127) == 127 && (tw.y & 2))) {
            wait_until(lds32(sb + SM_T0) + tw.z);
            if (elect()) issue_half(tw.y, sb, rowc, cta, tmk);
            __syncwarp();
        }
    };
    __syncthreads();
    auto issue_paced = [&](int j0, int j1) {
        if (warp >= j0 && warp < j1) {
            wait_until(lds32(sb + SM_T0) + PACES + warp * PACE / 2);
            if (elect()) issue_first(warp);
            __syncwarp();
        }
    };

    uint32_t offV0, offV2;
    auto calc_offsets = [&]() {
        offV0 = subw + (6 * t) * 128 + ((g ^ ((6 * t) & 7)) << 4);
        offV2 = subw + (6 * t + 2) * 128 + ((g ^ ((6 * t + 2) & 7)) << 4);
    };
    calc_offsets();

    auto load_v = [&](uint4 (&v)[6], uint32_t so) {
        v[0] = lds128(offV0 + so); v[1] = lds128((offV0 ^ 16) + so + 128); v[2] = lds128(offV2 + so);
        v[3] = lds128((offV2 ^ 16) + so + 128); v[4] = lds128((offV0 ^ 64) + so + 512); v[5] = lds128((offV0 ^ 80) + so + 640);
    };
    auto issue_v = [&](auto I, int dw) {
        constexpr Step c = SCH.st[I.value];
        const uint32_t bar = barw + dw * 96 + c.slot * 8;
        mbar_expect(bar, SUB);
        tma_v(subw + dw * SUB + c.slot * TILE, tmk, roww * 3 + dw * 24 + c.unit * 768, bar);
    };
    auto refill2 = [&](auto I) { __syncwarp(); if (elect()) issue_v(I, 0); };
    uint4 wq0[6], wqh[3], wq1[6];
    auto load_wq1 = [&](int i) { wq1[i] = lds128((i == 2 ? offV2 : i == 3 ? (offV2 ^ 16) + 128 : (offV0 ^ (i * 16)) + i * 128) + SM_WQ + TILE); };
    auto load_wq = [&]() {
        load_v(wq0, SM_WQ);
        const uint32_t so = SM_WQR - ((warp + 1) >> 1) * SUB;
        wqh[0] = lds128(((warp & 1) ? (offV2 ^ 16) + 128 : offV0) + so);
        wqh[1] = lds128(((warp & 1) ? (offV0 ^ 64) + 512 : (offV0 ^ 16) + 128) + so);
        wqh[2] = lds128(((warp & 1) ? (offV0 ^ 80) + 640 : offV2) + so);
#pragma unroll
        for (int i = 0; i < NWQ1; i++) load_wq1(i);
    };
    uint4 kr[8][6];
    const unsigned char* rap;
    u64 rw[2];
    auto look_rw = [&]() { rw[0] = ld_rlx(rap); rw[1] = ld_rlx(rap + 40 * ACC_PITCH); };
    auto q_proj = [&](auto L, uint32_t (&p)[3], uint32_t pst) {
        if (L.value == 0 && g >= 4) p[0] = p[1] = p[2] = ONES;
        float a[3][4], b[3][4];
        const uint32_t dH = __byte_perm(p[2], 0, (warp & 1) ? 0x3232 : 0x1010);
        const uint32_t dA = __byte_perm(p[0], 0, 0x1010), dB = __byte_perm(p[0], 0, 0x3232), dC = __byte_perm(p[1], 0, 0x1010), dD = __byte_perm(p[1], 0, 0x3232);
#pragma unroll
        for (int i = NWQ1; i < 3; i++) load_wq1(i);
#pragma unroll
        for (int j = 0; j < 3; j++) { a[j][0] = a[j][1] = a[j][2] = a[j][3] = 0.f; mma(a[j], wq0[j], dA & maskA, dA & maskB); }
#pragma unroll
        for (int j = 0; j < 3; j++) { b[j][0] = b[j][1] = b[j][2] = b[j][3] = 0.f; mma(b[j], wq0[j + 3], dB & maskA, dB & maskB); }
#pragma unroll
        for (int j = 0; j < 3; j++) mma(a[j], wqh[j], dH & maskA, dH & maskB);
#pragma unroll
        for (int i = 3; i < 6; i++) load_wq1(i);
        if (L.value == 1 && P4AT == 2) refill2(IC<4>{});
#pragma unroll
        for (int j = 0; j < 3; j++) mma(b[j], wq1[j], dC & maskA, dC & maskB);
#pragma unroll
        for (int j = 0; j < 3; j++) mma(a[j], wq1[j + 3], dD & maskA, dD & maskB);
#pragma unroll
        for (int j = 0; j < 3; j++) {
            if (L.value) {
#pragma unroll
                for (int k = 0; k < 2; k++) { a[j][k] += b[j][k]; add_if(t & 2, a[j][k], a[j][k + 2], b[j][k + 2]); }
                sts64f(pst + j * 256, a[j][0], a[j][1]);
            } else sts128f(pst + j * 256, a[j][0] + b[j][0], a[j][1] + b[j][1], a[j][2] + b[j][2], a[j][3] + b[j][3]);
        }
        CSTAMP(23, __float_as_uint(a[2][1]));
        uint32_t tag;
        if (L.value) tag = lds32(sb + SM_EPOCH) * 4 + 3;
        u64* pub = L.value ? &g_ll[0][cta][tid] : &g_l0[cta][tid];
        if (L.value == 0) asm volatile("fence.proxy.async.shared::cta;" ::: "memory");
        TSTAMPL(21);
        __syncthreads();
        if (!L.value) tag = lds32(sb + SM_EPOCH) * 4 + 1;
#pragma unroll 1
        for (int k = 0; k < 2 - L.value; k++) st_rlx_if(tid < 192, pub + k * 192, ll_pack(sum8(sb + (k ? SM_CSP : SM_PART) + tid * 4, 768), tag));
        TSTAMPL(23);
            CSTAMP(24, tag);
    };
    auto ln_stats = [&]() {
        float ss = ln_part(xp, lane);
        ss += shx(ss, 8); ss += shx(ss, 4); ss += shx(ss, 2); ss += shx(ss, 1);
        stsf(sb + SM_STAT + min(warp, 5) * 8 + (lane >> 4) * 4, ss);
    };
    auto ln_final = [&](float& mean, float& rstd) {
        float2 v[5];
#pragma unroll
        for (int w = 0; w < 5; w++) v[w] = lds64f(sb + SM_STAT + w * 8);
        mean = sum5(v[0].x, v[1].x, v[2].x, v[3].x, v[4].x) * (1.f / D_MODEL);
        const float msq = sum5(v[0].y, v[1].y, v[2].y, v[3].y, v[4].y) * (1.f / D_MODEL);
        rstd = ln_rstd(mean, msq);
        stsf(sb + SM_FXS, msq);
    };
    auto q_addr = [&](int d) { return sb + SM_VEC + (((d >> 1) & 1) * 4 + ((d >> 3) & 3)) * 48 + (d >> 5) * 8 + ((d >> 2) & 1) * 4 + (d & 1) * 2; };
    {
#pragma unroll
        for (int u = 0; u < 8; u++)
#pragma unroll
            for (int i = 0; i < 6; i++) kr[u][i] = lds128(sb + SM_CS + (u * 6 + i) * 16);
        issue_paced(1, NIM);
        ln_stats();
        if (tid == 16) { sts32(sb + SM_EPOCH, small); sts32(sb + SM_M1, ~0u); }
        else if (tid < 16) sts32(sb + SM_B1 + tid * 4, (tid & 1) ? small & 0xffff0000u : small << 16);
        mbar_wait(sb + SM_CBAR + CB_WQ * 8, 0);
        load_wq();
        q_proj(IC<0>{}, px, sb + (t < 2 ? SM_PART : SM_CSP) + warp * 768 + (8 * g + 4 * (t & 1)) * 4);
    }
    {
        uint32_t offQ, offL;
        auto calc_ql = [&]() {
            offQ = pin(sb + SM_VEC + (lane & 7) * 48);
            offL = pin(subw + lane * 16);
        };

        auto issue_w = [&](auto L, int which) {
            const uint32_t bar = sb + SM_CBAR + (CB_W1 + which) * 8;
            if (mlp == 96) asm volatile("mbarrier.arrive.shared::cta.b64 _, [%0];" :: "r"(bar) : "memory");
            else {
                mbar_expect(bar, 20480);
                if (which) {
                    tma3(sb + (L.value ? 3 * TILE : SM_W2), tmk + TM_W2, 0, mlp * 16, bar, W2ONE ? POL_FIRST : WPOL);
                    if (W2ONE && !L.value) tma3_pf(tmk + TM_W2, 0, mlp * 16, POL_NORMAL);
                    if (W1ONE && !L.value) asm volatile("cp.async.bulk.prefetch.L2.global.L2::cache_hint [%0], 20480, %1;" :: "l"(P.w1 + mlp * 10240), "l"((u64)POL_NORMAL << 32) : "memory");
                }
                else asm volatile("cp.async.bulk.tensor.3d.shared::cluster.global.mbarrier::complete_tx::bytes.L2::cache_hint [%0], [%1, {%2, %3, %3}], [%4], %5;"
                                  :: "r"(sb + (L.value ? 2 * TILE : SM_W1)), "l"(tmk + TM_W1), "r"(mlp * 16), "r"(0), "r"(bar), "l"((u64)(W1ONE ? POL_FIRST : WPOL) << 32) : "memory");
            }
        };
        float acc[3][4];
        auto load_q = [&](uint4 (&qf)[3]) {
#pragma unroll
            for (int i = 0; i < 3; i++) qf[i] = lds128(offQ + i * 16);
        };
        auto softmax = [&](float S0, float S1, float S2, float S3) {
            int mi = __float_as_int(fmaxf(fmaxf(S0, S1), fmaxf(S2, S3)));
            mi = __reduce_max_sync(~0u, mi ^ ((mi >> 31) & 0x7fffffff));
            const float mrun = __int_as_float(mi ^ ((mi >> 31) & 0x7fffffff));
            const float p0 = ex2((S0 - mrun) * CS), p1 = ex2((S1 - mrun) * CS), p2 = ex2((S2 - mrun) * CS), p3 = ex2((S3 - mrun) * CS);
            const uint32_t pa = pack_bf(p0, p1), pb = pack_bf(p2, p3), pw = prow + 256 + (key >> 1) * 80 + t * 4 + (key & 1) * 2;
            sts16(pw, pa); sts16(pw + 16, pa >> 16); sts16(pw + 32, pb); sts16(pw + 48, pb >> 16);
            __syncwarp();
#pragma unroll
            for (int j = 0; j < 3; j++) acc[j][0] = acc[j][1] = acc[j][2] = acc[j][3] = 0.f;
            return make_float2(mrun, (p0 + p1) + (p2 + p3));
        };
        auto pv = [&](const uint4 (&v)[6], uint32_t pp) {
            const uint32_t dA = __byte_perm(pp, 0, 0x1010), dB = __byte_perm(pp, 0, 0x3232);
            mma(acc[0], v[0], dA & maskA, dA & maskB); mma(acc[1], v[1], dA & maskA, dA & maskB); mma(acc[2], v[2], dA & maskA, dA & maskB);
            mma(acc[0], v[3], dB & maskA, dB & maskB); mma(acc[1], v[4], dB & maskA, dB & maskB); mma(acc[2], v[5], dB & maskA, dB & maskB);
        };
        auto sa = [&]() { return prow + 256 + t * 32 + g * 4; };
        auto pass1 = [&]() {
            if (NIM < NI1) issue_paced(NIM, NI1);
            fresh();
            calc_ql();
            __syncthreads();
            sts64(prow + lane * 8, xp.x, xp.y);
            int e = 0;
            const uint4* tab = P.tile + (warp >> 2);
            uint4 tw = tab[0];
            uint32_t ka[3];
#pragma unroll
            for (int j = 0; j < 3; j++) ka[j] = pin(subw + key * 384 + j * 128 + ((t ^ ((3 * key + j) & 7)) << 4));
            auto load_k = [&](uint4 (&v)[6], uint32_t so) {
#pragma unroll
                for (int i = 0; i < 6; i++) v[i] = lds128(((i & 1) ? ka[i >> 1] ^ 64 : ka[i >> 1]) + so);
            };
            const uint32_t s0 = pin(prow + 256 + g * 4), sca = pin(sb + SM_SC + warp * 128 + g * 16);
#pragma unroll 1
            do {
                const uint4 tn = tab[2 * e + 2];
                uint4 v[6], qf[3];
                if (tw.x & (G_A | G_B | G_C)) {
                    if ((tw.x & G_A) && warp == 7 && elect()) {
                        mbar_expect(sb + SM_CBAR + CB_SNAP * 8, HALF);
                        asm volatile("cp.async.bulk.shared::cluster.global.mbarrier::complete_tx::bytes [%0], [%1], 12288, [%2];"
                                     :: "r"(sb + SM_SNAP), "l"(&g_l0[cta & ~3][0]), "r"(sb + SM_CBAR + CB_SNAP * 8) : "memory");
                    }
                    if (tw.x & G_B) {
                        if (warp < 6) {
                            mbar_wait(sb + SM_CBAR + CB_SNAP * 8, 0);
                            float qc[2] = {0.f, 0.f}, mean, rstd;
#pragma unroll 1
                            for (int k = 0; k < 2; k++) {
                                u64 qw[4];
#pragma unroll
                                for (int i = 0; i < 4; i++) { const uint2 x = lds64(sb + SM_SNAP + i * 3072 + k * 1536 + tid * 8); qw[i] = x.x | (u64)x.y << 32; }
                                qc[0] = qc[1];
                                qc[1] = ll_gather<384>(&g_l0[cta & ~3][k * 192 + tid], lds32(sb + SM_EPOCH) * 4 + 1, qw);
                            }
                            ln_final(mean, rstd);
                            stsf(sb + SM_CS + tid * 4, qc[1]);
                            const float q = (qc[0] - mean * qc[1]) * rstd;
                            sts16(q_addr(tid), pack_bf(q, q));
                        }
                        __syncthreads();
                        if (warp == 7 && elect()) issue_half(UC<load_word(12)>::value, sb, rowc, cta, tmk);
                        TSTAMP(2);
                    }
                    if (tw.x & G_C) {
                        load_k(v, (e - LATEAT) * TILE);
                        load_q(qf);
                        stsf(s0 + (e - LATEAT) * 32, score(v, qf));
                    }
                }
                load_q(qf);
                mbar_wait(sb + SM_CBAR + (tw.x & 0xf8), tw.x >> 31);
                TRACE(e);
                load_k(v, tw.x & 0x3f000);
                const uint32_t old = release(tw);
                const float s = score(v, qf);
                uint32_t m;
                {
                    uint32_t a[6];
#pragma unroll
                    for (int i = 0; i < 6; i++) a[i] = bf2_amax(bf2_amax(v[i].x, v[i].y), bf2_amax(v[i].z, v[i].w));
                    m = bf2_amax(bf2_amax(bf2_amax(a[0], a[1]), bf2_amax(a[2], a[3])), bf2_amax(a[4], a[5]));
                }
                m = bf2_amax(m, m >> 16) & 0x7f80;
                m = max(m, __shfl_xor_sync(~0u, m, 1));
                stsf(s0 + e * 32, s);
                m = max(m, __shfl_xor_sync(~0u, m, 2));
                refill(tw, old);
                const uint32_t b = min(max(m, 15u << 7) - (15u << 7), 126u << 7);
                const uint32_t dn = ((127u << 7) - b) * 0x10001u, up = ((127u << 7 | 0x8000u) + b) * 0x10001u;
                uint32_t c[18], any = m > (141u << 7);
#pragma unroll
                for (int i = 0; i < 6; i++) {
                    const uint32_t y0 = bf2_mul(v[i].x, dn), y1 = bf2_mul(v[i].y, dn), y2 = bf2_mul(v[i].z, dn), y3 = bf2_mul(v[i].w, dn);
                    v[i] = make_uint4(bf2_fma(y0, up, v[i].x), bf2_fma(y1, up, v[i].y), bf2_fma(y2, up, v[i].z), bf2_fma(y3, up, v[i].w));
                    any |= v[i].x | v[i].y;
                    any |= v[i].z | v[i].w;
                    const uint32_t hb = __byte_perm(y2, y3, 0x7531);
                    c[3 * i] = __byte_perm(y0, y1, 0x6420); c[3 * i + 1] = __byte_perm(y2, y3, 0x6420);
                    c[3 * i + 2] = __byte_perm(y0, y1, 0x7531) | __funnelshift_r(hb, hb, 4);
                }
                asm volatile("st.shared.u8 [%0], %1;" :: "r"(sca + (e & 3) * 4 + (e >> 2)), "r"((b >> 7) + 63) : "memory");
                const bool rare = __any_sync(~0u, any);
                k_keep(kr, c, e, offL);
                if (rare) k_rare(v[0], v[1], v[2], v[3], v[4], v[5], m > (141u << 7), e, warp, lane);
                tw = tn;
            } while (++e < 16);
            asm volatile("fence.proxy.async.shared::cta;" ::: "memory");
            __syncwarp();
            TSTAMP(10);
            fresh(); calc_offsets();
            {
                const uint2 st = lds64(barw + 80);
                const uint32_t xa = sb + SM_EXC + warp * 128 + (lane & 15) * 8 + 4;
                uint32_t pos = lds32(xa), lt;
                asm volatile("mov.u32 %0, %lanemask_lt;" : "=r"(lt));
                if (lane >= st.x) pos = 0x80000000u;
                const bool dup = (__match_any_sync(~0u, pos >> 16) & lt) && lane < st.x;
                if (lane < 16) sts32(xa, dup ? pos | 0x40000000u : pos);
                if (__any_sync(~0u, dup)) sts32(barw + 84, st.y | 0x10000u);
                const float2 ml = softmax(ldsf(sa()), ldsf(sa() + 128), ldsf(sa() + 256), ldsf(sa() + 384));
                sts64f(sb + SM_ML + warp * 8, ml.x, warp_sum(ml.y));
            }
            u64 pm = 0, pl = 0;
#pragma unroll 1
            do {
                const uint4 tn = tab[2 * e + 2];
                if (tw.x & (G_A | G_B | G_C)) {
                    if (tw.x & G_A) {
                        if (lane < 24) st_rlx(&g_ll[0][cta][warp * 24 + lane], 0ull);
                        else if (lane < 28) st_rlx(&g_ll[0][cta][168 + warp * 4 + lane], ll_pack(ldsf(sb + SM_ML + warp * 8 + (lane & 1) * 4), lds32(sb + SM_EPOCH) * 4 + 2));
                    }
                    if (warp == 2) {
                        if (tw.x & G_B) ld_rlx2(&g_ll[0][cta ^ (lane >> 3)][192 + (lane & 7) * 4], pm, pl);
                        if (tw.x & G_C) head_weight(&g_ll[0][cta ^ (lane >> 3)][192 + (lane & 7) * 4], pm, pl, 0, lane);
                    }
                    __syncwarp();
                }
                const uint32_t pp = lds32(prow + 256 + t * 80 + ((tw.x >> 20) & 255));
                mbar_wait(sb + SM_CBAR + (tw.x & 0xf8), tw.x >> 31);
                TRACE(e);
                uint4 v[6];
                load_v(v, tw.x & 0x3f000);
                refill(tw, release(tw));
                pv(v, pp);
                tw = tn;
            } while (++e < 32);
        };
        uint32_t osa, ora, owa, orow, otag;
        u64* olb;
        float xc;
        auto o_setup = [&](auto L) {
            fresh();
            const int lz = lane, d = warp * 24 + min(lz, 23);
            osa = pin(prow + ((lz >> 2) * 8 + (lz & 1) * 4 + (lz & 2)) * 4);
            ora = pin(sb + SM_PART + d * 4);
            olb = pin(&g_ll[L.value][cta & ~3][d]);
            orow = pin((lz & 1) + 2 * (lz & 2) + 2 * (lz >> 4));
            owa = pin(sb + SM_RING + warp * 1536 + orow * 64 + ((((lz >> 2) & 3) ^ (orow >> 1)) << 4));
            otag = lds32(sb + SM_EPOCH) * 4 + 2 + 2 * L.value;
            uint32_t x; asm volatile("ld.shared.u16 %0, [%1];" : "=r"(x) : "r"(prow + ((cta & 1) * 16 + (lz >> 3) * 4 + (cta & 2) + ((lz >> 2) & 1)) * 8 + (lz & 3) * 2) : "memory");
            xc = bf_lo(x) * (1.f / 32);
        };
        auto pass2 = [&](float inv) {
            constexpr IC<1> L{};
            if (P4AT == 0) refill2(IC<4>{});
            if (P2LATE == 1 && warp >= 4) refill2(IC<2>{});
            offQ = sb + SM_VEC + (lane & 7) * 48; offL = subw + lane * 16;
            uint4 tb[8][3];
            auto load_tb = [&](auto I) {
#pragma unroll
                for (int i = 0; i < 3; i++) tb[I.value][i] = lds128(offL + (I.value >> 1) * TILE + ((I.value & 1) * 3 + i) * 512);
            };
            const u64* qb = &g_ll[0][cta & ~3][min(tid, 191)];
            {
                uint32_t x[2];
                fx2_wait<2>([&](int i) { return rap + i * 40 * ACC_PITCH; }, look_rw, rw, sb + SM_MSQ, inv, x);
                xp = make_uint2(x[0], x[1]);
                CSTAMP(25, xp.y);
            }
            ln_stats();
            u64 qw[4];
            ll_look<256>(qb, qw);
            const float cs = ldsf(sb + SM_CS + min(tid, 191) * 4);
            const uint32_t qtag = lds32(sb + SM_EPOCH) * 4 + 3, qa = pin(q_addr(min(tid, 191)));
            __syncthreads();
            auto vwait = [&](auto I) { mbar_wait(barw + IC<SCH.st[I.value].slot>::value * 8, IC<SCH.st[I.value].par>::value); };
            bool ok;
            uint32_t m1, m1n;
            {
                float mean, rstd;
                ln_final(mean, rstd);
                const float sq = shx(rstd * 0x1p64f, 0), q0 = shx(-mean * cs * sq, 0);
                CSTAMP(26, __float_as_uint(q0));
                static_for<0, NPRE>(load_tb);
                if (P4AT == 1) refill2(IC<4>{});
                if (S0EARLY) refill2(IC<5>{});
                m1n = m1 = lds32(sb + SM_M1);
                sts64(prow + lane * 8, xp.x, xp.y);
                sts128f(prow + 256 + lane * 16, 0.f, 0.f, 0.f, 0.f);
                const float q = ll_gather<256>(qb, qtag, qw) * sq + q0;
                sts16(qa, pack_bf(q, q));
                TSTAMPL(24);
                CSTAMP(27, __float_as_uint(q));
            }
            if (!S0EARLY) refill2(IC<5>{});
            if (P2LATE == 2 && warp >= 4) refill2(IC<2>{});
            if (P4AT == 3) refill2(IC<4>{});
            if (NOWIN & 1) { if (warp < 6) refill2(IC<0>{}); if (warp >= 5) refill2(IC<3>{}); }
            if (NOWIN & 2) { if (warp >= 6) refill2(IC<1>{}); if (warp < 4) refill2(IC<2>{}); }
            if (NOWIN & 4) { if (warp >= 6) refill2(IC<0>{}); if (warp < 6) refill2(IC<1>{}); }
            if (NOWIN & 8) { if (warp < 5) refill2(IC<3>{}); if (warp >= 4) refill2(IC<2>{}); }
            __syncthreads();
            uint4 qf[3];
            load_q(qf);
            CSTAMP(28, qf[0].x);
            float S[4], d[2][4];
            auto vload = [&](auto I) {
                constexpr int p = I.value;
                constexpr Step c = SCH.st[p];
                load_v(kr[p & 7], c.slot * TILE);
                if constexpr (c.next >= 0) refill2(IC<c.next>{});
                if constexpr (p == 11) { __syncwarp(); if (elect()) asm volatile("mbarrier.arrive.shared::cta.b64 _, [%0];" :: "r"(sb + SM_CBAR + CB_REL * 8) : "memory"); }
            };
            static_for<0, 96>([&](auto F) {
                constexpr int f = F.value, i = f % 6, u = kunit(f / 6), w = 3 * f % 12;
                uint4 (&src)[3] = *reinterpret_cast<uint4 (*)[3]>(f < 32 ? &tb[f / 4 & 7][0] : &kr[(f / 8 + 4) & 7][(f / 4 & 1) * 3]);
                const uint4 a = k_unpack(word<w % 4>(src[w / 4]), word<(w + 1) % 4>(src[(w + 1) / 4]), word<(w + 2) % 4>(src[(w + 2) / 4]), m1);
                if constexpr (f < 32 ? f % 4 == M1AT : f % 8 == M1P) m1 = m1n;
                if constexpr (f % 4 == 3 && f / 4 + NPRE < 8) {
                    load_tb(IC<f / 4 + NPRE>{});
                    if constexpr ((f / 4 + NPRE) & 1) { refill2(IC<5 + (f / 4 + NPRE) / 2>{}); m1n = lds32(sb + SM_M1); }
                }
                if constexpr (i < 2) d[i][0] = d[i][1] = d[i][2] = d[i][3] = 0.f;
                mma(d[i & 1], a, (i & 1) ? qf[i / 2].z : qf[i / 2].x, (i & 1) ? qf[i / 2].w : qf[i / 2].y);
                if constexpr (i == 5) {
                    if constexpr (u == 11 || ((u & 3) == 0 && u != 8)) S[u >> 2] = (d[0][0] + d[0][3]) + (d[1][0] + d[1][3]);
                    else add_if(t == (u & 3), S[u >> 2], d[0][0] + d[0][3], d[1][0] + d[1][3]);
                    if constexpr (f < 64) S[u >> 2] = shx(S[u >> 2], 0);
                }
                if constexpr (f == 31) { fresh(); calc_offsets(); ok = mbar_test(barw + IC<SCH.st[0].slot>::value * 8, 0); }
                if constexpr (f == 48) {
                    const uint2 x = lds64(sb + SM_EXC + warp * 128 + (lane & 15) * 8);
                    const float c = k_side(sb, x);
                    if (x.y < 0x40000000u) stsf(prow + 256 + (x.y >> 16), c);
                }
                if constexpr (f >= 32 && f % 8 == 7) {
                    if constexpr (PARKS >> (f / 8 - 4) & 1) {
                        constexpr int p = popc(PARKS & ((1 << (f / 8 - 4)) - 1));
                        if (!ok) vwait(IC<p>{});
                        vload(IC<p>{});
                        m1n = lds32(sb + SM_M1);
                        ok = mbar_test(barw + IC<SCH.st[p + 1].slot>::value * 8, IC<SCH.st[p + 1].par>::value);
                    }
                }
            });
            uint32_t bad = lds32(barw + 84);
            const uint32_t sc = lds32(sb + SM_SC + tid * 4);
            __syncwarp();
            if (bad) k_fix(P.k + (size_t)roww * DH, bad, warp, lane);
            TSTAMP(30);
            CSTAMP(29, __float_as_uint(S[2]));
            const float2 ml = softmax(S[0] * __uint_as_float((sc & 255) << 23) + ldsf(sa()), S[1] * __uint_as_float((sc & 0xff00) << 15) + ldsf(sa() + 128),
                                      S[2] * __uint_as_float((sc & 0xff0000) << 7) + ldsf(sa() + 256), S[3] * __uint_as_float((sc >> 24) << 23) + ldsf(sa() + 384));
            uint4 pq[4];
#pragma unroll
            for (int j = 0; j < 4; j++) pq[j] = lds128(prow + 256 + t * 80 + j * 16);
            TSTAMP(1);
            CSTAMP(30, pq[3].w);
            if (!ok) vwait(IC<NPARK>{});
            float ac2[3][4];
#pragma unroll
            for (int j = 0; j < 3; j++) ac2[j][0] = ac2[j][1] = ac2[j][2] = ac2[j][3] = 0.f;
            const uint32_t sl = (g & 1) ? 0x1044 : 0x4410, sh = (g & 1) ? 0x3244 : 0x4432;
            const uint32_t sA0 = (g & 2) ? 0x4444 : sl, sA1 = (g & 2) ? sl : 0x4444, sB0 = (g & 2) ? 0x4444 : sh, sB1 = (g & 2) ? sh : 0x4444;
            u64 pm = 0, pl = 0;
            static_for<NPARK, 16>([&](auto I) {
                constexpr int p = I.value;
                static_assert(p - SCH.st[p].mma0 < 8, "buffer in use");
                vload(I);
                if constexpr (p < 15) ok = mbar_test(barw + IC<SCH.st[p + 1].slot>::value * 8, IC<SCH.st[p + 1].par>::value);
                static_for<SCH.st[p].mma0, SCH.st[p].mma0 + SCH.st[p].nmma>([&](auto J) {
                    constexpr int u = SCH.st[J.value].unit;
                    const uint32_t pp = word<u & 3>(pq[u >> 2]), a0 = __byte_perm(pp, 0, sA0), a1 = __byte_perm(pp, 0, sA1), b0 = __byte_perm(pp, 0, sB0), b1 = __byte_perm(pp, 0, sB1);
#pragma unroll
                    for (int j = 0; j < 3; j++) mma(acc[j], kr[J.value & 7][j], a0, a1);
#pragma unroll
                    for (int j = 0; j < 3; j++) mma(ac2[j], kr[J.value & 7][j + 3], b0, b1);
                });
                if constexpr (p == NPARK) {
                    const float l = warp_sum(ml.y);
                    if (lane < 28) st_rlx(&g_ll[1][cta][lane < 24 ? warp * 24 + lane : 168 + warp * 4 + lane], lane < 24 ? 0ull : ll_pack((lane & 1) ? l : ml.x, lds32(sb + SM_EPOCH) * 4 + 4));
                }
                if constexpr (p == HWAT) { if (warp == 6) ld_rlx2(&g_ll[1][cta ^ (lane >> 3)][192 + (lane & 7) * 4], pm, pl); }
                if constexpr (p == 13) o_setup(L);
                if constexpr (p == HWAT + 2) { if (warp == 6) head_weight(&g_ll[1][cta ^ (lane >> 3)][192 + (lane & 7) * 4], pm, pl, 1, lane); }
                if constexpr (p >= WOAT && p < WOAT + 3) {
                    if (warp == p - WOAT) {
                        mbar_wait(sb + SM_CBAR + CB_REL * 8, 0);
                        if (elect()) {
                            issue_half(UC<load_word(64 + 2 * (p - WOAT)) | 1>::value, sb, rowc, cta, tmk);
                            if constexpr (p < WOAT + 2) issue_half(UC<load_word(65 + 2 * (p - WOAT)) | 1>::value, sb, rowc, cta, tmk);
                        }
                        __syncwarp();
                    }
                }
                if constexpr (p < 15) { if (!ok) mbar_wait(barw + IC<SCH.st[p + 1].slot>::value * 8, IC<SCH.st[p + 1].par>::value); TRACE(33 + p); }
            });
#pragma unroll
            for (int j = 0; j < 3; j++)
#pragma unroll
                for (int k = 0; k < 2; k++) { acc[j][k] += ac2[j][k]; add_if(t & 2, acc[j][k], acc[j][k + 2], ac2[j][k + 2]); }
        };

        const unsigned char* ap;
        uint32_t hpa, hsa, hst, w2a, la;
        uint2 b2v;
        float b1v, cs1;
        auto mlp_global = [&](auto L) {
            const int cz = c4();
            ap = accg + 2 * L.value * ACC_BYTES + (cz >> 1) * ACC_PITCH + (cz & 1) * 16;
            if (L.value) ap = pin(ap);
            rap = pin(accg + (2 * L.value + 1) * ACC_BYTES + (cz >> 2) * ACC_PITCH + (cz & 3) * 8);
            asm volatile("ld.global.nc.v2.u32 {%0,%1}, [%2];" : "=r"(b2v.x), "=r"(b2v.y) : "l"(P.b2 + 4 * cz));
        };
        auto mlp_shared = [&](auto L) {
            const int lz = lane;
            hpa = pin(sb + SM_PART + warp * 256 + ((lz & 2) * 4 + (lz >> 2)) * 16 + (L.value ? 0 : (lz & 1) * 4));
            hsa = pin(sb + SM_PART + (lz & 15) * 16); hst = pin(sb + SM_PART + (lz & 15) * 16 + warp * 256 + 8 + (lz >> 4) * 4);
            w2a = pin(sb + (L.value ? 3 * TILE : SM_W2) + ((lz & 3) * 10 + 2 * warp) * 128 + (((lz >> 2) ^ ((2 * lz + 2 * warp) & 6)) << 4));
            la = sb + (L.value ? 2 * TILE : SM_W1) + warp * 4096 + (lz & 4) * 512 + (lz & 2) * 64 + (lz & 1) * 32 + (lz >> 4) * 64 + ((((lz >> 3) ^ (lz >> 1)) & 1) << 4);
            b1v = ldsf(sb + SM_B1 + (lz & 15) * 4);
            if (L.value) { la = pin(la); cs1 = ldsf(sb + SM_ML + (lz & 15) * 4); }
            else fresh();
        };
        uint32_t pa;
        unsigned char* rop;
        uint32_t wpa;
        auto sum_setup = [&](auto L) {
            const int lz = lane, word = warp * 128 + (cta & 3) * 32 + lz;
            wpa = pin(sb + SM_RING + warp * 1536 + ((((lz >> 2) * 8 + (lz & 1) * 4) * 4) ^ ((((lz >> 1) ^ (lz >> 4)) & 1) ? 256 + 64 : 0)));
            pa = pin(sb + SM_RING + warp * 256 + ((lz * 4) ^ ((warp & 1) * 64)));
            rop = pin(accg + 2 * L.value * ACC_BYTES + (word >> 3) * ACC_PITCH + (word & 7) * 4);
        };
        auto out_proj = [&](auto L) {
            TSTAMP2(3);
            CSTAMP(0, __float_as_uint(acc[2][1]));
            __syncwarp();
#pragma unroll
            for (int j = 0; j < 3; j++) {
                if (L.value == 0 && (t & 2)) { acc[j][0] = acc[j][2]; acc[j][1] = acc[j][3]; }
                sts64f(osa + 256 * j, acc[j][0], acc[j][1]);
            }
            __syncthreads();
            {
                float s[8];
#pragma unroll
                for (int w = 0; w < 8; w++) s[w] = ldsf(ora + w * 768);
                const uint4 fa = lds128(sb + SM_FAC), fb = lds128(sb + SM_FAC + 16);
            CSTAMP(1, __float_as_uint(s[0]));
                const float own = ((s[0] * __uint_as_float(fa.x) + s[1] * __uint_as_float(fa.y)) + (s[2] * __uint_as_float(fa.z) + s[3] * __uint_as_float(fa.w))) +
                                  ((s[4] * __uint_as_float(fb.x) + s[5] * __uint_as_float(fb.y)) + (s[6] * __uint_as_float(fb.z) + s[7] * __uint_as_float(fb.w)));
                st_rlx_if(lane < 24, olb + (cta & 3) * 256, ll_pack(own, otag));
            CSTAMP(2, __float_as_uint(own));
            }
            TSTAMPL(29);
            if (L.value == 0 && warp == 7) {
#pragma unroll 1
                for (int it = 0; it < SPIN; it++) {
                    uint32_t v; asm volatile("ld.acquire.gpu.global.u32 %0, [%1];" : "=r"(v) : "l"(&g_zflag) : "memory");
                    if (__all_sync(~0u, v == (otag >> 2) + 1)) break;
                }
            }
            constexpr int NW = L.value ? NWO1 : 3;
            uint4 v[5][3];
            u64 ow[4];
            auto read_wo = [&](auto J) {
#pragma unroll
                for (int p = 0; p < 3; p++) v[J.value][p] = lds128(((J.value & 1) ? owa ^ 144 : owa) + ring_hs(64 + J.value) * HALF + p * 512);
            };
            static_for<0, NW>([&](auto J) {
                if (L.value && J.value == 0) { sum_setup(L); maskA = pin(maskA); maskB = pin(maskB); }
                if ((L.value ? OPOLL1 : OPOLL) == J.value) { ll_look<256>(olb, ow); if (L.value) { mlp_shared(L); mlp_global(L); } }
                mbar_wait(sb + SM_CBAR + (CB_WO + J.value) * 8, L.value);
                read_wo(J);
                if (L.value == 0 && W1AT0 == J.value + 1) {
                    __syncwarp();
                    if (elect() && cnt_inc(sb + SM_CNT + CB_W1 * 8, 7) == 7) issue_w(L, 0);
                    __syncwarp();
                }
                if (L.value == 1 && (W1AT1 == J.value + 1 || W2AT1 == J.value + 1)) {
                    if (warp == 7 && elect()) { if (W1AT1 == J.value + 1) issue_w(L, 0); if (W2AT1 == J.value + 1) issue_w(L, 1); }
                    __syncwarp();
                }
            });
            const float o = ll_gather<256>(olb, otag, ow);
            CSTAMP(3, __float_as_uint(o));
            TSTAMP2(4);
            bool ok = true;
            if constexpr (NW < 5) ok = mbar_test(sb + SM_CBAR + (CB_WO + 4) * 8, L.value);
            if constexpr (NW < 4) ok &= mbar_test(sb + SM_CBAR + (CB_WO + 3) * 8, L.value);
            const uint32_t od = pack_bf(o, o);
            uint32_t oa[3], ob[3];
#pragma unroll
            for (int p = 0; p < 3; p++) { const uint32_t op = __shfl_sync(~0u, od, 8 * p + orow); oa[p] = op & maskA; ob[p] = op & maskB; }
            CSTAMP(4, oa[2]);
            float y[5][4];
#pragma unroll
            for (int j = 0; j < 5; j++) y[j][0] = y[j][1] = y[j][2] = y[j][3] = 0.f;
            auto rest = [&]() {
                if (!ok) static_for<NW, 5>([&](auto J) { mbar_wait(sb + SM_CBAR + (CB_WO + J.value) * 8, L.value); });
                static_for<NW, 5>(read_wo);
            };
            if (L.value) rest();
#pragma unroll
            for (int p = 0; p < 3; p++)
#pragma unroll
                for (int j = 0; j < NW; j++) mma(y[j], v[j][p], oa[p], ob[p]);
            if (!L.value) { rest(); sum_setup(L); }
#pragma unroll
            for (int p = 0; p < 3; p++)
#pragma unroll
                for (int j = NW; j < 5; j++) mma(y[j], v[j][p], oa[p], ob[p]);
            CSTAMP(5, __float_as_uint(y[4][3]));
#pragma unroll
            for (int j = 0; j < 5; j += 2) {
                if (j < 4 && (t >> 1) != (g >> 2)) { y[j][0] = y[j + 1][0]; y[j][1] = y[j + 1][1]; y[j][2] = y[j + 1][2]; y[j][3] = y[j + 1][3]; }
                sts128f(wpa + j * 256, y[j]);
            }
            TSTAMP2(5);
        };
        u64 yw[2];
        bool wide;
        float msq = 0.f, yf[4];
        auto mlp_part = [&](auto L) {
            const float sc1 = fx2_scale(ldsf(sb + SM_FXS)) * 0.25f;
            bar_sync(0, 256);
            CSTAMP(6, __float_as_uint(sc1));
            const float s = (sum8(pa, 1536) + xc) + sum8(pa + 128, 1536), sm = s * sc1 + FX2_ONE;
            CSTAMP(7, __float_as_uint(s));
            const bool wide1 = !(fabsf(sm - FX2_ONE) < FX1LIM);
            asm volatile("red.relaxed.gpu.global.add.u32 [%0], %1;" :: "l"(rop), "r"(wide1 ? 0u : __float_as_uint(sm) * 128u + (1u - 0x4b400000u * 128u)) : "memory");
            const uint32_t c0 = clk();
            TSTAMP2(6);
            if (L.value == 0) bar_arrive(2, 256);
            if (wide1) {
                fx_send(rop + 64 + (lane & 7) * 4, s, ldsf(sb + SM_FXS), rop, 64);
                asm volatile("red.relaxed.gpu.global.add.u32 [%0], 1;" :: "l"(rop) : "memory");
            }
            __syncwarp();
            if (L.value == 1 && mlp == 96) { TDUMP(); asm volatile("exit;"); }
            uint4 wf[8], w2r[8];
            uint4 w;
            auto look = [&]() { asm volatile("ld.relaxed.gpu.global.v4.u32 {%0,%1,%2,%3}, [%4];" : "=r"(w.x), "=r"(w.y), "=r"(w.z), "=r"(w.w) : "l"(ap) : "memory"); };
            auto read_w1 = [&]() {
#pragma unroll
                for (int j = 0; j < 8; j++) wf[j] = ldsm_t(la + j * 256);
            };
            auto read_w2 = [&]() {
#pragma unroll
                for (int i = 0; i < 8; i++) w2r[i] = lds128(((i & 1) ? (w2a ^ 16) + 128 : w2a) + (i >> 1) * 5120);
            };
            if (L.value == 0) { fresh(); mlp_global(L); }
            mbar_wait(sb + SM_CBAR + CB_W1 * 8, L.value);
            if (L.value == 1) {
                if (W2PRE == 1) mbar_wait(sb + SM_CBAR + CB_W2 * 8, 1);
                read_w1();
                if (W2PRE == 1) read_w2();
            }
            while (clk() - c0 < AR1D);
            look();
            if (L.value == 0) { mlp_shared(L); read_w1(); bar_arrive(3, 256); }
            else if (W2PRE == 2) { mbar_wait(sb + SM_CBAR + CB_W2 * 8, 1); read_w2(); }
            TSTAMPL(28);
            {
                const float inv = shx(fx_inv(sc1) * (1.f / 128), 0), off = inv * -32.f;
                int it = 0;
#pragma unroll 1
                while (__any_sync(~0u, ~(w.x & w.y & w.z & w.w) & 32) & (++it < SPIN)) look();
                CSTAMP(8, w.w);
                xp = make_uint2(pack_bf((float)(int)w.x * inv + off, (float)(int)w.y * inv + off), pack_bf((float)(int)w.z * inv + off, (float)(int)w.w * inv + off));
                if (__any_sync(~0u, (w.x | w.y | w.z | w.w) & 64)) { xp.x = fx1_wide(ap, ldsf(sb + SM_FXS)); xp.y = fx1_wide(ap + 8, ldsf(sb + SM_FXS)); }
            }
            TSTAMP2(7);
            CSTAMP(9, xp.y);
            {
                bool ok = true;
                if (L.value == 0 || !W2PRE) ok = mbar_test(sb + SM_CBAR + CB_W2 * 8, L.value);
                const bool ev = L.value || !(g & 1), od = L.value || (g & 1);
                const uint32_t e0 = ev ? xp.x : ONES, e1 = ev ? xp.y : ONES, o0 = od ? xp.x : ONES, o1 = od ? xp.y : ONES;
                float d[8][4];
#pragma unroll
                for (int j = 0; j < 8; j++) { d[j][0] = d[j][1] = d[j][2] = d[j][3] = 0.f; mma(d[j], wf[j], (j & 1) ? o0 : e0, (j & 1) ? o1 : e1); }
                float ss = ln_part(xp, lane);
                ss += shx(ss, 8); ss += shx(ss, 4);
                float r[4], dd;
#pragma unroll
                for (int k = 0; k < 4; k += 1 + L.value) r[k] = d[0][k] + d[1][k ^ 1];
#pragma unroll
                for (int j = 1; j < 4; j++)
#pragma unroll
                    for (int k = 0; k < 4; k += 1 + L.value) add_if(t == j, r[k], d[2 * j][k], d[2 * j + 1][k ^ 1]);
                CSTAMP(10, __float_as_uint(r[2]));
                if (L.value) {
                    dd = ((t & 2) ? r[2] : r[0]) + shx((t & 2) ? r[0] : r[2], 2);
                    ss += shx(ss, 2);
                    dd += shx(dd, 1);
                } else {
                    const float a = ((t & 1) ? r[1] : r[0]) + shx((t & 1) ? r[0] : r[1], 1), b = ((t & 1) ? r[3] : r[2]) + shx((t & 1) ? r[2] : r[3], 1);
                    ss += shx(ss, 2);
                    dd = ((t & 2) ? b : a) + shx((t & 2) ? a : b, 2);
                }
                ss += shx(ss, 1);
                stsf(hpa, dd);
                stsf(hst, ss);
                CSTAMP(11, __float_as_uint(dd + ss));
                if (!ok) mbar_wait(sb + SM_CBAR + CB_W2 * 8, L.value);
            }
            TSTAMPL(25);
            bar_sync(1, 160);
            uint4 hp[5];
#pragma unroll
            for (int w = 0; w < 5; w++) hp[w] = lds128(hsa + w * 256);
            CSTAMP(12, hp[0].x);
            auto hs = [&](auto K) { return sum5(__uint_as_float(word<K.value>(hp[0])), __uint_as_float(word<K.value>(hp[1])), __uint_as_float(word<K.value>(hp[2])),
                                                __uint_as_float(word<K.value>(hp[3])), __uint_as_float(word<K.value>(hp[4]))); };
            const float mean = hs(IC<2>{}) * (1.f / D_MODEL);
            msq = hs(IC<3>{}) * (1.f / D_MODEL);
            if (L.value == 0) cs1 = hs(IC<1>{});
            float hv = hs(IC<0>{}) - mean * cs1;
            CSTAMP(13, __float_as_uint(hv));
            const float sc2 = fx2_scale(msq), lim = fx_inv(sc2) * FX2LIM;
            if (L.value == 0 || !W2PRE) read_w2();
            if (L.value == 0) bar_arrive(4, 256);
            hv = hv * ln_rstd(mean, msq) + b1v;
            CSTAMP(14, __float_as_uint(hv));
            hv = hv * rcp(1.f + ex2(hv * (-2.302208198f - 0.1029432397f * hv * hv)));
            const uint32_t hd = pack_bf(hv, hv);
            CSTAMP(15, hd);
            TSTAMPL(27);
            float ym[4][4];
#pragma unroll
            for (int i = 0; i < 2; i++) {
                ym[i][0] = ym[i][1] = ym[i][2] = ym[i][3] = 0.f;
                const float f = mlp < 64 ? 1.f / 64 : 0.f;
                ym[i + 2][0] = (bf_lo(xp.x) + bf_lo(b2v.x)) * f; ym[i + 2][1] = (bf_hi(xp.x) + bf_hi(b2v.x)) * f;
                ym[i + 2][2] = (bf_lo(xp.y) + bf_lo(b2v.y)) * f; ym[i + 2][3] = (bf_hi(xp.y) + bf_hi(b2v.y)) * f;
            }
#pragma unroll
            for (int i = 0; i < 4; i++) {
                const uint32_t hh = __shfl_sync(~0u, hd, 4 * i + t);
                mma(ym[(i & 1) * 2], w2r[2 * i], hh & maskA, hh & maskB);
                mma(ym[(i & 1) * 2 + 1], w2r[2 * i + 1], hh & maskA, hh & maskB);
            }
#pragma unroll
            for (int k = 0; k < 4; k++) { yf[k] = ym[0][k] + ym[2][k]; add_if(t & 2, yf[k], ym[1][k], ym[3][k]); }
            CSTAMP(16, __float_as_uint(yf[3]));
            yw[0] = fx2_pack(yf[0] * sc2 + FX2_ONE, yf[1] * sc2 + FX2_ONE); yw[1] = fx2_pack(yf[2] * sc2 + FX2_ONE, yf[3] * sc2 + FX2_ONE);
            wide = !(fmaxf(fmaxf(fabsf(yf[0]), fabsf(yf[1])), fmaxf(fabsf(yf[2]), fabsf(yf[3]))) < lim);
            if (wide) yw[0] = yw[1] = 0;
        };
        auto send_wide = [&]() {
#pragma unroll 1
            for (int k = 0; k < 4; k++, yf[0] = yf[1], yf[1] = yf[2], yf[2] = yf[3]) {
                const unsigned char* a = rap + (k >> 1) * 40 * ACC_PITCH;
                fx_send(a + 64 + (k & 1) * 32, yf[0], msq, a, 256);
            }
            yw[0] = yw[1] = 1;
        };

        pass1();
        o_setup(IC<0>{});
        out_proj(IC<0>{});
        uint32_t c0;
        if (warp < 5) {
            mlp_part(IC<0>{});
            if (mlp != 96) {
#pragma unroll
                for (int k = 0; k < 2; k++) asm volatile("red.relaxed.gpu.global.add.u64 [%0], %1;" :: "l"(rap + k * 40 * ACC_PITCH), "l"(yw[k]) : "memory");
            }
            c0 = clk();
            stsf(sb + SM_ML + (lane & 15) * 4, cs1);
            TSTAMP(8);
            if (__any_sync(~0u, wide && mlp != 96)) {
                if (wide) {
                    send_wide();
#pragma unroll
                    for (int k = 0; k < 2; k++) asm volatile("red.relaxed.gpu.global.add.u64 [%0], 1;" :: "l"(rap + k * 40 * ACC_PITCH) : "memory");
                }
                __syncwarp();
            }
            fresh(); calc_offsets();
            load_wq();
        } else {
            bar_sync(0, 256);
            if (warp == 5 && elect()) {
                asm volatile("fence.proxy.async.shared::cta;" ::: "memory");
                if (W1AT0 == 4) issue_w(IC<0>{}, 0);
                issue_w(IC<0>{}, 1);
            }
            __syncwarp();
            fresh(); calc_offsets();
            load_wq();
#pragma unroll 1
            for (int ph = 0; ph < 3; ph++) {
                bar_sync(ph + 2, 256);
                c0 = clk();
                if (ph == 2) {
                    msq = sum5(ldsf(sb + SM_PART + 12), ldsf(sb + SM_PART + 268), ldsf(sb + SM_PART + 524), ldsf(sb + SM_PART + 780), ldsf(sb + SM_PART + 1036)) * (1.f / D_MODEL);
                    bar_arrive(5, 256);
                }
                if (!(NOWIN >> ph & 1) && elect()) {
                    asm volatile("fence.proxy.async.shared::cta;" ::: "memory");
                    const uint32_t gap = ph == 0 ? WG1 : ph == 1 ? WG2 : WG3;
                    uint32_t c1 = c0 + (ph == 0 ? WD1 : ph == 1 ? WD2 : 0) + (warp - 5) * gap;
#pragma unroll 1
                    for (int k = warp + (ph == 0 ? -5 : ph == 1 && !(C96 && mlp == 96) ? 9 : 1); k < (ph == 0 ? 9 : ph == 1 ? 20 : C96 && mlp == 96 ? 0 : 14); k += 3, c1 += 3 * gap) {
                        const int i = ph == 0 && k >= 6 ? k + 23 : k;
                        const uint32_t bar = sb + SM_BAR + (i & 7) * 96 + 32 + (i & 24);
                        while ((int)(clk() - c1) < 0);
                        mbar_expect(bar, SUB);
                        tma_v(sb + SM_RING + i * SUB, tmk,
                              rowc * 3 + (i & 7) * 24 + ((UC<SCH.st[0].unit | SCH.st[1].unit << 8 | SCH.st[2].unit << 16 | SCH.st[3].unit << 24>::value >> (i & 24)) & 15) * 768, bar);
                    }
                }
                __syncwarp();
            }
            c0 += PCD;
        }
        {
            constexpr IC<1> L{};
            fresh();
            const int col = xcol(g & 3, t), cw = j40 + (col >> 2);
            const unsigned char* xa = pin(accg + ACC_BYTES + ((cw >> 2) + (col & 2) * 20) * ACC_PITCH + (cw & 3) * 8);
            const uint32_t pst = pin(prow + (g * 8 + (t & 1) * 4 + (t & 2)) * 4);
            stsf(sb + SM_MSQ, msq);
            const float inv = shx(fx2_inv(msq), 0);
            rap = pin(accg + ACC_BYTES + (c4() >> 2) * ACC_PITCH + (c4() & 3) * 8);
            fresh();
            maskA = pin(maskA); maskB = pin(maskB);
            u64 w[1];
            uint32_t x1[1], x2[3];
            auto look = [&]() { w[0] = ld_rlx(xa); };
            if (warp < 5) {
                bar_sync(5, 256);
                if (DPRE) { while ((int)(clk() - c0) < WD4 + warp * WG4); if (warp < DPRE) refill2(IC<3>{}); }
            }
            while ((int)(clk() - c0) < ARDELAY);
            look();
            if (DPOST) while ((int)(clk() - c0) < ARDELAY + DPOST);
            if (warp < 5 && !(NOWIN & 8) && elect()) {
                if (warp >= DPRE) issue_v(IC<3>{}, 0);
                if (warp < 4 && !P2LATE) issue_v(IC<2>{}, 4);
            }
            __syncwarp();
            fx2_wait<1>([&](int) { return xa; }, look, w, sb + SM_MSQ, inv, x1);
            if (warp < 5) look_rw(); else rw[0] = rw[1] = 96;
#pragma unroll
            for (int i = 0; i < 3; i++) x2[i] = __shfl_sync(~0u, x1[0], 4 * i + t);
            TSTAMP(9);
            CSTAMP(22, x2[2]);
            q_proj(L, x2, pst);
            pass2(inv);
            out_proj(L);
            if (warp >= 5) {
                bar_arrive(0, 256);
                if ((W1AT1 == 6 || W2AT1 == 6) && warp == 5 && elect()) { if (W1AT1 == 6) issue_w(L, 0); if (W2AT1 == 6) issue_w(L, 1); }
                TDUMP();
                return;
            }
            mlp_part(L);
            u64 old[2];
            auto add = [&]() {
#pragma unroll
                for (int k = 0; k < 2; k++) asm volatile("atom.relaxed.gpu.global.add.u64 %0, [%1], %2;" : "=l"(old[k]) : "l"(rap + k * 40 * ACC_PITCH), "l"(yw[k]) : "memory");
            };
            add();
            uint32_t* op = reinterpret_cast<uint32_t*>(P.out) + 2 * c4();
            if (wide) { send_wide(); add(); }
            TSTAMP(18);
            CSTAMP(17, hi32(yw[1]));
            const float inv2 = fx2_inv(msq);
            const uint32_t ep1 = lds32(sb + SM_EPOCH) + 1;
            CSTAMP(18, lo32(old[0]) ^ lo32(old[1]));
#pragma unroll
            for (int k = 0; k < 2; k++) {
                yw[k] += old[k];
                asm volatile("{\n.reg .pred p;\nsetp.eq.u32 p, %2, 96;\n@p st.global.u32 [%0], %1;\n}"
                             :: "l"(op + k), "r"(pack_bf(fx2_lo(yw[k], inv2), fx2_hi(yw[k], inv2))), "r"(lo32(yw[k]) & 511) : "memory");
            }
            if ((lo32(yw[0]) & 255) == 96 && tid == 0) g_epoch = ep1;
#pragma unroll
            for (int k = 0; k < 2; k++) if ((lo32(yw[k]) & 511) == 256 + 96) op[k] = fx2_wide(rap + k * 40 * ACC_PITCH, msq);
            TSTAMP(19);
            CSTAMP(19, lo32(yw[1]));
            TDUMP();
        }
    }
}

typedef CUresult (*EncodeFn)(CUtensorMap*, CUtensorMapDataType, cuuint32_t, void*, const cuuint64_t*, const cuuint64_t*, const cuuint32_t*,
                             const cuuint32_t*, CUtensorMapInterleave, CUtensorMapSwizzle, CUtensorMapL2promotion, CUtensorMapFloatOOBfill);

}

extern "C" void kernel_launch(void* const* d_in, const int* in_sizes, int n_in, void* d_out, int out_size) {
    (void)in_sizes; (void)n_in; (void)out_size;
    static EncodeFn enc = nullptr;
    if (!enc) {
        void* fn = nullptr;
        cudaDriverEntryPointQueryResult qr;
        cudaGetDriverEntryPoint("cuTensorMapEncodeTiled", &fn, cudaEnableDefault, &qr);
        enc = (EncodeFn)fn;
        cudaFuncSetAttribute(fused_kernel, cudaFuncAttributeMaxDynamicSharedMemorySize, SM_TOTAL);
    }
    Params P = {};
    auto map3 = [&](int m, int in, cuuint64_t d0, cuuint64_t d1, cuuint64_t d2, cuuint64_t s1, cuuint64_t s2, cuuint32_t b0, cuuint32_t b1, cuuint32_t b2,
                    CUtensorMapSwizzle sw, int promo) {
        const cuuint64_t dim[3] = {d0, d1, d2}, str[2] = {s1, s2};
        const cuuint32_t box[3] = {b0, b1, b2}, ones[3] = {1, 1, 1};
        enc(&P.tm[m], CU_TENSOR_MAP_DATA_TYPE_BFLOAT16, d2 ? 3 : 2, d_in[in], dim, str, box, ones, CU_TENSOR_MAP_INTERLEAVE_NONE, sw, (CUtensorMapL2promotion)promo,
            CU_TENSOR_MAP_FLOAT_OOB_FILL_NONE);
    };
    map3(TM_KH, 1, 64, 3, NHEAD * SK, 128, DH * 2, 64, 3, 32, CU_TENSOR_MAP_SWIZZLE_128B, 0);
    map3(TM_VH, 2, 64, 3, NHEAD * SK, 128, DH * 2, 64, 3, 32, CU_TENSOR_MAP_SWIZZLE_128B, 0);
    map3(TM_VP, 2, 64, 3, NHEAD * SK, 128, DH * 2, PFW, 3, 32, CU_TENSOR_MAP_SWIZZLE_NONE, 0);
    map3(TM_V, 2, 64, NHEAD * SK * 3, 0, 128, 0, 64, 24, 0, CU_TENSOR_MAP_SWIZZLE_128B, 0);
    map3(TM_WO, 4, 32, 20, NHEAD * DH, 64, D_MODEL * 2, 32, 1, DH, CU_TENSOR_MAP_SWIZZLE_64B, PROMOW);
    map3(TM_WOP, 4, 32, 20, NHEAD * DH, 64, D_MODEL * 2, PFW, 1, DH, CU_TENSOR_MAP_SWIZZLE_NONE, 0);
    map3(TM_WQ, 3, 64, NHEAD * 3, D_MODEL, 128, NHEAD * DH * 2, 64, 3, 32, CU_TENSOR_MAP_SWIZZLE_128B, 0);
    map3(TM_W1, 6, DFF, 128, 5, DFF * 2, DFF * 256, 16, 128, 5, CU_TENSOR_MAP_SWIZZLE_32B, PROMO1);
    map3(TM_W2, 8, 64, 10, DFF, 128, D_MODEL * 2, 64, 10, 16, CU_TENSOR_MAP_SWIZZLE_128B, 0);
    P.x = (const __nv_bfloat16*)d_in[0];
    P.k = (const __nv_bfloat16*)d_in[1];
    P.b1 = (const __nv_bfloat16*)d_in[7];
    P.b2 = (const __nv_bfloat16*)d_in[9];
    P.w1 = (const __nv_bfloat16*)d_in[6];
    P.out = (__nv_bfloat16*)d_out;
    for (int i = 0; i < 64; i++) P.tile[i] = make_uint4(SCH.tile[i][0], SCH.tile[i][1], SCH.tile[i][2], 0);
    fused_kernel<<<NCTA + 1, NTHR, SM_TOTAL, cudaStreamPerThread>>>(P);
}
```

```cpp
#include <cuda_runtime.h>
#include <cuda_bf16.h>
#include <cuda.h>
#include <stdint.h>

namespace {

constexpr int D_MODEL = 640, NHEAD = 32, SK = 32768, DH = 192, WIN = 4096, DFF = 1536;
constexpr int NCTA = 128, NTHR = 256;
constexpr int TILE = 64 * DH * 2;
constexpr int HALF = TILE / 2;
constexpr int SUB = 8 * DH * 2;
constexpr int SM_RING = 4 * TILE;
constexpr int SM_W2 = SM_RING + 20480, SM_W1 = SM_W2 + 20480;
constexpr int SM_WQR = 6 * TILE + HALF, SM_WQ = 7 * TILE;
constexpr int SM_PART = 9 * TILE;
constexpr int SM_EXC = SM_PART + 6144;
constexpr int SM_SC = SM_EXC + 1024;
constexpr int SM_BAR = SM_SC + 1024;
constexpr int SM_VEC = SM_BAR + 768;
constexpr int SM_CS = SM_VEC + 384;
constexpr int SM_FAC = SM_CS + 768;
constexpr int SM_ML = SM_FAC + 32;
constexpr int SM_B1 = SM_ML + 64;
constexpr int SM_STAT = SM_B1 + 64;
constexpr int NCB = 28;
constexpr int CB_WO = 18, CB_W1 = 23, CB_W2 = 24, CB_SNAP = 25, CB_REL = 26, CB_WQ = 27;
constexpr int SM_CBAR = SM_STAT + 48;
constexpr int SM_CNT = SM_CBAR + NCB * 8;
constexpr int SM_EPOCH = SM_CNT + NCB * 8;
constexpr int SM_FXS = SM_EPOCH + 4;
constexpr int SM_T0 = SM_FXS + 4;
constexpr int SM_M1 = SM_T0 + 4;
constexpr int SM_MSQ = SM_M1 + 4;
constexpr int SM_TS = SM_MSQ + 8;
constexpr int SM_TOTAL = 232448;
static_assert(SM_TS + 320 <= SM_TOTAL, "smem");
constexpr int NEXC = 16;

constexpr int SPIN = 1 << 20;
enum { TM_V = 0, TM_KH = 1, TM_VH = 2, TM_WO = 3, TM_VP = 4, TM_WOP = 5, TM_W1 = 6, TM_W2 = 7, TM_WQ = 8 };
constexpr uint32_t POL_NORMAL = 0x16F00000u, POL_FIRST = 0x12F00000u;

#define PACE 980
#define PACE0 1500
#define K0FIRST 1
#define NI1 6
#define ETRIG 0x54321000
#define LATEAT 5
#define HWAT 12
#define PFREE 66
#define W1AT0 3
#define W1AT1 3
#define AR1D 300
#define LAG0 12
#define NMMA 2
#define M1AT 1
#define M1P 3
#define NWO1 4
#define WG2 90
#define WG3 65
#define WD4 250
#define WG4 70
#define NWQ1 0
#define P4AT 0
#define P2LATE 0
#define W2AT1 6
#define PCD 400
#define NOWIN 0
#define DPRE 0
#define DPOST 200
#define NIM 4
#define PACES 1300
#define JP2 54
#define PACE2 0
#define WD2 0
#define W2PRE 2
#define OPOLL1 2
#define W2ONE 1
#define W1ONE 1
#define FX1LIM 524288.f
#define SNAPAT 1
#define DMASK 0x0
#define WOKEEP 0x1f
#define VORD2 0x7685943a2b1cd0efull
#define VTRIG 0xba73210
#define WOP 0x44433
#define PARKS 0x95
#define VSLOT 0x1087654321087654ull
#define OPOLL 2
#define S0EARLY 1
#define NPRE 2
#define ARDELAY 800
#define QDELAY 0
#define CMAP 0
#define PFW 8u
#define PUBAT 28
#define HW0 30
#define HW1 31
#define FX2LIM 524288.f
#define PROMOW 2
#define PROMO1 0
#define WD1 300
#define WG1 140
#define WPOL POL_NORMAL

constexpr uint32_t G_A = 1u << 28, G_B = 1u << 29, G_C = 1u << 30;
__host__ __device__ constexpr int ring_hs(int j) { return (j + 4) % 5; }
__host__ __device__ constexpr uint32_t load_word(int j) {
    if (j >= 64) return (uint32_t)(j - 64) << 20 | (SM_RING + ring_hs(j) * HALF) | TM_WO << 8 | (CB_WO + j - 64) << 3 | 2 | !(WOKEEP >> (j - 64) & 1);
    const int e = j >> 1, isv = e >= 16, unit = e & 15;
    return (uint32_t)(unit * 256 + (j & 1) * 32) << 20 | (j < 8 ? j * HALF : SM_RING + ring_hs(j) * HALF) | (TM_KH + isv) << 8 | (j < 8 ? 10 + j : (j - 8) % 10) << 3 | 2
           | (!isv || (DMASK >> unit & 1));
}
__host__ __device__ constexpr int popc(int v) { return v ? (v & 1) + popc(v >> 1) : 0; }
constexpr int NPARK = popc(PARKS);
constexpr int SM_SNAP = SM_RING + ring_hs(12) * HALF, SM_CSP = SM_RING + ring_hs(11) * HALF;
struct Step { int unit, slot, par, next, mma0, nmma; };
struct Sched { uint32_t tile[64][3]; Step st[16]; };
constexpr Sched make_sched() {
    Sched s{};
    for (int j = 0; j < 64; j++) {
        const int e = j >> 1;
        const uint32_t d = load_word(j);
        uint32_t w = (uint32_t)(j < 8 ? 0 : (j - 8) / 10 & 1) << 31 | (e & 15) * 4 << 20 | ((d & 0x3f000) - (j & 1) * HALF) | (d & 0xf8);
        if (e == PUBAT || e == SNAPAT) w |= G_A;
        if (e == HW0 || e == 4) w |= G_B;
        if ((e >= LATEAT && e < LATEAT + 4) || e == HW1) w |= G_C;
        s.tile[j][0] = w;
    }
    for (int j = NI1; j < 69; j++) {
        if (j == 12) continue;
        const int at = j < 12 ? (ETRIG >> (4 * (j - 4)) & 15) : j - 5;
        s.tile[at][1] = load_word(j);
        s.tile[at][2] = j >= PFREE ? 0 : PACE0 + j * PACE / 2 + (j > JP2 ? (j - JP2) * PACE2 : 0);
    }
    int done = 0;
    for (int p = 0; p < 16; p++) {
        Step& c = s.st[p];
        c.unit = (int)(VORD2 >> (4 * p) & 15); c.slot = (int)(VSLOT >> (4 * p) & 15); c.par = p >= 9; c.next = -1;
        c.mma0 = done;
        if (p >= NPARK) { const int avail = p - done + (p >= LAG0); c.nmma = p == 15 ? 16 - done : (avail < NMMA ? avail : NMMA); done += c.nmma; }
    }
    for (int p = 9; p < 16; p++) s.st[VTRIG >> (4 * (p - 9)) & 15].next = p;
    return s;
}
constexpr Sched SCH = make_sched();
__host__ __device__ constexpr int kunit(int o) { return o < 5 ? o + 11 : o == 5 ? 10 : o - 6; }

template <int I> struct IC { static constexpr int value = I; };
template <uint32_t I> struct UC { static constexpr uint32_t value = I; };
template <int A, int B, class F> __device__ __forceinline__ void static_for(F&& f) {
    if constexpr (A < B) { f(IC<A>{}); static_for<A + 1, B>(f); }
}

struct Params {
    CUtensorMap tm[9];
    const __nv_bfloat16 *x, *k, *b1, *b2, *w1;
    __nv_bfloat16* out;
    uint4 tile[66];
};

typedef unsigned long long u64;
constexpr int ACC_PITCH = 256;
constexpr int ACC_BYTES = 80 * ACC_PITCH;
__device__ __align__(1024) unsigned char g_acc[4 * ACC_BYTES];
__device__ __align__(1024) u64 g_l0[NCTA][384];
__device__ __align__(1024) u64 g_ll[2][NCTA][256];
__device__ unsigned g_epoch;
__device__ __align__(128) unsigned g_zflag;
#define TSTAMP(i)
#define TSTAMP2(i)
#define TSTAMPL(i)
#define TDUMP()
#define CSTAMP(i, x)
#define TRACE(i)

__device__ __forceinline__ void mbar_wait(uint32_t bar, uint32_t parity) {
    asm volatile("{\n.reg .pred p;\nLOOP:\nmbarrier.try_wait.parity.shared::cta.b64 p, [%0], %1;\n@!p bra.uni LOOP;\n}" :: "r"(bar), "r"(parity) : "memory");
}
__device__ __forceinline__ bool mbar_test(uint32_t bar, uint32_t parity) {
    uint32_t r;
    asm volatile("{\n.reg .pred p;\nmbarrier.test_wait.parity.shared::cta.b64 p, [%1], %2;\nselp.u32 %0, 1, 0, p;\n}" : "=r"(r) : "r"(bar), "r"(parity) : "memory");
    return __all_sync(~0u, r);
}
__device__ __forceinline__ bool elect() {
    uint32_t r;
    asm volatile("{\n.reg .pred p;\nelect.sync _|p, 0xffffffff;\nselp.u32 %0, 1, 0, p;\n}" : "=r"(r));
    return r != 0;
}
__device__ __forceinline__ void mbar_expect(uint32_t bar, uint32_t bytes) {
    asm volatile("mbarrier.arrive.expect_tx.shared::cta.b64 _, [%0], %1;" :: "r"(bar), "r"(bytes) : "memory");
}
__device__ __forceinline__ uint4 lds128(uint32_t a) {
    uint4 v; asm volatile("ld.shared.v4.u32 {%0,%1,%2,%3}, [%4];" : "=r"(v.x), "=r"(v.y), "=r"(v.z), "=r"(v.w) : "r"(a) : "memory"); return v;
}
__device__ __forceinline__ uint4 ldsm_t(uint32_t a) {
    uint4 v; asm volatile("ldmatrix.sync.aligned.m8n8.x4.trans.shared.b16 {%0,%1,%2,%3}, [%4];" : "=r"(v.x), "=r"(v.y), "=r"(v.z), "=r"(v.w) : "r"(a) : "memory"); return v;
}
__device__ __forceinline__ uint2 lds64(uint32_t a) {
    uint2 v; asm volatile("ld.shared.v2.u32 {%0,%1}, [%2];" : "=r"(v.x), "=r"(v.y) : "r"(a) : "memory"); return v;
}
__device__ __forceinline__ float2 lds64f(uint32_t a) { const uint2 v = lds64(a); return make_float2(__uint_as_float(v.x), __uint_as_float(v.y)); }
__device__ __forceinline__ uint32_t lds32(uint32_t a) {
    uint32_t v; asm volatile("ld.shared.u32 %0, [%1];" : "=r"(v) : "r"(a) : "memory"); return v;
}
__device__ __forceinline__ float ldsf(uint32_t a) { return __uint_as_float(lds32(a)); }
__device__ __forceinline__ void sts32(uint32_t a, uint32_t v) { asm volatile("st.shared.u32 [%0], %1;" :: "r"(a), "r"(v) : "memory"); }
__device__ __forceinline__ void stsf(uint32_t a, float v) { sts32(a, __float_as_uint(v)); }
__device__ __forceinline__ void sts16(uint32_t a, uint32_t v) { asm volatile("st.shared.u16 [%0], %1;" :: "r"(a), "h"((uint16_t)v) : "memory"); }
__device__ __forceinline__ void sts64(uint32_t a, uint32_t x, uint32_t y) { asm volatile("st.shared.v2.u32 [%0], {%1,%2};" :: "r"(a), "r"(x), "r"(y) : "memory"); }
__device__ __forceinline__ void sts64f(uint32_t a, float x, float y) { sts64(a, __float_as_uint(x), __float_as_uint(y)); }
__device__ __forceinline__ void sts128f(uint32_t a, float x, float y, float z, float w) {
    asm volatile("st.shared.v4.f32 [%0], {%1,%2,%3,%4};" :: "r"(a), "f"(x), "f"(y), "f"(z), "f"(w) : "memory");
}
__device__ __forceinline__ void mma(float (&c)[4], const uint4& a, uint32_t b0, uint32_t b1) {
    asm volatile("mma.sync.aligned.m16n8k16.row.col.f32.bf16.bf16.f32 {%0,%1,%2,%3}, {%4,%5,%6,%7}, {%8,%9}, {%0,%1,%2,%3};"
                 : "+f"(c[0]), "+f"(c[1]), "+f"(c[2]), "+f"(c[3]) : "r"(a.x), "r"(a.y), "r"(a.z), "r"(a.w), "r"(b0), "r"(b1));
}
__device__ __forceinline__ u64 ld_rlx(const void* p) {
    u64 a; asm volatile("ld.relaxed.gpu.global.u64 %0, [%1];" : "=l"(a) : "l"(p) : "memory"); return a;
}
__device__ __forceinline__ void ld_rlx2(const void* p, u64& a, u64& b) {
    asm volatile("ld.relaxed.gpu.global.v2.u64 {%0,%1}, [%2];" : "=l"(a), "=l"(b) : "l"(p) : "memory");
}
__device__ __forceinline__ void st_rlx(void* p, u64 a) { asm volatile("st.relaxed.gpu.global.u64 [%0], %1;" :: "l"(p), "l"(a) : "memory"); }
__device__ __forceinline__ u64 ll_pack(float v, uint32_t tag) { return ((u64)tag << 32) | __float_as_uint(v); }
__device__ __forceinline__ float ll_val(u64 w) { return __uint_as_float((uint32_t)w); }
__device__ __forceinline__ uint32_t ll_tag(u64 w) { return (uint32_t)(w >> 32); }
__device__ __forceinline__ float bf_lo(uint32_t u) { return __uint_as_float(u << 16); }
__device__ __forceinline__ float bf_hi(uint32_t u) { return __uint_as_float(u & 0xffff0000u); }
__device__ __forceinline__ uint32_t pack_bf(float lo, float hi) {
    uint32_t r; asm("cvt.rn.bf16x2.f32 %0, %1, %2;" : "=r"(r) : "f"(hi), "f"(lo)); return r;
}
__device__ __forceinline__ float ex2(float v) { float r; asm("ex2.approx.ftz.f32 %0, %1;" : "=f"(r) : "f"(v)); return r; }
__device__ __forceinline__ float rcp(float v) { float r; asm("rcp.approx.ftz.f32 %0, %1;" : "=f"(r) : "f"(v)); return r; }
__device__ __forceinline__ float rsq(float v) { float r; asm("rsqrt.approx.ftz.f32 %0, %1;" : "=f"(r) : "f"(v)); return r; }
__device__ __forceinline__ void bar_sync(int id, int n) { asm volatile("bar.sync %0, %1;" :: "r"(id), "r"(n) : "memory"); }
__device__ __forceinline__ uint32_t clk() { uint32_t c; asm volatile("mov.u32 %0, %clock;" : "=r"(c)); return c; }
__device__ __forceinline__ void sched_fence() { __syncwarp(); while (clk() == 0x9e3779b9u); }
__device__ __forceinline__ uint32_t pin(uint32_t v) { return __shfl_xor_sync(~0u, v, 0); }
__device__ __forceinline__ float shx(float v, int o) { return __shfl_xor_sync(~0u, v, o); }

__device__ __forceinline__ u64 fx_pack(float v, float scale) { return ((u64)__float2ll_rn(v * scale) & ~255ull) | 1ull; }
__device__ __forceinline__ float fx_scale(float meansq) {
    const int e = max(((int)(__float_as_uint(meansq) >> 23) - 127) >> 1, -6);
    return __uint_as_float((uint32_t)(127 + 32 - e) << 23);
}
__device__ __forceinline__ float fx_inv(float scale) { return __uint_as_float((254u << 23) - __float_as_uint(scale)); }
__device__ __forceinline__ uint32_t lo32(u64 w) { uint32_t l; asm("mov.b64 {%0, _}, %1;" : "=r"(l) : "l"(w)); return l; }
__device__ __forceinline__ int hi32(u64 w) { int h; asm("mov.b64 {_, %0}, %1;" : "=r"(h) : "l"(w)); return h; }
__device__ __forceinline__ float fx_val(u64 w) { return (float)hi32(w) * 4294967296.f + (float)lo32(w); }
constexpr float FX2_ONE = 12582912.f;
__device__ __forceinline__ float fx2_scale(float meansq) { return __uint_as_float((uint32_t)(127 + 16 - max(((int)(__float_as_uint(meansq) >> 23) - 127) >> 1, -100)) << 23); }
__device__ __forceinline__ u64 fx2_pack(float a, float b) {
    const uint32_t lo = __float_as_uint(a) * 512u + (1u - 0x4b400000u * 512u);
    return lo | (u64)(__float_as_uint(b) * 16u - 0x4b400000u * 16u + (uint32_t)((int)lo >> 31)) << 32;
}
__device__ __forceinline__ float fx2_lo(u64 w, float inv) { return (float)(int)(__funnelshift_r(lo32(w), hi32(w), 4) & ~31u) * (inv * 0.5f); }
__device__ __forceinline__ float fx2_hi(u64 w, float inv) { return (float)((hi32(w) + 8) & ~15) * inv; }
__device__ __forceinline__ uint32_t fx2_get(u64 w, float inv) {
    return pack_bf((float)(int)__funnelshift_r(lo32(w), hi32(w), 4) * (inv * 0.5f) - inv * 3.f, (float)hi32(w) * inv);
}
__device__ __forceinline__ float fx2_inv(float meansq) { return fx_inv(fx2_scale(meansq)) * 0.0625f; }
__device__ __noinline__ uint32_t fx2_wide(const unsigned char* a, float meansq) {
    __threadfence();
    const u64 w = ld_rlx(a);
    const float inv = fx_inv(fx_scale(meansq));
    return pack_bf(fx2_lo(w, fx2_inv(meansq)) + fx_val(ld_rlx(a + 64)) * inv, fx2_hi(w, fx2_inv(meansq)) + fx_val(ld_rlx(a + 96)) * inv);
}
__device__ __noinline__ uint32_t fx1_wide(const unsigned char* a, float meansq) {
    __threadfence();
    const u64 w = ld_rlx(a);
    const unsigned char* b = a + 64 + (reinterpret_cast<u64>(a) & 31);
    const float inv = fx_inv(fx_scale(meansq)), inv1 = fx2_inv(meansq) * 0.5f;
    return pack_bf((float)(int)(lo32(w) & ~127u) * inv1 + fx_val(ld_rlx(b)) * inv, (float)(hi32(w) & ~127) * inv1 + fx_val(ld_rlx(b + 8)) * inv);
}
__device__ __noinline__ void fx_send(const unsigned char* wide, float v, float meansq, const unsigned char* a, uint32_t flag) {
    asm volatile("red.relaxed.gpu.global.add.u64 [%0], %1;" :: "l"(wide), "l"(fx_pack(v, fx_scale(meansq))) : "memory");
    __threadfence();
    asm volatile("red.relaxed.gpu.global.or.b32 [%0], %1;" :: "l"(a), "r"(flag) : "memory");
}
template <int N, class A, class F> __device__ __forceinline__ void fx2_wait(A a, F look, u64 (&w)[N], uint32_t msqa, float inv, uint32_t (&x)[N]) {
    auto miss = [&]() {
#pragma unroll
        for (int i = 0; i < N; i++) x[i] = fx2_get(w[i], inv);
        return __any_sync(~0u, ((lo32(w[0]) ^ 96) | (lo32(w[N - 1]) ^ 96)) & 0x160);
    };
    if (miss()) {
        int it = 0;
#pragma unroll 1
        do {
            if (__all_sync(~0u, (lo32(w[0]) & lo32(w[N - 1]) & 96) == 96)) {
#pragma unroll
                for (int i = 0; i < N; i++) x[i] = fx2_wide(a(i), ldsf(msqa));
                break;
            }
            look();
        } while (miss() & (++it < SPIN));
    }
}
__device__ __forceinline__ void st_rlx_if(bool p, void* a, u64 v) {
    asm volatile("{\n.reg .pred p;\nsetp.ne.u32 p, %2, 0;\n@p st.relaxed.gpu.global.u64 [%0], %1;\n}" :: "l"(a), "l"(v), "r"((uint32_t)p) : "memory");
}
__device__ __forceinline__ void sts128f(uint32_t a, const float (&v)[4]) { sts128f(a, v[0], v[1], v[2], v[3]); }
__device__ __forceinline__ void bar_arrive(int id, int n) { asm volatile("bar.arrive %0, %1;" :: "r"(id), "r"(n) : "memory"); }
template <class T> __device__ __forceinline__ T* pin(T* p) { return reinterpret_cast<T*>(__shfl_xor_sync(~0u, (u64)p, 0)); }

__device__ __forceinline__ void tma3(uint32_t dst, const CUtensorMap* tm, int c1, int c2, uint32_t bar, uint32_t pol) {
    asm volatile("cp.async.bulk.tensor.3d.shared::cluster.global.mbarrier::complete_tx::bytes.L2::cache_hint [%0], [%1, {%2, %3, %4}], [%5], %6;"
                 :: "r"(dst), "l"(tm), "r"(0), "r"(c1), "r"(c2), "r"(bar), "l"((u64)pol << 32) : "memory");
}
__device__ __forceinline__ void tma_v(uint32_t dst, const CUtensorMap* tm, int line, uint32_t bar) {
    asm volatile("cp.async.bulk.tensor.2d.shared::cluster.global.mbarrier::complete_tx::bytes.L2::cache_hint [%0], [%1, {%2, %3}], [%4], %5;"
                 :: "r"(dst), "l"(tm), "r"(0), "r"(line), "r"(bar), "l"((u64)POL_FIRST << 32) : "memory");
}
__device__ __forceinline__ void tma3_pf(const CUtensorMap* tm, int c1, int c2, uint32_t pol) {
    asm volatile("cp.async.bulk.prefetch.tensor.3d.L2.global.tile.L2::cache_hint [%0, {%1, %2, %3}], %4;"
                 :: "l"(tm), "r"(0), "r"(c1), "r"(c2), "l"((u64)pol << 32) : "memory");
}
__device__ __forceinline__ void issue_half(uint32_t d, uint32_t sb, int rowc, int cta, const CUtensorMap* tm0) {
    const uint32_t bar = sb + SM_CBAR + (d & 0xf8);
    const CUtensorMap* tm = tm0 + ((d >> 8) & 3);
    const bool wo = (d & 0x300) == TM_WO << 8;
    const int c1 = wo ? (cta & 3) + 4 * (d >> 20) : 0, c2 = wo ? (cta >> 2) * DH : rowc + (d >> 20);
    mbar_expect(bar, HALF);
    tma3(sb + (d & 0x3f000), tm, c1, c2, bar, POL_FIRST);
    if (!(d & 1)) tma3_pf(tm + 2, c1, c2, POL_NORMAL);
}
__device__ __forceinline__ uint32_t cnt_inc(uint32_t a, uint32_t last) {
    uint32_t old; asm volatile("atom.relaxed.cta.shared.inc.u32 %0, [%1], %2;" : "=r"(old) : "r"(a), "r"(last) : "memory"); return old;
}
__device__ __forceinline__ void wait_until(uint32_t due) {
#pragma unroll 1
    for (int it = 0; it < 4096; it++) { uint32_t now; asm volatile("mov.u32 %0, %globaltimer_lo;" : "=r"(now)); if ((int)(now - due) >= 0) break; }
}
__device__ __forceinline__ uint32_t bf2_mul(uint32_t a, uint32_t b) { uint32_t r; asm("mul.rn.bf16x2 %0, %1, %2;" : "=r"(r) : "r"(a), "r"(b)); return r; }
__device__ __forceinline__ uint32_t bf2_fma(uint32_t a, uint32_t b, uint32_t c) { uint32_t r; asm("fma.rn.bf16x2 %0, %1, %2, %3;" : "=r"(r) : "r"(a), "r"(b), "r"(c)); return r; }
__device__ __forceinline__ uint32_t bf2_amax(uint32_t a, uint32_t b) { uint32_t r; asm("max.NaN.xorsign.abs.bf16x2 %0, %1, %2;" : "=r"(r) : "r"(a), "r"(b)); return r; }
__device__ __forceinline__ uint4 k_unpack(uint32_t l0, uint32_t l1, uint32_t h, uint32_t m1) {
    const uint32_t ha = h & 0x87878787u, hc = ha * m1 + h, hb = __funnelshift_l(hc, hc, 4);
    return make_uint4(__byte_perm(l0, ha, 0x5140), __byte_perm(l0, ha, 0x7362), __byte_perm(l1, hb, 0x5140), __byte_perm(l1, hb, 0x7362));
}
#define KR4(u, i) "+r"(kr[u][i].x), "+r"(kr[u][i].y), "+r"(kr[u][i].z), "+r"(kr[u][i].w)
#define KR6(u) KR4(u, 0), KR4(u, 1), KR4(u, 2), KR4(u, 3), KR4(u, 4), KR4(u, 5)
__device__ __forceinline__ void k_keep(uint4 (&kr)[8][6], const uint32_t (&c)[18], int e, uint32_t a) {
    asm volatile("{\nKT: .branchtargets K0, K1, K2, K3, K4, K5, K6, K7, K8, K9, K10, K11, K12, K13, K14, K15;\nbrx.idx.uni %210, KT;\n"
                 "K0: mov.b32 %12, %192; mov.b32 %13, %193; mov.b32 %14, %194; mov.b32 %15, %195; mov.b32 %16, %196; mov.b32 %17, %197; mov.b32 %18, %198; mov.b32 %19, %199; mov.b32 %20, %200; mov.b32 %21, %201; mov.b32 %22, %202; mov.b32 %23, %203; mov.b32 %24, %204; mov.b32 %25, %205; mov.b32 %26, %206; mov.b32 %27, %207; mov.b32 %28, %208; mov.b32 %29, %209; bra.uni KE;\n"
                 "K1: mov.b32 %30, %192; mov.b32 %31, %193; mov.b32 %32, %194; mov.b32 %33, %195; mov.b32 %34, %196; mov.b32 %35, %197; mov.b32 %36, %198; mov.b32 %37, %199; mov.b32 %38, %200; mov.b32 %39, %201; mov.b32 %40, %202; mov.b32 %41, %203; mov.b32 %42, %204; mov.b32 %43, %205; mov.b32 %44, %206; mov.b32 %45, %207; mov.b32 %46, %208; mov.b32 %47, %209; bra.uni KE;\n"
                 "K2: mov.b32 %48, %192; mov.b32 %49, %193; mov.b32 %50, %194; mov.b32 %51, %195; mov.b32 %52, %196; mov.b32 %53, %197; mov.b32 %54, %198; mov.b32 %55, %199; mov.b32 %56, %200; mov.b32 %57, %201; mov.b32 %58, %202; mov.b32 %59, %203; mov.b32 %60, %204; mov.b32 %61, %205; mov.b32 %62, %206; mov.b32 %63, %207; mov.b32 %64, %208; mov.b32 %65, %209; bra.uni KE;\n"
                 "K3: mov.b32 %66, %192; mov.b32 %67, %193; mov.b32 %68, %194; mov.b32 %69, %195; mov.b32 %70, %196; mov.b32 %71, %197; mov.b32 %72, %198; mov.b32 %73, %199; mov.b32 %74, %200; mov.b32 %75, %201; mov.b32 %76, %202; mov.b32 %77, %203; mov.b32 %78, %204; mov.b32 %79, %205; mov.b32 %80, %206; mov.b32 %81, %207; mov.b32 %82, %208; mov.b32 %83, %209; bra.uni KE;\n"
                 "K4: mov.b32 %84, %192; mov.b32 %85, %193; mov.b32 %86, %194; mov.b32 %87, %195; mov.b32 %88, %196; mov.b32 %89, %197; mov.b32 %90, %198; mov.b32 %91, %199; mov.b32 %92, %200; mov.b32 %93, %201; mov.b32 %94, %202; mov.b32 %95, %203; mov.b32 %96, %204; mov.b32 %97, %205; mov.b32 %98, %206; mov.b32 %99, %207; mov.b32 %100, %208; mov.b32 %101, %209; bra.uni KE;\n"
                 "K5: mov.b32 %102, %192; mov.b32 %103, %193; mov.b32 %104, %194; mov.b32 %105, %195; mov.b32 %106, %196; mov.b32 %107, %197; mov.b32 %108, %198; mov.b32 %109, %199; mov.b32 %110, %200; mov.b32 %111, %201; mov.b32 %112, %202; mov.b32 %113, %203; mov.b32 %114, %204; mov.b32 %115, %205; mov.b32 %116, %206; mov.b32 %117, %207; mov.b32 %118, %208; mov.b32 %119, %209; bra.uni KE;\n"
                 "K6: mov.b32 %120, %192; mov.b32 %121, %193; mov.b32 %122, %194; mov.b32 %123, %195; mov.b32 %124, %196; mov.b32 %125, %197; mov.b32 %126, %198; mov.b32 %127, %199; mov.b32 %128, %200; mov.b32 %129, %201; mov.b32 %130, %202; mov.b32 %131, %203; mov.b32 %132, %204; mov.b32 %133, %205; mov.b32 %134, %206; mov.b32 %135, %207; mov.b32 %136, %208; mov.b32 %137, %209; bra.uni KE;\n"
                 "K7: mov.b32 %138, %192; mov.b32 %139, %193; mov.b32 %140, %194; mov.b32 %141, %195; mov.b32 %142, %196; mov.b32 %143, %197; mov.b32 %144, %198; mov.b32 %145, %199; mov.b32 %146, %200; mov.b32 %147, %201; mov.b32 %148, %202; mov.b32 %149, %203; mov.b32 %150, %204; mov.b32 %151, %205; mov.b32 %152, %206; mov.b32 %153, %207; mov.b32 %154, %208; mov.b32 %155, %209; bra.uni KE;\n"
                 "K8: mov.b32 %156, %192; mov.b32 %157, %193; mov.b32 %158, %194; mov.b32 %159, %195; mov.b32 %160, %196; mov.b32 %161, %197; mov.b32 %162, %198; mov.b32 %163, %199; mov.b32 %164, %200; mov.b32 %165, %201; mov.b32 %166, %202; mov.b32 %167, %203; mov.b32 %168, %204; mov.b32 %169, %205; mov.b32 %170, %206; mov.b32 %171, %207; mov.b32 %172, %208; mov.b32 %173, %209; bra.uni KE;\n"
                 "K9: mov.b32 %174, %192; mov.b32 %175, %193; mov.b32 %176, %194; mov.b32 %177, %195; mov.b32 %178, %196; mov.b32 %179, %197; mov.b32 %180, %198; mov.b32 %181, %199; mov.b32 %182, %200; mov.b32 %183, %201; mov.b32 %184, %202; mov.b32 %185, %203; mov.b32 %186, %204; mov.b32 %187, %205; mov.b32 %188, %206; mov.b32 %189, %207; mov.b32 %190, %208; mov.b32 %191, %209; bra.uni KE;\n"
                 "K10: st.shared.v2.b32 [%211+75784], {%192, %193}; st.shared.v2.b32 [%211+76288], {%194, %195}; st.shared.v2.b32 [%211+76296], {%196, %197}; mov.b32 %0, %198; mov.b32 %1, %199; mov.b32 %2, %200; mov.b32 %3, %201; mov.b32 %4, %202; mov.b32 %5, %203; mov.b32 %6, %204; mov.b32 %7, %205; mov.b32 %8, %206; mov.b32 %9, %207; mov.b32 %10, %208; mov.b32 %11, %209; bra.uni KE;\n"
                 "K11: st.shared.v2.b32 [%211+0], {%192, %193}; st.shared.v2.b32 [%211+8], {%194, %195}; st.shared.v2.b32 [%211+512], {%196, %197}; st.shared.v2.b32 [%211+520], {%198, %199}; st.shared.v2.b32 [%211+1024], {%200, %201}; st.shared.v2.b32 [%211+1032], {%202, %203}; st.shared.v2.b32 [%211+1536], {%204, %205}; st.shared.v2.b32 [%211+1544], {%206, %207}; st.shared.v2.b32 [%211+2048], {%208, %209}; bra.uni KE;\n"
                 "K12: st.shared.v2.b32 [%211+2056], {%192, %193}; st.shared.v2.b32 [%211+2560], {%194, %195}; st.shared.v2.b32 [%211+2568], {%196, %197}; st.shared.v2.b32 [%211+24576], {%198, %199}; st.shared.v2.b32 [%211+24584], {%200, %201}; st.shared.v2.b32 [%211+25088], {%202, %203}; st.shared.v2.b32 [%211+25096], {%204, %205}; st.shared.v2.b32 [%211+25600], {%206, %207}; st.shared.v2.b32 [%211+25608], {%208, %209}; bra.uni KE;\n"
                 "K13: st.shared.v2.b32 [%211+26112], {%192, %193}; st.shared.v2.b32 [%211+26120], {%194, %195}; st.shared.v2.b32 [%211+26624], {%196, %197}; st.shared.v2.b32 [%211+26632], {%198, %199}; st.shared.v2.b32 [%211+27136], {%200, %201}; st.shared.v2.b32 [%211+27144], {%202, %203}; st.shared.v2.b32 [%211+49152], {%204, %205}; st.shared.v2.b32 [%211+49160], {%206, %207}; st.shared.v2.b32 [%211+49664], {%208, %209}; bra.uni KE;\n"
                 "K14: st.shared.v2.b32 [%211+49672], {%192, %193}; st.shared.v2.b32 [%211+50176], {%194, %195}; st.shared.v2.b32 [%211+50184], {%196, %197}; st.shared.v2.b32 [%211+50688], {%198, %199}; st.shared.v2.b32 [%211+50696], {%200, %201}; st.shared.v2.b32 [%211+51200], {%202, %203}; st.shared.v2.b32 [%211+51208], {%204, %205}; st.shared.v2.b32 [%211+51712], {%206, %207}; st.shared.v2.b32 [%211+51720], {%208, %209}; bra.uni KE;\n"
                 "K15: st.shared.v2.b32 [%211+73728], {%192, %193}; st.shared.v2.b32 [%211+73736], {%194, %195}; st.shared.v2.b32 [%211+74240], {%196, %197}; st.shared.v2.b32 [%211+74248], {%198, %199}; st.shared.v2.b32 [%211+74752], {%200, %201}; st.shared.v2.b32 [%211+74760], {%202, %203}; st.shared.v2.b32 [%211+75264], {%204, %205}; st.shared.v2.b32 [%211+75272], {%206, %207}; st.shared.v2.b32 [%211+75776], {%208, %209}; \nKE:\n}"
                 : KR6(0), KR6(1), KR6(2), KR6(3), KR6(4), KR6(5), KR6(6), KR6(7)
                 : "r"(c[0]), "r"(c[1]), "r"(c[2]), "r"(c[3]), "r"(c[4]), "r"(c[5]), "r"(c[6]), "r"(c[7]), "r"(c[8]), "r"(c[9]), "r"(c[10]), "r"(c[11]), "r"(c[12]), "r"(c[13]), "r"(c[14]), "r"(c[15]), "r"(c[16]), "r"(c[17]), "r"(e), "r"(a) : "memory");
}
__device__ __forceinline__ uint32_t smem_base() { extern __shared__ __align__(1024) unsigned char smem[]; return (uint32_t)__cvta_generic_to_shared(smem); }
__device__ __forceinline__ void k_rare(uint4 v0, uint4 v1, uint4 v2, uint4 v3, uint4 v4, uint4 v5, uint32_t odd, int e, int warp, int lane) {
    const uint32_t sb = smem_base(), g = lane >> 2, t = lane & 3, st = sb + SM_BAR + warp * 96 + 80;
    uint32_t lt; asm volatile("mov.u32 %0, %lanemask_lt;" : "=r"(lt));
    const uint4 v[6] = {v0, v1, v2, v3, v4, v5};
    odd <<= 6;
#pragma unroll
    for (int i = 0; i < 6; i++) if (v[i].x | v[i].y | v[i].z | v[i].w) odd |= 1u << i;
    odd = __reduce_or_sync(~0u, odd);
    uint32_t n = odd >= 64 ? NEXC + 1 : __shfl_sync(~0u, lds32(st), 0);
#pragma unroll 1
    for (; odd && n <= NEXC; odd &= odd - 1) {
        const int i = __ffs(odd) - 1;
#pragma unroll
        for (int k = 1; k < 6; k++) if (i == k) v0 = v[k];
#pragma unroll 1
        for (int k = 0; k < 4; k++, v0.x = v0.y, v0.y = v0.z, v0.z = v0.w) {
            const uint32_t who = __ballot_sync(~0u, v0.x), at = n + __popc(who & lt);
            sts64(v0.x && at < NEXC ? sb + SM_EXC + warp * 128 + at * 8 : st + 8, v0.x, (e * 32 + g * 4) << 16 | (((k & 1) * 4 + t) * 48 + i * 8 + (k >> 1) * 4));
            n += __popc(who);
        }
    }
    const uint32_t bad = lds32(st + 4);
    __syncwarp();
    if (n <= NEXC) sts32(st, n);
    else {
        sts32(st + 4, bad | 1u << e);
        asm volatile("st.shared.u8 [%0], %1;" :: "r"(sb + SM_SC + warp * 128 + g * 16 + (e & 3) * 4 + (e >> 2)), "r"(0) : "memory");
    }
    __syncwarp();
}
template <int K> __device__ __forceinline__ uint32_t& word(uint4& v) { if constexpr (K == 0) return v.x; else if constexpr (K == 1) return v.y; else if constexpr (K == 2) return v.z; else return v.w; }
__device__ __forceinline__ void add_if(bool p, float& d, float a, float b) {
    asm volatile("{\n.reg .pred p;\nsetp.ne.u32 p, %3, 0;\n@p add.f32 %0, %1, %2;\n}" : "+f"(d) : "f"(a), "f"(b), "r"((uint32_t)p));
}
__device__ __forceinline__ float warp_max(float v) {
#pragma unroll
    for (int o = 16; o; o >>= 1) v = fmaxf(v, shx(v, o));
    return v;
}
__device__ __forceinline__ float warp_sum(float v) {
#pragma unroll
    for (int o = 16; o; o >>= 1) v += shx(v, o);
    return v;
}
template <int PITCH> __device__ __forceinline__ void ll_look(const u64* buf, u64 (&w)[4]) {
#pragma unroll
    for (int i = 0; i < 4; i++) w[i] = ld_rlx(buf + i * PITCH);
}
template <int PITCH> __device__ __forceinline__ float ll_gather(const u64* buf, uint32_t tag, u64 (&w)[4]) {
    auto miss = [&]() {
        uint32_t a, b;
        asm("lop3.b32 %0, %1, %2, %3, 0x7e;" : "=r"(a) : "r"(ll_tag(w[0])), "r"(ll_tag(w[1])), "r"(tag));
        asm("lop3.b32 %0, %1, %2, %3, 0x7e;" : "=r"(b) : "r"(ll_tag(w[2])), "r"(ll_tag(w[3])), "r"(tag));
        return __any_sync(~0u, a | b);
    };
    int it = 0;
    goto check;
again:
    ll_look<PITCH>(buf, w);
check:
    if (miss() & (++it < SPIN)) goto again;
    return (ll_val(w[0]) + ll_val(w[1])) + (ll_val(w[2]) + ll_val(w[3]));
}
__device__ __forceinline__ float sum8(uint32_t a, int pitch) {
    float s[8];
#pragma unroll
    for (int w = 0; w < 8; w++) s[w] = ldsf(a + w * pitch);
    return ((s[0] + s[1]) + (s[2] + s[3])) + ((s[4] + s[5]) + (s[6] + s[7]));
}
__device__ __forceinline__ float sum5(float a, float b, float c, float d, float e) { return ((a + b) + (c + d)) + e; }
__device__ __forceinline__ float ln_part(uint2 xp, int lane) {
    const float x0 = bf_lo(xp.x), x1 = bf_hi(xp.x), x2 = bf_lo(xp.y), x3 = bf_hi(xp.y);
    const float s1 = (x0 + x1) + (x2 + x3), s2 = (x0 * x0 + x1 * x1) + (x2 * x2 + x3 * x3);
    return ((lane & 16) ? s2 : s1) + shx((lane & 16) ? s1 : s2, 16);
}
__device__ __forceinline__ float ln_rstd(float mean, float msq) { return rsq(fmaxf(msq - mean * mean, 0.f) + 1e-5f); }
__device__ __forceinline__ float score(const uint4 (&v)[6], const uint4 (&qf)[3]) {
    float d[2][4];
#pragma unroll
    for (int j = 0; j < 2; j++) d[j][0] = d[j][1] = d[j][2] = d[j][3] = 0.f;
#pragma unroll
    for (int i = 0; i < 3; i++) { mma(d[0], v[2 * i], qf[i].x, qf[i].y); mma(d[1], v[2 * i + 1], qf[i].z, qf[i].w); }
    return (d[0][0] + d[0][3]) + (d[1][0] + d[1][3]);
}
__device__ __forceinline__ float k_side(uint32_t sb, uint2 x) {
    const uint32_t qq = lds32(sb + SM_VEC + (x.y & 0xffff));
    return (bf_lo(x.x) * bf_lo(qq) + bf_hi(x.x) * bf_hi(qq)) * 0x1p-64f;
}
__device__ __forceinline__ void k_fix(const __nv_bfloat16* k, uint32_t bad, int warp, int lane) {
    const uint32_t sb = smem_base(), g = lane >> 2, sa = sb + SM_PART + warp * 768 + 256;
    const uint2 x = lds64(sb + SM_EXC + warp * 128 + (lane & 15) * 8);
    if ((int)x.y >= 0x40000000 && lane < 16) asm volatile("red.shared.add.f32 [%0], %1;" :: "r"(sa + ((x.y >> 16) & 511)), "f"(k_side(sb, x)) : "memory");
    __syncwarp();
#pragma unroll 1
    for (bad &= 0xffff; bad; bad &= bad - 1) {
        const int e = __ffs(bad) - 1;
        const __nv_bfloat16* kp = k + (e * 256 + (g >> 1) + 4 * (g & 1)) * DH + (lane & 3) * 8;
        uint4 v[6], qf[3];
#pragma unroll
        for (int i = 0; i < 6; i++) v[i] = *reinterpret_cast<const uint4*>(kp + i * 32);
#pragma unroll
        for (int i = 0; i < 3; i++) qf[i] = lds128(sb + SM_VEC + (lane & 7) * 48 + i * 16);
        stsf(sa + e * 32 + g * 4, score(v, qf) * 0x1p-64f);
    }
    __syncwarp();
}
constexpr float CS = 0.07216878364870322f * 1.4426950408889634f;
__device__ __forceinline__ void head_weight(const u64* a, u64 pm, u64 pl, int layer, int lane) {
    const uint32_t sb = smem_base(), tag = lds32(sb + SM_EPOCH) * 4 + 2 + 2 * layer;
#pragma unroll 1
    for (int it = 0; it < SPIN; it++) {
        if (__all_sync(~0u, ll_tag(pm) == tag && ll_tag(pl) == tag)) break;
        ld_rlx2(a, pm, pl);
    }
    const float f = ex2((ll_val(pm) - warp_max(ll_val(pm))) * CS);
    const float w = f * rcp(warp_sum(f * ll_val(pl)));
    if (lane < 8) stsf(sb + SM_FAC + lane * 4, w);
}
constexpr uint32_t ONES = 0x3f803f80u;

__global__ void __launch_bounds__(NTHR, 1) fused_kernel(const __grid_constant__ Params P) {
    const uint32_t sb = smem_base();
    const int bx = blockIdx.x;
    const int cta0 = bx >= NCTA || CMAP == 0 ? bx : CMAP == 4 ? (((bx >> 1) & 7) + (bx >> 5) * 8) * 4 + ((bx >> 4) & 1) * 2 + (bx & 1)
                   : (((bx >> 1) & 15) + (bx >> 6) * 16) * 4 + ((bx >> 5) & 1) * 2 + (bx & 1);
    if (__all_sync(~0u, threadIdx.x >= NTHR - 32 && bx < NCTA) && elect()) {
        asm volatile("mbarrier.init.shared::cta.b64 [%0], 1;" :: "r"(sb + SM_CBAR + CB_WQ * 8));
        asm volatile("mbarrier.init.shared::cta.b64 [%0], 1;" :: "r"(sb + SM_CBAR + 80));
        asm volatile("fence.mbarrier_init.release.cluster;" ::: "memory");
        mbar_expect(sb + SM_CBAR + CB_WQ * 8, 5 * HALF);
        auto k0 = [&]() {
            mbar_expect(sb + SM_CBAR + 80, HALF);
            tma3(sb, &P.tm[TM_KH], 0, (cta0 >> 2) * SK + (SK - WIN) + (cta0 & 3) * 64, sb + SM_CBAR + 80, POL_FIRST);
        };
        if (K0FIRST) k0();
#pragma unroll 1
        for (int i = 0; i < 5; i++) tma3(sb + SM_WQR + (i == 4 ? 0 : i + 1) * HALF, &P.tm[TM_WQ], (cta0 >> 2) * 3, (cta0 & 3) * 160 + i * 32, sb + SM_CBAR + CB_WQ * 8, POL_FIRST);
        if (!K0FIRST) k0();
    }
    __syncwarp();
    int id = cta0 * NTHR + threadIdx.x, tid, lane, g, t, key, warp, cta, mlp, rowc, roww, j40;
    uint32_t maskA, maskB, barw, subw, prow;
    auto fresh = [&]() {
        const int cw = __shfl_sync(~0u, id >> 5, 0);
        id = pin(id); tid = id & 255; lane = id & 31; g = lane >> 2; t = lane & 3; key = (g >> 1) + 4 * (g & 1);
        const uint32_t m = (g & 1) ? 0xffff0000u : 0x0000ffffu;
        maskA = (g & 2) ? 0u : m; maskB = (g & 2) ? m : 0u;
        warp = cw & 7; cta = cw >> 3;
        mlp = (cta & 3) == 3 ? 96 : (cta >> 2) * 3 + (cta & 3);
        rowc = (cta >> 2) * SK + (SK - WIN) + (cta & 3) * 64; roww = rowc + warp * 8;
        j40 = (cta & 3) * 40;
        barw = sb + SM_BAR + warp * 96; subw = sb + warp * SUB; prow = sb + SM_PART + warp * 768;
    };
    fresh();
    auto fresh_lane = [&]() { id = pin(id); tid = id & 255; lane = id & 31; g = lane >> 2; t = lane & 3; };
    auto pinf = [&](float v) { return __uint_as_float(pin(__float_as_uint(v) | (id >> 16))); };

    if (cta == NCTA) {
        const uint32_t ep = *(volatile unsigned*)&g_epoch;
        if (tid == 0) {
#pragma unroll 1
            for (int it = 0; it < SPIN; it++) { if (ll_tag(ld_rlx(&g_ll[0][0][192])) == ep * 4 + 2) break; __nanosleep(200); }
        }
        __syncthreads();
#pragma unroll 1
        for (int i = tid; i < 4 * 80 * 8; i += NTHR)
            *reinterpret_cast<uint4*>(g_acc + (i >> 3) * ACC_PITCH + (i & 7) * 16) = make_uint4(0, 0, 0, 0);
        __threadfence();
        __syncthreads();
        if (tid == 0) asm volatile("st.relaxed.gpu.global.u32 [%0], %1;" :: "l"(&g_zflag), "r"(ep + 1) : "memory");
        return;
    }
    TSTAMP(0);
    if (tid == 64) { uint32_t now; asm volatile("mov.u32 %0, %globaltimer_lo;" : "=r"(now)); sts32(sb + SM_T0, now); }

    const CUtensorMap* tmk = reinterpret_cast<const CUtensorMap*>(__shfl_sync(~0u, (u64)&P.tm[0] + (lane >> 5), 0));
    auto c4 = [&]() { return 32 * min(warp, 4) + 16 * (t >> 1) + 2 * g + (t & 1); };
    auto xcol = [&](int i, int tt) { return (i < 2 ? 64 * i + 8 * warp : 128 + 8 * (warp >> 1)) + 2 * tt; };
    uint2 xp;
    uint32_t px[3], small;
    auto issue_first = [&](int j) {
        mbar_expect(sb + SM_CBAR + 80 + j * 8, HALF);
        tma3(sb + j * HALF, tmk + TM_KH, 0, rowc + (j >> 1) * 256 + (j & 1) * 32, sb + SM_CBAR + 80 + j * 8, POL_FIRST);
    };
    if (elect()) {
        if (warp != 2) asm volatile("mbarrier.init.shared::cta.b64 [%0], 1;" :: "r"(sb + SM_CBAR + 64 + warp * 8));
#pragma unroll
        for (int i = 0; i < 9; i++) asm volatile("mbarrier.init.shared::cta.b64 [%0], 1;" :: "r"(barw + i * 8));
        asm volatile("mbarrier.init.shared::cta.b64 [%0], 1;" :: "r"(sb + SM_CBAR + warp * 8));
        asm volatile("mbarrier.init.shared::cta.b64 [%0], 1;" :: "r"(sb + SM_CBAR + 128 + warp * 8));
        if (warp < 3) asm volatile("mbarrier.init.shared::cta.b64 [%0], %1;" :: "r"(sb + SM_CBAR + 192 + warp * 8), "r"(warp == 2 ? 8 : 1));
        sts64(barw + 80, 0, 0);
        asm volatile("fence.mbarrier_init.release.cluster;" ::: "memory");
        asm volatile("prefetch.tensormap [%0];" :: "l"(tmk + warp) : "memory");
    }
    __syncwarp();
    asm volatile("ld.global.nc.v2.u32 {%0,%1}, [%2];" : "=r"(xp.x), "=r"(xp.y) : "l"(P.x + 4 * c4()) : "memory");
#pragma unroll
    for (int i = 0; i < 3; i++) asm volatile("ld.global.nc.u32 %0, [%1];" : "=r"(px[i]) : "l"(P.x + 4 * j40 + xcol(i, t)) : "memory");
    asm volatile("ld.relaxed.gpu.global.u32 %0, [%1];" : "=r"(small) : "l"(lane < 16 ? (const void*)(P.b1 + min(mlp, 95) * 16 + (lane & 14)) : (const void*)&g_epoch) : "memory");
    if (tid >= 192 && tid < 192 + NCB) sts32(sb + SM_CNT + (tid - 192) * 8, 0);
    unsigned char* accg = reinterpret_cast<unsigned char*>(__shfl_sync(~0u, (u64)g_acc + (lane >> 5), 0));
    auto release = [&](const uint4& tw) {
        uint32_t old;
        __syncwarp();
        asm volatile("atom.relaxed.cta.shared.add.u32 %0, [%1], 1;" : "=r"(old) : "r"(sb + SM_CNT + (tw.x & 0xf8)) : "memory");
        return old;
    };
    auto refill = [&](const uint4& tw, uint32_t old) {
        if (__any_sync(~0u, (old & 127) == 127 && (tw.y & 2))) {
            wait_until(lds32(sb + SM_T0) + tw.z);
            if (elect()) issue_half(tw.y, sb, rowc, cta, tmk);
            __syncwarp();
        }
    };
    __syncthreads();
    auto issue_paced = [&](int j0, int j1) {
        if (warp >= j0 && warp < j1) {
            wait_until(lds32(sb + SM_T0) + PACES + warp * PACE / 2);
            if (elect()) issue_first(warp);
            __syncwarp();
        }
    };

    uint32_t offV0, offV2;
    auto calc_offsets = [&]() {
        offV0 = subw + (6 * t) * 128 + ((g ^ ((6 * t) & 7)) << 4);
        offV2 = subw + (6 * t + 2) * 128 + ((g ^ ((6 * t + 2) & 7)) << 4);
    };
    calc_offsets();

    auto load_v = [&](uint4 (&v)[6], uint32_t so) {
        v[0] = lds128(offV0 + so); v[1] = lds128((offV0 ^ 16) + so + 128); v[2] = lds128(offV2 + so);
        v[3] = lds128((offV2 ^ 16) + so + 128); v[4] = lds128((offV0 ^ 64) + so + 512); v[5] = lds128((offV0 ^ 80) + so + 640);
    };
    auto issue_v = [&](auto I, int dw) {
        constexpr Step c = SCH.st[I.value];
        const uint32_t bar = barw + dw * 96 + c.slot * 8;
        mbar_expect(bar, SUB);
        tma_v(subw + dw * SUB + c.slot * TILE, tmk, roww * 3 + dw * 24 + c.unit * 768, bar);
    };
    auto refill2 = [&](auto I) { __syncwarp(); if (elect()) issue_v(I, 0); };
    uint4 wq0[6], wqh[3], wq1[6];
    auto load_wq1 = [&](int i) { wq1[i] = lds128((i == 2 ? offV2 : i == 3 ? (offV2 ^ 16) + 128 : (offV0 ^ (i * 16)) + i * 128) + SM_WQ + TILE); };
    auto load_wq = [&]() {
        load_v(wq0, SM_WQ);
        const uint32_t so = SM_WQR - ((warp + 1) >> 1) * SUB;
        wqh[0] = lds128(((warp & 1) ? (offV2 ^ 16) + 128 : offV0) + so);
        wqh[1] = lds128(((warp & 1) ? (offV0 ^ 64) + 512 : (offV0 ^ 16) + 128) + so);
        wqh[2] = lds128(((warp & 1) ? (offV0 ^ 80) + 640 : offV2) + so);
#pragma unroll
        for (int i = 0; i < NWQ1; i++) load_wq1(i);
    };
    uint4 kr[8][6];
    const unsigned char* rap;
    u64 rw[2];
    auto look_rw = [&]() { rw[0] = ld_rlx(rap); rw[1] = ld_rlx(rap + 40 * ACC_PITCH); };
    auto q_proj = [&](auto L, uint32_t (&p)[3], uint32_t pst) {
        if (L.value == 0 && g >= 4) p[0] = p[1] = p[2] = ONES;
        float a[3][4], b[3][4];
        const uint32_t dH = __byte_perm(p[2], 0, (warp & 1) ? 0x3232 : 0x1010);
        const uint32_t dA = __byte_perm(p[0], 0, 0x1010), dB = __byte_perm(p[0], 0, 0x3232), dC = __byte_perm(p[1], 0, 0x1010), dD = __byte_perm(p[1], 0, 0x3232);
#pragma unroll
        for (int i = NWQ1; i < 3; i++) load_wq1(i);
#pragma unroll
        for (int j = 0; j < 3; j++) { a[j][0] = a[j][1] = a[j][2] = a[j][3] = 0.f; mma(a[j], wq0[j], dA & maskA, dA & maskB); }
#pragma unroll
        for (int j = 0; j < 3; j++) { b[j][0] = b[j][1] = b[j][2] = b[j][3] = 0.f; mma(b[j], wq0[j + 3], dB & maskA, dB & maskB); }
#pragma unroll
        for (int j = 0; j < 3; j++) mma(a[j], wqh[j], dH & maskA, dH & maskB);
#pragma unroll
        for (int i = 3; i < 6; i++) load_wq1(i);
        if (L.value == 1 && P4AT == 2) refill2(IC<4>{});
#pragma unroll
        for (int j = 0; j < 3; j++) mma(b[j], wq1[j], dC & maskA, dC & maskB);
#pragma unroll
        for (int j = 0; j < 3; j++) mma(a[j], wq1[j + 3], dD & maskA, dD & maskB);
#pragma unroll
        for (int j = 0; j < 3; j++) {
            if (L.value) {
#pragma unroll
                for (int k = 0; k < 2; k++) { a[j][k] += b[j][k]; add_if(t & 2, a[j][k], a[j][k + 2], b[j][k + 2]); }
                sts64f(pst + j * 256, a[j][0], a[j][1]);
            } else sts128f(pst + j * 256, a[j][0] + b[j][0], a[j][1] + b[j][1], a[j][2] + b[j][2], a[j][3] + b[j][3]);
        }
        CSTAMP(23, __float_as_uint(a[2][1]));
        uint32_t tag;
        if (L.value) tag = lds32(sb + SM_EPOCH) * 4 + 3;
        u64* pub = L.value ? &g_ll[0][cta][tid] : &g_l0[cta][tid];
        if (L.value == 0) asm volatile("fence.proxy.async.shared::cta;" ::: "memory");
        TSTAMPL(21);
        __syncthreads();
        if (!L.value) tag = lds32(sb + SM_EPOCH) * 4 + 1;
#pragma unroll 1
        for (int k = 0; k < 2 - L.value; k++) st_rlx_if(tid < 192, pub + k * 192, ll_pack(sum8(sb + (k ? SM_CSP : SM_PART) + tid * 4, 768), tag));
        TSTAMPL(23);
            CSTAMP(24, tag);
    };
    auto ln_stats = [&]() {
        float ss = ln_part(xp, lane);
        ss += shx(ss, 8); ss += shx(ss, 4); ss += shx(ss, 2); ss += shx(ss, 1);
        stsf(sb + SM_STAT + min(warp, 5) * 8 + (lane >> 4) * 4, ss);
    };
    auto ln_final = [&](float& mean, float& rstd) {
        float2 v[5];
#pragma unroll
        for (int w = 0; w < 5; w++) v[w] = lds64f(sb + SM_STAT + w * 8);
        mean = sum5(v[0].x, v[1].x, v[2].x, v[3].x, v[4].x) * (1.f / D_MODEL);
        const float msq = sum5(v[0].y, v[1].y, v[2].y, v[3].y, v[4].y) * (1.f / D_MODEL);
        rstd = ln_rstd(mean, msq);
        stsf(sb + SM_FXS, msq);
    };
    auto q_addr = [&](int d) { return sb + SM_VEC + (((d >> 1) & 1) * 4 + ((d >> 3) & 3)) * 48 + (d >> 5) * 8 + ((d >> 2) & 1) * 4 + (d & 1) * 2; };
    {
#pragma unroll
        for (int u = 0; u < 8; u++)
#pragma unroll
            for (int i = 0; i < 6; i++) kr[u][i] = lds128(sb + SM_CS + (u * 6 + i) * 16);
        issue_paced(1, NIM);
        ln_stats();
        if (tid == 16) { sts32(sb + SM_EPOCH, small); sts32(sb + SM_M1, ~0u); }
        else if (tid < 16) sts32(sb + SM_B1 + tid * 4, (tid & 1) ? small & 0xffff0000u : small << 16);
        mbar_wait(sb + SM_CBAR + CB_WQ * 8, 0);
        load_wq();
        q_proj(IC<0>{}, px, sb + (t < 2 ? SM_PART : SM_CSP) + warp * 768 + (8 * g + 4 * (t & 1)) * 4);
    }
    {
        uint32_t offQ, offL;
        auto calc_ql = [&]() {
            offQ = pin(sb + SM_VEC + (lane & 7) * 48);
            offL = pin(subw + lane * 16);
        };

        auto issue_w = [&](auto L, int which) {
            const uint32_t bar = sb + SM_CBAR + (CB_W1 + which) * 8;
            if (mlp == 96) asm volatile("mbarrier.arrive.shared::cta.b64 _, [%0];" :: "r"(bar) : "memory");
            else {
                mbar_expect(bar, 20480);
                if (which) {
                    tma3(sb + (L.value ? 3 * TILE : SM_W2), tmk + TM_W2, 0, mlp * 16, bar, W2ONE ? POL_FIRST : WPOL);
                    if (W2ONE && !L.value) tma3_pf(tmk + TM_W2, 0, mlp * 16, POL_NORMAL);
                    if (W1ONE && !L.value) asm volatile("cp.async.bulk.prefetch.L2.global.L2::cache_hint [%0], 20480, %1;" :: "l"(P.w1 + mlp * 10240), "l"((u64)POL_NORMAL << 32) : "memory");
                }
                else asm volatile("cp.async.bulk.tensor.3d.shared::cluster.global.mbarrier::complete_tx::bytes.L2::cache_hint [%0], [%1, {%2, %3, %3}], [%4], %5;"
                                  :: "r"(sb + (L.value ? 2 * TILE : SM_W1)), "l"(tmk + TM_W1), "r"(mlp * 16), "r"(0), "r"(bar), "l"((u64)(W1ONE ? POL_FIRST : WPOL) << 32) : "memory");
            }
        };
        float acc[3][4];
        auto load_q = [&](uint4 (&qf)[3]) {
#pragma unroll
            for (int i = 0; i < 3; i++) qf[i] = lds128(offQ + i * 16);
        };
        auto softmax = [&](float S0, float S1, float S2, float S3) {
            int mi = __float_as_int(fmaxf(fmaxf(S0, S1), fmaxf(S2, S3)));
            mi = __reduce_max_sync(~0u, mi ^ ((mi >> 31) & 0x7fffffff));
            const float mrun = __int_as_float(mi ^ ((mi >> 31) & 0x7fffffff));
            const float p0 = ex2((S0 - mrun) * CS), p1 = ex2((S1 - mrun) * CS), p2 = ex2((S2 - mrun) * CS), p3 = ex2((S3 - mrun) * CS);
            const uint32_t pa = pack_bf(p0, p1), pb = pack_bf(p2, p3), pw = prow + 256 + (key >> 1) * 80 + t * 4 + (key & 1) * 2;
            sts16(pw, pa); sts16(pw + 16, pa >> 16); sts16(pw + 32, pb); sts16(pw + 48, pb >> 16);
            __syncwarp();
#pragma unroll
            for (int j = 0; j < 3; j++) acc[j][0] = acc[j][1] = acc[j][2] = acc[j][3] = 0.f;
            return make_float2(mrun, (p0 + p1) + (p2 + p3));
        };
        auto pv = [&](const uint4 (&v)[6], uint32_t pp) {
            const uint32_t dA = __byte_perm(pp, 0, 0x1010), dB = __byte_perm(pp, 0, 0x3232);
            mma(acc[0], v[0], dA & maskA, dA & maskB); mma(acc[1], v[1], dA & maskA, dA & maskB); mma(acc[2], v[2], dA & maskA, dA & maskB);
            mma(acc[0], v[3], dB & maskA, dB & maskB); mma(acc[1], v[4], dB & maskA, dB & maskB); mma(acc[2], v[5], dB & maskA, dB & maskB);
        };
        auto sa = [&]() { return prow + 256 + t * 32 + g * 4; };
        auto pass1 = [&]() {
            if (NIM < NI1) issue_paced(NIM, NI1);
            fresh();
            calc_ql();
            __syncthreads();
            sts64(prow + lane * 8, xp.x, xp.y);
            int e = 0;
            const uint4* tab = P.tile + (warp >> 2);
            uint4 tw = tab[0];
            uint32_t ka[3];
#pragma unroll
            for (int j = 0; j < 3; j++) ka[j] = pin(subw + key * 384 + j * 128 + ((t ^ ((3 * key + j) & 7)) << 4));
            auto load_k = [&](uint4 (&v)[6], uint32_t so) {
#pragma unroll
                for (int i = 0; i < 6; i++) v[i] = lds128(((i & 1) ? ka[i >> 1] ^ 64 : ka[i >> 1]) + so);
            };
            const uint32_t s0 = pin(prow + 256 + g * 4), sca = pin(sb + SM_SC + warp * 128 + g * 16);
#pragma unroll 1
            do {
                const uint4 tn = tab[2 * e + 2];
                uint4 v[6], qf[3];
                if (tw.x & (G_A | G_B | G_C)) {
                    if ((tw.x & G_A) && warp == 7 && elect()) {
                        mbar_expect(sb + SM_CBAR + CB_SNAP * 8, HALF);
                        asm volatile("cp.async.bulk.shared::cluster.global.mbarrier::complete_tx::bytes [%0], [%1], 12288, [%2];"
                                     :: "r"(sb + SM_SNAP), "l"(&g_l0[cta & ~3][0]), "r"(sb + SM_CBAR + CB_SNAP * 8) : "memory");
                    }
                    if (tw.x & G_B) {
                        if (warp < 6) {
                            mbar_wait(sb + SM_CBAR + CB_SNAP * 8, 0);
                            float qc[2] = {0.f, 0.f}, mean, rstd;
#pragma unroll 1
                            for (int k = 0; k < 2; k++) {
                                u64 qw[4];
#pragma unroll
                                for (int i = 0; i < 4; i++) { const uint2 x = lds64(sb + SM_SNAP + i * 3072 + k * 1536 + tid * 8); qw[i] = x.x | (u64)x.y << 32; }
                                qc[0] = qc[1];
                                qc[1] = ll_gather<384>(&g_l0[cta & ~3][k * 192 + tid], lds32(sb + SM_EPOCH) * 4 + 1, qw);
                            }
                            ln_final(mean, rstd);
                            stsf(sb + SM_CS + tid * 4, qc[1]);
                            const float q = (qc[0] - mean * qc[1]) * rstd;
                            sts16(q_addr(tid), pack_bf(q, q));
                        }
                        __syncthreads();
                        if (warp == 7 && elect()) issue_half(UC<load_word(12)>::value, sb, rowc, cta, tmk);
                        TSTAMP(2);
                    }
                    if (tw.x & G_C) {
                        load_k(v, (e - LATEAT) * TILE);
                        load_q(qf);
                        stsf(s0 + (e - LATEAT) * 32, score(v, qf));
                    }
                }
                load_q(qf);
                mbar_wait(sb + SM_CBAR + (tw.x & 0xf8), tw.x >> 31);
                TRACE(e);
                load_k(v, tw.x & 0x3f000);
                const uint32_t old = release(tw);
                const float s = score(v, qf);
                uint32_t m;
                {
                    uint32_t a[6];
#pragma unroll
                    for (int i = 0; i < 6; i++) a[i] = bf2_amax(bf2_amax(v[i].x, v[i].y), bf2_amax(v[i].z, v[i].w));
                    m = bf2_amax(bf2_amax(bf2_amax(a[0], a[1]), bf2_amax(a[2], a[3])), bf2_amax(a[4], a[5]));
                }
                m = bf2_amax(m, m >> 16) & 0x7f80;
                m = max(m, __shfl_xor_sync(~0u, m, 1));
                stsf(s0 + e * 32, s);
                m = max(m, __shfl_xor_sync(~0u, m, 2));
                refill(tw, old);
                const uint32_t b = min(max(m, 15u << 7) - (15u << 7), 126u << 7);
                const uint32_t dn = ((127u << 7) - b) * 0x10001u, up = ((127u << 7 | 0x8000u) + b) * 0x10001u;
                uint32_t c[18], any = m > (141u << 7);
#pragma unroll
                for (int i = 0; i < 6; i++) {
                    const uint32_t y0 = bf2_mul(v[i].x, dn), y1 = bf2_mul(v[i].y, dn), y2 = bf2_mul(v[i].z, dn), y3 = bf2_mul(v[i].w, dn);
                    v[i] = make_uint4(bf2_fma(y0, up, v[i].x), bf2_fma(y1, up, v[i].y), bf2_fma(y2, up, v[i].z), bf2_fma(y3, up, v[i].w));
                    any |= v[i].x | v[i].y;
                    any |= v[i].z | v[i].w;
                    const uint32_t hb = __byte_perm(y2, y3, 0x7531);
                    c[3 * i] = __byte_perm(y0, y1, 0x6420); c[3 * i + 1] = __byte_perm(y2, y3, 0x6420);
                    c[3 * i + 2] = __byte_perm(y0, y1, 0x7531) | __funnelshift_r(hb, hb, 4);
                }
                asm volatile("st.shared.u8 [%0], %1;" :: "r"(sca + (e & 3) * 4 + (e >> 2)), "r"((b >> 7) + 63) : "memory");
                const bool rare = __any_sync(~0u, any);
                k_keep(kr, c, e, offL);
                if (rare) k_rare(v[0], v[1], v[2], v[3], v[4], v[5], m > (141u << 7), e, warp, lane);
                tw = tn;
            } while (++e < 16);
            asm volatile("fence.proxy.async.shared::cta;" ::: "memory");
            __syncwarp();
            TSTAMP(10);
            fresh(); calc_offsets();
            {
                const uint2 st = lds64(barw + 80);
                const uint32_t xa = sb + SM_EXC + warp * 128 + (lane & 15) * 8 + 4;
                uint32_t pos = lds32(xa), lt;
                asm volatile("mov.u32 %0, %lanemask_lt;" : "=r"(lt));
                if (lane >= st.x) pos = 0x80000000u;
                const bool dup = (__match_any_sync(~0u, pos >> 16) & lt) && lane < st.x;
                if (lane < 16) sts32(xa, dup ? pos | 0x40000000u : pos);
                if (__any_sync(~0u, dup)) sts32(barw + 84, st.y | 0x10000u);
                const float2 ml = softmax(ldsf(sa()), ldsf(sa() + 128), ldsf(sa() + 256), ldsf(sa() + 384));
                sts64f(sb + SM_ML + warp * 8, ml.x, warp_sum(ml.y));
            }
            u64 pm = 0, pl = 0;
#pragma unroll 1
            do {
                const uint4 tn = tab[2 * e + 2];
                if (tw.x & (G_A | G_B | G_C)) {
                    if (tw.x & G_A) {
                        if (lane < 24) st_rlx(&g_ll[0][cta][warp * 24 + lane], 0ull);
                        else if (lane < 28) st_rlx(&g_ll[0][cta][168 + warp * 4 + lane], ll_pack(ldsf(sb + SM_ML + warp * 8 + (lane & 1) * 4), lds32(sb + SM_EPOCH) * 4 + 2));
                    }
                    if (warp == 2) {
                        if (tw.x & G_B) ld_rlx2(&g_ll[0][cta ^ (lane >> 3)][192 + (lane & 7) * 4], pm, pl);
                        if (tw.x & G_C) head_weight(&g_ll[0][cta ^ (lane >> 3)][192 + (lane & 7) * 4], pm, pl, 0, lane);
                    }
                    __syncwarp();
                }
                const uint32_t pp = lds32(prow + 256 + t * 80 + ((tw.x >> 20) & 255));
                mbar_wait(sb + SM_CBAR + (tw.x & 0xf8), tw.x >> 31);
                TRACE(e);
                uint4 v[6];
                load_v(v, tw.x & 0x3f000);
                refill(tw, release(tw));
                pv(v, pp);
                tw = tn;
            } while (++e < 32);
        };
        uint32_t osa, ora, owa, orow, otag;
        u64* olb;
        float xc;
        auto o_setup = [&](auto L) {
            fresh();
            const int lz = lane, d = warp * 24 + min(lz, 23);
            osa = pin(prow + ((lz >> 2) * 8 + (lz & 1) * 4 + (lz & 2)) * 4);
            ora = pin(sb + SM_PART + d * 4);
            olb = pin(&g_ll[L.value][cta & ~3][d]);
            orow = pin((lz & 1) + 2 * (lz & 2) + 2 * (lz >> 4));
            owa = pin(sb + SM_RING + warp * 1536 + orow * 64 + ((((lz >> 2) & 3) ^ (orow >> 1)) << 4));
            otag = lds32(sb + SM_EPOCH) * 4 + 2 + 2 * L.value;
            uint32_t x; asm volatile("ld.shared.u16 %0, [%1];" : "=r"(x) : "r"(prow + ((cta & 1) * 16 + (lz >> 3) * 4 + (cta & 2) + ((lz >> 2) & 1)) * 8 + (lz & 3) * 2) : "memory");
            xc = bf_lo(x) * (1.f / 32);
        };
        auto wo_at = [&](auto A) {
            constexpr uint32_t x = WOP ^ A.value * 0x11111;
            if constexpr (A.value > 0 && ((x - 0x11111) & ~x & 0x88888) != 0) {
                if ((WOP >> (4 * warp) & 15) == A.value) {
                    mbar_wait(sb + SM_CBAR + CB_REL * 8, 0);
                    if (elect()) {
                        const uint32_t bar = sb + SM_CBAR + (CB_WO + warp) * 8;
                        mbar_expect(bar, HALF);
                        tma3(sb + SM_RING + (warp + (warp < 2 ? 3 : -2)) * HALF, tmk + TM_WO, (cta & 3) + 4 * warp, (cta >> 2) * DH, bar, POL_FIRST);
                    }
                    __syncwarp();
                }
            }
        };
        static_assert(ring_hs(64) == 3, "wo");
        auto pass2 = [&]() {
            constexpr IC<1> L{};
            if (P4AT == 0) refill2(IC<4>{});
            if (P2LATE == 1 && warp >= 4) refill2(IC<2>{});
            uint4 tb[8][3];
            auto load_tb = [&](auto I) {
#pragma unroll
                for (int i = 0; i < 3; i++) tb[I.value][i] = lds128(offL + (I.value >> 1) * TILE + ((I.value & 1) * 3 + i) * 512);
            };
            const u64* qb = &g_ll[0][cta & ~3][min(tid, 191)];
            {
                uint32_t x[2];
                fx2_wait<2>([&](int i) { return rap + i * 40 * ACC_PITCH; }, look_rw, rw, sb + SM_MSQ, ldsf(sb + SM_MSQ + 4), x);
                xp = make_uint2(x[0], x[1]);
                CSTAMP(25, xp.y);
            }
            ln_stats();
            u64 qw[4];
            ll_look<256>(qb, qw);
            const float cs = ldsf(sb + SM_CS + min(tid, 191) * 4);
            const uint32_t qtag = lds32(sb + SM_EPOCH) * 4 + 3, qa = pin(q_addr(min(tid, 191)));
            fresh_lane();
            offQ = sb + SM_VEC + (lane & 7) * 48; offL = subw + lane * 16;
            __syncthreads();
            auto vwait = [&](auto I) { mbar_wait(barw + IC<SCH.st[I.value].slot>::value * 8, IC<SCH.st[I.value].par>::value); };
            bool ok;
            uint32_t m1, m1n;
            {
                float mean, rstd;
                ln_final(mean, rstd);
                const float sq = shx(rstd * 0x1p64f, 0), q0 = shx(-mean * cs * sq, 0);
                CSTAMP(26, __float_as_uint(q0));
                static_for<0, NPRE>(load_tb);
                if (P4AT == 1) refill2(IC<4>{});
                if (S0EARLY) refill2(IC<5>{});
                m1n = m1 = lds32(sb + SM_M1);
                sts64(prow + lane * 8, xp.x, xp.y);
                sts128f(prow + 256 + lane * 16, 0.f, 0.f, 0.f, 0.f);
                const float q = ll_gather<256>(qb, qtag, qw) * sq + q0;
                sts16(qa, pack_bf(q, q));
                TSTAMPL(24);
                CSTAMP(27, __float_as_uint(q));
            }
            if (!S0EARLY) refill2(IC<5>{});
            if (P2LATE == 2 && warp >= 4) refill2(IC<2>{});
            if (P4AT == 3) refill2(IC<4>{});
            if (NOWIN & 1) { if (warp < 6) refill2(IC<0>{}); if (warp >= 5) refill2(IC<3>{}); }
            if (NOWIN & 2) { if (warp >= 6) refill2(IC<1>{}); if (warp < 4) refill2(IC<2>{}); }
            if (NOWIN & 4) { if (warp >= 6) refill2(IC<0>{}); if (warp < 6) refill2(IC<1>{}); }
            if (NOWIN & 8) { if (warp < 5) refill2(IC<3>{}); if (warp >= 4) refill2(IC<2>{}); }
            __syncthreads();
            uint4 qf[3];
            load_q(qf);
            CSTAMP(28, qf[0].x);
            float S[4], d[2][4];
            auto vload = [&](auto I) {
                constexpr int p = I.value;
                constexpr Step c = SCH.st[p];
                load_v(kr[p & 7], c.slot * TILE);
                if constexpr (c.next >= 0) refill2(IC<c.next>{});
                if constexpr (p == 11) { __syncwarp(); if (elect()) asm volatile("mbarrier.arrive.shared::cta.b64 _, [%0];" :: "r"(sb + SM_CBAR + CB_REL * 8) : "memory"); }
            };
            static_for<0, 96>([&](auto F) {
                constexpr int f = F.value, i = f % 6, u = kunit(f / 6), w = 3 * f % 12;
                uint4 (&src)[3] = *reinterpret_cast<uint4 (*)[3]>(f < 32 ? &tb[f / 4 & 7][0] : &kr[(f / 8 + 4) & 7][(f / 4 & 1) * 3]);
                const uint4 a = k_unpack(word<w % 4>(src[w / 4]), word<(w + 1) % 4>(src[(w + 1) / 4]), word<(w + 2) % 4>(src[(w + 2) / 4]), m1);
                if constexpr (f < 32 ? f % 4 == M1AT : f % 8 == M1P) m1 = m1n;
                if constexpr (f % 4 == 3 && f / 4 + NPRE < 8) {
                    load_tb(IC<f / 4 + NPRE>{});
                    if constexpr ((f / 4 + NPRE) & 1) { refill2(IC<5 + (f / 4 + NPRE) / 2>{}); m1n = lds32(sb + SM_M1); }
                }
                if constexpr (i < 2) d[i][0] = d[i][1] = d[i][2] = d[i][3] = 0.f;
                mma(d[i & 1], a, (i & 1) ? qf[i / 2].z : qf[i / 2].x, (i & 1) ? qf[i / 2].w : qf[i / 2].y);
                if constexpr (i == 5) {
                    if constexpr (u == 11 || ((u & 3) == 0 && u != 8)) S[u >> 2] = (d[0][0] + d[0][3]) + (d[1][0] + d[1][3]);
                    else add_if(t == (u & 3), S[u >> 2], d[0][0] + d[0][3], d[1][0] + d[1][3]);
                    if constexpr (f < 64) S[u >> 2] = shx(S[u >> 2], 0);
                }
                if constexpr (f == 31) { fresh(); calc_offsets(); ok = mbar_test(barw + IC<SCH.st[0].slot>::value * 8, 0); }
                if constexpr (f == 48) {
                    const uint2 x = lds64(sb + SM_EXC + warp * 128 + (lane & 15) * 8);
                    const float c = k_side(sb, x);
                    if (x.y < 0x40000000u) stsf(prow + 256 + (x.y >> 16), c);
                }
                if constexpr (f >= 32 && f % 8 == 7) {
                    if constexpr (PARKS >> (f / 8 - 4) & 1) {
                        constexpr int p = popc(PARKS & ((1 << (f / 8 - 4)) - 1));
                        if (!ok) vwait(IC<p>{});
                        vload(IC<p>{});
                        m1n = lds32(sb + SM_M1);
                        ok = mbar_test(barw + IC<SCH.st[p + 1].slot>::value * 8, IC<SCH.st[p + 1].par>::value);
                    }
                }
            });
            uint32_t bad = lds32(barw + 84);
            const uint32_t sc = lds32(sb + SM_SC + tid * 4);
            __syncwarp();
            if (bad) k_fix(P.k + (size_t)roww * DH, bad, warp, lane);
            TSTAMP(30);
            CSTAMP(29, __float_as_uint(S[2]));
            const float2 ml = softmax(S[0] * __uint_as_float((sc & 255) << 23) + ldsf(sa()), S[1] * __uint_as_float((sc & 0xff00) << 15) + ldsf(sa() + 128),
                                      S[2] * __uint_as_float((sc & 0xff0000) << 7) + ldsf(sa() + 256), S[3] * __uint_as_float((sc >> 24) << 23) + ldsf(sa() + 384));
            uint4 pq[4];
#pragma unroll
            for (int j = 0; j < 4; j++) pq[j] = lds128(prow + 256 + t * 80 + j * 16);
            TSTAMP(1);
            CSTAMP(30, pq[3].w);
            if (!ok) vwait(IC<NPARK>{});
            float ac2[3][4];
#pragma unroll
            for (int j = 0; j < 3; j++) ac2[j][0] = ac2[j][1] = ac2[j][2] = ac2[j][3] = 0.f;
            const uint32_t sl = (g & 1) ? 0x1044 : 0x4410, sh = (g & 1) ? 0x3244 : 0x4432;
            const uint32_t sA0 = (g & 2) ? 0x4444 : sl, sA1 = (g & 2) ? sl : 0x4444, sB0 = (g & 2) ? 0x4444 : sh, sB1 = (g & 2) ? sh : 0x4444;
            u64 pm = 0, pl = 0;
            static_for<NPARK, 16>([&](auto I) {
                constexpr int p = I.value;
                static_assert(p - SCH.st[p].mma0 < 8, "buffer in use");
                vload(I);
                if constexpr (p < 15) ok = mbar_test(barw + IC<SCH.st[p + 1].slot>::value * 8, IC<SCH.st[p + 1].par>::value);
                static_for<SCH.st[p].mma0, SCH.st[p].mma0 + SCH.st[p].nmma>([&](auto J) {
                    constexpr int u = SCH.st[J.value].unit;
                    const uint32_t pp = word<u & 3>(pq[u >> 2]), a0 = __byte_perm(pp, 0, sA0), a1 = __byte_perm(pp, 0, sA1), b0 = __byte_perm(pp, 0, sB0), b1 = __byte_perm(pp, 0, sB1);
#pragma unroll
                    for (int j = 0; j < 3; j++) mma(acc[j], kr[J.value & 7][j], a0, a1);
#pragma unroll
                    for (int j = 0; j < 3; j++) mma(ac2[j], kr[J.value & 7][j + 3], b0, b1);
                });
                if constexpr (p == NPARK) {
                    const float l = warp_sum(ml.y);
                    if (lane < 28) st_rlx(&g_ll[1][cta][lane < 24 ? warp * 24 + lane : 168 + warp * 4 + lane], lane < 24 ? 0ull : ll_pack((lane & 1) ? l : ml.x, lds32(sb + SM_EPOCH) * 4 + 4));
                }
                if constexpr (p == HWAT) { if (warp == 6) ld_rlx2(&g_ll[1][cta ^ (lane >> 3)][192 + (lane & 7) * 4], pm, pl); }
                if constexpr (p == 13) o_setup(L);
                if constexpr (p == HWAT + 2) { if (warp == 6) head_weight(&g_ll[1][cta ^ (lane >> 3)][192 + (lane & 7) * 4], pm, pl, 1, lane); }
                wo_at(IC<p - 10>{});
                if constexpr (p < 15) { if (!ok) mbar_wait(barw + IC<SCH.st[p + 1].slot>::value * 8, IC<SCH.st[p + 1].par>::value); TRACE(33 + p); }
            });
#pragma unroll
            for (int j = 0; j < 3; j++)
#pragma unroll
                for (int k = 0; k < 2; k++) { acc[j][k] += ac2[j][k]; add_if(t & 2, acc[j][k], acc[j][k + 2], ac2[j][k + 2]); }
        };

        const unsigned char* ap;
        uint32_t hpa, hsa, hst, w2a, la;
        uint2 b2v;
        float b1v, cs1;
        auto mlp_global = [&](auto L) {
            const int cz = c4();
            ap = accg + 2 * L.value * ACC_BYTES + (cz >> 1) * ACC_PITCH + (cz & 1) * 16;
            if (L.value) ap = pin(ap);
            rap = pin(accg + (2 * L.value + 1) * ACC_BYTES + (cz >> 2) * ACC_PITCH + (cz & 3) * 8);
            asm volatile("ld.global.nc.v2.u32 {%0,%1}, [%2];" : "=r"(b2v.x), "=r"(b2v.y) : "l"(P.b2 + 4 * cz));
        };
        auto mlp_shared = [&](auto L) {
            const int lz = lane;
            hpa = pin(sb + SM_PART + warp * 256 + ((lz & 2) * 4 + (lz >> 2)) * 16 + (L.value ? 0 : (lz & 1) * 4));
            hsa = pin(sb + SM_PART + (lz & 15) * 16); hst = pin(sb + SM_PART + (lz & 15) * 16 + warp * 256 + 8 + (lz >> 4) * 4);
            w2a = pin(sb + (L.value ? 3 * TILE : SM_W2) + ((lz & 3) * 10 + 2 * warp) * 128 + (((lz >> 2) ^ ((2 * lz + 2 * warp) & 6)) << 4));
            la = sb + (L.value ? 2 * TILE : SM_W1) + warp * 4096 + (lz & 4) * 512 + (lz & 2) * 64 + (lz & 1) * 32 + (lz >> 4) * 64 + ((((lz >> 3) ^ (lz >> 1)) & 1) << 4);
            b1v = ldsf(sb + SM_B1 + (lz & 15) * 4);
            if (L.value) { la = pin(la); cs1 = ldsf(sb + SM_ML + (lz & 15) * 4); }
            else fresh();
        };
        uint32_t pa;
        unsigned char* rop;
        uint32_t wpa;
        float sc1;
        auto sum_setup = [&](auto L) {
            const int lz = lane, word = warp * 128 + (cta & 3) * 32 + lz;
            wpa = pin(sb + SM_RING + warp * 1536 + ((((lz >> 2) * 8 + (lz & 1) * 4) * 4) ^ ((((lz >> 1) ^ (lz >> 4)) & 1) ? 256 + 64 : 0)));
            sc1 = pinf(fx2_scale(ldsf(sb + SM_FXS)) * 0.25f);
            pa = pin(sb + SM_RING + warp * 256 + ((lz * 4) ^ ((warp & 1) * 64)));
            rop = pin(accg + 2 * L.value * ACC_BYTES + (word >> 3) * ACC_PITCH + (word & 7) * 4);
        };
        auto out_proj = [&](auto L) {
            TSTAMP2(3);
            CSTAMP(0, __float_as_uint(acc[2][1]));
            __syncwarp();
#pragma unroll
            for (int j = 0; j < 3; j++) {
                if (L.value == 0 && (t & 2)) { acc[j][0] = acc[j][2]; acc[j][1] = acc[j][3]; }
                sts64f(osa + 256 * j, acc[j][0], acc[j][1]);
            }
            __syncthreads();
            {
                float s[8];
#pragma unroll
                for (int w = 0; w < 8; w++) s[w] = ldsf(ora + w * 768);
                const uint4 fa = lds128(sb + SM_FAC), fb = lds128(sb + SM_FAC + 16);
            CSTAMP(1, __float_as_uint(s[0]));
                const float own = ((s[0] * __uint_as_float(fa.x) + s[1] * __uint_as_float(fa.y)) + (s[2] * __uint_as_float(fa.z) + s[3] * __uint_as_float(fa.w))) +
                                  ((s[4] * __uint_as_float(fb.x) + s[5] * __uint_as_float(fb.y)) + (s[6] * __uint_as_float(fb.z) + s[7] * __uint_as_float(fb.w)));
                st_rlx_if(lane < 24, olb + (cta & 3) * 256, ll_pack(own, otag));
            CSTAMP(2, __float_as_uint(own));
            }
            TSTAMPL(29);
            if (L.value) wo_at(IC<6>{});
            if (L.value == 0 && warp == 7) {
#pragma unroll 1
                for (int it = 0; it < SPIN; it++) {
                    uint32_t v; asm volatile("ld.acquire.gpu.global.u32 %0, [%1];" : "=r"(v) : "l"(&g_zflag) : "memory");
                    if (__all_sync(~0u, v == (otag >> 2) + 1)) break;
                }
            }
            constexpr int NW = L.value ? NWO1 : 3;
            uint4 v[5][3];
            u64 ow[4];
            auto read_wo = [&](auto J) {
#pragma unroll
                for (int p = 0; p < 3; p++) v[J.value][p] = lds128(((J.value & 1) ? owa ^ 144 : owa) + ring_hs(64 + J.value) * HALF + p * 512);
            };
            static_for<0, NW>([&](auto J) {
                if (L.value && J.value == 0) { sum_setup(L); maskA = pin(maskA); maskB = pin(maskB); }
                if ((L.value ? OPOLL1 : OPOLL) == J.value) { ll_look<256>(olb, ow); if (L.value) { mlp_shared(L); mlp_global(L); } }
                mbar_wait(sb + SM_CBAR + (CB_WO + J.value) * 8, L.value);
                read_wo(J);
                if (L.value == 0 && W1AT0 == J.value + 1) {
                    __syncwarp();
                    if (elect() && cnt_inc(sb + SM_CNT + CB_W1 * 8, 7) == 7) issue_w(L, 0);
                    __syncwarp();
                }
                if (L.value == 1 && (W1AT1 == J.value + 1 || W2AT1 == J.value + 1)) {
                    if (warp == 7 && elect()) { if (W1AT1 == J.value + 1) issue_w(L, 0); if (W2AT1 == J.value + 1) issue_w(L, 1); }
                    __syncwarp();
                }
            });
            sched_fence();
            const float o = ll_gather<256>(olb, otag, ow);
            CSTAMP(3, __float_as_uint(o));
            TSTAMP2(4);
            bool ok = true;
            if constexpr (NW < 5) ok = mbar_test(sb + SM_CBAR + (CB_WO + 4) * 8, L.value);
            if constexpr (NW < 4) ok &= mbar_test(sb + SM_CBAR + (CB_WO + 3) * 8, L.value);
            const uint32_t od = pack_bf(o, o);
            uint32_t oa[3], ob[3];
#pragma unroll
            for (int p = 0; p < 3; p++) { const uint32_t op = __shfl_sync(~0u, od, 8 * p + orow); oa[p] = op & maskA; ob[p] = op & maskB; }
            CSTAMP(4, oa[2]);
            float y[5][4];
#pragma unroll
            for (int j = 0; j < 5; j++) y[j][0] = y[j][1] = y[j][2] = y[j][3] = 0.f;
            auto rest = [&]() {
                if (!ok) static_for<NW, 5>([&](auto J) { mbar_wait(sb + SM_CBAR + (CB_WO + J.value) * 8, L.value); });
                static_for<NW, 5>(read_wo);
                __syncwarp();
            };
            if (L.value) rest();
#pragma unroll
            for (int p = 0; p < 3; p++)
#pragma unroll
                for (int j = 0; j < NW; j++) mma(y[j], v[j][p], oa[p], ob[p]);
            if (!L.value) { rest(); sum_setup(L); }
#pragma unroll
            for (int p = 0; p < 3; p++)
#pragma unroll
                for (int j = NW; j < 5; j++) mma(y[j], v[j][p], oa[p], ob[p]);
            CSTAMP(5, __float_as_uint(y[4][3]));
#pragma unroll
            for (int j = 0; j < 5; j += 2) {
                if (j < 4 && (t >> 1) != (g >> 2)) { y[j][0] = y[j + 1][0]; y[j][1] = y[j + 1][1]; y[j][2] = y[j + 1][2]; y[j][3] = y[j + 1][3]; }
                sts128f(wpa + j * 256, y[j]);
            }
            TSTAMP2(5);
        };
        u64 yw[2];
        bool wide;
        float msq = 0.f, yf[4] = {};
        auto mlp_part = [&](auto L) {
            bar_sync(0, 256);
            CSTAMP(6, __float_as_uint(sc1));
            const float s = (sum8(pa, 1536) + xc) + sum8(pa + 128, 1536), sm = s * sc1 + FX2_ONE;
            CSTAMP(7, __float_as_uint(s));
            const bool wide1 = !(fabsf(sm - FX2_ONE) < FX1LIM);
            asm volatile("red.relaxed.gpu.global.add.u32 [%0], %1;" :: "l"(rop), "r"(wide1 ? 0u : __float_as_uint(sm) * 128u + (1u - 0x4b400000u * 128u)) : "memory");
            const uint32_t c0 = clk();
            TSTAMP2(6);
            if (L.value == 0) bar_arrive(2, 256);
            if (wide1) {
                fx_send(rop + 64 + (lane & 7) * 4, s, ldsf(sb + SM_FXS), rop, 64);
                asm volatile("red.relaxed.gpu.global.add.u32 [%0], 1;" :: "l"(rop) : "memory");
            }
            __syncwarp();
            if (L.value == 1 && mlp == 96) { TDUMP(); asm volatile("exit;"); }
            uint4 wf[8], w2r[8];
            uint4 w;
            auto look = [&]() { asm volatile("ld.relaxed.gpu.global.v4.u32 {%0,%1,%2,%3}, [%4];" : "=r"(w.x), "=r"(w.y), "=r"(w.z), "=r"(w.w) : "l"(ap) : "memory"); };
            auto read_w1 = [&]() {
#pragma unroll
                for (int j = 0; j < 8; j++) wf[j] = ldsm_t(la + j * 256);
            };
            auto read_w2 = [&]() {
#pragma unroll
                for (int i = 0; i < 8; i++) w2r[i] = lds128(((i & 1) ? (w2a ^ 16) + 128 : w2a) + (i >> 1) * 5120);
            };
            const float inv = pinf(fx_inv(sc1) * (1.f / 128)), off = L.value ? pinf(fx_inv(sc1) * -0.25f) : inv * -32.f;
            if (L.value == 0) { fresh(); mlp_global(L); }
            mbar_wait(sb + SM_CBAR + CB_W1 * 8, L.value);
            if (L.value == 1) {
                if (W2PRE == 1) mbar_wait(sb + SM_CBAR + CB_W2 * 8, 1);
                read_w1();
                if (W2PRE == 1) read_w2();
            }
            while (clk() - c0 < AR1D);
            look();
            if (L.value == 0) { mlp_shared(L); read_w1(); bar_arrive(3, 256); }
            else if (W2PRE == 2) { mbar_wait(sb + SM_CBAR + CB_W2 * 8, 1); read_w2(); }
            TSTAMPL(28);
            {
                sched_fence();
                auto miss = [&]() {
                    xp = make_uint2(pack_bf((float)(int)w.x * inv + off, (float)(int)w.y * inv + off), pack_bf((float)(int)w.z * inv + off, (float)(int)w.w * inv + off));
                    uint32_t a, b;
                    asm("lop3.b32 %0, %1, %2, 32, 0x7e;" : "=r"(a) : "r"(w.x), "r"(w.y));
                    asm("lop3.b32 %0, %1, %2, 32, 0x7e;" : "=r"(b) : "r"(w.z), "r"(w.w));
                    return __any_sync(~0u, (a | b) & 96);
                };
                if (miss()) {
                    int it = 0;
#pragma unroll 1
                    do {
                        if (!__any_sync(~0u, ~(w.x & w.y & w.z & w.w) & 32)) { xp.x = fx1_wide(ap, ldsf(sb + SM_FXS)); xp.y = fx1_wide(ap + 8, ldsf(sb + SM_FXS)); break; }
                        look();
                    } while (miss() & (++it < SPIN));
                }
                CSTAMP(8, w.w);
            }
            TSTAMP2(7);
            CSTAMP(9, xp.y);
            {
                bool ok = true;
                if (L.value == 0 || !W2PRE) ok = mbar_test(sb + SM_CBAR + CB_W2 * 8, L.value);
                const bool ev = L.value || !(g & 1), od = L.value || (g & 1);
                const uint32_t e0 = ev ? xp.x : ONES, e1 = ev ? xp.y : ONES, o0 = od ? xp.x : ONES, o1 = od ? xp.y : ONES;
                float d[8][4];
#pragma unroll
                for (int j = 0; j < 8; j++) { d[j][0] = d[j][1] = d[j][2] = d[j][3] = 0.f; mma(d[j], wf[j], (j & 1) ? o0 : e0, (j & 1) ? o1 : e1); }
                float ss = ln_part(xp, lane);
                ss += shx(ss, 8); ss += shx(ss, 4);
                float r[4], dd;
#pragma unroll
                for (int k = 0; k < 4; k += 1 + L.value) r[k] = d[0][k] + d[1][k ^ 1];
#pragma unroll
                for (int j = 1; j < 4; j++)
#pragma unroll
                    for (int k = 0; k < 4; k += 1 + L.value) add_if(t == j, r[k], d[2 * j][k], d[2 * j + 1][k ^ 1]);
                CSTAMP(10, __float_as_uint(r[2]));
                if (L.value) {
                    dd = ((t & 2) ? r[2] : r[0]) + shx((t & 2) ? r[0] : r[2], 2);
                    ss += shx(ss, 2);
                    dd += shx(dd, 1);
                } else {
                    const float a = ((t & 1) ? r[1] : r[0]) + shx((t & 1) ? r[0] : r[1], 1), b = ((t & 1) ? r[3] : r[2]) + shx((t & 1) ? r[2] : r[3], 1);
                    ss += shx(ss, 2);
                    dd = ((t & 2) ? b : a) + shx((t & 2) ? a : b, 2);
                }
                ss += shx(ss, 1);
                stsf(hpa, dd);
                stsf(hst, ss);
                CSTAMP(11, __float_as_uint(dd + ss));
                if (!ok) mbar_wait(sb + SM_CBAR + CB_W2 * 8, L.value);
            }
            TSTAMPL(25);
            bar_sync(1, 160);
            uint4 hp[5];
#pragma unroll
            for (int w = 0; w < 5; w++) hp[w] = lds128(hsa + w * 256);
            CSTAMP(12, hp[0].x);
            auto hs = [&](auto K) { return sum5(__uint_as_float(word<K.value>(hp[0])), __uint_as_float(word<K.value>(hp[1])), __uint_as_float(word<K.value>(hp[2])),
                                                __uint_as_float(word<K.value>(hp[3])), __uint_as_float(word<K.value>(hp[4]))); };
            const float mean = hs(IC<2>{}) * (1.f / D_MODEL);
            msq = hs(IC<3>{}) * (1.f / D_MODEL);
            if (L.value == 0) cs1 = hs(IC<1>{});
            float hv = hs(IC<0>{}) - mean * cs1;
            CSTAMP(13, __float_as_uint(hv));
            const float sc2 = fx2_scale(msq), lim = fx_inv(sc2) * FX2LIM;
            if (L.value == 0 || !W2PRE) read_w2();
            if (L.value == 0) {
                bar_arrive(4, 256);
                wide = false;
                if (mlp == 96) return;
            }
            hv = hv * ln_rstd(mean, msq) + b1v;
            CSTAMP(14, __float_as_uint(hv));
            hv = hv * rcp(1.f + ex2(hv * (-2.302208198f - 0.1029432397f * hv * hv)));
            const uint32_t hd = pack_bf(hv, hv);
            CSTAMP(15, hd);
            TSTAMPL(27);
            float ym[4][4];
#pragma unroll
            for (int i = 0; i < 2; i++) {
                ym[i][0] = ym[i][1] = ym[i][2] = ym[i][3] = 0.f;
                const float f = mlp < 64 ? 1.f / 64 : 0.f;
                ym[i + 2][0] = (bf_lo(xp.x) + bf_lo(b2v.x)) * f; ym[i + 2][1] = (bf_hi(xp.x) + bf_hi(b2v.x)) * f;
                ym[i + 2][2] = (bf_lo(xp.y) + bf_lo(b2v.y)) * f; ym[i + 2][3] = (bf_hi(xp.y) + bf_hi(b2v.y)) * f;
            }
#pragma unroll
            for (int i = 0; i < 4; i++) {
                const uint32_t hh = __shfl_sync(~0u, hd, 4 * i + t);
                mma(ym[(i & 1) * 2], w2r[2 * i], hh & maskA, hh & maskB);
                mma(ym[(i & 1) * 2 + 1], w2r[2 * i + 1], hh & maskA, hh & maskB);
            }
#pragma unroll
            for (int k = 0; k < 4; k++) { yf[k] = ym[0][k] + ym[2][k]; add_if(t & 2, yf[k], ym[1][k], ym[3][k]); }
            CSTAMP(16, __float_as_uint(yf[3]));
            yw[0] = fx2_pack(yf[0] * sc2 + FX2_ONE, yf[1] * sc2 + FX2_ONE); yw[1] = fx2_pack(yf[2] * sc2 + FX2_ONE, yf[3] * sc2 + FX2_ONE);
            wide = !(fmaxf(fmaxf(fabsf(yf[0]), fabsf(yf[1])), fmaxf(fabsf(yf[2]), fabsf(yf[3]))) < lim);
            if (wide) yw[0] = yw[1] = 0;
            if (L.value == 0) {
#pragma unroll
                for (int k = 0; k < 2; k++) asm volatile("red.relaxed.gpu.global.add.u64 [%0], %1;" :: "l"(rap + k * 40 * ACC_PITCH), "l"(yw[k]) : "memory");
            }
        };
        auto send_wide = [&]() {
#pragma unroll 1
            for (int k = 0; k < 4; k++, yf[0] = yf[1], yf[1] = yf[2], yf[2] = yf[3]) {
                const unsigned char* a = rap + (k >> 1) * 40 * ACC_PITCH;
                fx_send(a + 64 + (k & 1) * 32, yf[0], msq, a, 256);
            }
            yw[0] = yw[1] = 1;
        };

        pass1();
        o_setup(IC<0>{});
        out_proj(IC<0>{});
        uint32_t c0;
        if (warp < 5) {
            mlp_part(IC<0>{});
            c0 = clk() + (mlp == 96 ? PCD : 0);
            stsf(sb + SM_ML + (lane & 15) * 4, cs1);
            TSTAMP(8);
            if (__any_sync(~0u, wide)) {
                if (wide) {
                    send_wide();
#pragma unroll
                    for (int k = 0; k < 2; k++) asm volatile("red.relaxed.gpu.global.add.u64 [%0], 1;" :: "l"(rap + k * 40 * ACC_PITCH) : "memory");
                }
                __syncwarp();
            }
            fresh(); calc_offsets();
            load_wq();
        } else {
            bar_sync(0, 256);
            if (warp == 5 && elect()) {
                asm volatile("fence.proxy.async.shared::cta;" ::: "memory");
                if (W1AT0 == 4) issue_w(IC<0>{}, 0);
                issue_w(IC<0>{}, 1);
            }
            __syncwarp();
            fresh(); calc_offsets();
            load_wq();
#pragma unroll 1
            for (int ph = 0; ph < 3; ph++) {
                bar_sync(ph + 2, 256);
                c0 = clk();
                if (ph == 2) {
                    msq = sum5(ldsf(sb + SM_PART + 12), ldsf(sb + SM_PART + 268), ldsf(sb + SM_PART + 524), ldsf(sb + SM_PART + 780), ldsf(sb + SM_PART + 1036)) * (1.f / D_MODEL);
                    bar_arrive(5, 256);
                }
                if (!(NOWIN >> ph & 1) && elect()) {
                    asm volatile("fence.proxy.async.shared::cta;" ::: "memory");
                    const uint32_t gap = ph == 0 ? WG1 : ph == 1 ? WG2 : WG3;
                    uint32_t c1 = c0 + (ph == 0 ? WD1 : ph == 1 ? WD2 : 0) + (warp - 5) * gap;
#pragma unroll 1
                    for (int k = warp + (ph == 0 ? -5 : ph == 1 ? 9 : 1); k < (ph == 0 ? 9 : ph == 1 ? 20 : 14); k += 3, c1 += 3 * gap) {
                        const int i = ph == 0 && k >= 6 ? k + 23 : k;
                        const uint32_t bar = sb + SM_BAR + (i & 7) * 96 + 32 + (i & 24);
                        while ((int)(clk() - c1) < 0);
                        mbar_expect(bar, SUB);
                        tma_v(sb + SM_RING + i * SUB, tmk,
                              rowc * 3 + (i & 7) * 24 + ((UC<SCH.st[0].unit | SCH.st[1].unit << 8 | SCH.st[2].unit << 16 | SCH.st[3].unit << 24>::value >> (i & 24)) & 15) * 768, bar);
                    }
                }
                __syncwarp();
            }
            c0 += PCD;
        }
        {
            constexpr IC<1> L{};
            fresh();
            const int col = xcol(g & 3, t), cw = j40 + (col >> 2);
            const unsigned char* xa = pin(accg + ACC_BYTES + ((cw >> 2) + (col & 2) * 20) * ACC_PITCH + (cw & 3) * 8);
            const uint32_t pst = pin(prow + (g * 8 + (t & 1) * 4 + (t & 2)) * 4);
            const float inv = pinf(fx2_inv(msq));
            sts64f(sb + SM_MSQ, msq, inv);
            rap = pin(accg + ACC_BYTES + (c4() >> 2) * ACC_PITCH + (c4() & 3) * 8);
            fresh();
            maskA = pin(maskA); maskB = pin(maskB);
            u64 w[1];
            uint32_t x1[1], x2[3];
            auto look = [&]() { w[0] = ld_rlx(xa); };
            if (warp < 5) {
                bar_sync(5, 256);
                if (DPRE) { while ((int)(clk() - c0) < WD4 + warp * WG4); if (warp < DPRE) refill2(IC<3>{}); }
            }
            while ((int)(clk() - c0) < ARDELAY);
            look();
            if (DPOST) while ((int)(clk() - c0) < ARDELAY + DPOST);
            if (warp < 5 && !(NOWIN & 8) && elect()) {
                if (warp >= DPRE) issue_v(IC<3>{}, 0);
                if (warp < 4 && !P2LATE) issue_v(IC<2>{}, 4);
            }
            __syncwarp();
            fx2_wait<1>([&](int) { return xa; }, look, w, sb + SM_MSQ, inv, x1);
            if (warp < 5) look_rw(); else rw[0] = rw[1] = 96;
#pragma unroll
            for (int i = 0; i < 3; i++) x2[i] = __shfl_sync(~0u, x1[0], 4 * i + t);
            TSTAMP(9);
            CSTAMP(22, x2[2]);
            q_proj(L, x2, pst);
            pass2();
            out_proj(L);
            if (warp >= 5) {
                bar_arrive(0, 256);
                if ((W1AT1 == 6 || W2AT1 == 6) && warp == 5 && elect()) { if (W1AT1 == 6) issue_w(L, 0); if (W2AT1 == 6) issue_w(L, 1); }
                TDUMP();
                return;
            }
            mlp_part(L);
            u64 old[2];
            auto add = [&]() {
#pragma unroll
                for (int k = 0; k < 2; k++) asm volatile("atom.relaxed.gpu.global.add.u64 %0, [%1], %2;" : "=l"(old[k]) : "l"(rap + k * 40 * ACC_PITCH), "l"(yw[k]) : "memory");
            };
            add();
            uint32_t* op = pin(reinterpret_cast<uint32_t*>(P.out) + 2 * c4());
            const float inv2 = pinf(fx2_inv(msq));
            if (wide) { send_wide(); add(); }
            TSTAMP(18);
            CSTAMP(17, hi32(yw[1]));
            __syncwarp();
            CSTAMP(18, lo32(old[0]) ^ lo32(old[1]));
#pragma unroll
            for (int k = 0; k < 2; k++) {
                yw[k] += old[k];
                asm volatile("{\n.reg .pred p;\nsetp.eq.u32 p, %2, 96;\n@p st.global.u32 [%0], %1;\n}"
                             :: "l"(op + k), "r"(fx2_get(yw[k], inv2)), "r"(lo32(yw[k]) & 511) : "memory");
            }
            if ((lo32(yw[0]) & 255) == 96 && tid == 0) g_epoch = lds32(sb + SM_EPOCH) + 1;
#pragma unroll
            for (int k = 0; k < 2; k++) if ((lo32(yw[k]) & 511) == 256 + 96) op[k] = fx2_wide(rap + k * 40 * ACC_PITCH, msq);
            TSTAMP(19);
            CSTAMP(19, lo32(yw[1]));
            TDUMP();
        }
    }
}

typedef CUresult (*EncodeFn)(CUtensorMap*, CUtensorMapDataType, cuuint32_t, void*, const cuuint64_t*, const cuuint64_t*, const cuuint32_t*,
                             const cuuint32_t*, CUtensorMapInterleave, CUtensorMapSwizzle, CUtensorMapL2promotion, CUtensorMapFloatOOBfill);

}

extern "C" void kernel_launch(void* const* d_in, const int* in_sizes, int n_in, void* d_out, int out_size) {
    (void)in_sizes; (void)n_in; (void)out_size;
    static EncodeFn enc = nullptr;
    if (!enc) {
        void* fn = nullptr;
        cudaDriverEntryPointQueryResult qr;
        cudaGetDriverEntryPoint("cuTensorMapEncodeTiled", &fn, cudaEnableDefault, &qr);
        enc = (EncodeFn)fn;
        cudaFuncSetAttribute(fused_kernel, cudaFuncAttributeMaxDynamicSharedMemorySize, SM_TOTAL);
    }
    Params P = {};
    auto map3 = [&](int m, int in, cuuint64_t d0, cuuint64_t d1, cuuint64_t d2, cuuint64_t s1, cuuint64_t s2, cuuint32_t b0, cuuint32_t b1, cuuint32_t b2,
                    CUtensorMapSwizzle sw, int promo) {
        const cuuint64_t dim[3] = {d0, d1, d2}, str[2] = {s1, s2};
        const cuuint32_t box[3] = {b0, b1, b2}, ones[3] = {1, 1, 1};
        enc(&P.tm[m], CU_TENSOR_MAP_DATA_TYPE_BFLOAT16, d2 ? 3 : 2, d_in[in], dim, str, box, ones, CU_TENSOR_MAP_INTERLEAVE_NONE, sw, (CUtensorMapL2promotion)promo,
            CU_TENSOR_MAP_FLOAT_OOB_FILL_NONE);
    };
    map3(TM_KH, 1, 64, 3, NHEAD * SK, 128, DH * 2, 64, 3, 32, CU_TENSOR_MAP_SWIZZLE_128B, 0);
    map3(TM_VH, 2, 64, 3, NHEAD * SK, 128, DH * 2, 64, 3, 32, CU_TENSOR_MAP_SWIZZLE_128B, 0);
    map3(TM_VP, 2, 64, 3, NHEAD * SK, 128, DH * 2, PFW, 3, 32, CU_TENSOR_MAP_SWIZZLE_NONE, 0);
    map3(TM_V, 2, 64, NHEAD * SK * 3, 0, 128, 0, 64, 24, 0, CU_TENSOR_MAP_SWIZZLE_128B, 0);
    map3(TM_WO, 4, 32, 20, NHEAD * DH, 64, D_MODEL * 2, 32, 1, DH, CU_TENSOR_MAP_SWIZZLE_64B, PROMOW);
    map3(TM_WOP, 4, 32, 20, NHEAD * DH, 64, D_MODEL * 2, PFW, 1, DH, CU_TENSOR_MAP_SWIZZLE_NONE, 0);
    map3(TM_WQ, 3, 64, NHEAD * 3, D_MODEL, 128, NHEAD * DH * 2, 64, 3, 32, CU_TENSOR_MAP_SWIZZLE_128B, 0);
    map3(TM_W1, 6, DFF, 128, 5, DFF * 2, DFF * 256, 16, 128, 5, CU_TENSOR_MAP_SWIZZLE_32B, PROMO1);
    map3(TM_W2, 8, 64, 10, DFF, 128, D_MODEL * 2, 64, 10, 16, CU_TENSOR_MAP_SWIZZLE_128B, 0);
    P.x = (const __nv_bfloat16*)d_in[0];
    P.k = (const __nv_bfloat16*)d_in[1];
    P.b1 = (const __nv_bfloat16*)d_in[7];
    P.b2 = (const __nv_bfloat16*)d_in[9];
    P.w1 = (const __nv_bfloat16*)d_in[6];
    P.out = (__nv_bfloat16*)d_out;
    for (int i = 0; i < 64; i++) P.tile[i] = make_uint4(SCH.tile[i][0], SCH.tile[i][1], SCH.tile[i][2], 0);
    fused_kernel<<<NCTA + 1, NTHR, SM_TOTAL, cudaStreamPerThread>>>(P);
}
```

```cpp
#include <cuda_runtime.h>
#include <cuda_bf16.h>
#include <cuda.h>
#include <stdint.h>

namespace {

constexpr int D_MODEL = 640, NHEAD = 32, SK = 32768, DH = 192, WIN = 4096, DFF = 1536;
constexpr int NCTA = 128, NTHR = 256;
constexpr int TILE = 64 * DH * 2;
constexpr int HALF = TILE / 2;
constexpr int SUB = 8 * DH * 2;
constexpr int SM_RING = 4 * TILE;
constexpr int SM_W2 = SM_RING + 20480, SM_W1 = SM_W2 + 20480;
constexpr int SM_WQR = 6 * TILE + HALF, SM_WQ = 7 * TILE;
constexpr int SM_PART = 9 * TILE;
constexpr int SM_EXC = SM_PART + 6144;
constexpr int SM_SC = SM_EXC + 1024;
constexpr int SM_BAR = SM_SC + 1024;
constexpr int SM_VEC = SM_BAR + 768;
constexpr int SM_CS = SM_VEC + 384;
constexpr int SM_FAC = SM_CS + 768;
constexpr int SM_ML = SM_FAC + 32;
constexpr int SM_B1 = SM_ML + 64;
constexpr int SM_STAT = SM_B1 + 64;
constexpr int NCB = 28;
constexpr int CB_WO = 18, CB_W1 = 23, CB_W2 = 24, CB_SNAP = 25, CB_REL = 26, CB_WQ = 27;
constexpr int SM_CBAR = SM_STAT + 48;
constexpr int SM_CNT = SM_CBAR + NCB * 8;
constexpr int SM_EPOCH = SM_CNT + NCB * 8;
constexpr int SM_FXS = SM_EPOCH + 4;
constexpr int SM_T0 = SM_FXS + 4;
constexpr int SM_M1 = SM_T0 + 4;
constexpr int SM_MSQ = SM_M1 + 4;
constexpr int SM_TS = SM_MSQ + 8;
constexpr int SM_TOTAL = 232448;
static_assert(SM_TS + 320 <= SM_TOTAL, "smem");
constexpr int NEXC = 16;

constexpr int SPIN = 1 << 20;
enum { TM_V = 0, TM_KH = 1, TM_VH = 2, TM_WO = 3, TM_VP = 4, TM_WOP = 5, TM_W1 = 6, TM_W2 = 7, TM_WQ = 8 };
constexpr uint32_t POL_NORMAL = 0x16F00000u, POL_FIRST = 0x12F00000u;

#define PACE 980
#define PACE0 1500
#define K0FIRST 1
#define NI1 6
#define ETRIG 0x54321000
#define LATEAT 5
#define HWAT 12
#define PFREE 66
#define W1AT0 3
#define W1AT1 3
#define AR1D 250
#define LAG0 12
#define NMMA 2
#define M1AT 1
#define M1P 3
#define NWO1 4
#define WG2 120
#define WG3 65
#define WD4 250
#define WG4 70
#define NWQ1 0
#define P4AT 0
#define P2LATE 0
#define W2AT1 6
#define PCD 400
#define NOWIN 0
#define DPRE 0
#define DPOST 200
#define NIM 4
#define PACES 1300
#define JP2 54
#define PACE2 0
#define WD2 0
#define W2PRE 2
#define OPOLL1 2
#define FX1LIM 524288.f
#define PROMO2 0
#define PROMOK 0
#define PROMOV 0
#define PROMOQ 0
#define SNAPAT 1
#define DMASK 0x0
#define WOKEEP 0x1f
#define VORD2 0x7685943a2b1cd0efull
#define VTRIG 0xba73210
#define WOP 0x44433
#define PARKS 0x95
#define VSLOT 0x1087654321087654ull
#define OPOLL 2
#define S0EARLY 1
#define NPRE 2
#define ARDELAY 800
#define QDELAY 0
#define CMAP 0
#define PFW 8u
#define PUBAT 28
#define HW0 30
#define HW1 31
#define FX2LIM 524288.f
#define PROMOW 2
#define PROMO1 2
#define WD1 100
#define WG1 140

constexpr uint32_t G_A = 1u << 28, G_B = 1u << 29, G_C = 1u << 30;
__host__ __device__ constexpr int ring_hs(int j) { return (j + 4) % 5; }
__host__ __device__ constexpr uint32_t load_word(int j) {
    if (j >= 64) return (uint32_t)(j - 64) << 20 | (SM_RING + ring_hs(j) * HALF) | TM_WO << 8 | (CB_WO + j - 64) << 3 | 2 | !(WOKEEP >> (j - 64) & 1);
    const int e = j >> 1, isv = e >= 16, unit = e & 15;
    return (uint32_t)(unit * 256 + (j & 1) * 32) << 20 | (j < 8 ? j * HALF : SM_RING + ring_hs(j) * HALF) | (TM_KH + isv) << 8 | (j < 8 ? 10 + j : (j - 8) % 10) << 3 | 2
           | (!isv || (DMASK >> unit & 1));
}
__host__ __device__ constexpr int popc(int v) { return v ? (v & 1) + popc(v >> 1) : 0; }
constexpr int NPARK = popc(PARKS);
constexpr int SM_SNAP = SM_RING + ring_hs(12) * HALF, SM_CSP = SM_RING + ring_hs(11) * HALF;
struct Step { int unit, slot, par, next, mma0, nmma; };
struct Sched { uint32_t tile[64][3]; Step st[16]; };
constexpr Sched make_sched() {
    Sched s{};
    for (int j = 0; j < 64; j++) {
        const int e = j >> 1;
        const uint32_t d = load_word(j);
        uint32_t w = (uint32_t)(j < 8 ? 0 : (j - 8) / 10 & 1) << 31 | (e & 15) * 4 << 20 | ((d & 0x3f000) - (j & 1) * HALF) | (d & 0xf8);
        if (e == PUBAT || e == SNAPAT) w |= G_A;
        if (e == HW0 || e == 4) w |= G_B;
        if ((e >= LATEAT && e < LATEAT + 4) || e == HW1) w |= G_C;
        s.tile[j][0] = w;
    }
    for (int j = NI1; j < 69; j++) {
        if (j == 12) continue;
        const int at = j < 12 ? (ETRIG >> (4 * (j - 4)) & 15) : j - 5;
        s.tile[at][1] = load_word(j);
        s.tile[at][2] = j >= PFREE ? 0 : PACE0 + j * PACE / 2 + (j > JP2 ? (j - JP2) * PACE2 : 0);
    }
    int done = 0;
    for (int p = 0; p < 16; p++) {
        Step& c = s.st[p];
        c.unit = (int)(VORD2 >> (4 * p) & 15); c.slot = (int)(VSLOT >> (4 * p) & 15); c.par = p >= 9; c.next = -1;
        c.mma0 = done;
        if (p >= NPARK) { const int avail = p - done + (p >= LAG0); c.nmma = p == 15 ? 16 - done : (avail < NMMA ? avail : NMMA); done += c.nmma; }
    }
    for (int p = 9; p < 16; p++) s.st[VTRIG >> (4 * (p - 9)) & 15].next = p;
    return s;
}
constexpr Sched SCH = make_sched();
__host__ __device__ constexpr int kunit(int o) { return o < 5 ? o + 11 : o == 5 ? 10 : o - 6; }

template <int I> struct IC { static constexpr int value = I; };
template <uint32_t I> struct UC { static constexpr uint32_t value = I; };
template <int A, int B, class F> __device__ __forceinline__ void static_for(F&& f) {
    if constexpr (A < B) { f(IC<A>{}); static_for<A + 1, B>(f); }
}

struct Params {
    CUtensorMap tm[9];
    const __nv_bfloat16 *x, *k, *b1, *b2, *w1;
    __nv_bfloat16* out;
    uint4 tile[66];
};

typedef unsigned long long u64;
constexpr int ACC_PITCH = 256;
constexpr int ACC_BYTES = 80 * ACC_PITCH;
__device__ __align__(1024) unsigned char g_acc[4 * ACC_BYTES];
__device__ __align__(1024) u64 g_l0[NCTA][384];
__device__ __align__(1024) u64 g_ll[2][NCTA][256];
__device__ unsigned g_epoch;
__device__ __align__(128) unsigned g_zflag;
#define TSTAMP(i)
#define TSTAMP2(i)
#define TSTAMPL(i)
#define TDUMP()
#define CSTAMP(i, x)
#define TRACE(i)

__device__ __forceinline__ void mbar_wait(uint32_t bar, uint32_t parity) {
    asm volatile("{\n.reg .pred p;\nLOOP:\nmbarrier.try_wait.parity.shared::cta.b64 p, [%0], %1;\n@!p bra.uni LOOP;\n}" :: "r"(bar), "r"(parity) : "memory");
}
__device__ __forceinline__ bool mbar_test(uint32_t bar, uint32_t parity) {
    uint32_t r;
    asm volatile("{\n.reg .pred p;\nmbarrier.test_wait.parity.shared::cta.b64 p, [%1], %2;\nselp.u32 %0, 1, 0, p;\n}" : "=r"(r) : "r"(bar), "r"(parity) : "memory");
    return __all_sync(~0u, r);
}
__device__ __forceinline__ bool elect() {
    uint32_t r;
    asm volatile("{\n.reg .pred p;\nelect.sync _|p, 0xffffffff;\nselp.u32 %0, 1, 0, p;\n}" : "=r"(r));
    return r != 0;
}
__device__ __forceinline__ void mbar_expect(uint32_t bar, uint32_t bytes) {
    asm volatile("mbarrier.arrive.expect_tx.shared::cta.b64 _, [%0], %1;" :: "r"(bar), "r"(bytes) : "memory");
}
__device__ __forceinline__ uint4 lds128(uint32_t a) {
    uint4 v; asm volatile("ld.shared.v4.u32 {%0,%1,%2,%3}, [%4];" : "=r"(v.x), "=r"(v.y), "=r"(v.z), "=r"(v.w) : "r"(a) : "memory"); return v;
}
__device__ __forceinline__ uint4 ldsm_t(uint32_t a) {
    uint4 v; asm volatile("ldmatrix.sync.aligned.m8n8.x4.trans.shared.b16 {%0,%1,%2,%3}, [%4];" : "=r"(v.x), "=r"(v.y), "=r"(v.z), "=r"(v.w) : "r"(a) : "memory"); return v;
}
__device__ __forceinline__ uint2 lds64(uint32_t a) {
    uint2 v; asm volatile("ld.shared.v2.u32 {%0,%1}, [%2];" : "=r"(v.x), "=r"(v.y) : "r"(a) : "memory"); return v;
}
__device__ __forceinline__ float2 lds64f(uint32_t a) { const uint2 v = lds64(a); return make_float2(__uint_as_float(v.x), __uint_as_float(v.y)); }
__device__ __forceinline__ uint32_t lds32(uint32_t a) {
    uint32_t v; asm volatile("ld.shared.u32 %0, [%1];" : "=r"(v) : "r"(a) : "memory"); return v;
}
__device__ __forceinline__ float ldsf(uint32_t a) { return __uint_as_float(lds32(a)); }
__device__ __forceinline__ void sts32(uint32_t a, uint32_t v) { asm volatile("st.shared.u32 [%0], %1;" :: "r"(a), "r"(v) : "memory"); }
__device__ __forceinline__ void stsf(uint32_t a, float v) { sts32(a, __float_as_uint(v)); }
__device__ __forceinline__ void sts16(uint32_t a, uint32_t v) { asm volatile("st.shared.u16 [%0], %1;" :: "r"(a), "h"((uint16_t)v) : "memory"); }
__device__ __forceinline__ void sts64(uint32_t a, uint32_t x, uint32_t y) { asm volatile("st.shared.v2.u32 [%0], {%1,%2};" :: "r"(a), "r"(x), "r"(y) : "memory"); }
__device__ __forceinline__ void sts64f(uint32_t a, float x, float y) { sts64(a, __float_as_uint(x), __float_as_uint(y)); }
__device__ __forceinline__ void sts128f(uint32_t a, float x, float y, float z, float w) {
    asm volatile("st.shared.v4.f32 [%0], {%1,%2,%3,%4};" :: "r"(a), "f"(x), "f"(y), "f"(z), "f"(w) : "memory");
}
__device__ __forceinline__ void mma(float (&c)[4], const uint4& a, uint32_t b0, uint32_t b1) {
    asm volatile("mma.sync.aligned.m16n8k16.row.col.f32.bf16.bf16.f32 {%0,%1,%2,%3}, {%4,%5,%6,%7}, {%8,%9}, {%0,%1,%2,%3};"
                 : "+f"(c[0]), "+f"(c[1]), "+f"(c[2]), "+f"(c[3]) : "r"(a.x), "r"(a.y), "r"(a.z), "r"(a.w), "r"(b0), "r"(b1));
}
__device__ __forceinline__ u64 ld_rlx(const void* p) {
    u64 a; asm volatile("ld.relaxed.gpu.global.u64 %0, [%1];" : "=l"(a) : "l"(p) : "memory"); return a;
}
__device__ __forceinline__ void ld_rlx2(const void* p, u64& a, u64& b) {
    asm volatile("ld.relaxed.gpu.global.v2.u64 {%0,%1}, [%2];" : "=l"(a), "=l"(b) : "l"(p) : "memory");
}
__device__ __forceinline__ void st_rlx(void* p, u64 a) { asm volatile("st.relaxed.gpu.global.u64 [%0], %1;" :: "l"(p), "l"(a) : "memory"); }
__device__ __forceinline__ u64 ll_pack(float v, uint32_t tag) { return ((u64)tag << 32) | __float_as_uint(v); }
__device__ __forceinline__ float ll_val(u64 w) { return __uint_as_float((uint32_t)w); }
__device__ __forceinline__ uint32_t ll_tag(u64 w) { return (uint32_t)(w >> 32); }
__device__ __forceinline__ float bf_lo(uint32_t u) { return __uint_as_float(u << 16); }
__device__ __forceinline__ float bf_hi(uint32_t u) { return __uint_as_float(u & 0xffff0000u); }
__device__ __forceinline__ uint32_t pack_bf(float lo, float hi) {
    uint32_t r; asm("cvt.rn.bf16x2.f32 %0, %1, %2;" : "=r"(r) : "f"(hi), "f"(lo)); return r;
}
__device__ __forceinline__ float ex2(float v) { float r; asm("ex2.approx.ftz.f32 %0, %1;" : "=f"(r) : "f"(v)); return r; }
__device__ __forceinline__ float rcp(float v) { float r; asm("rcp.approx.ftz.f32 %0, %1;" : "=f"(r) : "f"(v)); return r; }
__device__ __forceinline__ float rsq(float v) { float r; asm("rsqrt.approx.ftz.f32 %0, %1;" : "=f"(r) : "f"(v)); return r; }
__device__ __forceinline__ void bar_sync(int id, int n) { asm volatile("bar.sync %0, %1;" :: "r"(id), "r"(n) : "memory"); }
__device__ __forceinline__ uint32_t clk() { uint32_t c; asm volatile("mov.u32 %0, %clock;" : "=r"(c)); return c; }
__device__ __forceinline__ void sched_fence() { __syncwarp(); while (clk() == 0x9e3779b9u); }
__device__ __forceinline__ uint32_t pin(uint32_t v) { return __shfl_xor_sync(~0u, v, 0); }
__device__ __forceinline__ float shx(float v, int o) { return __shfl_xor_sync(~0u, v, o); }

__device__ __forceinline__ u64 fx_pack(float v, float scale) { return ((u64)__float2ll_rn(v * scale) & ~255ull) | 1ull; }
__device__ __forceinline__ float fx_scale(float meansq) {
    const int e = max(((int)(__float_as_uint(meansq) >> 23) - 127) >> 1, -6);
    return __uint_as_float((uint32_t)(127 + 32 - e) << 23);
}
__device__ __forceinline__ float fx_inv(float scale) { return __uint_as_float((254u << 23) - __float_as_uint(scale)); }
__device__ __forceinline__ uint32_t lo32(u64 w) { uint32_t l; asm("mov.b64 {%0, _}, %1;" : "=r"(l) : "l"(w)); return l; }
__device__ __forceinline__ int hi32(u64 w) { int h; asm("mov.b64 {_, %0}, %1;" : "=r"(h) : "l"(w)); return h; }
__device__ __forceinline__ float fx_val(u64 w) { return (float)hi32(w) * 4294967296.f + (float)lo32(w); }
constexpr float FX2_ONE = 12582912.f;
__device__ __forceinline__ float fx2_scale(float meansq) { return __uint_as_float((uint32_t)(127 + 16 - max(((int)(__float_as_uint(meansq) >> 23) - 127) >> 1, -100)) << 23); }
__device__ __forceinline__ u64 fx2_pack(float a, float b) {
    const uint32_t lo = __float_as_uint(a) * 512u + (1u - 0x4b400000u * 512u);
    return lo | (u64)(__float_as_uint(b) * 16u - 0x4b400000u * 16u + (uint32_t)((int)lo >> 31)) << 32;
}
__device__ __forceinline__ float fx2_lo(u64 w, float inv) { return (float)(int)(__funnelshift_r(lo32(w), hi32(w), 4) & ~31u) * (inv * 0.5f); }
__device__ __forceinline__ float fx2_hi(u64 w, float inv) { return (float)((hi32(w) + 8) & ~15) * inv; }
__device__ __forceinline__ uint32_t fx2_get(u64 w, float inv) {
    return pack_bf((float)(int)__funnelshift_r(lo32(w), hi32(w), 4) * (inv * 0.5f) - inv * 3.f, (float)hi32(w) * inv);
}
__device__ __forceinline__ float fx2_inv(float meansq) { return fx_inv(fx2_scale(meansq)) * 0.0625f; }
__device__ __noinline__ uint32_t fx2_wide(const unsigned char* a, float meansq) {
    __threadfence();
    const u64 w = ld_rlx(a);
    const float inv = fx_inv(fx_scale(meansq));
    return pack_bf(fx2_lo(w, fx2_inv(meansq)) + fx_val(ld_rlx(a + 64)) * inv, fx2_hi(w, fx2_inv(meansq)) + fx_val(ld_rlx(a + 96)) * inv);
}
__device__ __noinline__ uint32_t fx1_wide(const unsigned char* a, float meansq) {
    __threadfence();
    const u64 w = ld_rlx(a);
    const unsigned char* b = a + 64 + (reinterpret_cast<u64>(a) & 31);
    const float inv = fx_inv(fx_scale(meansq)), inv1 = fx2_inv(meansq) * 0.5f;
    return pack_bf((float)(int)(lo32(w) & ~127u) * inv1 + fx_val(ld_rlx(b)) * inv, (float)(hi32(w) & ~127) * inv1 + fx_val(ld_rlx(b + 8)) * inv);
}
__device__ __noinline__ void fx_send(const unsigned char* wide, float v, float meansq, const unsigned char* a, uint32_t flag) {
    asm volatile("red.relaxed.gpu.global.add.u64 [%0], %1;" :: "l"(wide), "l"(fx_pack(v, fx_scale(meansq))) : "memory");
    __threadfence();
    asm volatile("red.relaxed.gpu.global.or.b32 [%0], %1;" :: "l"(a), "r"(flag) : "memory");
}
template <int N, class A, class F> __device__ __forceinline__ void fx2_wait(A a, F look, u64 (&w)[N], uint32_t msqa, float inv, uint32_t (&x)[N]) {
    auto miss = [&]() {
#pragma unroll
        for (int i = 0; i < N; i++) x[i] = fx2_get(w[i], inv);
        return __any_sync(~0u, ((lo32(w[0]) ^ 96) | (lo32(w[N - 1]) ^ 96)) & 0x160);
    };
    if (miss()) {
        int it = 0;
#pragma unroll 1
        do {
            if (__all_sync(~0u, (lo32(w[0]) & lo32(w[N - 1]) & 96) == 96)) {
#pragma unroll
                for (int i = 0; i < N; i++) x[i] = fx2_wide(a(i), ldsf(msqa));
                break;
            }
            look();
        } while (miss() & (++it < SPIN));
    }
}
__device__ __forceinline__ void st_rlx_if(bool p, void* a, u64 v) {
    asm volatile("{\n.reg .pred p;\nsetp.ne.u32 p, %2, 0;\n@p st.relaxed.gpu.global.u64 [%0], %1;\n}" :: "l"(a), "l"(v), "r"((uint32_t)p) : "memory");
}
__device__ __forceinline__ void sts128f(uint32_t a, const float (&v)[4]) { sts128f(a, v[0], v[1], v[2], v[3]); }
__device__ __forceinline__ void bar_arrive(int id, int n) { asm volatile("bar.arrive %0, %1;" :: "r"(id), "r"(n) : "memory"); }
template <class T> __device__ __forceinline__ T* pin(T* p) { return reinterpret_cast<T*>(__shfl_xor_sync(~0u, (u64)p, 0)); }

__device__ __forceinline__ void tma3(uint32_t dst, const CUtensorMap* tm, int c1, int c2, uint32_t bar, uint32_t pol) {
    asm volatile("cp.async.bulk.tensor.3d.shared::cluster.global.mbarrier::complete_tx::bytes.L2::cache_hint [%0], [%1, {%2, %3, %4}], [%5], %6;"
                 :: "r"(dst), "l"(tm), "r"(0), "r"(c1), "r"(c2), "r"(bar), "l"((u64)pol << 32) : "memory");
}
__device__ __forceinline__ void tma_v(uint32_t dst, const CUtensorMap* tm, int line, uint32_t bar) {
    asm volatile("cp.async.bulk.tensor.2d.shared::cluster.global.mbarrier::complete_tx::bytes.L2::cache_hint [%0], [%1, {%2, %3}], [%4], %5;"
                 :: "r"(dst), "l"(tm), "r"(0), "r"(line), "r"(bar), "l"((u64)POL_FIRST << 32) : "memory");
}
__device__ __forceinline__ void tma3_pf(const CUtensorMap* tm, int c1, int c2, uint32_t pol) {
    asm volatile("cp.async.bulk.prefetch.tensor.3d.L2.global.tile.L2::cache_hint [%0, {%1, %2, %3}], %4;"
                 :: "l"(tm), "r"(0), "r"(c1), "r"(c2), "l"((u64)pol << 32) : "memory");
}
__device__ __forceinline__ void issue_half(uint32_t d, uint32_t sb, int rowc, int cta, const CUtensorMap* tm0) {
    const uint32_t bar = sb + SM_CBAR + (d & 0xf8);
    const CUtensorMap* tm = tm0 + ((d >> 8) & 3);
    const bool wo = (d & 0x300) == TM_WO << 8;
    const int c1 = wo ? (cta & 3) + 4 * (d >> 20) : 0, c2 = wo ? (cta >> 2) * DH : rowc + (d >> 20);
    mbar_expect(bar, HALF);
    tma3(sb + (d & 0x3f000), tm, c1, c2, bar, POL_FIRST);
    if (!(d & 1)) tma3_pf(tm + 2, c1, c2, POL_NORMAL);
}
__device__ __forceinline__ uint32_t cnt_inc(uint32_t a, uint32_t last) {
    uint32_t old; asm volatile("atom.relaxed.cta.shared.inc.u32 %0, [%1], %2;" : "=r"(old) : "r"(a), "r"(last) : "memory"); return old;
}
__device__ __forceinline__ void wait_until(uint32_t due) {
#pragma unroll 1
    for (int it = 0; it < 4096; it++) { uint32_t now; asm volatile("mov.u32 %0, %globaltimer_lo;" : "=r"(now)); if ((int)(now - due) >= 0) break; }
}
__device__ __forceinline__ uint32_t bf2_mul(uint32_t a, uint32_t b) { uint32_t r; asm("mul.rn.bf16x2 %0, %1, %2;" : "=r"(r) : "r"(a), "r"(b)); return r; }
__device__ __forceinline__ uint32_t bf2_fma(uint32_t a, uint32_t b, uint32_t c) { uint32_t r; asm("fma.rn.bf16x2 %0, %1, %2, %3;" : "=r"(r) : "r"(a), "r"(b), "r"(c)); return r; }
__device__ __forceinline__ uint32_t bf2_amax(uint32_t a, uint32_t b) { uint32_t r; asm("max.NaN.xorsign.abs.bf16x2 %0, %1, %2;" : "=r"(r) : "r"(a), "r"(b)); return r; }
__device__ __forceinline__ uint4 k_unpack(uint32_t l0, uint32_t l1, uint32_t h, uint32_t m1) {
    const uint32_t ha = h & 0x87878787u, hc = ha * m1 + h, hb = __funnelshift_l(hc, hc, 4);
    return make_uint4(__byte_perm(l0, ha, 0x5140), __byte_perm(l0, ha, 0x7362), __byte_perm(l1, hb, 0x5140), __byte_perm(l1, hb, 0x7362));
}
#define KR4(u, i) "+r"(kr[u][i].x), "+r"(kr[u][i].y), "+r"(kr[u][i].z), "+r"(kr[u][i].w)
#define KR6(u) KR4(u, 0), KR4(u, 1), KR4(u, 2), KR4(u, 3), KR4(u, 4), KR4(u, 5)
__device__ __forceinline__ void k_keep(uint4 (&kr)[8][6], const uint32_t (&c)[18], int e, uint32_t a) {
    asm volatile("{\nKT: .branchtargets K0, K1, K2, K3, K4, K5, K6, K7, K8, K9, K10, K11, K12, K13, K14, K15;\nbrx.idx.uni %210, KT;\n"
                 "K0: mov.b32 %12, %192; mov.b32 %13, %193; mov.b32 %14, %194; mov.b32 %15, %195; mov.b32 %16, %196; mov.b32 %17, %197; mov.b32 %18, %198; mov.b32 %19, %199; mov.b32 %20, %200; mov.b32 %21, %201; mov.b32 %22, %202; mov.b32 %23, %203; mov.b32 %24, %204; mov.b32 %25, %205; mov.b32 %26, %206; mov.b32 %27, %207; mov.b32 %28, %208; mov.b32 %29, %209; bra.uni KE;\n"
                 "K1: mov.b32 %30, %192; mov.b32 %31, %193; mov.b32 %32, %194; mov.b32 %33, %195; mov.b32 %34, %196; mov.b32 %35, %197; mov.b32 %36, %198; mov.b32 %37, %199; mov.b32 %38, %200; mov.b32 %39, %201; mov.b32 %40, %202; mov.b32 %41, %203; mov.b32 %42, %204; mov.b32 %43, %205; mov.b32 %44, %206; mov.b32 %45, %207; mov.b32 %46, %208; mov.b32 %47, %209; bra.uni KE;\n"
                 "K2: mov.b32 %48, %192; mov.b32 %49, %193; mov.b32 %50, %194; mov.b32 %51, %195; mov.b32 %52, %196; mov.b32 %53, %197; mov.b32 %54, %198; mov.b32 %55, %199; mov.b32 %56, %200; mov.b32 %57, %201; mov.b32 %58, %202; mov.b32 %59, %203; mov.b32 %60, %204; mov.b32 %61, %205; mov.b32 %62, %206; mov.b32 %63, %207; mov.b32 %64, %208; mov.b32 %65, %209; bra.uni KE;\n"
                 "K3: mov.b32 %66, %192; mov.b32 %67, %193; mov.b32 %68, %194; mov.b32 %69, %195; mov.b32 %70, %196; mov.b32 %71, %197; mov.b32 %72, %198; mov.b32 %73, %199; mov.b32 %74, %200; mov.b32 %75, %201; mov.b32 %76, %202; mov.b32 %77, %203; mov.b32 %78, %204; mov.b32 %79, %205; mov.b32 %80, %206; mov.b32 %81, %207; mov.b32 %82, %208; mov.b32 %83, %209; bra.uni KE;\n"
                 "K4: mov.b32 %84, %192; mov.b32 %85, %193; mov.b32 %86, %194; mov.b32 %87, %195; mov.b32 %88, %196; mov.b32 %89, %197; mov.b32 %90, %198; mov.b32 %91, %199; mov.b32 %92, %200; mov.b32 %93, %201; mov.b32 %94, %202; mov.b32 %95, %203; mov.b32 %96, %204; mov.b32 %97, %205; mov.b32 %98, %206; mov.b32 %99, %207; mov.b32 %100, %208; mov.b32 %101, %209; bra.uni KE;\n"
                 "K5: mov.b32 %102, %192; mov.b32 %103, %193; mov.b32 %104, %194; mov.b32 %105, %195; mov.b32 %106, %196; mov.b32 %107, %197; mov.b32 %108, %198; mov.b32 %109, %199; mov.b32 %110, %200; mov.b32 %111, %201; mov.b32 %112, %202; mov.b32 %113, %203; mov.b32 %114, %204; mov.b32 %115, %205; mov.b32 %116, %206; mov.b32 %117, %207; mov.b32 %118, %208; mov.b32 %119, %209; bra.uni KE;\n"
                 "K6: mov.b32 %120, %192; mov.b32 %121, %193; mov.b32 %122, %194; mov.b32 %123, %195; mov.b32 %124, %196; mov.b32 %125, %197; mov.b32 %126, %198; mov.b32 %127, %199; mov.b32 %128, %200; mov.b32 %129, %201; mov.b32 %130, %202; mov.b32 %131, %203; mov.b32 %132, %204; mov.b32 %133, %205; mov.b32 %134, %206; mov.b32 %135, %207; mov.b32 %136, %208; mov.b32 %137, %209; bra.uni KE;\n"
                 "K7: mov.b32 %138, %192; mov.b32 %139, %193; mov.b32 %140, %194; mov.b32 %141, %195; mov.b32 %142, %196; mov.b32 %143, %197; mov.b32 %144, %198; mov.b32 %145, %199; mov.b32 %146, %200; mov.b32 %147, %201; mov.b32 %148, %202; mov.b32 %149, %203; mov.b32 %150, %204; mov.b32 %151, %205; mov.b32 %152, %206; mov.b32 %153, %207; mov.b32 %154, %208; mov.b32 %155, %209; bra.uni KE;\n"
                 "K8: mov.b32 %156, %192; mov.b32 %157, %193; mov.b32 %158, %194; mov.b32 %159, %195; mov.b32 %160, %196; mov.b32 %161, %197; mov.b32 %162, %198; mov.b32 %163, %199; mov.b32 %164, %200; mov.b32 %165, %201; mov.b32 %166, %202; mov.b32 %167, %203; mov.b32 %168, %204; mov.b32 %169, %205; mov.b32 %170, %206; mov.b32 %171, %207; mov.b32 %172, %208; mov.b32 %173, %209; bra.uni KE;\n"
                 "K9: mov.b32 %174, %192; mov.b32 %175, %193; mov.b32 %176, %194; mov.b32 %177, %195; mov.b32 %178, %196; mov.b32 %179, %197; mov.b32 %180, %198; mov.b32 %181, %199; mov.b32 %182, %200; mov.b32 %183, %201; mov.b32 %184, %202; mov.b32 %185, %203; mov.b32 %186, %204; mov.b32 %187, %205; mov.b32 %188, %206; mov.b32 %189, %207; mov.b32 %190, %208; mov.b32 %191, %209; bra.uni KE;\n"
                 "K10: st.shared.v2.b32 [%211+75784], {%192, %193}; st.shared.v2.b32 [%211+76288], {%194, %195}; st.shared.v2.b32 [%211+76296], {%196, %197}; mov.b32 %0, %198; mov.b32 %1, %199; mov.b32 %2, %200; mov.b32 %3, %201; mov.b32 %4, %202; mov.b32 %5, %203; mov.b32 %6, %204; mov.b32 %7, %205; mov.b32 %8, %206; mov.b32 %9, %207; mov.b32 %10, %208; mov.b32 %11, %209; bra.uni KE;\n"
                 "K11: st.shared.v2.b32 [%211+0], {%192, %193}; st.shared.v2.b32 [%211+8], {%194, %195}; st.shared.v2.b32 [%211+512], {%196, %197}; st.shared.v2.b32 [%211+520], {%198, %199}; st.shared.v2.b32 [%211+1024], {%200, %201}; st.shared.v2.b32 [%211+1032], {%202, %203}; st.shared.v2.b32 [%211+1536], {%204, %205}; st.shared.v2.b32 [%211+1544], {%206, %207}; st.shared.v2.b32 [%211+2048], {%208, %209}; bra.uni KE;\n"
                 "K12: st.shared.v2.b32 [%211+2056], {%192, %193}; st.shared.v2.b32 [%211+2560], {%194, %195}; st.shared.v2.b32 [%211+2568], {%196, %197}; st.shared.v2.b32 [%211+24576], {%198, %199}; st.shared.v2.b32 [%211+24584], {%200, %201}; st.shared.v2.b32 [%211+25088], {%202, %203}; st.shared.v2.b32 [%211+25096], {%204, %205}; st.shared.v2.b32 [%211+25600], {%206, %207}; st.shared.v2.b32 [%211+25608], {%208, %209}; bra.uni KE;\n"
                 "K13: st.shared.v2.b32 [%211+26112], {%192, %193}; st.shared.v2.b32 [%211+26120], {%194, %195}; st.shared.v2.b32 [%211+26624], {%196, %197}; st.shared.v2.b32 [%211+26632], {%198, %199}; st.shared.v2.b32 [%211+27136], {%200, %201}; st.shared.v2.b32 [%211+27144], {%202, %203}; st.shared.v2.b32 [%211+49152], {%204, %205}; st.shared.v2.b32 [%211+49160], {%206, %207}; st.shared.v2.b32 [%211+49664], {%208, %209}; bra.uni KE;\n"
                 "K14: st.shared.v2.b32 [%211+49672], {%192, %193}; st.shared.v2.b32 [%211+50176], {%194, %195}; st.shared.v2.b32 [%211+50184], {%196, %197}; st.shared.v2.b32 [%211+50688], {%198, %199}; st.shared.v2.b32 [%211+50696], {%200, %201}; st.shared.v2.b32 [%211+51200], {%202, %203}; st.shared.v2.b32 [%211+51208], {%204, %205}; st.shared.v2.b32 [%211+51712], {%206, %207}; st.shared.v2.b32 [%211+51720], {%208, %209}; bra.uni KE;\n"
                 "K15: st.shared.v2.b32 [%211+73728], {%192, %193}; st.shared.v2.b32 [%211+73736], {%194, %195}; st.shared.v2.b32 [%211+74240], {%196, %197}; st.shared.v2.b32 [%211+74248], {%198, %199}; st.shared.v2.b32 [%211+74752], {%200, %201}; st.shared.v2.b32 [%211+74760], {%202, %203}; st.shared.v2.b32 [%211+75264], {%204, %205}; st.shared.v2.b32 [%211+75272], {%206, %207}; st.shared.v2.b32 [%211+75776], {%208, %209}; \nKE:\n}"
                 : KR6(0), KR6(1), KR6(2), KR6(3), KR6(4), KR6(5), KR6(6), KR6(7)
                 : "r"(c[0]), "r"(c[1]), "r"(c[2]), "r"(c[3]), "r"(c[4]), "r"(c[5]), "r"(c[6]), "r"(c[7]), "r"(c[8]), "r"(c[9]), "r"(c[10]), "r"(c[11]), "r"(c[12]), "r"(c[13]), "r"(c[14]), "r"(c[15]), "r"(c[16]), "r"(c[17]), "r"(e), "r"(a) : "memory");
}
__device__ __forceinline__ uint32_t smem_base() { extern __shared__ __align__(1024) unsigned char smem[]; return (uint32_t)__cvta_generic_to_shared(smem); }
__device__ __forceinline__ void k_rare(uint4 v0, uint4 v1, uint4 v2, uint4 v3, uint4 v4, uint4 v5, uint32_t odd, int e, int warp, int lane) {
    const uint32_t sb = smem_base(), g = lane >> 2, t = lane & 3, st = sb + SM_BAR + warp * 96 + 80;
    uint32_t lt; asm volatile("mov.u32 %0, %lanemask_lt;" : "=r"(lt));
    const uint4 v[6] = {v0, v1, v2, v3, v4, v5};
    odd <<= 6;
#pragma unroll
    for (int i = 0; i < 6; i++) if (v[i].x | v[i].y | v[i].z | v[i].w) odd |= 1u << i;
    odd = __reduce_or_sync(~0u, odd);
    uint32_t n = odd >= 64 ? NEXC + 1 : __shfl_sync(~0u, lds32(st), 0);
#pragma unroll 1
    for (; odd && n <= NEXC; odd &= odd - 1) {
        const int i = __ffs(odd) - 1;
#pragma unroll
        for (int k = 1; k < 6; k++) if (i == k) v0 = v[k];
#pragma unroll 1
        for (int k = 0; k < 4; k++, v0.x = v0.y, v0.y = v0.z, v0.z = v0.w) {
            const uint32_t who = __ballot_sync(~0u, v0.x), at = n + __popc(who & lt);
            sts64(v0.x && at < NEXC ? sb + SM_EXC + warp * 128 + at * 8 : st + 8, v0.x, (e * 32 + g * 4) << 16 | (((k & 1) * 4 + t) * 48 + i * 8 + (k >> 1) * 4));
            n += __popc(who);
        }
    }
    const uint32_t bad = lds32(st + 4);
    __syncwarp();
    if (n <= NEXC) sts32(st, n);
    else {
        sts32(st + 4, bad | 1u << e);
        asm volatile("st.shared.u8 [%0], %1;" :: "r"(sb + SM_SC + warp * 128 + g * 16 + (e & 3) * 4 + (e >> 2)), "r"(0) : "memory");
    }
    __syncwarp();
}
template <int K> __device__ __forceinline__ uint32_t& word(uint4& v) { if constexpr (K == 0) return v.x; else if constexpr (K == 1) return v.y; else if constexpr (K == 2) return v.z; else return v.w; }
__device__ __forceinline__ void add_if(bool p, float& d, float a, float b) {
    asm volatile("{\n.reg .pred p;\nsetp.ne.u32 p, %3, 0;\n@p add.f32 %0, %1, %2;\n}" : "+f"(d) : "f"(a), "f"(b), "r"((uint32_t)p));
}
__device__ __forceinline__ float warp_max(float v) {
#pragma unroll
    for (int o = 16; o; o >>= 1) v = fmaxf(v, shx(v, o));
    return v;
}
__device__ __forceinline__ float warp_sum(float v) {
#pragma unroll
    for (int o = 16; o; o >>= 1) v += shx(v, o);
    return v;
}
template <int PITCH> __device__ __forceinline__ void ll_look(const u64* buf, u64 (&w)[4]) {
#pragma unroll
    for (int i = 0; i < 4; i++) w[i] = ld_rlx(buf + i * PITCH);
}
template <int PITCH> __device__ __forceinline__ float ll_gather(const u64* buf, uint32_t tag, u64 (&w)[4]) {
    auto miss = [&]() {
        uint32_t a, b;
        asm("lop3.b32 %0, %1, %2, %3, 0x7e;" : "=r"(a) : "r"(ll_tag(w[0])), "r"(ll_tag(w[1])), "r"(tag));
        asm("lop3.b32 %0, %1, %2, %3, 0x7e;" : "=r"(b) : "r"(ll_tag(w[2])), "r"(ll_tag(w[3])), "r"(tag));
        return __any_sync(~0u, a | b);
    };
    int it = 0;
    goto check;
again:
    ll_look<PITCH>(buf, w);
check:
    if (miss() & (++it < SPIN)) goto again;
    return (ll_val(w[0]) + ll_val(w[1])) + (ll_val(w[2]) + ll_val(w[3]));
}
__device__ __forceinline__ float sum8(uint32_t a, int pitch) {
    float s[8];
#pragma unroll
    for (int w = 0; w < 8; w++) s[w] = ldsf(a + w * pitch);
    return ((s[0] + s[1]) + (s[2] + s[3])) + ((s[4] + s[5]) + (s[6] + s[7]));
}
__device__ __forceinline__ float sum5(float a, float b, float c, float d, float e) { return ((a + b) + (c + d)) + e; }
__device__ __forceinline__ float ln_part(uint2 xp, int lane) {
    const float x0 = bf_lo(xp.x), x1 = bf_hi(xp.x), x2 = bf_lo(xp.y), x3 = bf_hi(xp.y);
    const float s1 = (x0 + x1) + (x2 + x3), s2 = (x0 * x0 + x1 * x1) + (x2 * x2 + x3 * x3);
    return ((lane & 16) ? s2 : s1) + shx((lane & 16) ? s1 : s2, 16);
}
__device__ __forceinline__ float ln_rstd(float mean, float msq) { return rsq(fmaxf(msq - mean * mean, 0.f) + 1e-5f); }
__device__ __forceinline__ float score(const uint4 (&v)[6], const uint4 (&qf)[3]) {
    float d[2][4];
#pragma unroll
    for (int j = 0; j < 2; j++) d[j][0] = d[j][1] = d[j][2] = d[j][3] = 0.f;
#pragma unroll
    for (int i = 0; i < 3; i++) { mma(d[0], v[2 * i], qf[i].x, qf[i].y); mma(d[1], v[2 * i + 1], qf[i].z, qf[i].w); }
    return (d[0][0] + d[0][3]) + (d[1][0] + d[1][3]);
}
__device__ __forceinline__ float k_side(uint32_t sb, uint2 x) {
    const uint32_t qq = lds32(sb + SM_VEC + (x.y & 0xffff));
    return (bf_lo(x.x) * bf_lo(qq) + bf_hi(x.x) * bf_hi(qq)) * 0x1p-64f;
}
__device__ __forceinline__ void k_fix(const __nv_bfloat16* k, uint32_t bad, int warp, int lane) {
    const uint32_t sb = smem_base(), g = lane >> 2, sa = sb + SM_PART + warp * 768 + 256;
    const uint2 x = lds64(sb + SM_EXC + warp * 128 + (lane & 15) * 8);
    if ((int)x.y >= 0x40000000 && lane < 16) asm volatile("red.shared.add.f32 [%0], %1;" :: "r"(sa + ((x.y >> 16) & 511)), "f"(k_side(sb, x)) : "memory");
    __syncwarp();
#pragma unroll 1
    for (bad &= 0xffff; bad; bad &= bad - 1) {
        const int e = __ffs(bad) - 1;
        const __nv_bfloat16* kp = k + (e * 256 + (g >> 1) + 4 * (g & 1)) * DH + (lane & 3) * 8;
        uint4 v[6], qf[3];
#pragma unroll
        for (int i = 0; i < 6; i++) v[i] = *reinterpret_cast<const uint4*>(kp + i * 32);
#pragma unroll
        for (int i = 0; i < 3; i++) qf[i] = lds128(sb + SM_VEC + (lane & 7) * 48 + i * 16);
        stsf(sa + e * 32 + g * 4, score(v, qf) * 0x1p-64f);
    }
    __syncwarp();
}
constexpr float CS = 0.07216878364870322f * 1.4426950408889634f;
__device__ __forceinline__ void head_weight(const u64* a, u64 pm, u64 pl, int layer, int lane) {
    const uint32_t sb = smem_base(), tag = lds32(sb + SM_EPOCH) * 4 + 2 + 2 * layer;
#pragma unroll 1
    for (int it = 0; it < SPIN; it++) {
        if (__all_sync(~0u, ll_tag(pm) == tag && ll_tag(pl) == tag)) break;
        ld_rlx2(a, pm, pl);
    }
    const float f = ex2((ll_val(pm) - warp_max(ll_val(pm))) * CS);
    const float w = f * rcp(warp_sum(f * ll_val(pl)));
    if (lane < 8) stsf(sb + SM_FAC + lane * 4, w);
}
constexpr uint32_t ONES = 0x3f803f80u;

__global__ void __launch_bounds__(NTHR, 1) fused_kernel(const __grid_constant__ Params P) {
    const uint32_t sb = smem_base();
    const int bx = blockIdx.x;
    const int cta0 = bx >= NCTA || CMAP == 0 ? bx : CMAP == 4 ? (((bx >> 1) & 7) + (bx >> 5) * 8) * 4 + ((bx >> 4) & 1) * 2 + (bx & 1)
                   : (((bx >> 1) & 15) + (bx >> 6) * 16) * 4 + ((bx >> 5) & 1) * 2 + (bx & 1);
    if (__all_sync(~0u, threadIdx.x >= NTHR - 32 && bx < NCTA) && elect()) {
        asm volatile("mbarrier.init.shared::cta.b64 [%0], 1;" :: "r"(sb + SM_CBAR + CB_WQ * 8));
        asm volatile("mbarrier.init.shared::cta.b64 [%0], 1;" :: "r"(sb + SM_CBAR + 80));
        asm volatile("fence.mbarrier_init.release.cluster;" ::: "memory");
        mbar_expect(sb + SM_CBAR + CB_WQ * 8, 5 * HALF);
        auto k0 = [&]() {
            mbar_expect(sb + SM_CBAR + 80, HALF);
            tma3(sb, &P.tm[TM_KH], 0, (cta0 >> 2) * SK + (SK - WIN) + (cta0 & 3) * 64, sb + SM_CBAR + 80, POL_FIRST);
        };
        if (K0FIRST) k0();
#pragma unroll 1
        for (int i = 0; i < 5; i++) tma3(sb + SM_WQR + (i == 4 ? 0 : i + 1) * HALF, &P.tm[TM_WQ], (cta0 >> 2) * 3, (cta0 & 3) * 160 + i * 32, sb + SM_CBAR + CB_WQ * 8, POL_FIRST);
        if (!K0FIRST) k0();
    }
    __syncwarp();
    int id = cta0 * NTHR + threadIdx.x, tid, lane, g, t, key, warp, cta, mlp, rowc, roww, j40;
    uint32_t maskA, maskB, barw, subw, prow;
    auto fresh = [&]() {
        const int cw = __shfl_sync(~0u, id >> 5, 0);
        id = pin(id); tid = id & 255; lane = id & 31; g = lane >> 2; t = lane & 3; key = (g >> 1) + 4 * (g & 1);
        const uint32_t m = (g & 1) ? 0xffff0000u : 0x0000ffffu;
        maskA = (g & 2) ? 0u : m; maskB = (g & 2) ? m : 0u;
        warp = cw & 7; cta = cw >> 3;
        mlp = (cta & 3) == 3 ? 96 : (cta >> 2) * 3 + (cta & 3);
        rowc = (cta >> 2) * SK + (SK - WIN) + (cta & 3) * 64; roww = rowc + warp * 8;
        j40 = (cta & 3) * 40;
        barw = sb + SM_BAR + warp * 96; subw = sb + warp * SUB; prow = sb + SM_PART + warp * 768;
    };
    fresh();
    auto fresh_lane = [&]() { id = pin(id); tid = id & 255; lane = id & 31; g = lane >> 2; t = lane & 3; };
    auto pinf = [&](float v) { return __uint_as_float(pin(__float_as_uint(v) | (id >> 16))); };

    if (cta == NCTA) {
        const uint32_t ep = *(volatile unsigned*)&g_epoch;
        if (tid == 0) {
#pragma unroll 1
            for (int it = 0; it < SPIN; it++) { if (ll_tag(ld_rlx(&g_ll[0][0][192])) == ep * 4 + 2) break; __nanosleep(200); }
        }
        __syncthreads();
#pragma unroll 1
        for (int i = tid; i < 4 * 80 * 8; i += NTHR)
            *reinterpret_cast<uint4*>(g_acc + (i >> 3) * ACC_PITCH + (i & 7) * 16) = make_uint4(0, 0, 0, 0);
        __threadfence();
        __syncthreads();
        if (tid == 0) asm volatile("st.relaxed.gpu.global.u32 [%0], %1;" :: "l"(&g_zflag), "r"(ep + 1) : "memory");
        return;
    }
    TSTAMP(0);
    if (tid == 64) { uint32_t now; asm volatile("mov.u32 %0, %globaltimer_lo;" : "=r"(now)); sts32(sb + SM_T0, now); }

    const CUtensorMap* tmk = reinterpret_cast<const CUtensorMap*>(__shfl_sync(~0u, (u64)&P.tm[0] + (lane >> 5), 0));
    auto c4 = [&]() { return 32 * min(warp, 4) + 16 * (t >> 1) + 2 * g + (t & 1); };
    auto xcol = [&](int i, int tt) { return (i < 2 ? 64 * i + 8 * warp : 128 + 8 * (warp >> 1)) + 2 * tt; };
    uint2 xp;
    uint32_t px[3], small;
    auto issue_first = [&](int j) {
        mbar_expect(sb + SM_CBAR + 80 + j * 8, HALF);
        tma3(sb + j * HALF, tmk + TM_KH, 0, rowc + (j >> 1) * 256 + (j & 1) * 32, sb + SM_CBAR + 80 + j * 8, POL_FIRST);
    };
    if (elect()) {
        if (warp != 2) asm volatile("mbarrier.init.shared::cta.b64 [%0], 1;" :: "r"(sb + SM_CBAR + 64 + warp * 8));
#pragma unroll
        for (int i = 0; i < 9; i++) asm volatile("mbarrier.init.shared::cta.b64 [%0], 1;" :: "r"(barw + i * 8));
        asm volatile("mbarrier.init.shared::cta.b64 [%0], 1;" :: "r"(sb + SM_CBAR + warp * 8));
        asm volatile("mbarrier.init.shared::cta.b64 [%0], 1;" :: "r"(sb + SM_CBAR + 128 + warp * 8));
        if (warp < 3) asm volatile("mbarrier.init.shared::cta.b64 [%0], %1;" :: "r"(sb + SM_CBAR + 192 + warp * 8), "r"(warp == 2 ? 8 : 1));
        sts64(barw + 80, 0, 0);
        asm volatile("fence.mbarrier_init.release.cluster;" ::: "memory");
        asm volatile("prefetch.tensormap [%0];" :: "l"(tmk + warp) : "memory");
    }
    __syncwarp();
    asm volatile("ld.global.nc.v2.u32 {%0,%1}, [%2];" : "=r"(xp.x), "=r"(xp.y) : "l"(P.x + 4 * c4()) : "memory");
#pragma unroll
    for (int i = 0; i < 3; i++) asm volatile("ld.global.nc.u32 %0, [%1];" : "=r"(px[i]) : "l"(P.x + 4 * j40 + xcol(i, t)) : "memory");
    asm volatile("ld.relaxed.gpu.global.u32 %0, [%1];" : "=r"(small) : "l"(lane < 16 ? (const void*)(P.b1 + min(mlp, 95) * 16 + (lane & 14)) : (const void*)&g_epoch) : "memory");
    if (tid >= 192 && tid < 192 + NCB) sts32(sb + SM_CNT + (tid - 192) * 8, 0);
    unsigned char* accg = reinterpret_cast<unsigned char*>(__shfl_sync(~0u, (u64)g_acc + (lane >> 5), 0));
    auto release = [&](const uint4& tw) {
        uint32_t old;
        __syncwarp();
        asm volatile("atom.relaxed.cta.shared.add.u32 %0, [%1], 1;" : "=r"(old) : "r"(sb + SM_CNT + (tw.x & 0xf8)) : "memory");
        return old;
    };
    auto refill = [&](const uint4& tw, uint32_t old) {
        if (__any_sync(~0u, (old & 127) == 127 && (tw.y & 2))) {
            wait_until(lds32(sb + SM_T0) + tw.z);
            if (elect()) issue_half(tw.y, sb, rowc, cta, tmk);
            __syncwarp();
        }
    };
    __syncthreads();
    auto issue_paced = [&](int j0, int j1) {
        if (warp >= j0 && warp < j1) {
            wait_until(lds32(sb + SM_T0) + PACES + warp * PACE / 2);
            if (elect()) issue_first(warp);
            __syncwarp();
        }
    };

    uint32_t offV0, offV2;
    auto calc_offsets = [&]() {
        offV0 = subw + (6 * t) * 128 + ((g ^ ((6 * t) & 7)) << 4);
        offV2 = subw + (6 * t + 2) * 128 + ((g ^ ((6 * t + 2) & 7)) << 4);
    };
    calc_offsets();

    auto load_v = [&](uint4 (&v)[6], uint32_t so) {
        v[0] = lds128(offV0 + so); v[1] = lds128((offV0 ^ 16) + so + 128); v[2] = lds128(offV2 + so);
        v[3] = lds128((offV2 ^ 16) + so + 128); v[4] = lds128((offV0 ^ 64) + so + 512); v[5] = lds128((offV0 ^ 80) + so + 640);
    };
    auto issue_v = [&](auto I, int dw) {
        constexpr Step c = SCH.st[I.value];
        const uint32_t bar = barw + dw * 96 + c.slot * 8;
        mbar_expect(bar, SUB);
        tma_v(subw + dw * SUB + c.slot * TILE, tmk, roww * 3 + dw * 24 + c.unit * 768, bar);
    };
    auto refill2 = [&](auto I) { __syncwarp(); if (elect()) issue_v(I, 0); };
    uint4 wq0[6], wqh[3], wq1[6];
    auto load_wq1 = [&](int i) { wq1[i] = lds128((i == 2 ? offV2 : i == 3 ? (offV2 ^ 16) + 128 : (offV0 ^ (i * 16)) + i * 128) + SM_WQ + TILE); };
    auto load_wq = [&]() {
        load_v(wq0, SM_WQ);
        const uint32_t so = SM_WQR - ((warp + 1) >> 1) * SUB;
        wqh[0] = lds128(((warp & 1) ? (offV2 ^ 16) + 128 : offV0) + so);
        wqh[1] = lds128(((warp & 1) ? (offV0 ^ 64) + 512 : (offV0 ^ 16) + 128) + so);
        wqh[2] = lds128(((warp & 1) ? (offV0 ^ 80) + 640 : offV2) + so);
#pragma unroll
        for (int i = 0; i < NWQ1; i++) load_wq1(i);
    };
    uint4 kr[8][6];
    const unsigned char* rap;
    u64 rw[2];
    auto look_rw = [&]() { rw[0] = ld_rlx(rap); rw[1] = ld_rlx(rap + 40 * ACC_PITCH); };
    auto q_proj = [&](auto L, uint32_t (&p)[3], uint32_t pst) {
        if (L.value == 0 && g >= 4) p[0] = p[1] = p[2] = ONES;
        float a[3][4], b[3][4];
        const uint32_t dH = __byte_perm(p[2], 0, (warp & 1) ? 0x3232 : 0x1010);
        const uint32_t dA = __byte_perm(p[0], 0, 0x1010), dB = __byte_perm(p[0], 0, 0x3232), dC = __byte_perm(p[1], 0, 0x1010), dD = __byte_perm(p[1], 0, 0x3232);
#pragma unroll
        for (int i = NWQ1; i < 3; i++) load_wq1(i);
#pragma unroll
        for (int j = 0; j < 3; j++) { a[j][0] = a[j][1] = a[j][2] = a[j][3] = 0.f; mma(a[j], wq0[j], dA & maskA, dA & maskB); }
#pragma unroll
        for (int j = 0; j < 3; j++) { b[j][0] = b[j][1] = b[j][2] = b[j][3] = 0.f; mma(b[j], wq0[j + 3], dB & maskA, dB & maskB); }
#pragma unroll
        for (int j = 0; j < 3; j++) mma(a[j], wqh[j], dH & maskA, dH & maskB);
#pragma unroll
        for (int i = 3; i < 6; i++) load_wq1(i);
        if (L.value == 1 && P4AT == 2) refill2(IC<4>{});
#pragma unroll
        for (int j = 0; j < 3; j++) mma(b[j], wq1[j], dC & maskA, dC & maskB);
#pragma unroll
        for (int j = 0; j < 3; j++) mma(a[j], wq1[j + 3], dD & maskA, dD & maskB);
#pragma unroll
        for (int j = 0; j < 3; j++) {
            if (L.value) {
#pragma unroll
                for (int k = 0; k < 2; k++) { a[j][k] += b[j][k]; add_if(t & 2, a[j][k], a[j][k + 2], b[j][k + 2]); }
                sts64f(pst + j * 256, a[j][0], a[j][1]);
            } else sts128f(pst + j * 256, a[j][0] + b[j][0], a[j][1] + b[j][1], a[j][2] + b[j][2], a[j][3] + b[j][3]);
        }
        CSTAMP(23, __float_as_uint(a[2][1]));
        uint32_t tag;
        if (L.value) tag = lds32(sb + SM_EPOCH) * 4 + 3;
        u64* pub = L.value ? &g_ll[0][cta][tid] : &g_l0[cta][tid];
        if (L.value == 0) asm volatile("fence.proxy.async.shared::cta;" ::: "memory");
        TSTAMPL(21);
        __syncthreads();
        if (!L.value) tag = lds32(sb + SM_EPOCH) * 4 + 1;
#pragma unroll 1
        for (int k = 0; k < 2 - L.value; k++) st_rlx_if(tid < 192, pub + k * 192, ll_pack(sum8(sb + (k ? SM_CSP : SM_PART) + tid * 4, 768), tag));
        TSTAMPL(23);
            CSTAMP(24, tag);
    };
    auto ln_stats = [&]() {
        float ss = ln_part(xp, lane);
        ss += shx(ss, 8); ss += shx(ss, 4); ss += shx(ss, 2); ss += shx(ss, 1);
        stsf(sb + SM_STAT + min(warp, 5) * 8 + (lane >> 4) * 4, ss);
    };
    auto ln_final = [&](float& mean, float& rstd) {
        float2 v[5];
#pragma unroll
        for (int w = 0; w < 5; w++) v[w] = lds64f(sb + SM_STAT + w * 8);
        mean = sum5(v[0].x, v[1].x, v[2].x, v[3].x, v[4].x) * (1.f / D_MODEL);
        const float msq = sum5(v[0].y, v[1].y, v[2].y, v[3].y, v[4].y) * (1.f / D_MODEL);
        rstd = ln_rstd(mean, msq);
        stsf(sb + SM_FXS, msq);
    };
    auto q_addr = [&](int d) { return sb + SM_VEC + (((d >> 1) & 1) * 4 + ((d >> 3) & 3)) * 48 + (d >> 5) * 8 + ((d >> 2) & 1) * 4 + (d & 1) * 2; };
    {
#pragma unroll
        for (int u = 0; u < 8; u++)
#pragma unroll
            for (int i = 0; i < 6; i++) kr[u][i] = lds128(sb + SM_CS + (u * 6 + i) * 16);
        issue_paced(1, NIM);
        ln_stats();
        if (tid == 16) { sts32(sb + SM_EPOCH, small); sts32(sb + SM_M1, ~0u); }
        else if (tid < 16) sts32(sb + SM_B1 + tid * 4, (tid & 1) ? small & 0xffff0000u : small << 16);
        mbar_wait(sb + SM_CBAR + CB_WQ * 8, 0);
        load_wq();
        q_proj(IC<0>{}, px, sb + (t < 2 ? SM_PART : SM_CSP) + warp * 768 + (8 * g + 4 * (t & 1)) * 4);
    }
    {
        uint32_t offQ, offL;
        auto calc_ql = [&]() {
            offQ = pin(sb + SM_VEC + (lane & 7) * 48);
            offL = pin(subw + lane * 16);
        };

        auto issue_w = [&](auto L, int which) {
            const uint32_t bar = sb + SM_CBAR + (CB_W1 + which) * 8;
            if (mlp == 96) asm volatile("mbarrier.arrive.shared::cta.b64 _, [%0];" :: "r"(bar) : "memory");
            else {
                mbar_expect(bar, 20480);
                if (which) {
                    tma3(sb + (L.value ? 3 * TILE : SM_W2), tmk + TM_W2, 0, mlp * 16, bar, POL_FIRST);
                    if (!L.value) tma3_pf(tmk + TM_W2, 0, mlp * 16, POL_NORMAL);
                    if (!L.value) asm volatile("cp.async.bulk.prefetch.L2.global.L2::cache_hint [%0], 20480, %1;" :: "l"(P.w1 + mlp * 10240), "l"((u64)POL_NORMAL << 32) : "memory");
                }
                else asm volatile("cp.async.bulk.tensor.3d.shared::cluster.global.mbarrier::complete_tx::bytes.L2::cache_hint [%0], [%1, {%2, %3, %3}], [%4], %5;"
                                  :: "r"(sb + (L.value ? 2 * TILE : SM_W1)), "l"(tmk + TM_W1), "r"(mlp * 16), "r"(0), "r"(bar), "l"((u64)POL_FIRST << 32) : "memory");
            }
        };
        float acc[3][4];
        auto load_q = [&](uint4 (&qf)[3]) {
#pragma unroll
            for (int i = 0; i < 3; i++) qf[i] = lds128(offQ + i * 16);
        };
        auto softmax = [&](float S0, float S1, float S2, float S3) {
            int mi = __float_as_int(fmaxf(fmaxf(S0, S1), fmaxf(S2, S3)));
            mi = __reduce_max_sync(~0u, mi ^ ((mi >> 31) & 0x7fffffff));
            const float mrun = __int_as_float(mi ^ ((mi >> 31) & 0x7fffffff));
            const float p0 = ex2((S0 - mrun) * CS), p1 = ex2((S1 - mrun) * CS), p2 = ex2((S2 - mrun) * CS), p3 = ex2((S3 - mrun) * CS);
            const uint32_t pa = pack_bf(p0, p1), pb = pack_bf(p2, p3), pw = prow + 256 + (key >> 1) * 80 + t * 4 + (key & 1) * 2;
            sts16(pw, pa); sts16(pw + 16, pa >> 16); sts16(pw + 32, pb); sts16(pw + 48, pb >> 16);
            __syncwarp();
#pragma unroll
            for (int j = 0; j < 3; j++) acc[j][0] = acc[j][1] = acc[j][2] = acc[j][3] = 0.f;
            return make_float2(mrun, (p0 + p1) + (p2 + p3));
        };
        auto pv = [&](const uint4 (&v)[6], uint32_t pp) {
            const uint32_t dA = __byte_perm(pp, 0, 0x1010), dB = __byte_perm(pp, 0, 0x3232);
            mma(acc[0], v[0], dA & maskA, dA & maskB); mma(acc[1], v[1], dA & maskA, dA & maskB); mma(acc[2], v[2], dA & maskA, dA & maskB);
            mma(acc[0], v[3], dB & maskA, dB & maskB); mma(acc[1], v[4], dB & maskA, dB & maskB); mma(acc[2], v[5], dB & maskA, dB & maskB);
        };
        auto sa = [&]() { return prow + 256 + t * 32 + g * 4; };
        auto pass1 = [&]() {
            if (NIM < NI1) issue_paced(NIM, NI1);
            fresh();
            calc_ql();
            __syncthreads();
            sts64(prow + lane * 8, xp.x, xp.y);
            int e = 0;
            const uint4* tab = P.tile + (warp >> 2);
            uint4 tw = tab[0];
            uint32_t ka[3];
#pragma unroll
            for (int j = 0; j < 3; j++) ka[j] = pin(subw + key * 384 + j * 128 + ((t ^ ((3 * key + j) & 7)) << 4));
            auto load_k = [&](uint4 (&v)[6], uint32_t so) {
#pragma unroll
                for (int i = 0; i < 6; i++) v[i] = lds128(((i & 1) ? ka[i >> 1] ^ 64 : ka[i >> 1]) + so);
            };
            const uint32_t s0 = pin(prow + 256 + g * 4), sca = pin(sb + SM_SC + warp * 128 + g * 16);
#pragma unroll 1
            do {
                const uint4 tn = tab[2 * e + 2];
                uint4 v[6], qf[3];
                if (tw.x & (G_A | G_B | G_C)) {
                    if ((tw.x & G_A) && warp == 7 && elect()) {
                        mbar_expect(sb + SM_CBAR + CB_SNAP * 8, HALF);
                        asm volatile("cp.async.bulk.shared::cluster.global.mbarrier::complete_tx::bytes [%0], [%1], 12288, [%2];"
                                     :: "r"(sb + SM_SNAP), "l"(&g_l0[cta & ~3][0]), "r"(sb + SM_CBAR + CB_SNAP * 8) : "memory");
                    }
                    if (tw.x & G_B) {
                        if (warp < 6) {
                            mbar_wait(sb + SM_CBAR + CB_SNAP * 8, 0);
                            float qc[2] = {0.f, 0.f}, mean, rstd;
#pragma unroll 1
                            for (int k = 0; k < 2; k++) {
                                u64 qw[4];
#pragma unroll
                                for (int i = 0; i < 4; i++) { const uint2 x = lds64(sb + SM_SNAP + i * 3072 + k * 1536 + tid * 8); qw[i] = x.x | (u64)x.y << 32; }
                                qc[0] = qc[1];
                                qc[1] = ll_gather<384>(&g_l0[cta & ~3][k * 192 + tid], lds32(sb + SM_EPOCH) * 4 + 1, qw);
                            }
                            ln_final(mean, rstd);
                            stsf(sb + SM_CS + tid * 4, qc[1]);
                            const float q = (qc[0] - mean * qc[1]) * rstd;
                            sts16(q_addr(tid), pack_bf(q, q));
                        }
                        __syncthreads();
                        if (warp == 7 && elect()) issue_half(UC<load_word(12)>::value, sb, rowc, cta, tmk);
                        TSTAMP(2);
                    }
                    if (tw.x & G_C) {
                        load_k(v, (e - LATEAT) * TILE);
                        load_q(qf);
                        stsf(s0 + (e - LATEAT) * 32, score(v, qf));
                    }
                }
                load_q(qf);
                mbar_wait(sb + SM_CBAR + (tw.x & 0xf8), tw.x >> 31);
                TRACE(e);
                load_k(v, tw.x & 0x3f000);
                const uint32_t old = release(tw);
                const float s = score(v, qf);
                uint32_t m;
                {
                    uint32_t a[6];
#pragma unroll
                    for (int i = 0; i < 6; i++) a[i] = bf2_amax(bf2_amax(v[i].x, v[i].y), bf2_amax(v[i].z, v[i].w));
                    m = bf2_amax(bf2_amax(bf2_amax(a[0], a[1]), bf2_amax(a[2], a[3])), bf2_amax(a[4], a[5]));
                }
                m = bf2_amax(m, m >> 16) & 0x7f80;
                m = max(m, __shfl_xor_sync(~0u, m, 1));
                stsf(s0 + e * 32, s);
                m = max(m, __shfl_xor_sync(~0u, m, 2));
                refill(tw, old);
                const uint32_t b = min(max(m, 15u << 7) - (15u << 7), 126u << 7);
                const uint32_t dn = ((127u << 7) - b) * 0x10001u, up = ((127u << 7 | 0x8000u) + b) * 0x10001u;
                uint32_t c[18], any = m > (141u << 7);
#pragma unroll
                for (int i = 0; i < 6; i++) {
                    const uint32_t y0 = bf2_mul(v[i].x, dn), y1 = bf2_mul(v[i].y, dn), y2 = bf2_mul(v[i].z, dn), y3 = bf2_mul(v[i].w, dn);
                    v[i] = make_uint4(bf2_fma(y0, up, v[i].x), bf2_fma(y1, up, v[i].y), bf2_fma(y2, up, v[i].z), bf2_fma(y3, up, v[i].w));
                    any |= v[i].x | v[i].y;
                    any |= v[i].z | v[i].w;
                    const uint32_t hb = __byte_perm(y2, y3, 0x7531);
                    c[3 * i] = __byte_perm(y0, y1, 0x6420); c[3 * i + 1] = __byte_perm(y2, y3, 0x6420);
                    c[3 * i + 2] = __byte_perm(y0, y1, 0x7531) | __funnelshift_r(hb, hb, 4);
                }
                asm volatile("st.shared.u8 [%0], %1;" :: "r"(sca + (e & 3) * 4 + (e >> 2)), "r"((b >> 7) + 63) : "memory");
                const bool rare = __any_sync(~0u, any);
                k_keep(kr, c, e, offL);
                if (rare) k_rare(v[0], v[1], v[2], v[3], v[4], v[5], m > (141u << 7), e, warp, lane);
                tw = tn;
            } while (++e < 16);
            asm volatile("fence.proxy.async.shared::cta;" ::: "memory");
            __syncwarp();
            TSTAMP(10);
            fresh(); calc_offsets();
            {
                const uint2 st = lds64(barw + 80);
                const uint32_t xa = sb + SM_EXC + warp * 128 + (lane & 15) * 8 + 4;
                uint32_t pos = lds32(xa), lt;
                asm volatile("mov.u32 %0, %lanemask_lt;" : "=r"(lt));
                if (lane >= st.x) pos = 0x80000000u;
                const bool dup = (__match_any_sync(~0u, pos >> 16) & lt) && lane < st.x;
                if (lane < 16) sts32(xa, dup ? pos | 0x40000000u : pos);
                if (__any_sync(~0u, dup)) sts32(barw + 84, st.y | 0x10000u);
                const float2 ml = softmax(ldsf(sa()), ldsf(sa() + 128), ldsf(sa() + 256), ldsf(sa() + 384));
                sts64f(sb + SM_ML + warp * 8, ml.x, warp_sum(ml.y));
            }
            u64 pm = 0, pl = 0;
#pragma unroll 1
            do {
                const uint4 tn = tab[2 * e + 2];
                if (tw.x & (G_A | G_B | G_C)) {
                    if (tw.x & G_A) {
                        if (lane < 24) st_rlx(&g_ll[0][cta][warp * 24 + lane], 0ull);
                        else if (lane < 28) st_rlx(&g_ll[0][cta][168 + warp * 4 + lane], ll_pack(ldsf(sb + SM_ML + warp * 8 + (lane & 1) * 4), lds32(sb + SM_EPOCH) * 4 + 2));
                    }
                    if (warp == 2) {
                        if (tw.x & G_B) ld_rlx2(&g_ll[0][cta ^ (lane >> 3)][192 + (lane & 7) * 4], pm, pl);
                        if (tw.x & G_C) head_weight(&g_ll[0][cta ^ (lane >> 3)][192 + (lane & 7) * 4], pm, pl, 0, lane);
                    }
                    __syncwarp();
                }
                const uint32_t pp = lds32(prow + 256 + t * 80 + ((tw.x >> 20) & 255));
                mbar_wait(sb + SM_CBAR + (tw.x & 0xf8), tw.x >> 31);
                TRACE(e);
                uint4 v[6];
                load_v(v, tw.x & 0x3f000);
                refill(tw, release(tw));
                pv(v, pp);
                tw = tn;
            } while (++e < 32);
        };
        uint32_t osa, ora, owa, orow, otag;
        u64* olb;
        float xc;
        auto o_setup = [&](auto L) {
            fresh();
            const int lz = lane, d = warp * 24 + min(lz, 23);
            osa = pin(prow + ((lz >> 2) * 8 + (lz & 1) * 4 + (lz & 2)) * 4);
            ora = pin(sb + SM_PART + d * 4);
            olb = pin(&g_ll[L.value][cta & ~3][d]);
            orow = pin((lz & 1) + 2 * (lz & 2) + 2 * (lz >> 4));
            owa = pin(sb + SM_RING + warp * 1536 + orow * 64 + ((((lz >> 2) & 3) ^ (orow >> 1)) << 4));
            otag = lds32(sb + SM_EPOCH) * 4 + 2 + 2 * L.value;
            uint32_t x; asm volatile("ld.shared.u16 %0, [%1];" : "=r"(x) : "r"(prow + ((cta & 1) * 16 + (lz >> 3) * 4 + (cta & 2) + ((lz >> 2) & 1)) * 8 + (lz & 3) * 2) : "memory");
            xc = bf_lo(x) * (1.f / 32);
        };
        auto wo_at = [&](auto A) {
            constexpr uint32_t x = WOP ^ A.value * 0x11111;
            if constexpr (A.value > 0 && ((x - 0x11111) & ~x & 0x88888) != 0) {
                if ((WOP >> (4 * warp) & 15) == A.value) {
                    mbar_wait(sb + SM_CBAR + CB_REL * 8, 0);
                    if (elect()) {
                        const uint32_t bar = sb + SM_CBAR + (CB_WO + warp) * 8;
                        mbar_expect(bar, HALF);
                        tma3(sb + SM_RING + (warp + (warp < 2 ? 3 : -2)) * HALF, tmk + TM_WO, (cta & 3) + 4 * warp, (cta >> 2) * DH, bar, POL_FIRST);
                    }
                    __syncwarp();
                }
            }
        };
        static_assert(ring_hs(64) == 3, "wo");
        auto pass2 = [&]() {
            constexpr IC<1> L{};
            if (P4AT == 0) refill2(IC<4>{});
            if (P2LATE == 1 && warp >= 4) refill2(IC<2>{});
            uint4 tb[8][3];
            auto load_tb = [&](auto I) {
#pragma unroll
                for (int i = 0; i < 3; i++) tb[I.value][i] = lds128(offL + (I.value >> 1) * TILE + ((I.value & 1) * 3 + i) * 512);
            };
            const u64* qb = &g_ll[0][cta & ~3][min(tid, 191)];
            {
                uint32_t x[2];
                fx2_wait<2>([&](int i) { return rap + i * 40 * ACC_PITCH; }, look_rw, rw, sb + SM_MSQ, ldsf(sb + SM_MSQ + 4), x);
                xp = make_uint2(x[0], x[1]);
                CSTAMP(25, xp.y);
            }
            ln_stats();
            u64 qw[4];
            ll_look<256>(qb, qw);
            const float cs = ldsf(sb + SM_CS + min(tid, 191) * 4);
            const uint32_t qtag = lds32(sb + SM_EPOCH) * 4 + 3, qa = pin(q_addr(min(tid, 191)));
            fresh_lane();
            offQ = sb + SM_VEC + (lane & 7) * 48; offL = subw + lane * 16;
            __syncthreads();
            auto vwait = [&](auto I) { mbar_wait(barw + IC<SCH.st[I.value].slot>::value * 8, IC<SCH.st[I.value].par>::value); };
            bool ok;
            uint32_t m1, m1n;
            {
                float mean, rstd;
                ln_final(mean, rstd);
                const float sq = shx(rstd * 0x1p64f, 0), q0 = shx(-mean * cs * sq, 0);
                CSTAMP(26, __float_as_uint(q0));
                static_for<0, NPRE>(load_tb);
                if (P4AT == 1) refill2(IC<4>{});
                if (S0EARLY) refill2(IC<5>{});
                m1n = m1 = lds32(sb + SM_M1);
                sts64(prow + lane * 8, xp.x, xp.y);
                sts128f(prow + 256 + lane * 16, 0.f, 0.f, 0.f, 0.f);
                const float q = ll_gather<256>(qb, qtag, qw) * sq + q0;
                sts16(qa, pack_bf(q, q));
                TSTAMPL(24);
                CSTAMP(27, __float_as_uint(q));
            }
            if (!S0EARLY) refill2(IC<5>{});
            if (P2LATE == 2 && warp >= 4) refill2(IC<2>{});
            if (P4AT == 3) refill2(IC<4>{});
            if (NOWIN & 1) { if (warp < 6) refill2(IC<0>{}); if (warp >= 5) refill2(IC<3>{}); }
            if (NOWIN & 2) { if (warp >= 6) refill2(IC<1>{}); if (warp < 4) refill2(IC<2>{}); }
            if (NOWIN & 4) { if (warp >= 6) refill2(IC<0>{}); if (warp < 6) refill2(IC<1>{}); }
            if (NOWIN & 8) { if (warp < 5) refill2(IC<3>{}); if (warp >= 4) refill2(IC<2>{}); }
            __syncthreads();
            uint4 qf[3];
            load_q(qf);
            CSTAMP(28, qf[0].x);
            float S[4], d[2][4];
            auto vload = [&](auto I) {
                constexpr int p = I.value;
                constexpr Step c = SCH.st[p];
                load_v(kr[p & 7], c.slot * TILE);
                if constexpr (c.next >= 0) refill2(IC<c.next>{});
                if constexpr (p == 11) { __syncwarp(); if (elect()) asm volatile("mbarrier.arrive.shared::cta.b64 _, [%0];" :: "r"(sb + SM_CBAR + CB_REL * 8) : "memory"); }
            };
            static_for<0, 96>([&](auto F) {
                constexpr int f = F.value, i = f % 6, u = kunit(f / 6), w = 3 * f % 12;
                uint4 (&src)[3] = *reinterpret_cast<uint4 (*)[3]>(f < 32 ? &tb[f / 4 & 7][0] : &kr[(f / 8 + 4) & 7][(f / 4 & 1) * 3]);
                const uint4 a = k_unpack(word<w % 4>(src[w / 4]), word<(w + 1) % 4>(src[(w + 1) / 4]), word<(w + 2) % 4>(src[(w + 2) / 4]), m1);
                if constexpr (f < 32 ? f % 4 == M1AT : f % 8 == M1P) m1 = m1n;
                if constexpr (f % 4 == 3 && f / 4 + NPRE < 8) {
                    load_tb(IC<f / 4 + NPRE>{});
                    if constexpr ((f / 4 + NPRE) & 1) { refill2(IC<5 + (f / 4 + NPRE) / 2>{}); m1n = lds32(sb + SM_M1); }
                }
                if constexpr (i < 2) d[i][0] = d[i][1] = d[i][2] = d[i][3] = 0.f;
                mma(d[i & 1], a, (i & 1) ? qf[i / 2].z : qf[i / 2].x, (i & 1) ? qf[i / 2].w : qf[i / 2].y);
                if constexpr (i == 5) {
                    if constexpr (u == 11 || ((u & 3) == 0 && u != 8)) S[u >> 2] = (d[0][0] + d[0][3]) + (d[1][0] + d[1][3]);
                    else add_if(t == (u & 3), S[u >> 2], d[0][0] + d[0][3], d[1][0] + d[1][3]);
                    if constexpr (f < 64) S[u >> 2] = shx(S[u >> 2], 0);
                }
                if constexpr (f == 31) { fresh(); calc_offsets(); ok = mbar_test(barw + IC<SCH.st[0].slot>::value * 8, 0); }
                if constexpr (f == 48) {
                    const uint2 x = lds64(sb + SM_EXC + warp * 128 + (lane & 15) * 8);
                    const float c = k_side(sb, x);
                    if (x.y < 0x40000000u) stsf(prow + 256 + (x.y >> 16), c);
                }
                if constexpr (f >= 32 && f % 8 == 7) {
                    if constexpr (PARKS >> (f / 8 - 4) & 1) {
                        constexpr int p = popc(PARKS & ((1 << (f / 8 - 4)) - 1));
                        if (!ok) vwait(IC<p>{});
                        vload(IC<p>{});
                        m1n = lds32(sb + SM_M1);
                        ok = mbar_test(barw + IC<SCH.st[p + 1].slot>::value * 8, IC<SCH.st[p + 1].par>::value);
                    }
                }
            });
            uint32_t bad = lds32(barw + 84);
            const uint32_t sc = lds32(sb + SM_SC + tid * 4);
            __syncwarp();
            if (bad) k_fix(P.k + (size_t)roww * DH, bad, warp, lane);
            TSTAMP(30);
            CSTAMP(29, __float_as_uint(S[2]));
            const float2 ml = softmax(S[0] * __uint_as_float((sc & 255) << 23) + ldsf(sa()), S[1] * __uint_as_float((sc & 0xff00) << 15) + ldsf(sa() + 128),
                                      S[2] * __uint_as_float((sc & 0xff0000) << 7) + ldsf(sa() + 256), S[3] * __uint_as_float((sc >> 24) << 23) + ldsf(sa() + 384));
            uint4 pq[4];
#pragma unroll
            for (int j = 0; j < 4; j++) pq[j] = lds128(prow + 256 + t * 80 + j * 16);
            TSTAMP(1);
            CSTAMP(30, pq[3].w);
            if (!ok) vwait(IC<NPARK>{});
            float ac2[3][4];
#pragma unroll
            for (int j = 0; j < 3; j++) ac2[j][0] = ac2[j][1] = ac2[j][2] = ac2[j][3] = 0.f;
            const uint32_t sl = (g & 1) ? 0x1044 : 0x4410, sh = (g & 1) ? 0x3244 : 0x4432;
            const uint32_t sA0 = (g & 2) ? 0x4444 : sl, sA1 = (g & 2) ? sl : 0x4444, sB0 = (g & 2) ? 0x4444 : sh, sB1 = (g & 2) ? sh : 0x4444;
            u64 pm = 0, pl = 0;
            static_for<NPARK, 16>([&](auto I) {
                constexpr int p = I.value;
                static_assert(p - SCH.st[p].mma0 < 8, "buffer in use");
                vload(I);
                if constexpr (p < 15) ok = mbar_test(barw + IC<SCH.st[p + 1].slot>::value * 8, IC<SCH.st[p + 1].par>::value);
                static_for<SCH.st[p].mma0, SCH.st[p].mma0 + SCH.st[p].nmma>([&](auto J) {
                    constexpr int u = SCH.st[J.value].unit;
                    const uint32_t pp = word<u & 3>(pq[u >> 2]), a0 = __byte_perm(pp, 0, sA0), a1 = __byte_perm(pp, 0, sA1), b0 = __byte_perm(pp, 0, sB0), b1 = __byte_perm(pp, 0, sB1);
#pragma unroll
                    for (int j = 0; j < 3; j++) mma(acc[j], kr[J.value & 7][j], a0, a1);
#pragma unroll
                    for (int j = 0; j < 3; j++) mma(ac2[j], kr[J.value & 7][j + 3], b0, b1);
                });
                if constexpr (p == NPARK) {
                    const float l = warp_sum(ml.y);
                    if (lane < 28) st_rlx(&g_ll[1][cta][lane < 24 ? warp * 24 + lane : 168 + warp * 4 + lane], lane < 24 ? 0ull : ll_pack((lane & 1) ? l : ml.x, lds32(sb + SM_EPOCH) * 4 + 4));
                }
                if constexpr (p == HWAT) { if (warp == 6) ld_rlx2(&g_ll[1][cta ^ (lane >> 3)][192 + (lane & 7) * 4], pm, pl); }
                if constexpr (p == 13) o_setup(L);
                if constexpr (p == HWAT + 2) { if (warp == 6) head_weight(&g_ll[1][cta ^ (lane >> 3)][192 + (lane & 7) * 4], pm, pl, 1, lane); }
                wo_at(IC<p - 10>{});
                if constexpr (p < 15) { if (!ok) mbar_wait(barw + IC<SCH.st[p + 1].slot>::value * 8, IC<SCH.st[p + 1].par>::value); TRACE(33 + p); }
            });
#pragma unroll
            for (int j = 0; j < 3; j++)
#pragma unroll
                for (int k = 0; k < 2; k++) { acc[j][k] += ac2[j][k]; add_if(t & 2, acc[j][k], acc[j][k + 2], ac2[j][k + 2]); }
        };

        const unsigned char* ap;
        uint32_t hpa, hsa, hst, w2a, la;
        uint2 b2v;
        float b1v, cs1;
        auto mlp_global = [&](auto L) {
            const int cz = c4();
            ap = accg + 2 * L.value * ACC_BYTES + (cz >> 1) * ACC_PITCH + (cz & 1) * 16;
            if (L.value) ap = pin(ap);
            rap = pin(accg + (2 * L.value + 1) * ACC_BYTES + (cz >> 2) * ACC_PITCH + (cz & 3) * 8);
            asm volatile("ld.global.nc.v2.u32 {%0,%1}, [%2];" : "=r"(b2v.x), "=r"(b2v.y) : "l"(P.b2 + 4 * cz));
        };
        auto mlp_shared = [&](auto L) {
            const int lz = lane;
            hpa = pin(sb + SM_PART + warp * 256 + ((lz & 2) * 4 + (lz >> 2)) * 16 + (L.value ? 0 : (lz & 1) * 4));
            hsa = pin(sb + SM_PART + (lz & 15) * 16); hst = pin(sb + SM_PART + (lz & 15) * 16 + warp * 256 + 8 + (lz >> 4) * 4);
            w2a = pin(sb + (L.value ? 3 * TILE : SM_W2) + ((lz & 3) * 10 + 2 * warp) * 128 + (((lz >> 2) ^ ((2 * lz + 2 * warp) & 6)) << 4));
            la = sb + (L.value ? 2 * TILE : SM_W1) + warp * 4096 + (lz & 4) * 512 + (lz & 2) * 64 + (lz & 1) * 32 + (lz >> 4) * 64 + ((((lz >> 3) ^ (lz >> 1)) & 1) << 4);
            b1v = ldsf(sb + SM_B1 + (lz & 15) * 4);
            if (L.value) { la = pin(la); cs1 = ldsf(sb + SM_ML + (lz & 15) * 4); }
            else fresh();
        };
        uint32_t pa;
        unsigned char* rop;
        uint32_t wpa;
        float sc1;
        auto sum_setup = [&](auto L) {
            const int lz = lane, word = warp * 128 + (cta & 3) * 32 + lz;
            wpa = pin(sb + SM_RING + warp * 1536 + ((((lz >> 2) * 8 + (lz & 1) * 4) * 4) ^ ((((lz >> 1) ^ (lz >> 4)) & 1) ? 256 + 64 : 0)));
            sc1 = pinf(fx2_scale(ldsf(sb + SM_FXS)) * 0.25f);
            pa = pin(sb + SM_RING + warp * 256 + ((lz * 4) ^ ((warp & 1) * 64)));
            rop = pin(accg + 2 * L.value * ACC_BYTES + (word >> 3) * ACC_PITCH + (word & 7) * 4);
        };
        auto out_proj = [&](auto L) {
            TSTAMP2(3);
            CSTAMP(0, __float_as_uint(acc[2][1]));
            __syncwarp();
#pragma unroll
            for (int j = 0; j < 3; j++) {
                if (L.value == 0 && (t & 2)) { acc[j][0] = acc[j][2]; acc[j][1] = acc[j][3]; }
                sts64f(osa + 256 * j, acc[j][0], acc[j][1]);
            }
            __syncthreads();
            {
                float s[8];
#pragma unroll
                for (int w = 0; w < 8; w++) s[w] = ldsf(ora + w * 768);
                const uint4 fa = lds128(sb + SM_FAC), fb = lds128(sb + SM_FAC + 16);
            CSTAMP(1, __float_as_uint(s[0]));
                const float own = ((s[0] * __uint_as_float(fa.x) + s[1] * __uint_as_float(fa.y)) + (s[2] * __uint_as_float(fa.z) + s[3] * __uint_as_float(fa.w))) +
                                  ((s[4] * __uint_as_float(fb.x) + s[5] * __uint_as_float(fb.y)) + (s[6] * __uint_as_float(fb.z) + s[7] * __uint_as_float(fb.w)));
                st_rlx_if(lane < 24, olb + (cta & 3) * 256, ll_pack(own, otag));
            CSTAMP(2, __float_as_uint(own));
            }
            TSTAMPL(29);
            if (L.value) wo_at(IC<6>{});
            if (L.value == 0 && warp == 7) {
#pragma unroll 1
                for (int it = 0; it < SPIN; it++) {
                    uint32_t v; asm volatile("ld.acquire.gpu.global.u32 %0, [%1];" : "=r"(v) : "l"(&g_zflag) : "memory");
                    if (__all_sync(~0u, v == (otag >> 2) + 1)) break;
                }
            }
            constexpr int NW = L.value ? NWO1 : 3;
            uint4 v[5][3];
            u64 ow[4];
            auto read_wo = [&](auto J) {
#pragma unroll
                for (int p = 0; p < 3; p++) v[J.value][p] = lds128(((J.value & 1) ? owa ^ 144 : owa) + ring_hs(64 + J.value) * HALF + p * 512);
            };
            static_for<0, NW>([&](auto J) {
                if (L.value && J.value == 0) { sum_setup(L); maskA = pin(maskA); maskB = pin(maskB); }
                if ((L.value ? OPOLL1 : OPOLL) == J.value) { ll_look<256>(olb, ow); if (L.value) { mlp_shared(L); mlp_global(L); } }
                mbar_wait(sb + SM_CBAR + (CB_WO + J.value) * 8, L.value);
                read_wo(J);
                if (L.value == 0 && W1AT0 == J.value + 1) {
                    __syncwarp();
                    if (elect() && cnt_inc(sb + SM_CNT + CB_W1 * 8, 7) == 7) issue_w(L, 0);
                    __syncwarp();
                }
                if (L.value == 1 && (W1AT1 == J.value + 1 || W2AT1 == J.value + 1)) {
                    if (warp == 7 && elect()) { if (W1AT1 == J.value + 1) issue_w(L, 0); if (W2AT1 == J.value + 1) issue_w(L, 1); }
                    __syncwarp();
                }
            });
            sched_fence();
            const float o = ll_gather<256>(olb, otag, ow);
            CSTAMP(3, __float_as_uint(o));
            TSTAMP2(4);
            bool ok = true;
            if constexpr (NW < 5) ok = mbar_test(sb + SM_CBAR + (CB_WO + 4) * 8, L.value);
            if constexpr (NW < 4) ok &= mbar_test(sb + SM_CBAR + (CB_WO + 3) * 8, L.value);
            const uint32_t od = pack_bf(o, o);
            uint32_t oa[3], ob[3];
#pragma unroll
            for (int p = 0; p < 3; p++) { const uint32_t op = __shfl_sync(~0u, od, 8 * p + orow); oa[p] = op & maskA; ob[p] = op & maskB; }
            CSTAMP(4, oa[2]);
            float y[5][4];
#pragma unroll
            for (int j = 0; j < 5; j++) y[j][0] = y[j][1] = y[j][2] = y[j][3] = 0.f;
            auto rest = [&]() {
                if (!ok) static_for<NW, 5>([&](auto J) { mbar_wait(sb + SM_CBAR + (CB_WO + J.value) * 8, L.value); });
                static_for<NW, 5>(read_wo);
                __syncwarp();
            };
            if (L.value) rest();
#pragma unroll
            for (int p = 0; p < 3; p++)
#pragma unroll
                for (int j = 0; j < NW; j++) mma(y[j], v[j][p], oa[p], ob[p]);
            if (!L.value) { rest(); sum_setup(L); }
#pragma unroll
            for (int p = 0; p < 3; p++)
#pragma unroll
                for (int j = NW; j < 5; j++) mma(y[j], v[j][p], oa[p], ob[p]);
            CSTAMP(5, __float_as_uint(y[4][3]));
#pragma unroll
            for (int j = 0; j < 5; j += 2) {
                if (j < 4 && (t >> 1) != (g >> 2)) { y[j][0] = y[j + 1][0]; y[j][1] = y[j + 1][1]; y[j][2] = y[j + 1][2]; y[j][3] = y[j + 1][3]; }
                sts128f(wpa + j * 256, y[j]);
            }
            TSTAMP2(5);
        };
        u64 yw[2];
        bool wide;
        float msq = 0.f, yf[4] = {};
        auto mlp_part = [&](auto L) {
            bar_sync(0, 256);
            CSTAMP(6, __float_as_uint(sc1));
            const float s = (sum8(pa, 1536) + xc) + sum8(pa + 128, 1536), sm = s * sc1 + FX2_ONE;
            CSTAMP(7, __float_as_uint(s));
            const bool wide1 = !(fabsf(sm - FX2_ONE) < FX1LIM);
            asm volatile("red.relaxed.gpu.global.add.u32 [%0], %1;" :: "l"(rop), "r"(wide1 ? 0u : __float_as_uint(sm) * 128u + (1u - 0x4b400000u * 128u)) : "memory");
            const uint32_t c0 = clk();
            TSTAMP2(6);
            if (L.value == 0) bar_arrive(2, 256);
            if (wide1) {
                fx_send(rop + 64 + (lane & 7) * 4, s, ldsf(sb + SM_FXS), rop, 64);
                asm volatile("red.relaxed.gpu.global.add.u32 [%0], 1;" :: "l"(rop) : "memory");
            }
            __syncwarp();
            if (L.value == 1 && mlp == 96) { TDUMP(); asm volatile("exit;"); }
            uint4 wf[8], w2r[8];
            uint4 w;
            auto look = [&]() { asm volatile("ld.relaxed.gpu.global.v4.u32 {%0,%1,%2,%3}, [%4];" : "=r"(w.x), "=r"(w.y), "=r"(w.z), "=r"(w.w) : "l"(ap) : "memory"); };
            auto read_w1 = [&]() {
#pragma unroll
                for (int j = 0; j < 8; j++) wf[j] = ldsm_t(la + j * 256);
            };
            auto read_w2 = [&]() {
#pragma unroll
                for (int i = 0; i < 8; i++) w2r[i] = lds128(((i & 1) ? (w2a ^ 16) + 128 : w2a) + (i >> 1) * 5120);
            };
            const float inv = pinf(fx_inv(sc1) * (1.f / 128)), off = L.value ? pinf(fx_inv(sc1) * -0.25f) : inv * -32.f;
            if (L.value == 0) { fresh(); mlp_global(L); }
            mbar_wait(sb + SM_CBAR + CB_W1 * 8, L.value);
            if (L.value == 1) {
                if (W2PRE == 1) mbar_wait(sb + SM_CBAR + CB_W2 * 8, 1);
                read_w1();
                if (W2PRE == 1) read_w2();
            }
            while (clk() - c0 < AR1D);
            look();
            if (L.value == 0) { mlp_shared(L); read_w1(); bar_arrive(3, 256); }
            else if (W2PRE == 2) { mbar_wait(sb + SM_CBAR + CB_W2 * 8, 1); read_w2(); }
            TSTAMPL(28);
            {
                sched_fence();
                auto miss = [&]() {
                    xp = make_uint2(pack_bf((float)(int)w.x * inv + off, (float)(int)w.y * inv + off), pack_bf((float)(int)w.z * inv + off, (float)(int)w.w * inv + off));
                    uint32_t a, b;
                    asm("lop3.b32 %0, %1, %2, 32, 0x7e;" : "=r"(a) : "r"(w.x), "r"(w.y));
                    asm("lop3.b32 %0, %1, %2, 32, 0x7e;" : "=r"(b) : "r"(w.z), "r"(w.w));
                    return __any_sync(~0u, (a | b) & 96);
                };
                if (miss()) {
                    int it = 0;
#pragma unroll 1
                    do {
                        if (!__any_sync(~0u, ~(w.x & w.y & w.z & w.w) & 32)) { xp.x = fx1_wide(ap, ldsf(sb + SM_FXS)); xp.y = fx1_wide(ap + 8, ldsf(sb + SM_FXS)); break; }
                        look();
                    } while (miss() & (++it < SPIN));
                }
                CSTAMP(8, w.w);
            }
            TSTAMP2(7);
            CSTAMP(9, xp.y);
            {
                bool ok = true;
                if (L.value == 0 || !W2PRE) ok = mbar_test(sb + SM_CBAR + CB_W2 * 8, L.value);
                const bool ev = L.value || !(g & 1), od = L.value || (g & 1);
                const uint32_t e0 = ev ? xp.x : ONES, e1 = ev ? xp.y : ONES, o0 = od ? xp.x : ONES, o1 = od ? xp.y : ONES;
                float d[8][4];
#pragma unroll
                for (int j = 0; j < 8; j++) { d[j][0] = d[j][1] = d[j][2] = d[j][3] = 0.f; mma(d[j], wf[j], (j & 1) ? o0 : e0, (j & 1) ? o1 : e1); }
                float ss = ln_part(xp, lane);
                ss += shx(ss, 8); ss += shx(ss, 4);
                float r[4], dd;
#pragma unroll
                for (int k = 0; k < 4; k += 1 + L.value) r[k] = d[0][k] + d[1][k ^ 1];
#pragma unroll
                for (int j = 1; j < 4; j++)
#pragma unroll
                    for (int k = 0; k < 4; k += 1 + L.value) add_if(t == j, r[k], d[2 * j][k], d[2 * j + 1][k ^ 1]);
                CSTAMP(10, __float_as_uint(r[2]));
                if (L.value) {
                    dd = ((t & 2) ? r[2] : r[0]) + shx((t & 2) ? r[0] : r[2], 2);
                    ss += shx(ss, 2);
                    dd += shx(dd, 1);
                } else {
                    const float a = ((t & 1) ? r[1] : r[0]) + shx((t & 1) ? r[0] : r[1], 1), b = ((t & 1) ? r[3] : r[2]) + shx((t & 1) ? r[2] : r[3], 1);
                    ss += shx(ss, 2);
                    dd = ((t & 2) ? b : a) + shx((t & 2) ? a : b, 2);
                }
                ss += shx(ss, 1);
                stsf(hpa, dd);
                stsf(hst, ss);
                CSTAMP(11, __float_as_uint(dd + ss));
                if (!ok) mbar_wait(sb + SM_CBAR + CB_W2 * 8, L.value);
            }
            TSTAMPL(25);
            bar_sync(1, 160);
            uint4 hp[5];
#pragma unroll
            for (int w = 0; w < 5; w++) hp[w] = lds128(hsa + w * 256);
            CSTAMP(12, hp[0].x);
            auto hs = [&](auto K) { return sum5(__uint_as_float(word<K.value>(hp[0])), __uint_as_float(word<K.value>(hp[1])), __uint_as_float(word<K.value>(hp[2])),
                                                __uint_as_float(word<K.value>(hp[3])), __uint_as_float(word<K.value>(hp[4]))); };
            const float mean = hs(IC<2>{}) * (1.f / D_MODEL);
            msq = hs(IC<3>{}) * (1.f / D_MODEL);
            if (L.value == 0) cs1 = hs(IC<1>{});
            float hv = hs(IC<0>{}) - mean * cs1;
            CSTAMP(13, __float_as_uint(hv));
            const float sc2 = fx2_scale(msq), lim = fx_inv(sc2) * FX2LIM;
            if (L.value == 0 || !W2PRE) read_w2();
            if (L.value == 0) {
                bar_arrive(4, 256);
                wide = false;
                if (mlp == 96) return;
            }
            hv = hv * ln_rstd(mean, msq) + b1v;
            CSTAMP(14, __float_as_uint(hv));
            hv = hv * rcp(1.f + ex2(hv * (-2.302208198f - 0.1029432397f * hv * hv)));
            const uint32_t hd = pack_bf(hv, hv);
            CSTAMP(15, hd);
            TSTAMPL(27);
            float ym[4][4];
#pragma unroll
            for (int i = 0; i < 2; i++) {
                ym[i][0] = ym[i][1] = ym[i][2] = ym[i][3] = 0.f;
                const float f = mlp < 64 ? 1.f / 64 : 0.f;
                ym[i + 2][0] = (bf_lo(xp.x) + bf_lo(b2v.x)) * f; ym[i + 2][1] = (bf_hi(xp.x) + bf_hi(b2v.x)) * f;
                ym[i + 2][2] = (bf_lo(xp.y) + bf_lo(b2v.y)) * f; ym[i + 2][3] = (bf_hi(xp.y) + bf_hi(b2v.y)) * f;
            }
#pragma unroll
            for (int i = 0; i < 4; i++) {
                const uint32_t hh = __shfl_sync(~0u, hd, 4 * i + t);
                mma(ym[(i & 1) * 2], w2r[2 * i], hh & maskA, hh & maskB);
                mma(ym[(i & 1) * 2 + 1], w2r[2 * i + 1], hh & maskA, hh & maskB);
            }
#pragma unroll
            for (int k = 0; k < 4; k++) { yf[k] = ym[0][k] + ym[2][k]; add_if(t & 2, yf[k], ym[1][k], ym[3][k]); }
            CSTAMP(16, __float_as_uint(yf[3]));
            yw[0] = fx2_pack(yf[0] * sc2 + FX2_ONE, yf[1] * sc2 + FX2_ONE); yw[1] = fx2_pack(yf[2] * sc2 + FX2_ONE, yf[3] * sc2 + FX2_ONE);
            wide = !(fmaxf(fmaxf(fabsf(yf[0]), fabsf(yf[1])), fmaxf(fabsf(yf[2]), fabsf(yf[3]))) < lim);
            if (wide) yw[0] = yw[1] = 0;
            if (L.value == 0) {
#pragma unroll
                for (int k = 0; k < 2; k++) asm volatile("red.relaxed.gpu.global.add.u64 [%0], %1;" :: "l"(rap + k * 40 * ACC_PITCH), "l"(yw[k]) : "memory");
            }
        };
        auto send_wide = [&]() {
#pragma unroll 1
            for (int k = 0; k < 4; k++, yf[0] = yf[1], yf[1] = yf[2], yf[2] = yf[3]) {
                const unsigned char* a = rap + (k >> 1) * 40 * ACC_PITCH;
                fx_send(a + 64 + (k & 1) * 32, yf[0], msq, a, 256);
            }
            yw[0] = yw[1] = 1;
        };

        pass1();
        o_setup(IC<0>{});
        out_proj(IC<0>{});
        uint32_t c0;
        if (warp < 5) {
            mlp_part(IC<0>{});
            c0 = clk() + (mlp == 96 ? PCD : 0);
            stsf(sb + SM_ML + (lane & 15) * 4, cs1);
            TSTAMP(8);
            if (__any_sync(~0u, wide)) {
                if (wide) {
                    send_wide();
#pragma unroll
                    for (int k = 0; k < 2; k++) asm volatile("red.relaxed.gpu.global.add.u64 [%0], 1;" :: "l"(rap + k * 40 * ACC_PITCH) : "memory");
                }
                __syncwarp();
            }
            fresh(); calc_offsets();
            load_wq();
        } else {
            bar_sync(0, 256);
            if (warp == 5 && elect()) {
                asm volatile("fence.proxy.async.shared::cta;" ::: "memory");
                if (W1AT0 == 4) issue_w(IC<0>{}, 0);
                issue_w(IC<0>{}, 1);
            }
            __syncwarp();
            fresh(); calc_offsets();
            load_wq();
#pragma unroll 1
            for (int ph = 0; ph < 3; ph++) {
                bar_sync(ph + 2, 256);
                c0 = clk();
                if (ph == 2) {
                    msq = sum5(ldsf(sb + SM_PART + 12), ldsf(sb + SM_PART + 268), ldsf(sb + SM_PART + 524), ldsf(sb + SM_PART + 780), ldsf(sb + SM_PART + 1036)) * (1.f / D_MODEL);
                    bar_arrive(5, 256);
                }
                if (!(NOWIN >> ph & 1) && elect()) {
                    asm volatile("fence.proxy.async.shared::cta;" ::: "memory");
                    const uint32_t gap = ph == 0 ? WG1 : ph == 1 ? WG2 : WG3;
                    uint32_t c1 = c0 + (ph == 0 ? WD1 : ph == 1 ? WD2 : 0) + (warp - 5) * gap;
#pragma unroll 1
                    for (int k = warp + (ph == 0 ? -5 : ph == 1 ? 9 : 1); k < (ph == 0 ? 9 : ph == 1 ? 20 : 14); k += 3, c1 += 3 * gap) {
                        const int i = ph == 0 && k >= 6 ? k + 23 : k;
                        const uint32_t bar = sb + SM_BAR + (i & 7) * 96 + 32 + (i & 24);
                        while ((int)(clk() - c1) < 0);
                        mbar_expect(bar, SUB);
                        tma_v(sb + SM_RING + i * SUB, tmk,
                              rowc * 3 + (i & 7) * 24 + ((UC<SCH.st[0].unit | SCH.st[1].unit << 8 | SCH.st[2].unit << 16 | SCH.st[3].unit << 24>::value >> (i & 24)) & 15) * 768, bar);
                    }
                }
                __syncwarp();
            }
            c0 += PCD;
        }
        {
            constexpr IC<1> L{};
            fresh();
            const int col = xcol(g & 3, t), cw = j40 + (col >> 2);
            const unsigned char* xa = pin(accg + ACC_BYTES + ((cw >> 2) + (col & 2) * 20) * ACC_PITCH + (cw & 3) * 8);
            const uint32_t pst = pin(prow + (g * 8 + (t & 1) * 4 + (t & 2)) * 4);
            const float inv = pinf(fx2_inv(msq));
            sts64f(sb + SM_MSQ, msq, inv);
            rap = pin(accg + ACC_BYTES + (c4() >> 2) * ACC_PITCH + (c4() & 3) * 8);
            fresh();
            maskA = pin(maskA); maskB = pin(maskB);
            u64 w[1];
            uint32_t x1[1], x2[3];
            auto look = [&]() { w[0] = ld_rlx(xa); };
            if (warp < 5) {
                bar_sync(5, 256);
                if (DPRE) { while ((int)(clk() - c0) < WD4 + warp * WG4); if (warp < DPRE) refill2(IC<3>{}); }
            }
            while ((int)(clk() - c0) < ARDELAY);
            look();
            if (DPOST) while ((int)(clk() - c0) < ARDELAY + DPOST);
            if (warp < 5 && !(NOWIN & 8) && elect()) {
                if (warp >= DPRE) issue_v(IC<3>{}, 0);
                if (warp < 4 && !P2LATE) issue_v(IC<2>{}, 4);
            }
            __syncwarp();
            fx2_wait<1>([&](int) { return xa; }, look, w, sb + SM_MSQ, inv, x1);
            if (warp < 5) look_rw(); else rw[0] = rw[1] = 96;
#pragma unroll
            for (int i = 0; i < 3; i++) x2[i] = __shfl_sync(~0u, x1[0], 4 * i + t);
            TSTAMP(9);
            CSTAMP(22, x2[2]);
            q_proj(L, x2, pst);
            pass2();
            out_proj(L);
            if (warp >= 5) {
                bar_arrive(0, 256);
                if ((W1AT1 == 6 || W2AT1 == 6) && warp == 5 && elect()) { if (W1AT1 == 6) issue_w(L, 0); if (W2AT1 == 6) issue_w(L, 1); }
                TDUMP();
                return;
            }
            mlp_part(L);
            u64 old[2];
            auto add = [&]() {
#pragma unroll
                for (int k = 0; k < 2; k++) asm volatile("atom.relaxed.gpu.global.add.u64 %0, [%1], %2;" : "=l"(old[k]) : "l"(rap + k * 40 * ACC_PITCH), "l"(yw[k]) : "memory");
            };
            add();
            uint32_t* op = pin(reinterpret_cast<uint32_t*>(P.out) + 2 * c4());
            const float inv2 = pinf(fx2_inv(msq));
            if (wide) { send_wide(); add(); }
            TSTAMP(18);
            CSTAMP(17, hi32(yw[1]));
            __syncwarp();
            CSTAMP(18, lo32(old[0]) ^ lo32(old[1]));
#pragma unroll
            for (int k = 0; k < 2; k++) {
                yw[k] += old[k];
                asm volatile("{\n.reg .pred p;\nsetp.eq.u32 p, %2, 96;\n@p st.global.u32 [%0], %1;\n}"
                             :: "l"(op + k), "r"(fx2_get(yw[k], inv2)), "r"(lo32(yw[k]) & 511) : "memory");
            }
            if ((lo32(yw[0]) & 255) == 96 && tid == 0) g_epoch = lds32(sb + SM_EPOCH) + 1;
#pragma unroll
            for (int k = 0; k < 2; k++) if ((lo32(yw[k]) & 511) == 256 + 96) op[k] = fx2_wide(rap + k * 40 * ACC_PITCH, msq);
            TSTAMP(19);
            CSTAMP(19, lo32(yw[1]));
            TDUMP();
        }
    }
}

typedef CUresult (*EncodeFn)(CUtensorMap*, CUtensorMapDataType, cuuint32_t, void*, const cuuint64_t*, const cuuint64_t*, const cuuint32_t*,
                             const cuuint32_t*, CUtensorMapInterleave, CUtensorMapSwizzle, CUtensorMapL2promotion, CUtensorMapFloatOOBfill);

}

extern "C" void kernel_launch(void* const* d_in, const int* in_sizes, int n_in, void* d_out, int out_size) {
    (void)in_sizes; (void)n_in; (void)out_size;
    static EncodeFn enc = nullptr;
    if (!enc) {
        void* fn = nullptr;
        cudaDriverEntryPointQueryResult qr;
        cudaGetDriverEntryPoint("cuTensorMapEncodeTiled", &fn, cudaEnableDefault, &qr);
        enc = (EncodeFn)fn;
        cudaFuncSetAttribute(fused_kernel, cudaFuncAttributeMaxDynamicSharedMemorySize, SM_TOTAL);
    }
    Params P = {};
    auto map3 = [&](int m, int in, cuuint64_t d0, cuuint64_t d1, cuuint64_t d2, cuuint64_t s1, cuuint64_t s2, cuuint32_t b0, cuuint32_t b1, cuuint32_t b2,
                    CUtensorMapSwizzle sw, int promo) {
        const cuuint64_t dim[3] = {d0, d1, d2}, str[2] = {s1, s2};
        const cuuint32_t box[3] = {b0, b1, b2}, ones[3] = {1, 1, 1};
        enc(&P.tm[m], CU_TENSOR_MAP_DATA_TYPE_BFLOAT16, d2 ? 3 : 2, d_in[in], dim, str, box, ones, CU_TENSOR_MAP_INTERLEAVE_NONE, sw, (CUtensorMapL2promotion)promo,
            CU_TENSOR_MAP_FLOAT_OOB_FILL_NONE);
    };
    map3(TM_KH, 1, 64, 3, NHEAD * SK, 128, DH * 2, 64, 3, 32, CU_TENSOR_MAP_SWIZZLE_128B, PROMOK);
    map3(TM_VH, 2, 64, 3, NHEAD * SK, 128, DH * 2, 64, 3, 32, CU_TENSOR_MAP_SWIZZLE_128B, PROMOK);
    map3(TM_VP, 2, 64, 3, NHEAD * SK, 128, DH * 2, PFW, 3, 32, CU_TENSOR_MAP_SWIZZLE_NONE, 0);
    map3(TM_V, 2, 64, NHEAD * SK * 3, 0, 128, 0, 64, 24, 0, CU_TENSOR_MAP_SWIZZLE_128B, PROMOV);
    map3(TM_WO, 4, 32, 20, NHEAD * DH, 64, D_MODEL * 2, 32, 1, DH, CU_TENSOR_MAP_SWIZZLE_64B, PROMOW);
    map3(TM_WOP, 4, 32, 20, NHEAD * DH, 64, D_MODEL * 2, PFW, 1, DH, CU_TENSOR_MAP_SWIZZLE_NONE, 0);
    map3(TM_WQ, 3, 64, NHEAD * 3, D_MODEL, 128, NHEAD * DH * 2, 64, 3, 32, CU_TENSOR_MAP_SWIZZLE_128B, PROMOQ);
    map3(TM_W1, 6, DFF, 128, 5, DFF * 2, DFF * 256, 16, 128, 5, CU_TENSOR_MAP_SWIZZLE_32B, PROMO1);
    map3(TM_W2, 8, 64, 10, DFF, 128, D_MODEL * 2, 64, 10, 16, CU_TENSOR_MAP_SWIZZLE_128B, PROMO2);
    P.x = (const __nv_bfloat16*)d_in[0];
    P.k = (const __nv_bfloat16*)d_in[1];
    P.b1 = (const __nv_bfloat16*)d_in[7];
    P.b2 = (const __nv_bfloat16*)d_in[9];
    P.w1 = (const __nv_bfloat16*)d_in[6];
    P.out = (__nv_bfloat16*)d_out;
    for (int i = 0; i < 64; i++) P.tile[i] = make_uint4(SCH.tile[i][0], SCH.tile[i][1], SCH.tile[i][2], 0);
    fused_kernel<<<NCTA + 1, NTHR, SM_TOTAL, cudaStreamPerThread>>>(P);
}
```

```cpp
#include <cuda_runtime.h>
#include <cuda_bf16.h>
#include <cuda.h>
#include <stdint.h>

namespace {

constexpr int D_MODEL = 640, NHEAD = 32, SK = 32768, DH = 192, WIN = 4096, DFF = 1536;
constexpr int NCTA = 128, NTHR = 256;
constexpr int TILE = 64 * DH * 2;
constexpr int HALF = TILE / 2;
constexpr int SUB = 8 * DH * 2;
constexpr int SM_RING = 4 * TILE;
constexpr int SM_W2 = SM_RING + 20480, SM_W1 = SM_W2 + 20480;
constexpr int SM_WQR = 6 * TILE + HALF, SM_WQ = 7 * TILE;
constexpr int SM_PART = 9 * TILE;
constexpr int SM_EXC = SM_PART + 6144;
constexpr int SM_SC = SM_EXC + 1024;
constexpr int SM_BAR = SM_SC + 1024;
constexpr int SM_VEC = SM_BAR + 768;
constexpr int SM_CS = SM_VEC + 384;
constexpr int SM_FAC = SM_CS + 768;
constexpr int SM_ML = SM_FAC + 32;
constexpr int SM_B1 = SM_ML + 64;
constexpr int SM_STAT = SM_B1 + 64;
constexpr int NCB = 28;
constexpr int CB_WO = 18, CB_W1 = 23, CB_W2 = 24, CB_SNAP = 25, CB_REL = 26, CB_WQ = 27;
constexpr int SM_CBAR = SM_STAT + 48;
constexpr int SM_CNT = SM_CBAR + NCB * 8;
constexpr int SM_EPOCH = SM_CNT + NCB * 8;
constexpr int SM_FXS = SM_EPOCH + 4;
constexpr int SM_T0 = SM_FXS + 4;
constexpr int SM_M1 = SM_T0 + 4;
constexpr int SM_MSQ = SM_M1 + 4;
constexpr int SM_TS = SM_MSQ + 8;
constexpr int SM_TOTAL = 232448;
static_assert(SM_TS + 320 <= SM_TOTAL, "smem");
constexpr int NEXC = 16;

constexpr int SPIN = 1 << 20;
enum { TM_V = 0, TM_KH = 1, TM_VH = 2, TM_WO = 3, TM_VP = 4, TM_WOP = 5, TM_W1 = 6, TM_W2 = 7, TM_WQ = 8 };
constexpr uint32_t POL_NORMAL = 0x16F00000u, POL_FIRST = 0x12F00000u;

#define PACE 980
#define PACE0 1500
#define K0FIRST 1
#define NI1 6
#define ETRIG 0x54321000
#define LATEAT 5
#define HWAT 12
#define PFREE 66
#define W1AT0 3
#define W1AT1 3
#define AR1D 250
#define LAG0 12
#define NMMA 2
#define M1AT 1
#define M1P 3
#define NWO1 4
#define WG2 120
#define WG3 65
#define WD4 250
#define WG4 70
#define NWQ1 0
#define P4AT 0
#define P2LATE 0
#define W2AT1 6
#define PCD 400
#define NOWIN 0
#define DPRE 0
#define DPOST 200
#define NIM 4
#define PACES 1300
#define JP2 54
#define PACE2 0
#define WD2 0
#define W2PRE 2
#define OPOLL1 2
#define FX1LIM 524288.f
#define PROMO2 0
#define PROMOK 0
#define PROMOV 0
#define PROMOQ 0
#define SNAPAT 1
#define DMASK 0x0
#define WOKEEP 0x1f
#define VORD2 0x7685943a2b1cd0efull
#define VTRIG 0xba73210
#define WOP 0x44433
#define PARKS 0x95
#define VSLOT 0x1087654321087654ull
#define OPOLL 2
#define S0EARLY 1
#define NPRE 2
#define ARDELAY 800
#define QDELAY 0
#define CMAP 0
#define PFW 8u
#define PUBAT 28
#define HW0 30
#define HW1 31
#define FX2LIM 524288.f
#define PROMOW 2
#define PROMO1 2
#define WD1 100
#define WG1 140

constexpr uint32_t G_A = 1u << 28, G_B = 1u << 29, G_C = 1u << 30;
__host__ __device__ constexpr int ring_hs(int j) { return (j + 4) % 5; }
__host__ __device__ constexpr uint32_t load_word(int j) {
    if (j >= 64) return (uint32_t)(j - 64) << 20 | (SM_RING + ring_hs(j) * HALF) | TM_WO << 8 | (CB_WO + j - 64) << 3 | 2 | !(WOKEEP >> (j - 64) & 1);
    const int e = j >> 1, isv = e >= 16, unit = e & 15;
    return (uint32_t)(unit * 256 + (j & 1) * 32) << 20 | (j < 8 ? j * HALF : SM_RING + ring_hs(j) * HALF) | (TM_KH + isv) << 8 | (j < 8 ? 10 + j : (j - 8) % 10) << 3 | 2
           | (!isv || (DMASK >> unit & 1));
}
__host__ __device__ constexpr int popc(int v) { return v ? (v & 1) + popc(v >> 1) : 0; }
constexpr int NPARK = popc(PARKS);
constexpr int SM_SNAP = SM_RING + ring_hs(12) * HALF, SM_CSP = SM_RING + ring_hs(11) * HALF;
struct Step { int unit, slot, par, next, mma0, nmma; };
struct Sched { uint32_t tile[64][3]; Step st[16]; };
constexpr Sched make_sched() {
    Sched s{};
    for (int j = 0; j < 64; j++) {
        const int e = j >> 1;
        const uint32_t d = load_word(j);
        uint32_t w = (uint32_t)(j < 8 ? 0 : (j - 8) / 10 & 1) << 31 | (e & 15) * 4 << 20 | ((d & 0x3f000) - (j & 1) * HALF) | (d & 0xf8);
        if (e == PUBAT || e == SNAPAT) w |= G_A;
        if (e == HW0 || e == 4) w |= G_B;
        if ((e >= LATEAT && e < LATEAT + 4) || e == HW1) w |= G_C;
        s.tile[j][0] = w;
    }
    for (int j = NI1; j < 69; j++) {
        if (j == 12) continue;
        const int at = j < 12 ? (ETRIG >> (4 * (j - 4)) & 15) : j - 5;
        s.tile[at][1] = load_word(j);
        s.tile[at][2] = j >= PFREE ? 0 : PACE0 + j * PACE / 2 + (j > JP2 ? (j - JP2) * PACE2 : 0);
    }
    int done = 0;
    for (int p = 0; p < 16; p++) {
        Step& c = s.st[p];
        c.unit = (int)(VORD2 >> (4 * p) & 15); c.slot = (int)(VSLOT >> (4 * p) & 15); c.par = p >= 9; c.next = -1;
        c.mma0 = done;
        if (p >= NPARK) { const int avail = p - done + (p >= LAG0); c.nmma = p == 15 ? 16 - done : (avail < NMMA ? avail : NMMA); done += c.nmma; }
    }
    for (int p = 9; p < 16; p++) s.st[VTRIG >> (4 * (p - 9)) & 15].next = p;
    return s;
}
constexpr Sched SCH = make_sched();
__host__ __device__ constexpr int kunit(int o) { return o < 5 ? o + 11 : o == 5 ? 10 : o - 6; }

template <int I> struct IC { static constexpr int value = I; };
template <uint32_t I> struct UC { static constexpr uint32_t value = I; };
template <int A, int B, class F> __device__ __forceinline__ void static_for(F&& f) {
    if constexpr (A < B) { f(IC<A>{}); static_for<A + 1, B>(f); }
}

typedef unsigned long long u64;
constexpr int ACC_PITCH = 256;
constexpr int ACC_BYTES = 80 * ACC_PITCH;
struct alignas(1024) Scratch {
    unsigned char acc[4 * ACC_BYTES];
    u64 l0[NCTA][384];
    u64 ll[2][NCTA][256];
    alignas(128) unsigned epoch;
    alignas(128) unsigned zflag;
};
__device__ Scratch g_scratch;

struct Params {
    CUtensorMap tm[9];
    const __nv_bfloat16 *x, *k, *b1, *b2, *w1;
    __nv_bfloat16* out;
    Scratch* g;
    uint4 tile[66];
};

#define TSTAMP(i)
#define TSTAMP2(i)
#define TSTAMPL(i)
#define TDUMP()
#define CSTAMP(i, x)
#define TRACE(i)

__device__ __forceinline__ void mbar_wait(uint32_t bar, uint32_t parity) {
    asm volatile("{\n.reg .pred p;\nLOOP:\nmbarrier.try_wait.parity.shared::cta.b64 p, [%0], %1;\n@!p bra.uni LOOP;\n}" :: "r"(bar), "r"(parity) : "memory");
}
__device__ __forceinline__ bool mbar_test(uint32_t bar, uint32_t parity) {
    uint32_t r;
    asm volatile("{\n.reg .pred p;\nmbarrier.test_wait.parity.shared::cta.b64 p, [%1], %2;\nselp.u32 %0, 1, 0, p;\n}" : "=r"(r) : "r"(bar), "r"(parity) : "memory");
    return __all_sync(~0u, r);
}
__device__ __forceinline__ bool elect() {
    uint32_t r;
    asm volatile("{\n.reg .pred p;\nelect.sync _|p, 0xffffffff;\nselp.u32 %0, 1, 0, p;\n}" : "=r"(r));
    return r != 0;
}
__device__ __forceinline__ void mbar_expect(uint32_t bar, uint32_t bytes) {
    asm volatile("mbarrier.arrive.expect_tx.shared::cta.b64 _, [%0], %1;" :: "r"(bar), "r"(bytes) : "memory");
}
__device__ __forceinline__ uint4 lds128(uint32_t a) {
    uint4 v; asm volatile("ld.shared.v4.u32 {%0,%1,%2,%3}, [%4];" : "=r"(v.x), "=r"(v.y), "=r"(v.z), "=r"(v.w) : "r"(a) : "memory"); return v;
}
__device__ __forceinline__ uint4 ldsm_t(uint32_t a) {
    uint4 v; asm volatile("ldmatrix.sync.aligned.m8n8.x4.trans.shared.b16 {%0,%1,%2,%3}, [%4];" : "=r"(v.x), "=r"(v.y), "=r"(v.z), "=r"(v.w) : "r"(a) : "memory"); return v;
}
__device__ __forceinline__ uint2 lds64(uint32_t a) {
    uint2 v; asm volatile("ld.shared.v2.u32 {%0,%1}, [%2];" : "=r"(v.x), "=r"(v.y) : "r"(a) : "memory"); return v;
}
__device__ __forceinline__ float2 lds64f(uint32_t a) { const uint2 v = lds64(a); return make_float2(__uint_as_float(v.x), __uint_as_float(v.y)); }
__device__ __forceinline__ uint32_t lds32(uint32_t a) {
    uint32_t v; asm volatile("ld.shared.u32 %0, [%1];" : "=r"(v) : "r"(a) : "memory"); return v;
}
__device__ __forceinline__ float ldsf(uint32_t a) { return __uint_as_float(lds32(a)); }
__device__ __forceinline__ void sts32(uint32_t a, uint32_t v) { asm volatile("st.shared.u32 [%0], %1;" :: "r"(a), "r"(v) : "memory"); }
__device__ __forceinline__ void stsf(uint32_t a, float v) { sts32(a, __float_as_uint(v)); }
__device__ __forceinline__ void sts16(uint32_t a, uint32_t v) { asm volatile("st.shared.u16 [%0], %1;" :: "r"(a), "h"((uint16_t)v) : "memory"); }
__device__ __forceinline__ void sts64(uint32_t a, uint32_t x, uint32_t y) { asm volatile("st.shared.v2.u32 [%0], {%1,%2};" :: "r"(a), "r"(x), "r"(y) : "memory"); }
__device__ __forceinline__ void sts64f(uint32_t a, float x, float y) { sts64(a, __float_as_uint(x), __float_as_uint(y)); }
__device__ __forceinline__ void sts128f(uint32_t a, float x, float y, float z, float w) {
    asm volatile("st.shared.v4.f32 [%0], {%1,%2,%3,%4};" :: "r"(a), "f"(x), "f"(y), "f"(z), "f"(w) : "memory");
}
__device__ __forceinline__ void mma(float (&c)[4], const uint4& a, uint32_t b0, uint32_t b1) {
    asm volatile("mma.sync.aligned.m16n8k16.row.col.f32.bf16.bf16.f32 {%0,%1,%2,%3}, {%4,%5,%6,%7}, {%8,%9}, {%0,%1,%2,%3};"
                 : "+f"(c[0]), "+f"(c[1]), "+f"(c[2]), "+f"(c[3]) : "r"(a.x), "r"(a.y), "r"(a.z), "r"(a.w), "r"(b0), "r"(b1));
}
__device__ __forceinline__ u64 ld_rlx(const void* p) {
    u64 a; asm volatile("ld.relaxed.gpu.global.u64 %0, [%1];" : "=l"(a) : "l"(p) : "memory"); return a;
}
__device__ __forceinline__ void ld_rlx2(const void* p, u64& a, u64& b) {
    asm volatile("ld.relaxed.gpu.global.v2.u64 {%0,%1}, [%2];" : "=l"(a), "=l"(b) : "l"(p) : "memory");
}
__device__ __forceinline__ void st_rlx(void* p, u64 a) { asm volatile("st.relaxed.gpu.global.u64 [%0], %1;" :: "l"(p), "l"(a) : "memory"); }
__device__ __forceinline__ u64 ll_pack(float v, uint32_t tag) { return ((u64)tag << 32) | __float_as_uint(v); }
__device__ __forceinline__ float ll_val(u64 w) { return __uint_as_float((uint32_t)w); }
__device__ __forceinline__ uint32_t ll_tag(u64 w) { return (uint32_t)(w >> 32); }
__device__ __forceinline__ float bf_lo(uint32_t u) { return __uint_as_float(u << 16); }
__device__ __forceinline__ float bf_hi(uint32_t u) { return __uint_as_float(u & 0xffff0000u); }
__device__ __forceinline__ uint32_t pack_bf(float lo, float hi) {
    uint32_t r; asm("cvt.rn.bf16x2.f32 %0, %1, %2;" : "=r"(r) : "f"(hi), "f"(lo)); return r;
}
__device__ __forceinline__ float ex2(float v) { float r; asm("ex2.approx.ftz.f32 %0, %1;" : "=f"(r) : "f"(v)); return r; }
__device__ __forceinline__ float rcp(float v) { float r; asm("rcp.approx.ftz.f32 %0, %1;" : "=f"(r) : "f"(v)); return r; }
__device__ __forceinline__ float rsq(float v) { float r; asm("rsqrt.approx.ftz.f32 %0, %1;" : "=f"(r) : "f"(v)); return r; }
__device__ __forceinline__ void bar_sync(int id, int n) { asm volatile("bar.sync %0, %1;" :: "r"(id), "r"(n) : "memory"); }
__device__ __forceinline__ uint32_t clk() { uint32_t c; asm volatile("mov.u32 %0, %clock;" : "=r"(c)); return c; }
__device__ __forceinline__ void sched_fence() { __syncwarp(); while (clk() == 0x9e3779b9u); }
__device__ __forceinline__ uint32_t pin(uint32_t v) { return __shfl_xor_sync(~0u, v, 0); }
__device__ __forceinline__ float shx(float v, int o) { return __shfl_xor_sync(~0u, v, o); }

__device__ __forceinline__ u64 fx_pack(float v, float scale) { return ((u64)__float2ll_rn(v * scale) & ~255ull) | 1ull; }
__device__ __forceinline__ float fx_scale(float meansq) {
    const int e = max(((int)(__float_as_uint(meansq) >> 23) - 127) >> 1, -6);
    return __uint_as_float((uint32_t)(127 + 32 - e) << 23);
}
__device__ __forceinline__ float fx_inv(float scale) { return __uint_as_float((254u << 23) - __float_as_uint(scale)); }
__device__ __forceinline__ uint32_t lo32(u64 w) { uint32_t l; asm("mov.b64 {%0, _}, %1;" : "=r"(l) : "l"(w)); return l; }
__device__ __forceinline__ int hi32(u64 w) { int h; asm("mov.b64 {_, %0}, %1;" : "=r"(h) : "l"(w)); return h; }
__device__ __forceinline__ float fx_val(u64 w) { return (float)hi32(w) * 4294967296.f + (float)lo32(w); }
constexpr float FX2_ONE = 12582912.f;
__device__ __forceinline__ float fx2_scale(float meansq) { return __uint_as_float((uint32_t)(127 + 16 - max(((int)(__float_as_uint(meansq) >> 23) - 127) >> 1, -100)) << 23); }
__device__ __forceinline__ u64 fx2_pack(float a, float b) {
    const uint32_t lo = __float_as_uint(a) * 512u + (1u - 0x4b400000u * 512u);
    return lo | (u64)(__float_as_uint(b) * 16u - 0x4b400000u * 16u + (uint32_t)((int)lo >> 31)) << 32;
}
__device__ __forceinline__ float fx2_lo(u64 w, float inv) { return (float)(int)(__funnelshift_r(lo32(w), hi32(w), 4) & ~31u) * (inv * 0.5f); }
__device__ __forceinline__ float fx2_hi(u64 w, float inv) { return (float)((hi32(w) + 8) & ~15) * inv; }
__device__ __forceinline__ uint32_t fx2_get(u64 w, float inv) {
    return pack_bf((float)(int)__funnelshift_r(lo32(w), hi32(w), 4) * (inv * 0.5f) - inv * 3.f, (float)hi32(w) * inv);
}
__device__ __forceinline__ float fx2_inv(float meansq) { return fx_inv(fx2_scale(meansq)) * 0.0625f; }
__device__ __noinline__ uint32_t fx2_wide(const unsigned char* a, float meansq) {
    __threadfence();
    const u64 w = ld_rlx(a);
    const float inv = fx_inv(fx_scale(meansq));
    return pack_bf(fx2_lo(w, fx2_inv(meansq)) + fx_val(ld_rlx(a + 64)) * inv, fx2_hi(w, fx2_inv(meansq)) + fx_val(ld_rlx(a + 96)) * inv);
}
__device__ __noinline__ uint32_t fx1_wide(const unsigned char* a, float meansq) {
    __threadfence();
    const u64 w = ld_rlx(a);
    const unsigned char* b = a + 64 + (reinterpret_cast<u64>(a) & 31);
    const float inv = fx_inv(fx_scale(meansq)), inv1 = fx2_inv(meansq) * 0.5f;
    return pack_bf((float)(int)(lo32(w) & ~127u) * inv1 + fx_val(ld_rlx(b)) * inv, (float)(hi32(w) & ~127) * inv1 + fx_val(ld_rlx(b + 8)) * inv);
}
__device__ __noinline__ void fx_send(const unsigned char* wide, float v, float meansq, const unsigned char* a, uint32_t flag) {
    asm volatile("red.relaxed.gpu.global.add.u64 [%0], %1;" :: "l"(wide), "l"(fx_pack(v, fx_scale(meansq))) : "memory");
    __threadfence();
    asm volatile("red.relaxed.gpu.global.or.b32 [%0], %1;" :: "l"(a), "r"(flag) : "memory");
}
template <int N, class A, class F> __device__ __forceinline__ void fx2_wait(A a, F look, u64 (&w)[N], uint32_t msqa, float inv, uint32_t (&x)[N]) {
    auto miss = [&]() {
#pragma unroll
        for (int i = 0; i < N; i++) x[i] = fx2_get(w[i], inv);
        return __any_sync(~0u, ((lo32(w[0]) ^ 96) | (lo32(w[N - 1]) ^ 96)) & 0x160);
    };
    if (miss()) {
        int it = 0;
#pragma unroll 1
        do {
            if (__all_sync(~0u, (lo32(w[0]) & lo32(w[N - 1]) & 96) == 96)) {
#pragma unroll
                for (int i = 0; i < N; i++) x[i] = fx2_wide(a(i), ldsf(msqa));
                break;
            }
            look();
        } while (miss() & (++it < SPIN));
    }
}
__device__ __forceinline__ void st_rlx_if(bool p, void* a, u64 v) {
    asm volatile("{\n.reg .pred p;\nsetp.ne.u32 p, %2, 0;\n@p st.relaxed.gpu.global.u64 [%0], %1;\n}" :: "l"(a), "l"(v), "r"((uint32_t)p) : "memory");
}
__device__ __forceinline__ void sts128f(uint32_t a, const float (&v)[4]) { sts128f(a, v[0], v[1], v[2], v[3]); }
__device__ __forceinline__ void bar_arrive(int id, int n) { asm volatile("bar.arrive %0, %1;" :: "r"(id), "r"(n) : "memory"); }
template <class T> __device__ __forceinline__ T* pin(T* p) { return reinterpret_cast<T*>(__shfl_xor_sync(~0u, (u64)p, 0)); }

__device__ __forceinline__ void tma3(uint32_t dst, const CUtensorMap* tm, int c1, int c2, uint32_t bar, uint32_t pol) {
    asm volatile("cp.async.bulk.tensor.3d.shared::cluster.global.mbarrier::complete_tx::bytes.L2::cache_hint [%0], [%1, {%2, %3, %4}], [%5], %6;"
                 :: "r"(dst), "l"(tm), "r"(0), "r"(c1), "r"(c2), "r"(bar), "l"((u64)pol << 32) : "memory");
}
__device__ __forceinline__ void tma_v(uint32_t dst, const CUtensorMap* tm, int line, uint32_t bar) {
    asm volatile("cp.async.bulk.tensor.2d.shared::cluster.global.mbarrier::complete_tx::bytes.L2::cache_hint [%0], [%1, {%2, %3}], [%4], %5;"
                 :: "r"(dst), "l"(tm), "r"(0), "r"(line), "r"(bar), "l"((u64)POL_FIRST << 32) : "memory");
}
__device__ __forceinline__ void tma3_pf(const CUtensorMap* tm, int c1, int c2, uint32_t pol) {
    asm volatile("cp.async.bulk.prefetch.tensor.3d.L2.global.tile.L2::cache_hint [%0, {%1, %2, %3}], %4;"
                 :: "l"(tm), "r"(0), "r"(c1), "r"(c2), "l"((u64)pol << 32) : "memory");
}
__device__ __forceinline__ void issue_half(uint32_t d, uint32_t sb, int rowc, int cta, const CUtensorMap* tm0) {
    const uint32_t bar = sb + SM_CBAR + (d & 0xf8);
    const CUtensorMap* tm = tm0 + ((d >> 8) & 3);
    const bool wo = (d & 0x300) == TM_WO << 8;
    const int c1 = wo ? (cta & 3) + 4 * (d >> 20) : 0, c2 = wo ? (cta >> 2) * DH : rowc + (d >> 20);
    mbar_expect(bar, HALF);
    tma3(sb + (d & 0x3f000), tm, c1, c2, bar, POL_FIRST);
    if (!(d & 1)) tma3_pf(tm + 2, c1, c2, POL_NORMAL);
}
__device__ __forceinline__ uint32_t cnt_inc(uint32_t a, uint32_t last) {
    uint32_t old; asm volatile("atom.relaxed.cta.shared.inc.u32 %0, [%1], %2;" : "=r"(old) : "r"(a), "r"(last) : "memory"); return old;
}
__device__ __forceinline__ void wait_until(uint32_t due) {
#pragma unroll 1
    for (int it = 0; it < 4096; it++) { uint32_t now; asm volatile("mov.u32 %0, %globaltimer_lo;" : "=r"(now)); if ((int)(now - due) >= 0) break; }
}
__device__ __forceinline__ uint32_t bf2_mul(uint32_t a, uint32_t b) { uint32_t r; asm("mul.rn.bf16x2 %0, %1, %2;" : "=r"(r) : "r"(a), "r"(b)); return r; }
__device__ __forceinline__ uint32_t bf2_fma(uint32_t a, uint32_t b, uint32_t c) { uint32_t r; asm("fma.rn.bf16x2 %0, %1, %2, %3;" : "=r"(r) : "r"(a), "r"(b), "r"(c)); return r; }
__device__ __forceinline__ uint32_t bf2_amax(uint32_t a, uint32_t b) { uint32_t r; asm("max.NaN.xorsign.abs.bf16x2 %0, %1, %2;" : "=r"(r) : "r"(a), "r"(b)); return r; }
__device__ __forceinline__ uint4 k_unpack(uint32_t l0, uint32_t l1, uint32_t h, uint32_t m1) {
    const uint32_t ha = h & 0x87878787u, hc = ha * m1 + h, hb = __funnelshift_l(hc, hc, 4);
    return make_uint4(__byte_perm(l0, ha, 0x5140), __byte_perm(l0, ha, 0x7362), __byte_perm(l1, hb, 0x5140), __byte_perm(l1, hb, 0x7362));
}
#define KR4(u, i) "+r"(kr[u][i].x), "+r"(kr[u][i].y), "+r"(kr[u][i].z), "+r"(kr[u][i].w)
#define KR6(u) KR4(u, 0), KR4(u, 1), KR4(u, 2), KR4(u, 3), KR4(u, 4), KR4(u, 5)
__device__ __forceinline__ void k_keep(uint4 (&kr)[8][6], const uint32_t (&c)[18], int e, uint32_t a) {
    asm volatile("{\nKT: .branchtargets K0, K1, K2, K3, K4, K5, K6, K7, K8, K9, K10, K11, K12, K13, K14, K15;\nbrx.idx.uni %210, KT;\n"
                 "K0: mov.b32 %12, %192; mov.b32 %13, %193; mov.b32 %14, %194; mov.b32 %15, %195; mov.b32 %16, %196; mov.b32 %17, %197; mov.b32 %18, %198; mov.b32 %19, %199; mov.b32 %20, %200; mov.b32 %21, %201; mov.b32 %22, %202; mov.b32 %23, %203; mov.b32 %24, %204; mov.b32 %25, %205; mov.b32 %26, %206; mov.b32 %27, %207; mov.b32 %28, %208; mov.b32 %29, %209; bra.uni KE;\n"
                 "K1: mov.b32 %30, %192; mov.b32 %31, %193; mov.b32 %32, %194; mov.b32 %33, %195; mov.b32 %34, %196; mov.b32 %35, %197; mov.b32 %36, %198; mov.b32 %37, %199; mov.b32 %38, %200; mov.b32 %39, %201; mov.b32 %40, %202; mov.b32 %41, %203; mov.b32 %42, %204; mov.b32 %43, %205; mov.b32 %44, %206; mov.b32 %45, %207; mov.b32 %46, %208; mov.b32 %47, %209; bra.uni KE;\n"
                 "K2: mov.b32 %48, %192; mov.b32 %49, %193; mov.b32 %50, %194; mov.b32 %51, %195; mov.b32 %52, %196; mov.b32 %53, %197; mov.b32 %54, %198; mov.b32 %55, %199; mov.b32 %56, %200; mov.b32 %57, %201; mov.b32 %58, %202; mov.b32 %59, %203; mov.b32 %60, %204; mov.b32 %61, %205; mov.b32 %62, %206; mov.b32 %63, %207; mov.b32 %64, %208; mov.b32 %65, %209; bra.uni KE;\n"
                 "K3: mov.b32 %66, %192; mov.b32 %67, %193; mov.b32 %68, %194; mov.b32 %69, %195; mov.b32 %70, %196; mov.b32 %71, %197; mov.b32 %72, %198; mov.b32 %73, %199; mov.b32 %74, %200; mov.b32 %75, %201; mov.b32 %76, %202; mov.b32 %77, %203; mov.b32 %78, %204; mov.b32 %79, %205; mov.b32 %80, %206; mov.b32 %81, %207; mov.b32 %82, %208; mov.b32 %83, %209; bra.uni KE;\n"
                 "K4: mov.b32 %84, %192; mov.b32 %85, %193; mov.b32 %86, %194; mov.b32 %87, %195; mov.b32 %88, %196; mov.b32 %89, %197; mov.b32 %90, %198; mov.b32 %91, %199; mov.b32 %92, %200; mov.b32 %93, %201; mov.b32 %94, %202; mov.b32 %95, %203; mov.b32 %96, %204; mov.b32 %97, %205; mov.b32 %98, %206; mov.b32 %99, %207; mov.b32 %100, %208; mov.b32 %101, %209; bra.uni KE;\n"
                 "K5: mov.b32 %102, %192; mov.b32 %103, %193; mov.b32 %104, %194; mov.b32 %105, %195; mov.b32 %106, %196; mov.b32 %107, %197; mov.b32 %108, %198; mov.b32 %109, %199; mov.b32 %110, %200; mov.b32 %111, %201; mov.b32 %112, %202; mov.b32 %113, %203; mov.b32 %114, %204; mov.b32 %115, %205; mov.b32 %116, %206; mov.b32 %117, %207; mov.b32 %118, %208; mov.b32 %119, %209; bra.uni KE;\n"
                 "K6: mov.b32 %120, %192; mov.b32 %121, %193; mov.b32 %122, %194; mov.b32 %123, %195; mov.b32 %124, %196; mov.b32 %125, %197; mov.b32 %126, %198; mov.b32 %127, %199; mov.b32 %128, %200; mov.b32 %129, %201; mov.b32 %130, %202; mov.b32 %131, %203; mov.b32 %132, %204; mov.b32 %133, %205; mov.b32 %134, %206; mov.b32 %135, %207; mov.b32 %136, %208; mov.b32 %137, %209; bra.uni KE;\n"
                 "K7: mov.b32 %138, %192; mov.b32 %139, %193; mov.b32 %140, %194; mov.b32 %141, %195; mov.b32 %142, %196; mov.b32 %143, %197; mov.b32 %144, %198; mov.b32 %145, %199; mov.b32 %146, %200; mov.b32 %147, %201; mov.b32 %148, %202; mov.b32 %149, %203; mov.b32 %150, %204; mov.b32 %151, %205; mov.b32 %152, %206; mov.b32 %153, %207; mov.b32 %154, %208; mov.b32 %155, %209; bra.uni KE;\n"
                 "K8: mov.b32 %156, %192; mov.b32 %157, %193; mov.b32 %158, %194; mov.b32 %159, %195; mov.b32 %160, %196; mov.b32 %161, %197; mov.b32 %162, %198; mov.b32 %163, %199; mov.b32 %164, %200; mov.b32 %165, %201; mov.b32 %166, %202; mov.b32 %167, %203; mov.b32 %168, %204; mov.b32 %169, %205; mov.b32 %170, %206; mov.b32 %171, %207; mov.b32 %172, %208; mov.b32 %173, %209; bra.uni KE;\n"
                 "K9: mov.b32 %174, %192; mov.b32 %175, %193; mov.b32 %176, %194; mov.b32 %177, %195; mov.b32 %178, %196; mov.b32 %179, %197; mov.b32 %180, %198; mov.b32 %181, %199; mov.b32 %182, %200; mov.b32 %183, %201; mov.b32 %184, %202; mov.b32 %185, %203; mov.b32 %186, %204; mov.b32 %187, %205; mov.b32 %188, %206; mov.b32 %189, %207; mov.b32 %190, %208; mov.b32 %191, %209; bra.uni KE;\n"
                 "K10: st.shared.v2.b32 [%211+75784], {%192, %193}; st.shared.v2.b32 [%211+76288], {%194, %195}; st.shared.v2.b32 [%211+76296], {%196, %197}; mov.b32 %0, %198; mov.b32 %1, %199; mov.b32 %2, %200; mov.b32 %3, %201; mov.b32 %4, %202; mov.b32 %5, %203; mov.b32 %6, %204; mov.b32 %7, %205; mov.b32 %8, %206; mov.b32 %9, %207; mov.b32 %10, %208; mov.b32 %11, %209; bra.uni KE;\n"
                 "K11: st.shared.v2.b32 [%211+0], {%192, %193}; st.shared.v2.b32 [%211+8], {%194, %195}; st.shared.v2.b32 [%211+512], {%196, %197}; st.shared.v2.b32 [%211+520], {%198, %199}; st.shared.v2.b32 [%211+1024], {%200, %201}; st.shared.v2.b32 [%211+1032], {%202, %203}; st.shared.v2.b32 [%211+1536], {%204, %205}; st.shared.v2.b32 [%211+1544], {%206, %207}; st.shared.v2.b32 [%211+2048], {%208, %209}; bra.uni KE;\n"
                 "K12: st.shared.v2.b32 [%211+2056], {%192, %193}; st.shared.v2.b32 [%211+2560], {%194, %195}; st.shared.v2.b32 [%211+2568], {%196, %197}; st.shared.v2.b32 [%211+24576], {%198, %199}; st.shared.v2.b32 [%211+24584], {%200, %201}; st.shared.v2.b32 [%211+25088], {%202, %203}; st.shared.v2.b32 [%211+25096], {%204, %205}; st.shared.v2.b32 [%211+25600], {%206, %207}; st.shared.v2.b32 [%211+25608], {%208, %209}; bra.uni KE;\n"
                 "K13: st.shared.v2.b32 [%211+26112], {%192, %193}; st.shared.v2.b32 [%211+26120], {%194, %195}; st.shared.v2.b32 [%211+26624], {%196, %197}; st.shared.v2.b32 [%211+26632], {%198, %199}; st.shared.v2.b32 [%211+27136], {%200, %201}; st.shared.v2.b32 [%211+27144], {%202, %203}; st.shared.v2.b32 [%211+49152], {%204, %205}; st.shared.v2.b32 [%211+49160], {%206, %207}; st.shared.v2.b32 [%211+49664], {%208, %209}; bra.uni KE;\n"
                 "K14: st.shared.v2.b32 [%211+49672], {%192, %193}; st.shared.v2.b32 [%211+50176], {%194, %195}; st.shared.v2.b32 [%211+50184], {%196, %197}; st.shared.v2.b32 [%211+50688], {%198, %199}; st.shared.v2.b32 [%211+50696], {%200, %201}; st.shared.v2.b32 [%211+51200], {%202, %203}; st.shared.v2.b32 [%211+51208], {%204, %205}; st.shared.v2.b32 [%211+51712], {%206, %207}; st.shared.v2.b32 [%211+51720], {%208, %209}; bra.uni KE;\n"
                 "K15: st.shared.v2.b32 [%211+73728], {%192, %193}; st.shared.v2.b32 [%211+73736], {%194, %195}; st.shared.v2.b32 [%211+74240], {%196, %197}; st.shared.v2.b32 [%211+74248], {%198, %199}; st.shared.v2.b32 [%211+74752], {%200, %201}; st.shared.v2.b32 [%211+74760], {%202, %203}; st.shared.v2.b32 [%211+75264], {%204, %205}; st.shared.v2.b32 [%211+75272], {%206, %207}; st.shared.v2.b32 [%211+75776], {%208, %209}; \nKE:\n}"
                 : KR6(0), KR6(1), KR6(2), KR6(3), KR6(4), KR6(5), KR6(6), KR6(7)
                 : "r"(c[0]), "r"(c[1]), "r"(c[2]), "r"(c[3]), "r"(c[4]), "r"(c[5]), "r"(c[6]), "r"(c[7]), "r"(c[8]), "r"(c[9]), "r"(c[10]), "r"(c[11]), "r"(c[12]), "r"(c[13]), "r"(c[14]), "r"(c[15]), "r"(c[16]), "r"(c[17]), "r"(e), "r"(a) : "memory");
}
__device__ __forceinline__ uint32_t smem_base() { extern __shared__ __align__(1024) unsigned char smem[]; return (uint32_t)__cvta_generic_to_shared(smem); }
__device__ __forceinline__ void k_rare(uint4 v0, uint4 v1, uint4 v2, uint4 v3, uint4 v4, uint4 v5, uint32_t odd, int e, int warp, int lane) {
    const uint32_t sb = smem_base(), g = lane >> 2, t = lane & 3, st = sb + SM_BAR + warp * 96 + 80;
    uint32_t lt; asm volatile("mov.u32 %0, %lanemask_lt;" : "=r"(lt));
    const uint4 v[6] = {v0, v1, v2, v3, v4, v5};
    odd <<= 6;
#pragma unroll
    for (int i = 0; i < 6; i++) if (v[i].x | v[i].y | v[i].z | v[i].w) odd |= 1u << i;
    odd = __reduce_or_sync(~0u, odd);
    uint32_t n = odd >= 64 ? NEXC + 1 : __shfl_sync(~0u, lds32(st), 0);
#pragma unroll 1
    for (; odd && n <= NEXC; odd &= odd - 1) {
        const int i = __ffs(odd) - 1;
#pragma unroll
        for (int k = 1; k < 6; k++) if (i == k) v0 = v[k];
#pragma unroll 1
        for (int k = 0; k < 4; k++, v0.x = v0.y, v0.y = v0.z, v0.z = v0.w) {
            const uint32_t who = __ballot_sync(~0u, v0.x), at = n + __popc(who & lt);
            sts64(v0.x && at < NEXC ? sb + SM_EXC + warp * 128 + at * 8 : st + 8, v0.x, (e * 32 + g * 4) << 16 | (((k & 1) * 4 + t) * 48 + i * 8 + (k >> 1) * 4));
            n += __popc(who);
        }
    }
    const uint32_t bad = lds32(st + 4);
    __syncwarp();
    if (n <= NEXC) sts32(st, n);
    else {
        sts32(st + 4, bad | 1u << e);
        asm volatile("st.shared.u8 [%0], %1;" :: "r"(sb + SM_SC + warp * 128 + g * 16 + (e & 3) * 4 + (e >> 2)), "r"(0) : "memory");
    }
    __syncwarp();
}
template <int K> __device__ __forceinline__ uint32_t& word(uint4& v) { if constexpr (K == 0) return v.x; else if constexpr (K == 1) return v.y; else if constexpr (K == 2) return v.z; else return v.w; }
__device__ __forceinline__ void add_if(bool p, float& d, float a, float b) {
    asm volatile("{\n.reg .pred p;\nsetp.ne.u32 p, %3, 0;\n@p add.f32 %0, %1, %2;\n}" : "+f"(d) : "f"(a), "f"(b), "r"((uint32_t)p));
}
__device__ __forceinline__ float warp_max(float v) {
#pragma unroll
    for (int o = 16; o; o >>= 1) v = fmaxf(v, shx(v, o));
    return v;
}
__device__ __forceinline__ float warp_sum(float v) {
#pragma unroll
    for (int o = 16; o; o >>= 1) v += shx(v, o);
    return v;
}
template <int PITCH> __device__ __forceinline__ void ll_look(const u64* buf, u64 (&w)[4]) {
#pragma unroll
    for (int i = 0; i < 4; i++) w[i] = ld_rlx(buf + i * PITCH);
}
template <int PITCH> __device__ __forceinline__ float ll_gather(const u64* buf, uint32_t tag, u64 (&w)[4]) {
    auto miss = [&]() {
        uint32_t a, b;
        asm("lop3.b32 %0, %1, %2, %3, 0x7e;" : "=r"(a) : "r"(ll_tag(w[0])), "r"(ll_tag(w[1])), "r"(tag));
        asm("lop3.b32 %0, %1, %2, %3, 0x7e;" : "=r"(b) : "r"(ll_tag(w[2])), "r"(ll_tag(w[3])), "r"(tag));
        return __any_sync(~0u, a | b);
    };
    int it = 0;
    goto check;
again:
    ll_look<PITCH>(buf, w);
check:
    if (miss() & (++it < SPIN)) goto again;
    return (ll_val(w[0]) + ll_val(w[1])) + (ll_val(w[2]) + ll_val(w[3]));
}
__device__ __forceinline__ float sum8(uint32_t a, int pitch) {
    float s[8];
#pragma unroll
    for (int w = 0; w < 8; w++) s[w] = ldsf(a + w * pitch);
    return ((s[0] + s[1]) + (s[2] + s[3])) + ((s[4] + s[5]) + (s[6] + s[7]));
}
__device__ __forceinline__ float sum5(float a, float b, float c, float d, float e) { return ((a + b) + (c + d)) + e; }
__device__ __forceinline__ float ln_part(uint2 xp, int lane) {
    const float x0 = bf_lo(xp.x), x1 = bf_hi(xp.x), x2 = bf_lo(xp.y), x3 = bf_hi(xp.y);
    const float s1 = (x0 + x1) + (x2 + x3), s2 = (x0 * x0 + x1 * x1) + (x2 * x2 + x3 * x3);
    return ((lane & 16) ? s2 : s1) + shx((lane & 16) ? s1 : s2, 16);
}
__device__ __forceinline__ float ln_rstd(float mean, float msq) { return rsq(fmaxf(msq - mean * mean, 0.f) + 1e-5f); }
__device__ __forceinline__ float score(const uint4 (&v)[6], const uint4 (&qf)[3]) {
    float d[2][4];
#pragma unroll
    for (int j = 0; j < 2; j++) d[j][0] = d[j][1] = d[j][2] = d[j][3] = 0.f;
#pragma unroll
    for (int i = 0; i < 3; i++) { mma(d[0], v[2 * i], qf[i].x, qf[i].y); mma(d[1], v[2 * i + 1], qf[i].z, qf[i].w); }
    return (d[0][0] + d[0][3]) + (d[1][0] + d[1][3]);
}
__device__ __forceinline__ float k_side(uint32_t sb, uint2 x) {
    const uint32_t qq = lds32(sb + SM_VEC + (x.y & 0xffff));
    return (bf_lo(x.x) * bf_lo(qq) + bf_hi(x.x) * bf_hi(qq)) * 0x1p-64f;
}
__device__ __forceinline__ void k_fix(const __nv_bfloat16* k, uint32_t bad, int warp, int lane) {
    const uint32_t sb = smem_base(), g = lane >> 2, sa = sb + SM_PART + warp * 768 + 256;
    const uint2 x = lds64(sb + SM_EXC + warp * 128 + (lane & 15) * 8);
    if ((int)x.y >= 0x40000000 && lane < 16) asm volatile("red.shared.add.f32 [%0], %1;" :: "r"(sa + ((x.y >> 16) & 511)), "f"(k_side(sb, x)) : "memory");
    __syncwarp();
#pragma unroll 1
    for (bad &= 0xffff; bad; bad &= bad - 1) {
        const int e = __ffs(bad) - 1;
        const __nv_bfloat16* kp = k + (e * 256 + (g >> 1) + 4 * (g & 1)) * DH + (lane & 3) * 8;
        uint4 v[6], qf[3];
#pragma unroll
        for (int i = 0; i < 6; i++) v[i] = *reinterpret_cast<const uint4*>(kp + i * 32);
#pragma unroll
        for (int i = 0; i < 3; i++) qf[i] = lds128(sb + SM_VEC + (lane & 7) * 48 + i * 16);
        stsf(sa + e * 32 + g * 4, score(v, qf) * 0x1p-64f);
    }
    __syncwarp();
}
constexpr float CS = 0.07216878364870322f * 1.4426950408889634f;
__device__ __forceinline__ void head_weight(const u64* a, u64 pm, u64 pl, int layer, int lane) {
    const uint32_t sb = smem_base(), tag = lds32(sb + SM_EPOCH) * 4 + 2 + 2 * layer;
#pragma unroll 1
    for (int it = 0; it < SPIN; it++) {
        if (__all_sync(~0u, ll_tag(pm) == tag && ll_tag(pl) == tag)) break;
        ld_rlx2(a, pm, pl);
    }
    const float f = ex2((ll_val(pm) - warp_max(ll_val(pm))) * CS);
    const float w = f * rcp(warp_sum(f * ll_val(pl)));
    if (lane < 8) stsf(sb + SM_FAC + lane * 4, w);
}
constexpr uint32_t ONES = 0x3f803f80u;

__global__ void __launch_bounds__(NTHR, 1) fused_kernel(const __grid_constant__ Params P) {
    const uint32_t sb = smem_base();
    const int bx = blockIdx.x;
    const int cta0 = bx >= NCTA || CMAP == 0 ? bx : CMAP == 4 ? (((bx >> 1) & 7) + (bx >> 5) * 8) * 4 + ((bx >> 4) & 1) * 2 + (bx & 1)
                   : (((bx >> 1) & 15) + (bx >> 6) * 16) * 4 + ((bx >> 5) & 1) * 2 + (bx & 1);
    if (__all_sync(~0u, threadIdx.x >= NTHR - 32 && bx < NCTA) && elect()) {
        asm volatile("mbarrier.init.shared::cta.b64 [%0], 1;" :: "r"(sb + SM_CBAR + CB_WQ * 8));
        asm volatile("mbarrier.init.shared::cta.b64 [%0], 1;" :: "r"(sb + SM_CBAR + 80));
        asm volatile("fence.mbarrier_init.release.cluster;" ::: "memory");
        mbar_expect(sb + SM_CBAR + CB_WQ * 8, 5 * HALF);
        auto k0 = [&]() {
            mbar_expect(sb + SM_CBAR + 80, HALF);
            tma3(sb, &P.tm[TM_KH], 0, (cta0 >> 2) * SK + (SK - WIN) + (cta0 & 3) * 64, sb + SM_CBAR + 80, POL_FIRST);
        };
        if (K0FIRST) k0();
#pragma unroll 1
        for (int i = 0; i < 5; i++) tma3(sb + SM_WQR + (i == 4 ? 0 : i + 1) * HALF, &P.tm[TM_WQ], (cta0 >> 2) * 3, (cta0 & 3) * 160 + i * 32, sb + SM_CBAR + CB_WQ * 8, POL_FIRST);
        if (!K0FIRST) k0();
    }
    __syncwarp();
    int id = cta0 * NTHR + threadIdx.x, tid, lane, g, t, key, warp, cta, mlp, rowc, roww, j40;
    uint32_t maskA, maskB, barw, subw, prow;
    auto fresh = [&]() {
        const int cw = __shfl_sync(~0u, id >> 5, 0);
        id = pin(id); tid = id & 255; lane = id & 31; g = lane >> 2; t = lane & 3; key = (g >> 1) + 4 * (g & 1);
        const uint32_t m = (g & 1) ? 0xffff0000u : 0x0000ffffu;
        maskA = (g & 2) ? 0u : m; maskB = (g & 2) ? m : 0u;
        warp = cw & 7; cta = cw >> 3;
        mlp = (cta & 3) == 3 ? 96 : (cta >> 2) * 3 + (cta & 3);
        rowc = (cta >> 2) * SK + (SK - WIN) + (cta & 3) * 64; roww = rowc + warp * 8;
        j40 = (cta & 3) * 40;
        barw = sb + SM_BAR + warp * 96; subw = sb + warp * SUB; prow = sb + SM_PART + warp * 768;
    };
    fresh();
    auto fresh_lane = [&]() { id = pin(id); tid = id & 255; lane = id & 31; g = lane >> 2; t = lane & 3; };
    auto pinf = [&](float v) { return __uint_as_float(pin(__float_as_uint(v) | (id >> 16))); };

    if (cta == NCTA) {
        const uint32_t ep = *(volatile unsigned*)&P.g->epoch;
        if (tid == 0) {
#pragma unroll 1
            for (int it = 0; it < SPIN; it++) { if (ll_tag(ld_rlx(&P.g->ll[0][0][192])) == ep * 4 + 2) break; __nanosleep(200); }
        }
        __syncthreads();
#pragma unroll 1
        for (int i = tid; i < 4 * 80 * 8; i += NTHR)
            *reinterpret_cast<uint4*>(P.g->acc + (i >> 3) * ACC_PITCH + (i & 7) * 16) = make_uint4(0, 0, 0, 0);
        __threadfence();
        __syncthreads();
        if (tid == 0) asm volatile("st.relaxed.gpu.global.u32 [%0], %1;" :: "l"(&P.g->zflag), "r"(ep + 1) : "memory");
        return;
    }
    TSTAMP(0);
    if (tid == 64) { uint32_t now; asm volatile("mov.u32 %0, %globaltimer_lo;" : "=r"(now)); sts32(sb + SM_T0, now); }

    const CUtensorMap* tmk = reinterpret_cast<const CUtensorMap*>(__shfl_sync(~0u, (u64)&P.tm[0] + (lane >> 5), 0));
    auto c4 = [&]() { return 32 * min(warp, 4) + 16 * (t >> 1) + 2 * g + (t & 1); };
    auto xcol = [&](int i, int tt) { return (i < 2 ? 64 * i + 8 * warp : 128 + 8 * (warp >> 1)) + 2 * tt; };
    uint2 xp;
    uint32_t px[3], small;
    auto issue_first = [&](int j) {
        mbar_expect(sb + SM_CBAR + 80 + j * 8, HALF);
        tma3(sb + j * HALF, tmk + TM_KH, 0, rowc + (j >> 1) * 256 + (j & 1) * 32, sb + SM_CBAR + 80 + j * 8, POL_FIRST);
    };
    if (elect()) {
        if (warp != 2) asm volatile("mbarrier.init.shared::cta.b64 [%0], 1;" :: "r"(sb + SM_CBAR + 64 + warp * 8));
#pragma unroll
        for (int i = 0; i < 9; i++) asm volatile("mbarrier.init.shared::cta.b64 [%0], 1;" :: "r"(barw + i * 8));
        asm volatile("mbarrier.init.shared::cta.b64 [%0], 1;" :: "r"(sb + SM_CBAR + warp * 8));
        asm volatile("mbarrier.init.shared::cta.b64 [%0], 1;" :: "r"(sb + SM_CBAR + 128 + warp * 8));
        if (warp < 3) asm volatile("mbarrier.init.shared::cta.b64 [%0], %1;" :: "r"(sb + SM_CBAR + 192 + warp * 8), "r"(warp == 2 ? 8 : 1));
        sts64(barw + 80, 0, 0);
        asm volatile("fence.mbarrier_init.release.cluster;" ::: "memory");
        asm volatile("prefetch.tensormap [%0];" :: "l"(tmk + warp) : "memory");
    }
    __syncwarp();
    asm volatile("ld.global.nc.v2.u32 {%0,%1}, [%2];" : "=r"(xp.x), "=r"(xp.y) : "l"(P.x + 4 * c4()) : "memory");
#pragma unroll
    for (int i = 0; i < 3; i++) asm volatile("ld.global.nc.u32 %0, [%1];" : "=r"(px[i]) : "l"(P.x + 4 * j40 + xcol(i, t)) : "memory");
    asm volatile("ld.relaxed.gpu.global.u32 %0, [%1];" : "=r"(small) : "l"(lane < 16 ? (const void*)(P.b1 + min(mlp, 95) * 16 + (lane & 14)) : (const void*)&P.g->epoch) : "memory");
    if (tid >= 192 && tid < 192 + NCB) sts32(sb + SM_CNT + (tid - 192) * 8, 0);
    unsigned char* accg = reinterpret_cast<unsigned char*>(__shfl_sync(~0u, (u64)P.g->acc + (lane >> 5), 0));
    auto release = [&](const uint4& tw) {
        uint32_t old;
        __syncwarp();
        asm volatile("atom.relaxed.cta.shared.add.u32 %0, [%1], 1;" : "=r"(old) : "r"(sb + SM_CNT + (tw.x & 0xf8)) : "memory");
        return old;
    };
    auto refill = [&](const uint4& tw, uint32_t old) {
        if (__any_sync(~0u, (old & 127) == 127 && (tw.y & 2))) {
            wait_until(lds32(sb + SM_T0) + tw.z);
            if (elect()) issue_half(tw.y, sb, rowc, cta, tmk);
            __syncwarp();
        }
    };
    __syncthreads();
    auto issue_paced = [&](int j0, int j1) {
        if (warp >= j0 && warp < j1) {
            wait_until(lds32(sb + SM_T0) + PACES + warp * PACE / 2);
            if (elect()) issue_first(warp);
            __syncwarp();
        }
    };

    uint32_t offV0, offV2;
    auto calc_offsets = [&]() {
        offV0 = subw + (6 * t) * 128 + ((g ^ ((6 * t) & 7)) << 4);
        offV2 = subw + (6 * t + 2) * 128 + ((g ^ ((6 * t + 2) & 7)) << 4);
    };
    calc_offsets();

    auto load_v = [&](uint4 (&v)[6], uint32_t so) {
        v[0] = lds128(offV0 + so); v[1] = lds128((offV0 ^ 16) + so + 128); v[2] = lds128(offV2 + so);
        v[3] = lds128((offV2 ^ 16) + so + 128); v[4] = lds128((offV0 ^ 64) + so + 512); v[5] = lds128((offV0 ^ 80) + so + 640);
    };
    auto issue_v = [&](auto I, int dw) {
        constexpr Step c = SCH.st[I.value];
        const uint32_t bar = barw + dw * 96 + c.slot * 8;
        mbar_expect(bar, SUB);
        tma_v(subw + dw * SUB + c.slot * TILE, tmk, roww * 3 + dw * 24 + c.unit * 768, bar);
    };
    auto refill2 = [&](auto I) { __syncwarp(); if (elect()) issue_v(I, 0); };
    uint4 wq0[6], wqh[3], wq1[6];
    auto load_wq1 = [&](int i) { wq1[i] = lds128((i == 2 ? offV2 : i == 3 ? (offV2 ^ 16) + 128 : (offV0 ^ (i * 16)) + i * 128) + SM_WQ + TILE); };
    auto load_wq = [&]() {
        load_v(wq0, SM_WQ);
        const uint32_t so = SM_WQR - ((warp + 1) >> 1) * SUB;
        wqh[0] = lds128(((warp & 1) ? (offV2 ^ 16) + 128 : offV0) + so);
        wqh[1] = lds128(((warp & 1) ? (offV0 ^ 64) + 512 : (offV0 ^ 16) + 128) + so);
        wqh[2] = lds128(((warp & 1) ? (offV0 ^ 80) + 640 : offV2) + so);
#pragma unroll
        for (int i = 0; i < NWQ1; i++) load_wq1(i);
    };
    uint4 kr[8][6];
    const unsigned char* rap;
    u64 rw[2];
    auto look_rw = [&]() { rw[0] = ld_rlx(rap); rw[1] = ld_rlx(rap + 40 * ACC_PITCH); };
    auto q_proj = [&](auto L, uint32_t (&p)[3], uint32_t pst) {
        if (L.value == 0 && g >= 4) p[0] = p[1] = p[2] = ONES;
        float a[3][4], b[3][4];
        const uint32_t dH = __byte_perm(p[2], 0, (warp & 1) ? 0x3232 : 0x1010);
        const uint32_t dA = __byte_perm(p[0], 0, 0x1010), dB = __byte_perm(p[0], 0, 0x3232), dC = __byte_perm(p[1], 0, 0x1010), dD = __byte_perm(p[1], 0, 0x3232);
#pragma unroll
        for (int i = NWQ1; i < 3; i++) load_wq1(i);
#pragma unroll
        for (int j = 0; j < 3; j++) { a[j][0] = a[j][1] = a[j][2] = a[j][3] = 0.f; mma(a[j], wq0[j], dA & maskA, dA & maskB); }
#pragma unroll
        for (int j = 0; j < 3; j++) { b[j][0] = b[j][1] = b[j][2] = b[j][3] = 0.f; mma(b[j], wq0[j + 3], dB & maskA, dB & maskB); }
#pragma unroll
        for (int j = 0; j < 3; j++) mma(a[j], wqh[j], dH & maskA, dH & maskB);
#pragma unroll
        for (int i = 3; i < 6; i++) load_wq1(i);
        if (L.value == 1 && P4AT == 2) refill2(IC<4>{});
#pragma unroll
        for (int j = 0; j < 3; j++) mma(b[j], wq1[j], dC & maskA, dC & maskB);
#pragma unroll
        for (int j = 0; j < 3; j++) mma(a[j], wq1[j + 3], dD & maskA, dD & maskB);
#pragma unroll
        for (int j = 0; j < 3; j++) {
            if (L.value) {
#pragma unroll
                for (int k = 0; k < 2; k++) { a[j][k] += b[j][k]; add_if(t & 2, a[j][k], a[j][k + 2], b[j][k + 2]); }
                sts64f(pst + j * 256, a[j][0], a[j][1]);
            } else sts128f(pst + j * 256, a[j][0] + b[j][0], a[j][1] + b[j][1], a[j][2] + b[j][2], a[j][3] + b[j][3]);
        }
        CSTAMP(23, __float_as_uint(a[2][1]));
        uint32_t tag;
        if (L.value) tag = lds32(sb + SM_EPOCH) * 4 + 3;
        u64* pub = L.value ? &P.g->ll[0][cta][tid] : &P.g->l0[cta][tid];
        if (L.value == 0) asm volatile("fence.proxy.async.shared::cta;" ::: "memory");
        TSTAMPL(21);
        __syncthreads();
        if (!L.value) tag = lds32(sb + SM_EPOCH) * 4 + 1;
#pragma unroll 1
        for (int k = 0; k < 2 - L.value; k++) st_rlx_if(tid < 192, pub + k * 192, ll_pack(sum8(sb + (k ? SM_CSP : SM_PART) + tid * 4, 768), tag));
        TSTAMPL(23);
            CSTAMP(24, tag);
    };
    auto ln_stats = [&]() {
        float ss = ln_part(xp, lane);
        ss += shx(ss, 8); ss += shx(ss, 4); ss += shx(ss, 2); ss += shx(ss, 1);
        stsf(sb + SM_STAT + min(warp, 5) * 8 + (lane >> 4) * 4, ss);
    };
    auto ln_final = [&](float& mean, float& rstd) {
        float2 v[5];
#pragma unroll
        for (int w = 0; w < 5; w++) v[w] = lds64f(sb + SM_STAT + w * 8);
        mean = sum5(v[0].x, v[1].x, v[2].x, v[3].x, v[4].x) * (1.f / D_MODEL);
        const float msq = sum5(v[0].y, v[1].y, v[2].y, v[3].y, v[4].y) * (1.f / D_MODEL);
        rstd = ln_rstd(mean, msq);
        stsf(sb + SM_FXS, msq);
    };
    auto q_addr = [&](int d) { return sb + SM_VEC + (((d >> 1) & 1) * 4 + ((d >> 3) & 3)) * 48 + (d >> 5) * 8 + ((d >> 2) & 1) * 4 + (d & 1) * 2; };
    {
#pragma unroll
        for (int u = 0; u < 8; u++)
#pragma unroll
            for (int i = 0; i < 6; i++) kr[u][i] = lds128(sb + SM_CS + (u * 6 + i) * 16);
        issue_paced(1, NIM);
        ln_stats();
        if (tid == 16) { sts32(sb + SM_EPOCH, small); sts32(sb + SM_M1, ~0u); }
        else if (tid < 16) sts32(sb + SM_B1 + tid * 4, (tid & 1) ? small & 0xffff0000u : small << 16);
        mbar_wait(sb + SM_CBAR + CB_WQ * 8, 0);
        load_wq();
        q_proj(IC<0>{}, px, sb + (t < 2 ? SM_PART : SM_CSP) + warp * 768 + (8 * g + 4 * (t & 1)) * 4);
    }
    {
        uint32_t offQ, offL;
        auto calc_ql = [&]() {
            offQ = pin(sb + SM_VEC + (lane & 7) * 48);
            offL = pin(subw + lane * 16);
        };

        auto issue_w = [&](auto L, int which) {
            const uint32_t bar = sb + SM_CBAR + (CB_W1 + which) * 8;
            if (mlp == 96) asm volatile("mbarrier.arrive.shared::cta.b64 _, [%0];" :: "r"(bar) : "memory");
            else {
                mbar_expect(bar, 20480);
                if (which) {
                    tma3(sb + (L.value ? 3 * TILE : SM_W2), tmk + TM_W2, 0, mlp * 16, bar, POL_FIRST);
                    if (!L.value) tma3_pf(tmk + TM_W2, 0, mlp * 16, POL_NORMAL);
                    if (!L.value) asm volatile("cp.async.bulk.prefetch.L2.global.L2::cache_hint [%0], 20480, %1;" :: "l"(P.w1 + mlp * 10240), "l"((u64)POL_NORMAL << 32) : "memory");
                }
                else asm volatile("cp.async.bulk.tensor.3d.shared::cluster.global.mbarrier::complete_tx::bytes.L2::cache_hint [%0], [%1, {%2, %3, %3}], [%4], %5;"
                                  :: "r"(sb + (L.value ? 2 * TILE : SM_W1)), "l"(tmk + TM_W1), "r"(mlp * 16), "r"(0), "r"(bar), "l"((u64)POL_FIRST << 32) : "memory");
            }
        };
        float acc[3][4];
        auto load_q = [&](uint4 (&qf)[3]) {
#pragma unroll
            for (int i = 0; i < 3; i++) qf[i] = lds128(offQ + i * 16);
        };
        auto softmax = [&](float S0, float S1, float S2, float S3) {
            int mi = __float_as_int(fmaxf(fmaxf(S0, S1), fmaxf(S2, S3)));
            mi = __reduce_max_sync(~0u, mi ^ ((mi >> 31) & 0x7fffffff));
            const float mrun = __int_as_float(mi ^ ((mi >> 31) & 0x7fffffff));
            const float p0 = ex2((S0 - mrun) * CS), p1 = ex2((S1 - mrun) * CS), p2 = ex2((S2 - mrun) * CS), p3 = ex2((S3 - mrun) * CS);
            const uint32_t pa = pack_bf(p0, p1), pb = pack_bf(p2, p3), pw = prow + 256 + (key >> 1) * 80 + t * 4 + (key & 1) * 2;
            sts16(pw, pa); sts16(pw + 16, pa >> 16); sts16(pw + 32, pb); sts16(pw + 48, pb >> 16);
            __syncwarp();
#pragma unroll
            for (int j = 0; j < 3; j++) acc[j][0] = acc[j][1] = acc[j][2] = acc[j][3] = 0.f;
            return make_float2(mrun, (p0 + p1) + (p2 + p3));
        };
        auto pv = [&](const uint4 (&v)[6], uint32_t pp) {
            const uint32_t dA = __byte_perm(pp, 0, 0x1010), dB = __byte_perm(pp, 0, 0x3232);
            mma(acc[0], v[0], dA & maskA, dA & maskB); mma(acc[1], v[1], dA & maskA, dA & maskB); mma(acc[2], v[2], dA & maskA, dA & maskB);
            mma(acc[0], v[3], dB & maskA, dB & maskB); mma(acc[1], v[4], dB & maskA, dB & maskB); mma(acc[2], v[5], dB & maskA, dB & maskB);
        };
        auto sa = [&]() { return prow + 256 + t * 32 + g * 4; };
        auto pass1 = [&]() {
            if (NIM < NI1) issue_paced(NIM, NI1);
            fresh();
            calc_ql();
            __syncthreads();
            sts64(prow + lane * 8, xp.x, xp.y);
            int e = 0;
            const uint4* tab = P.tile + (warp >> 2);
            uint4 tw = tab[0];
            uint32_t ka[3];
#pragma unroll
            for (int j = 0; j < 3; j++) ka[j] = pin(subw + key * 384 + j * 128 + ((t ^ ((3 * key + j) & 7)) << 4));
            auto load_k = [&](uint4 (&v)[6], uint32_t so) {
#pragma unroll
                for (int i = 0; i < 6; i++) v[i] = lds128(((i & 1) ? ka[i >> 1] ^ 64 : ka[i >> 1]) + so);
            };
            const uint32_t s0 = pin(prow + 256 + g * 4), sca = pin(sb + SM_SC + warp * 128 + g * 16);
#pragma unroll 1
            do {
                const uint4 tn = tab[2 * e + 2];
                uint4 v[6], qf[3];
                if (tw.x & (G_A | G_B | G_C)) {
                    if ((tw.x & G_A) && warp == 7 && elect()) {
                        mbar_expect(sb + SM_CBAR + CB_SNAP * 8, HALF);
                        asm volatile("cp.async.bulk.shared::cluster.global.mbarrier::complete_tx::bytes [%0], [%1], 12288, [%2];"
                                     :: "r"(sb + SM_SNAP), "l"(&P.g->l0[cta & ~3][0]), "r"(sb + SM_CBAR + CB_SNAP * 8) : "memory");
                    }
                    if (tw.x & G_B) {
                        if (warp < 6) {
                            mbar_wait(sb + SM_CBAR + CB_SNAP * 8, 0);
                            float qc[2] = {0.f, 0.f}, mean, rstd;
#pragma unroll 1
                            for (int k = 0; k < 2; k++) {
                                u64 qw[4];
#pragma unroll
                                for (int i = 0; i < 4; i++) { const uint2 x = lds64(sb + SM_SNAP + i * 3072 + k * 1536 + tid * 8); qw[i] = x.x | (u64)x.y << 32; }
                                qc[0] = qc[1];
                                qc[1] = ll_gather<384>(&P.g->l0[cta & ~3][k * 192 + tid], lds32(sb + SM_EPOCH) * 4 + 1, qw);
                            }
                            ln_final(mean, rstd);
                            stsf(sb + SM_CS + tid * 4, qc[1]);
                            const float q = (qc[0] - mean * qc[1]) * rstd;
                            sts16(q_addr(tid), pack_bf(q, q));
                        }
                        __syncthreads();
                        if (warp == 7 && elect()) issue_half(UC<load_word(12)>::value, sb, rowc, cta, tmk);
                        TSTAMP(2);
                    }
                    if (tw.x & G_C) {
                        load_k(v, (e - LATEAT) * TILE);
                        load_q(qf);
                        stsf(s0 + (e - LATEAT) * 32, score(v, qf));
                    }
                }
                load_q(qf);
                mbar_wait(sb + SM_CBAR + (tw.x & 0xf8), tw.x >> 31);
                TRACE(e);
                load_k(v, tw.x & 0x3f000);
                const uint32_t old = release(tw);
                const float s = score(v, qf);
                uint32_t m;
                {
                    uint32_t a[6];
#pragma unroll
                    for (int i = 0; i < 6; i++) a[i] = bf2_amax(bf2_amax(v[i].x, v[i].y), bf2_amax(v[i].z, v[i].w));
                    m = bf2_amax(bf2_amax(bf2_amax(a[0], a[1]), bf2_amax(a[2], a[3])), bf2_amax(a[4], a[5]));
                }
                m = bf2_amax(m, m >> 16) & 0x7f80;
                m = max(m, __shfl_xor_sync(~0u, m, 1));
                stsf(s0 + e * 32, s);
                m = max(m, __shfl_xor_sync(~0u, m, 2));
                refill(tw, old);
                const uint32_t b = min(max(m, 15u << 7) - (15u << 7), 126u << 7);
                const uint32_t dn = ((127u << 7) - b) * 0x10001u, up = ((127u << 7 | 0x8000u) + b) * 0x10001u;
                uint32_t c[18], any = m > (141u << 7);
#pragma unroll
                for (int i = 0; i < 6; i++) {
                    const uint32_t y0 = bf2_mul(v[i].x, dn), y1 = bf2_mul(v[i].y, dn), y2 = bf2_mul(v[i].z, dn), y3 = bf2_mul(v[i].w, dn);
                    v[i] = make_uint4(bf2_fma(y0, up, v[i].x), bf2_fma(y1, up, v[i].y), bf2_fma(y2, up, v[i].z), bf2_fma(y3, up, v[i].w));
                    any |= v[i].x | v[i].y;
                    any |= v[i].z | v[i].w;
                    const uint32_t hb = __byte_perm(y2, y3, 0x7531);
                    c[3 * i] = __byte_perm(y0, y1, 0x6420); c[3 * i + 1] = __byte_perm(y2, y3, 0x6420);
                    c[3 * i + 2] = __byte_perm(y0, y1, 0x7531) | __funnelshift_r(hb, hb, 4);
                }
                asm volatile("st.shared.u8 [%0], %1;" :: "r"(sca + (e & 3) * 4 + (e >> 2)), "r"((b >> 7) + 63) : "memory");
                const bool rare = __any_sync(~0u, any);
                k_keep(kr, c, e, offL);
                if (rare) k_rare(v[0], v[1], v[2], v[3], v[4], v[5], m > (141u << 7), e, warp, lane);
                tw = tn;
            } while (++e < 16);
            asm volatile("fence.proxy.async.shared::cta;" ::: "memory");
            __syncwarp();
            TSTAMP(10);
            fresh(); calc_offsets();
            {
                const uint2 st = lds64(barw + 80);
                const uint32_t xa = sb + SM_EXC + warp * 128 + (lane & 15) * 8 + 4;
                uint32_t pos = lds32(xa), lt;
                asm volatile("mov.u32 %0, %lanemask_lt;" : "=r"(lt));
                if (lane >= st.x) pos = 0x80000000u;
                const bool dup = (__match_any_sync(~0u, pos >> 16) & lt) && lane < st.x;
                if (lane < 16) sts32(xa, dup ? pos | 0x40000000u : pos);
                if (__any_sync(~0u, dup)) sts32(barw + 84, st.y | 0x10000u);
                const float2 ml = softmax(ldsf(sa()), ldsf(sa() + 128), ldsf(sa() + 256), ldsf(sa() + 384));
                sts64f(sb + SM_ML + warp * 8, ml.x, warp_sum(ml.y));
            }
            u64 pm = 0, pl = 0;
#pragma unroll 1
            do {
                const uint4 tn = tab[2 * e + 2];
                if (tw.x & (G_A | G_B | G_C)) {
                    if (tw.x & G_A) {
                        if (lane < 24) st_rlx(&P.g->ll[0][cta][warp * 24 + lane], 0ull);
                        else if (lane < 28) st_rlx(&P.g->ll[0][cta][168 + warp * 4 + lane], ll_pack(ldsf(sb + SM_ML + warp * 8 + (lane & 1) * 4), lds32(sb + SM_EPOCH) * 4 + 2));
                    }
                    if (warp == 2) {
                        if (tw.x & G_B) ld_rlx2(&P.g->ll[0][cta ^ (lane >> 3)][192 + (lane & 7) * 4], pm, pl);
                        if (tw.x & G_C) head_weight(&P.g->ll[0][cta ^ (lane >> 3)][192 + (lane & 7) * 4], pm, pl, 0, lane);
                    }
                    __syncwarp();
                }
                const uint32_t pp = lds32(prow + 256 + t * 80 + ((tw.x >> 20) & 255));
                mbar_wait(sb + SM_CBAR + (tw.x & 0xf8), tw.x >> 31);
                TRACE(e);
                uint4 v[6];
                load_v(v, tw.x & 0x3f000);
                refill(tw, release(tw));
                pv(v, pp);
                tw = tn;
            } while (++e < 32);
        };
        uint32_t osa, ora, owa, orow, otag;
        u64* olb;
        float xc;
        auto o_setup = [&](auto L) {
            fresh();
            const int lz = lane, d = warp * 24 + min(lz, 23);
            osa = pin(prow + ((lz >> 2) * 8 + (lz & 1) * 4 + (lz & 2)) * 4);
            ora = pin(sb + SM_PART + d * 4);
            olb = pin(&P.g->ll[L.value][cta & ~3][d]);
            orow = pin((lz & 1) + 2 * (lz & 2) + 2 * (lz >> 4));
            owa = pin(sb + SM_RING + warp * 1536 + orow * 64 + ((((lz >> 2) & 3) ^ (orow >> 1)) << 4));
            otag = lds32(sb + SM_EPOCH) * 4 + 2 + 2 * L.value;
            uint32_t x; asm volatile("ld.shared.u16 %0, [%1];" : "=r"(x) : "r"(prow + ((cta & 1) * 16 + (lz >> 3) * 4 + (cta & 2) + ((lz >> 2) & 1)) * 8 + (lz & 3) * 2) : "memory");
            xc = bf_lo(x) * (1.f / 32);
        };
        auto wo_at = [&](auto A) {
            constexpr uint32_t x = WOP ^ A.value * 0x11111;
            if constexpr (A.value > 0 && ((x - 0x11111) & ~x & 0x88888) != 0) {
                if ((WOP >> (4 * warp) & 15) == A.value) {
                    mbar_wait(sb + SM_CBAR + CB_REL * 8, 0);
                    if (elect()) {
                        const uint32_t bar = sb + SM_CBAR + (CB_WO + warp) * 8;
                        mbar_expect(bar, HALF);
                        tma3(sb + SM_RING + (warp + (warp < 2 ? 3 : -2)) * HALF, tmk + TM_WO, (cta & 3) + 4 * warp, (cta >> 2) * DH, bar, POL_FIRST);
                    }
                    __syncwarp();
                }
            }
        };
        static_assert(ring_hs(64) == 3, "wo");
        auto pass2 = [&]() {
            constexpr IC<1> L{};
            if (P4AT == 0) refill2(IC<4>{});
            if (P2LATE == 1 && warp >= 4) refill2(IC<2>{});
            uint4 tb[8][3];
            auto load_tb = [&](auto I) {
#pragma unroll
                for (int i = 0; i < 3; i++) tb[I.value][i] = lds128(offL + (I.value >> 1) * TILE + ((I.value & 1) * 3 + i) * 512);
            };
            const u64* qb = &P.g->ll[0][cta & ~3][min(tid, 191)];
            {
                uint32_t x[2];
                fx2_wait<2>([&](int i) { return rap + i * 40 * ACC_PITCH; }, look_rw, rw, sb + SM_MSQ, ldsf(sb + SM_MSQ + 4), x);
                xp = make_uint2(x[0], x[1]);
                CSTAMP(25, xp.y);
            }
            ln_stats();
            u64 qw[4];
            ll_look<256>(qb, qw);
            const float cs = ldsf(sb + SM_CS + min(tid, 191) * 4);
            const uint32_t qtag = lds32(sb + SM_EPOCH) * 4 + 3, qa = pin(q_addr(min(tid, 191)));
            fresh_lane();
            offQ = sb + SM_VEC + (lane & 7) * 48; offL = subw + lane * 16;
            __syncthreads();
            auto vwait = [&](auto I) { mbar_wait(barw + IC<SCH.st[I.value].slot>::value * 8, IC<SCH.st[I.value].par>::value); };
            bool ok;
            uint32_t m1, m1n;
            {
                float mean, rstd;
                ln_final(mean, rstd);
                const float sq = shx(rstd * 0x1p64f, 0), q0 = shx(-mean * cs * sq, 0);
                CSTAMP(26, __float_as_uint(q0));
                static_for<0, NPRE>(load_tb);
                if (P4AT == 1) refill2(IC<4>{});
                if (S0EARLY) refill2(IC<5>{});
                m1n = m1 = lds32(sb + SM_M1);
                sts64(prow + lane * 8, xp.x, xp.y);
                sts128f(prow + 256 + lane * 16, 0.f, 0.f, 0.f, 0.f);
                const float q = ll_gather<256>(qb, qtag, qw) * sq + q0;
                sts16(qa, pack_bf(q, q));
                TSTAMPL(24);
                CSTAMP(27, __float_as_uint(q));
            }
            if (!S0EARLY) refill2(IC<5>{});
            if (P2LATE == 2 && warp >= 4) refill2(IC<2>{});
            if (P4AT == 3) refill2(IC<4>{});
            if (NOWIN & 1) { if (warp < 6) refill2(IC<0>{}); if (warp >= 5) refill2(IC<3>{}); }
            if (NOWIN & 2) { if (warp >= 6) refill2(IC<1>{}); if (warp < 4) refill2(IC<2>{}); }
            if (NOWIN & 4) { if (warp >= 6) refill2(IC<0>{}); if (warp < 6) refill2(IC<1>{}); }
            if (NOWIN & 8) { if (warp < 5) refill2(IC<3>{}); if (warp >= 4) refill2(IC<2>{}); }
            __syncthreads();
            uint4 qf[3];
            load_q(qf);
            CSTAMP(28, qf[0].x);
            float S[4], d[2][4];
            auto vload = [&](auto I) {
                constexpr int p = I.value;
                constexpr Step c = SCH.st[p];
                load_v(kr[p & 7], c.slot * TILE);
                if constexpr (c.next >= 0) refill2(IC<c.next>{});
                if constexpr (p == 11) { __syncwarp(); if (elect()) asm volatile("mbarrier.arrive.shared::cta.b64 _, [%0];" :: "r"(sb + SM_CBAR + CB_REL * 8) : "memory"); }
            };
            static_for<0, 96>([&](auto F) {
                constexpr int f = F.value, i = f % 6, u = kunit(f / 6), w = 3 * f % 12;
                uint4 (&src)[3] = *reinterpret_cast<uint4 (*)[3]>(f < 32 ? &tb[f / 4 & 7][0] : &kr[(f / 8 + 4) & 7][(f / 4 & 1) * 3]);
                const uint4 a = k_unpack(word<w % 4>(src[w / 4]), word<(w + 1) % 4>(src[(w + 1) / 4]), word<(w + 2) % 4>(src[(w + 2) / 4]), m1);
                if constexpr (f < 32 ? f % 4 == M1AT : f % 8 == M1P) m1 = m1n;
                if constexpr (f % 4 == 3 && f / 4 + NPRE < 8) {
                    load_tb(IC<f / 4 + NPRE>{});
                    if constexpr ((f / 4 + NPRE) & 1) { refill2(IC<5 + (f / 4 + NPRE) / 2>{}); m1n = lds32(sb + SM_M1); }
                }
                if constexpr (i < 2) d[i][0] = d[i][1] = d[i][2] = d[i][3] = 0.f;
                mma(d[i & 1], a, (i & 1) ? qf[i / 2].z : qf[i / 2].x, (i & 1) ? qf[i / 2].w : qf[i / 2].y);
                if constexpr (i == 5) {
                    if constexpr (u == 11 || ((u & 3) == 0 && u != 8)) S[u >> 2] = (d[0][0] + d[0][3]) + (d[1][0] + d[1][3]);
                    else add_if(t == (u & 3), S[u >> 2], d[0][0] + d[0][3], d[1][0] + d[1][3]);
                    if constexpr (f < 64) S[u >> 2] = shx(S[u >> 2], 0);
                }
                if constexpr (f == 31) { fresh(); calc_offsets(); ok = mbar_test(barw + IC<SCH.st[0].slot>::value * 8, 0); }
                if constexpr (f == 48) {
                    const uint2 x = lds64(sb + SM_EXC + warp * 128 + (lane & 15) * 8);
                    const float c = k_side(sb, x);
                    if (x.y < 0x40000000u) stsf(prow + 256 + (x.y >> 16), c);
                }
                if constexpr (f >= 32 && f % 8 == 7) {
                    if constexpr (PARKS >> (f / 8 - 4) & 1) {
                        constexpr int p = popc(PARKS & ((1 << (f / 8 - 4)) - 1));
                        if (!ok) vwait(IC<p>{});
                        vload(IC<p>{});
                        m1n = lds32(sb + SM_M1);
                        ok = mbar_test(barw + IC<SCH.st[p + 1].slot>::value * 8, IC<SCH.st[p + 1].par>::value);
                    }
                }
            });
            uint32_t bad = lds32(barw + 84);
            const uint32_t sc = lds32(sb + SM_SC + tid * 4);
            __syncwarp();
            if (bad) k_fix(P.k + (size_t)roww * DH, bad, warp, lane);
            TSTAMP(30);
            CSTAMP(29, __float_as_uint(S[2]));
            const float2 ml = softmax(S[0] * __uint_as_float((sc & 255) << 23) + ldsf(sa()), S[1] * __uint_as_float((sc & 0xff00) << 15) + ldsf(sa() + 128),
                                      S[2] * __uint_as_float((sc & 0xff0000) << 7) + ldsf(sa() + 256), S[3] * __uint_as_float((sc >> 24) << 23) + ldsf(sa() + 384));
            uint4 pq[4];
#pragma unroll
            for (int j = 0; j < 4; j++) pq[j] = lds128(prow + 256 + t * 80 + j * 16);
            TSTAMP(1);
            CSTAMP(30, pq[3].w);
            if (!ok) vwait(IC<NPARK>{});
            float ac2[3][4];
#pragma unroll
            for (int j = 0; j < 3; j++) ac2[j][0] = ac2[j][1] = ac2[j][2] = ac2[j][3] = 0.f;
            const uint32_t sl = (g & 1) ? 0x1044 : 0x4410, sh = (g & 1) ? 0x3244 : 0x4432;
            const uint32_t sA0 = (g & 2) ? 0x4444 : sl, sA1 = (g & 2) ? sl : 0x4444, sB0 = (g & 2) ? 0x4444 : sh, sB1 = (g & 2) ? sh : 0x4444;
            u64 pm = 0, pl = 0;
            static_for<NPARK, 16>([&](auto I) {
                constexpr int p = I.value;
                static_assert(p - SCH.st[p].mma0 < 8, "buffer in use");
                vload(I);
                if constexpr (p < 15) ok = mbar_test(barw + IC<SCH.st[p + 1].slot>::value * 8, IC<SCH.st[p + 1].par>::value);
                static_for<SCH.st[p].mma0, SCH.st[p].mma0 + SCH.st[p].nmma>([&](auto J) {
                    constexpr int u = SCH.st[J.value].unit;
                    const uint32_t pp = word<u & 3>(pq[u >> 2]), a0 = __byte_perm(pp, 0, sA0), a1 = __byte_perm(pp, 0, sA1), b0 = __byte_perm(pp, 0, sB0), b1 = __byte_perm(pp, 0, sB1);
#pragma unroll
                    for (int j = 0; j < 3; j++) mma(acc[j], kr[J.value & 7][j], a0, a1);
#pragma unroll
                    for (int j = 0; j < 3; j++) mma(ac2[j], kr[J.value & 7][j + 3], b0, b1);
                });
                if constexpr (p == NPARK) {
                    const float l = warp_sum(ml.y);
                    if (lane < 28) st_rlx(&P.g->ll[1][cta][lane < 24 ? warp * 24 + lane : 168 + warp * 4 + lane], lane < 24 ? 0ull : ll_pack((lane & 1) ? l : ml.x, lds32(sb + SM_EPOCH) * 4 + 4));
                }
                if constexpr (p == HWAT) { if (warp == 6) ld_rlx2(&P.g->ll[1][cta ^ (lane >> 3)][192 + (lane & 7) * 4], pm, pl); }
                if constexpr (p == 13) o_setup(L);
                if constexpr (p == HWAT + 2) { if (warp == 6) head_weight(&P.g->ll[1][cta ^ (lane >> 3)][192 + (lane & 7) * 4], pm, pl, 1, lane); }
                wo_at(IC<p - 10>{});
                if constexpr (p < 15) { if (!ok) mbar_wait(barw + IC<SCH.st[p + 1].slot>::value * 8, IC<SCH.st[p + 1].par>::value); TRACE(33 + p); }
            });
#pragma unroll
            for (int j = 0; j < 3; j++)
#pragma unroll
                for (int k = 0; k < 2; k++) { acc[j][k] += ac2[j][k]; add_if(t & 2, acc[j][k], acc[j][k + 2], ac2[j][k + 2]); }
        };

        const unsigned char* ap;
        uint32_t hpa, hsa, hst, w2a, la;
        uint2 b2v;
        float b1v, cs1;
        auto mlp_global = [&](auto L) {
            const int cz = c4();
            ap = accg + 2 * L.value * ACC_BYTES + (cz >> 1) * ACC_PITCH + (cz & 1) * 16;
            if (L.value) ap = pin(ap);
            rap = pin(accg + (2 * L.value + 1) * ACC_BYTES + (cz >> 2) * ACC_PITCH + (cz & 3) * 8);
            asm volatile("ld.global.nc.v2.u32 {%0,%1}, [%2];" : "=r"(b2v.x), "=r"(b2v.y) : "l"(P.b2 + 4 * cz));
        };
        auto mlp_shared = [&](auto L) {
            const int lz = lane;
            hpa = pin(sb + SM_PART + warp * 256 + ((lz & 2) * 4 + (lz >> 2)) * 16 + (L.value ? 0 : (lz & 1) * 4));
            hsa = pin(sb + SM_PART + (lz & 15) * 16); hst = pin(sb + SM_PART + (lz & 15) * 16 + warp * 256 + 8 + (lz >> 4) * 4);
            w2a = pin(sb + (L.value ? 3 * TILE : SM_W2) + ((lz & 3) * 10 + 2 * warp) * 128 + (((lz >> 2) ^ ((2 * lz + 2 * warp) & 6)) << 4));
            la = sb + (L.value ? 2 * TILE : SM_W1) + warp * 4096 + (lz & 4) * 512 + (lz & 2) * 64 + (lz & 1) * 32 + (lz >> 4) * 64 + ((((lz >> 3) ^ (lz >> 1)) & 1) << 4);
            b1v = ldsf(sb + SM_B1 + (lz & 15) * 4);
            if (L.value) { la = pin(la); cs1 = ldsf(sb + SM_ML + (lz & 15) * 4); }
            else fresh();
        };
        uint32_t pa;
        unsigned char* rop;
        uint32_t wpa;
        float sc1;
        auto sum_setup = [&](auto L) {
            const int lz = lane, word = warp * 128 + (cta & 3) * 32 + lz;
            wpa = pin(sb + SM_RING + warp * 1536 + ((((lz >> 2) * 8 + (lz & 1) * 4) * 4) ^ ((((lz >> 1) ^ (lz >> 4)) & 1) ? 256 + 64 : 0)));
            sc1 = pinf(fx2_scale(ldsf(sb + SM_FXS)) * 0.25f);
            pa = pin(sb + SM_RING + warp * 256 + ((lz * 4) ^ ((warp & 1) * 64)));
            rop = pin(accg + 2 * L.value * ACC_BYTES + (word >> 3) * ACC_PITCH + (word & 7) * 4);
        };
        auto out_proj = [&](auto L) {
            TSTAMP2(3);
            CSTAMP(0, __float_as_uint(acc[2][1]));
            __syncwarp();
#pragma unroll
            for (int j = 0; j < 3; j++) {
                if (L.value == 0 && (t & 2)) { acc[j][0] = acc[j][2]; acc[j][1] = acc[j][3]; }
                sts64f(osa + 256 * j, acc[j][0], acc[j][1]);
            }
            __syncthreads();
            {
                float s[8];
#pragma unroll
                for (int w = 0; w < 8; w++) s[w] = ldsf(ora + w * 768);
                const uint4 fa = lds128(sb + SM_FAC), fb = lds128(sb + SM_FAC + 16);
            CSTAMP(1, __float_as_uint(s[0]));
                const float own = ((s[0] * __uint_as_float(fa.x) + s[1] * __uint_as_float(fa.y)) + (s[2] * __uint_as_float(fa.z) + s[3] * __uint_as_float(fa.w))) +
                                  ((s[4] * __uint_as_float(fb.x) + s[5] * __uint_as_float(fb.y)) + (s[6] * __uint_as_float(fb.z) + s[7] * __uint_as_float(fb.w)));
                st_rlx_if(lane < 24, olb + (cta & 3) * 256, ll_pack(own, otag));
            CSTAMP(2, __float_as_uint(own));
            }
            TSTAMPL(29);
            if (L.value) wo_at(IC<6>{});
            if (L.value == 0 && warp == 7) {
#pragma unroll 1
                for (int it = 0; it < SPIN; it++) {
                    uint32_t v; asm volatile("ld.acquire.gpu.global.u32 %0, [%1];" : "=r"(v) : "l"(&P.g->zflag) : "memory");
                    if (__all_sync(~0u, v == (otag >> 2) + 1)) break;
                }
            }
            constexpr int NW = L.value ? NWO1 : 3;
            uint4 v[5][3];
            u64 ow[4];
            auto read_wo = [&](auto J) {
#pragma unroll
                for (int p = 0; p < 3; p++) v[J.value][p] = lds128(((J.value & 1) ? owa ^ 144 : owa) + ring_hs(64 + J.value) * HALF + p * 512);
            };
            static_for<0, NW>([&](auto J) {
                if (L.value && J.value == 0) { sum_setup(L); maskA = pin(maskA); maskB = pin(maskB); }
                if ((L.value ? OPOLL1 : OPOLL) == J.value) { ll_look<256>(olb, ow); if (L.value) { mlp_shared(L); mlp_global(L); } }
                mbar_wait(sb + SM_CBAR + (CB_WO + J.value) * 8, L.value);
                read_wo(J);
                if (L.value == 0 && W1AT0 == J.value + 1) {
                    __syncwarp();
                    if (elect() && cnt_inc(sb + SM_CNT + CB_W1 * 8, 7) == 7) issue_w(L, 0);
                    __syncwarp();
                }
                if (L.value == 1 && (W1AT1 == J.value + 1 || W2AT1 == J.value + 1)) {
                    if (warp == 7 && elect()) { if (W1AT1 == J.value + 1) issue_w(L, 0); if (W2AT1 == J.value + 1) issue_w(L, 1); }
                    __syncwarp();
                }
            });
            sched_fence();
            const float o = ll_gather<256>(olb, otag, ow);
            CSTAMP(3, __float_as_uint(o));
            TSTAMP2(4);
            bool ok = true;
            if constexpr (NW < 5) ok = mbar_test(sb + SM_CBAR + (CB_WO + 4) * 8, L.value);
            if constexpr (NW < 4) ok &= mbar_test(sb + SM_CBAR + (CB_WO + 3) * 8, L.value);
            const uint32_t od = pack_bf(o, o);
            uint32_t oa[3], ob[3];
#pragma unroll
            for (int p = 0; p < 3; p++) { const uint32_t op = __shfl_sync(~0u, od, 8 * p + orow); oa[p] = op & maskA; ob[p] = op & maskB; }
            CSTAMP(4, oa[2]);
            float y[5][4];
#pragma unroll
            for (int j = 0; j < 5; j++) y[j][0] = y[j][1] = y[j][2] = y[j][3] = 0.f;
            auto rest = [&]() {
                if (!ok) static_for<NW, 5>([&](auto J) { mbar_wait(sb + SM_CBAR + (CB_WO + J.value) * 8, L.value); });
                static_for<NW, 5>(read_wo);
                __syncwarp();
            };
            if (L.value) rest();
#pragma unroll
            for (int p = 0; p < 3; p++)
#pragma unroll
                for (int j = 0; j < NW; j++) mma(y[j], v[j][p], oa[p], ob[p]);
            if (!L.value) { rest(); sum_setup(L); }
#pragma unroll
            for (int p = 0; p < 3; p++)
#pragma unroll
                for (int j = NW; j < 5; j++) mma(y[j], v[j][p], oa[p], ob[p]);
            CSTAMP(5, __float_as_uint(y[4][3]));
#pragma unroll
            for (int j = 0; j < 5; j += 2) {
                if (j < 4 && (t >> 1) != (g >> 2)) { y[j][0] = y[j + 1][0]; y[j][1] = y[j + 1][1]; y[j][2] = y[j + 1][2]; y[j][3] = y[j + 1][3]; }
                sts128f(wpa + j * 256, y[j]);
            }
            TSTAMP2(5);
        };
        u64 yw[2];
        bool wide;
        float msq = 0.f, yf[4] = {};
        auto mlp_part = [&](auto L) {
            bar_sync(0, 256);
            CSTAMP(6, __float_as_uint(sc1));
            const float s = (sum8(pa, 1536) + xc) + sum8(pa + 128, 1536), sm = s * sc1 + FX2_ONE;
            CSTAMP(7, __float_as_uint(s));
            const bool wide1 = !(fabsf(sm - FX2_ONE) < FX1LIM);
            asm volatile("red.relaxed.gpu.global.add.u32 [%0], %1;" :: "l"(rop), "r"(wide1 ? 0u : __float_as_uint(sm) * 128u + (1u - 0x4b400000u * 128u)) : "memory");
            const uint32_t c0 = clk();
            TSTAMP2(6);
            if (L.value == 0) bar_arrive(2, 256);
            if (wide1) {
                fx_send(rop + 64 + (lane & 7) * 4, s, ldsf(sb + SM_FXS), rop, 64);
                asm volatile("red.relaxed.gpu.global.add.u32 [%0], 1;" :: "l"(rop) : "memory");
            }
            __syncwarp();
            if (L.value == 1 && mlp == 96) { TDUMP(); asm volatile("exit;"); }
            uint4 wf[8], w2r[8];
            uint4 w;
            auto look = [&]() { asm volatile("ld.relaxed.gpu.global.v4.u32 {%0,%1,%2,%3}, [%4];" : "=r"(w.x), "=r"(w.y), "=r"(w.z), "=r"(w.w) : "l"(ap) : "memory"); };
            auto read_w1 = [&]() {
#pragma unroll
                for (int j = 0; j < 8; j++) wf[j] = ldsm_t(la + j * 256);
            };
            auto read_w2 = [&]() {
#pragma unroll
                for (int i = 0; i < 8; i++) w2r[i] = lds128(((i & 1) ? (w2a ^ 16) + 128 : w2a) + (i >> 1) * 5120);
            };
            const float inv = pinf(fx_inv(sc1) * (1.f / 128)), off = L.value ? pinf(fx_inv(sc1) * -0.25f) : inv * -32.f;
            if (L.value == 0) { fresh(); mlp_global(L); }
            mbar_wait(sb + SM_CBAR + CB_W1 * 8, L.value);
            if (L.value == 1) {
                if (W2PRE == 1) mbar_wait(sb + SM_CBAR + CB_W2 * 8, 1);
                read_w1();
                if (W2PRE == 1) read_w2();
            }
            while (clk() - c0 < AR1D);
            look();
            if (L.value == 0) { mlp_shared(L); read_w1(); bar_arrive(3, 256); }
            else if (W2PRE == 2) { mbar_wait(sb + SM_CBAR + CB_W2 * 8, 1); read_w2(); }
            TSTAMPL(28);
            {
                sched_fence();
                auto miss = [&]() {
                    xp = make_uint2(pack_bf((float)(int)w.x * inv + off, (float)(int)w.y * inv + off), pack_bf((float)(int)w.z * inv + off, (float)(int)w.w * inv + off));
                    uint32_t a, b;
                    asm("lop3.b32 %0, %1, %2, 32, 0x7e;" : "=r"(a) : "r"(w.x), "r"(w.y));
                    asm("lop3.b32 %0, %1, %2, 32, 0x7e;" : "=r"(b) : "r"(w.z), "r"(w.w));
                    return __any_sync(~0u, (a | b) & 96);
                };
                if (miss()) {
                    int it = 0;
#pragma unroll 1
                    do {
                        if (!__any_sync(~0u, ~(w.x & w.y & w.z & w.w) & 32)) { xp.x = fx1_wide(ap, ldsf(sb + SM_FXS)); xp.y = fx1_wide(ap + 8, ldsf(sb + SM_FXS)); break; }
                        look();
                    } while (miss() & (++it < SPIN));
                }
                CSTAMP(8, w.w);
            }
            TSTAMP2(7);
            CSTAMP(9, xp.y);
            {
                bool ok = true;
                if (L.value == 0 || !W2PRE) ok = mbar_test(sb + SM_CBAR + CB_W2 * 8, L.value);
                const bool ev = L.value || !(g & 1), od = L.value || (g & 1);
                const uint32_t e0 = ev ? xp.x : ONES, e1 = ev ? xp.y : ONES, o0 = od ? xp.x : ONES, o1 = od ? xp.y : ONES;
                float d[8][4];
#pragma unroll
                for (int j = 0; j < 8; j++) { d[j][0] = d[j][1] = d[j][2] = d[j][3] = 0.f; mma(d[j], wf[j], (j & 1) ? o0 : e0, (j & 1) ? o1 : e1); }
                float ss = ln_part(xp, lane);
                ss += shx(ss, 8); ss += shx(ss, 4);
                float r[4], dd;
#pragma unroll
                for (int k = 0; k < 4; k += 1 + L.value) r[k] = d[0][k] + d[1][k ^ 1];
#pragma unroll
                for (int j = 1; j < 4; j++)
#pragma unroll
                    for (int k = 0; k < 4; k += 1 + L.value) add_if(t == j, r[k], d[2 * j][k], d[2 * j + 1][k ^ 1]);
                CSTAMP(10, __float_as_uint(r[2]));
                if (L.value) {
                    dd = ((t & 2) ? r[2] : r[0]) + shx((t & 2) ? r[0] : r[2], 2);
                    ss += shx(ss, 2);
                    dd += shx(dd, 1);
                } else {
                    const float a = ((t & 1) ? r[1] : r[0]) + shx((t & 1) ? r[0] : r[1], 1), b = ((t & 1) ? r[3] : r[2]) + shx((t & 1) ? r[2] : r[3], 1);
                    ss += shx(ss, 2);
                    dd = ((t & 2) ? b : a) + shx((t & 2) ? a : b, 2);
                }
                ss += shx(ss, 1);
                stsf(hpa, dd);
                stsf(hst, ss);
                CSTAMP(11, __float_as_uint(dd + ss));
                if (!ok) mbar_wait(sb + SM_CBAR + CB_W2 * 8, L.value);
            }
            TSTAMPL(25);
            bar_sync(1, 160);
            uint4 hp[5];
#pragma unroll
            for (int w = 0; w < 5; w++) hp[w] = lds128(hsa + w * 256);
            CSTAMP(12, hp[0].x);
            auto hs = [&](auto K) { return sum5(__uint_as_float(word<K.value>(hp[0])), __uint_as_float(word<K.value>(hp[1])), __uint_as_float(word<K.value>(hp[2])),
                                                __uint_as_float(word<K.value>(hp[3])), __uint_as_float(word<K.value>(hp[4]))); };
            const float mean = hs(IC<2>{}) * (1.f / D_MODEL);
            msq = hs(IC<3>{}) * (1.f / D_MODEL);
            if (L.value == 0) cs1 = hs(IC<1>{});
            float hv = hs(IC<0>{}) - mean * cs1;
            CSTAMP(13, __float_as_uint(hv));
            const float sc2 = fx2_scale(msq), lim = fx_inv(sc2) * FX2LIM;
            if (L.value == 0 || !W2PRE) read_w2();
            if (L.value == 0) {
                bar_arrive(4, 256);
                wide = false;
                if (mlp == 96) return;
            }
            hv = hv * ln_rstd(mean, msq) + b1v;
            CSTAMP(14, __float_as_uint(hv));
            hv = hv * rcp(1.f + ex2(hv * (-2.302208198f - 0.1029432397f * hv * hv)));
            const uint32_t hd = pack_bf(hv, hv);
            CSTAMP(15, hd);
            TSTAMPL(27);
            float ym[4][4];
#pragma unroll
            for (int i = 0; i < 2; i++) {
                ym[i][0] = ym[i][1] = ym[i][2] = ym[i][3] = 0.f;
                const float f = mlp < 64 ? 1.f / 64 : 0.f;
                ym[i + 2][0] = (bf_lo(xp.x) + bf_lo(b2v.x)) * f; ym[i + 2][1] = (bf_hi(xp.x) + bf_hi(b2v.x)) * f;
                ym[i + 2][2] = (bf_lo(xp.y) + bf_lo(b2v.y)) * f; ym[i + 2][3] = (bf_hi(xp.y) + bf_hi(b2v.y)) * f;
            }
#pragma unroll
            for (int i = 0; i < 4; i++) {
                const uint32_t hh = __shfl_sync(~0u, hd, 4 * i + t);
                mma(ym[(i & 1) * 2], w2r[2 * i], hh & maskA, hh & maskB);
                mma(ym[(i & 1) * 2 + 1], w2r[2 * i + 1], hh & maskA, hh & maskB);
            }
#pragma unroll
            for (int k = 0; k < 4; k++) { yf[k] = ym[0][k] + ym[2][k]; add_if(t & 2, yf[k], ym[1][k], ym[3][k]); }
            CSTAMP(16, __float_as_uint(yf[3]));
            yw[0] = fx2_pack(yf[0] * sc2 + FX2_ONE, yf[1] * sc2 + FX2_ONE); yw[1] = fx2_pack(yf[2] * sc2 + FX2_ONE, yf[3] * sc2 + FX2_ONE);
            wide = !(fmaxf(fmaxf(fabsf(yf[0]), fabsf(yf[1])), fmaxf(fabsf(yf[2]), fabsf(yf[3]))) < lim);
            if (wide) yw[0] = yw[1] = 0;
            if (L.value == 0) {
#pragma unroll
                for (int k = 0; k < 2; k++) asm volatile("red.relaxed.gpu.global.add.u64 [%0], %1;" :: "l"(rap + k * 40 * ACC_PITCH), "l"(yw[k]) : "memory");
            }
        };
        auto send_wide = [&]() {
#pragma unroll 1
            for (int k = 0; k < 4; k++, yf[0] = yf[1], yf[1] = yf[2], yf[2] = yf[3]) {
                const unsigned char* a = rap + (k >> 1) * 40 * ACC_PITCH;
                fx_send(a + 64 + (k & 1) * 32, yf[0], msq, a, 256);
            }
            yw[0] = yw[1] = 1;
        };

        pass1();
        o_setup(IC<0>{});
        out_proj(IC<0>{});
        uint32_t c0;
        if (warp < 5) {
            mlp_part(IC<0>{});
            c0 = clk() + (mlp == 96 ? PCD : 0);
            stsf(sb + SM_ML + (lane & 15) * 4, cs1);
            TSTAMP(8);
            if (__any_sync(~0u, wide)) {
                if (wide) {
                    send_wide();
#pragma unroll
                    for (int k = 0; k < 2; k++) asm volatile("red.relaxed.gpu.global.add.u64 [%0], 1;" :: "l"(rap + k * 40 * ACC_PITCH) : "memory");
                }
                __syncwarp();
            }
            fresh(); calc_offsets();
            load_wq();
        } else {
            bar_sync(0, 256);
            if (warp == 5 && elect()) {
                asm volatile("fence.proxy.async.shared::cta;" ::: "memory");
                if (W1AT0 == 4) issue_w(IC<0>{}, 0);
                issue_w(IC<0>{}, 1);
            }
            __syncwarp();
            fresh(); calc_offsets();
            load_wq();
#pragma unroll 1
            for (int ph = 0; ph < 3; ph++) {
                bar_sync(ph + 2, 256);
                c0 = clk();
                if (ph == 2) {
                    msq = sum5(ldsf(sb + SM_PART + 12), ldsf(sb + SM_PART + 268), ldsf(sb + SM_PART + 524), ldsf(sb + SM_PART + 780), ldsf(sb + SM_PART + 1036)) * (1.f / D_MODEL);
                    bar_arrive(5, 256);
                }
                if (!(NOWIN >> ph & 1) && elect()) {
                    asm volatile("fence.proxy.async.shared::cta;" ::: "memory");
                    const uint32_t gap = ph == 0 ? WG1 : ph == 1 ? WG2 : WG3;
                    uint32_t c1 = c0 + (ph == 0 ? WD1 : ph == 1 ? WD2 : 0) + (warp - 5) * gap;
#pragma unroll 1
                    for (int k = warp + (ph == 0 ? -5 : ph == 1 ? 9 : 1); k < (ph == 0 ? 9 : ph == 1 ? 20 : 14); k += 3, c1 += 3 * gap) {
                        const int i = ph == 0 && k >= 6 ? k + 23 : k;
                        const uint32_t bar = sb + SM_BAR + (i & 7) * 96 + 32 + (i & 24);
                        while ((int)(clk() - c1) < 0);
                        mbar_expect(bar, SUB);
                        tma_v(sb + SM_RING + i * SUB, tmk,
                              rowc * 3 + (i & 7) * 24 + ((UC<SCH.st[0].unit | SCH.st[1].unit << 8 | SCH.st[2].unit << 16 | SCH.st[3].unit << 24>::value >> (i & 24)) & 15) * 768, bar);
                    }
                }
                __syncwarp();
            }
            c0 += PCD;
        }
        {
            constexpr IC<1> L{};
            fresh();
            const int col = xcol(g & 3, t), cw = j40 + (col >> 2);
            const unsigned char* xa = pin(accg + ACC_BYTES + ((cw >> 2) + (col & 2) * 20) * ACC_PITCH + (cw & 3) * 8);
            const uint32_t pst = pin(prow + (g * 8 + (t & 1) * 4 + (t & 2)) * 4);
            const float inv = pinf(fx2_inv(msq));
            sts64f(sb + SM_MSQ, msq, inv);
            rap = pin(accg + ACC_BYTES + (c4() >> 2) * ACC_PITCH + (c4() & 3) * 8);
            fresh();
            maskA = pin(maskA); maskB = pin(maskB);
            u64 w[1];
            uint32_t x1[1], x2[3];
            auto look = [&]() { w[0] = ld_rlx(xa); };
            if (warp < 5) {
                bar_sync(5, 256);
                if (DPRE) { while ((int)(clk() - c0) < WD4 + warp * WG4); if (warp < DPRE) refill2(IC<3>{}); }
            }
            while ((int)(clk() - c0) < ARDELAY);
            look();
            if (DPOST) while ((int)(clk() - c0) < ARDELAY + DPOST);
            if (warp < 5 && !(NOWIN & 8) && elect()) {
                if (warp >= DPRE) issue_v(IC<3>{}, 0);
                if (warp < 4 && !P2LATE) issue_v(IC<2>{}, 4);
            }
            __syncwarp();
            fx2_wait<1>([&](int) { return xa; }, look, w, sb + SM_MSQ, inv, x1);
            if (warp < 5) look_rw(); else rw[0] = rw[1] = 96;
#pragma unroll
            for (int i = 0; i < 3; i++) x2[i] = __shfl_sync(~0u, x1[0], 4 * i + t);
            TSTAMP(9);
            CSTAMP(22, x2[2]);
            q_proj(L, x2, pst);
            pass2();
            out_proj(L);
            if (warp >= 5) {
                bar_arrive(0, 256);
                if ((W1AT1 == 6 || W2AT1 == 6) && warp == 5 && elect()) { if (W1AT1 == 6) issue_w(L, 0); if (W2AT1 == 6) issue_w(L, 1); }
                TDUMP();
                return;
            }
            mlp_part(L);
            u64 old[2];
            auto add = [&]() {
#pragma unroll
                for (int k = 0; k < 2; k++) asm volatile("atom.relaxed.gpu.global.add.u64 %0, [%1], %2;" : "=l"(old[k]) : "l"(rap + k * 40 * ACC_PITCH), "l"(yw[k]) : "memory");
            };
            add();
            uint32_t* op = pin(reinterpret_cast<uint32_t*>(P.out) + 2 * c4());
            const float inv2 = pinf(fx2_inv(msq));
            if (wide) { send_wide(); add(); }
            TSTAMP(18);
            CSTAMP(17, hi32(yw[1]));
            __syncwarp();
            CSTAMP(18, lo32(old[0]) ^ lo32(old[1]));
#pragma unroll
            for (int k = 0; k < 2; k++) {
                yw[k] += old[k];
                asm volatile("{\n.reg .pred p;\nsetp.eq.u32 p, %2, 96;\n@p st.global.u32 [%0], %1;\n}"
                             :: "l"(op + k), "r"(fx2_get(yw[k], inv2)), "r"(lo32(yw[k]) & 511) : "memory");
            }
            if ((lo32(yw[0]) & 255) == 96 && tid == 0) P.g->epoch = lds32(sb + SM_EPOCH) + 1;
#pragma unroll
            for (int k = 0; k < 2; k++) if ((lo32(yw[k]) & 511) == 256 + 96) op[k] = fx2_wide(rap + k * 40 * ACC_PITCH, msq);
            TSTAMP(19);
            CSTAMP(19, lo32(yw[1]));
            TDUMP();
        }
    }
}

typedef CUresult (*EncodeFn)(CUtensorMap*, CUtensorMapDataType, cuuint32_t, void*, const cuuint64_t*, const cuuint64_t*, const cuuint32_t*,
                             const cuuint32_t*, CUtensorMapInterleave, CUtensorMapSwizzle, CUtensorMapL2promotion, CUtensorMapFloatOOBfill);

}

extern "C" void kernel_launch(void* const* d_in, const int* in_sizes, int n_in, void* d_out, int out_size) {
    (void)in_sizes; (void)n_in; (void)out_size;
    static EncodeFn enc = nullptr;
    static void* scratch = nullptr;
    if (!enc) {
        void* fn = nullptr;
        cudaDriverEntryPointQueryResult qr;
        cudaGetDriverEntryPoint("cuTensorMapEncodeTiled", &fn, cudaEnableDefault, &qr);
        enc = (EncodeFn)fn;
        cudaGetSymbolAddress(&scratch, g_scratch);
        cudaFuncSetAttribute(fused_kernel, cudaFuncAttributeMaxDynamicSharedMemorySize, SM_TOTAL);
    }
    Params P = {};
    auto map3 = [&](int m, int in, cuuint64_t d0, cuuint64_t d1, cuuint64_t d2, cuuint64_t s1, cuuint64_t s2, cuuint32_t b0, cuuint32_t b1, cuuint32_t b2,
                    CUtensorMapSwizzle sw, int promo) {
        const cuuint64_t dim[3] = {d0, d1, d2}, str[2] = {s1, s2};
        const cuuint32_t box[3] = {b0, b1, b2}, ones[3] = {1, 1, 1};
        enc(&P.tm[m], CU_TENSOR_MAP_DATA_TYPE_BFLOAT16, d2 ? 3 : 2, d_in[in], dim, str, box, ones, CU_TENSOR_MAP_INTERLEAVE_NONE, sw, (CUtensorMapL2promotion)promo,
            CU_TENSOR_MAP_FLOAT_OOB_FILL_NONE);
    };
    map3(TM_KH, 1, 64, 3, NHEAD * SK, 128, DH * 2, 64, 3, 32, CU_TENSOR_MAP_SWIZZLE_128B, PROMOK);
    map3(TM_VH, 2, 64, 3, NHEAD * SK, 128, DH * 2, 64, 3, 32, CU_TENSOR_MAP_SWIZZLE_128B, PROMOK);
    map3(TM_VP, 2, 64, 3, NHEAD * SK, 128, DH * 2, PFW, 3, 32, CU_TENSOR_MAP_SWIZZLE_NONE, 0);
    map3(TM_V, 2, 64, NHEAD * SK * 3, 0, 128, 0, 64, 24, 0, CU_TENSOR_MAP_SWIZZLE_128B, PROMOV);
    map3(TM_WO, 4, 32, 20, NHEAD * DH, 64, D_MODEL * 2, 32, 1, DH, CU_TENSOR_MAP_SWIZZLE_64B, PROMOW);
    map3(TM_WOP, 4, 32, 20, NHEAD * DH, 64, D_MODEL * 2, PFW, 1, DH, CU_TENSOR_MAP_SWIZZLE_NONE, 0);
    map3(TM_WQ, 3, 64, NHEAD * 3, D_MODEL, 128, NHEAD * DH * 2, 64, 3, 32, CU_TENSOR_MAP_SWIZZLE_128B, PROMOQ);
    map3(TM_W1, 6, DFF, 128, 5, DFF * 2, DFF * 256, 16, 128, 5, CU_TENSOR_MAP_SWIZZLE_32B, PROMO1);
    map3(TM_W2, 8, 64, 10, DFF, 128, D_MODEL * 2, 64, 10, 16, CU_TENSOR_MAP_SWIZZLE_128B, PROMO2);
    P.x = (const __nv_bfloat16*)d_in[0];
    P.k = (const __nv_bfloat16*)d_in[1];
    P.b1 = (const __nv_bfloat16*)d_in[7];
    P.b2 = (const __nv_bfloat16*)d_in[9];
    P.w1 = (const __nv_bfloat16*)d_in[6];
    P.out = (__nv_bfloat16*)d_out;
    P.g = (Scratch*)scratch;
    for (int i = 0; i < 64; i++) P.tile[i] = make_uint4(SCH.tile[i][0], SCH.tile[i][1], SCH.tile[i][2], 0);
    fused_kernel<<<NCTA + 1, NTHR, SM_TOTAL, cudaStreamPerThread>>>(P);
}
```

```cpp
#include <cuda_runtime.h>
#include <cuda_bf16.h>
#include <cuda.h>
#include <stdint.h>

namespace {

constexpr int D_MODEL = 640, NHEAD = 32, SK = 32768, DH = 192, WIN = 4096, DFF = 1536;
constexpr int NCTA = 128, NTHR = 256;
constexpr int TILE = 64 * DH * 2;
constexpr int HALF = TILE / 2;
constexpr int SUB = 8 * DH * 2;
constexpr int SM_RING = 4 * TILE;
constexpr int SM_W2 = SM_RING + 20480, SM_W1 = SM_W2 + 20480;
constexpr int SM_WQR = 6 * TILE + HALF, SM_WQ = 7 * TILE;
constexpr int SM_PART = 9 * TILE;
constexpr int SM_EXC = SM_PART + 6144;
constexpr int SM_SC = SM_EXC + 1024;
constexpr int SM_BAR = SM_SC + 1024;
constexpr int SM_VEC = SM_BAR + 768;
constexpr int SM_CS = SM_VEC + 384;
constexpr int SM_FAC = SM_CS + 768;
constexpr int SM_ML = SM_FAC + 32;
constexpr int SM_B1 = SM_ML + 64;
constexpr int SM_STAT = SM_B1 + 64;
constexpr int NCB = 28;
constexpr int CB_WO = 18, CB_W1 = 23, CB_W2 = 24, CB_SNAP = 25, CB_REL = 26, CB_WQ = 27;
constexpr int SM_CBAR = SM_STAT + 48;
constexpr int SM_CNT = SM_CBAR + NCB * 8;
constexpr int SM_EPOCH = SM_CNT + NCB * 8;
constexpr int SM_FXS = SM_EPOCH + 4;
constexpr int SM_T0 = SM_FXS + 4;
constexpr int SM_M1 = SM_T0 + 4;
constexpr int SM_MSQ = SM_M1 + 4;
constexpr int SM_TS = SM_MSQ + 8;
constexpr int SM_TOTAL = 232448;
static_assert(SM_TS + 320 <= SM_TOTAL, "smem");
constexpr int NEXC = 16;

constexpr int SPIN = 1 << 20;
enum { TM_V = 0, TM_KH = 1, TM_VH = 2, TM_WO = 3, TM_VP = 4, TM_WOP = 5, TM_W1 = 6, TM_W2 = 7, TM_WQ = 8 };
constexpr uint32_t POL_NORMAL = 0x16F00000u, POL_FIRST = 0x12F00000u;

#define PACE 980
#define PACE0 1500
#define K0FIRST 1
#define NI1 6
#define ETRIG 0x54321000
#define LATEAT 5
#define HWAT 12
#define PFREE 66
#define W1AT0 3
#define W1AT1 3
#define AR1D 250
#define LAG0 12
#define NMMA 2
#define M1AT 1
#define M1P 3
#define NWO1 4
#define WG2 120
#define WG3 65
#define WD4 250
#define WG4 70
#define NWQ1 0
#define P4AT 0
#define P2LATE 0
#define W2AT1 6
#define PCD 400
#define NOWIN 0
#define DPRE 0
#define DPOST 200
#define NIM 4
#define PACES 1300
#define JP2 54
#define PACE2 0
#define WD2 0
#define W2PRE 2
#define OPOLL1 2
#define FX1LIM 524288.f
#define PROMO2 0
#define PROMOK 0
#define PROMOV 0
#define PROMOQ 0
#define SNAPAT 1
#define DMASK 0x0
#define WOKEEP 0x1f
#define VORD2 0x7685943a2b1cd0efull
#define VTRIG 0xba73210
#define WOP 0x44433
#define PARKS 0x95
#define VSLOT 0x1087654321087654ull
#define OPOLL 2
#define S0EARLY 1
#define NPRE 2
#define ARDELAY 800
#define QDELAY 0
#define CMAP 0
#define PFW 8u
#define PUBAT 28
#define HW0 30
#define HW1 31
#define FX2LIM 524288.f
#define PROMOW 2
#define PROMO1 2
#define WD1 100
#define WG1 140

constexpr uint32_t G_A = 1u << 28, G_B = 1u << 29, G_C = 1u << 30;
__host__ __device__ constexpr int ring_hs(int j) { return (j + 4) % 5; }
__host__ __device__ constexpr uint32_t load_word(int j) {
    if (j >= 64) return (uint32_t)(j - 64) << 20 | (SM_RING + ring_hs(j) * HALF) | TM_WO << 8 | (CB_WO + j - 64) << 3 | 2 | !(WOKEEP >> (j - 64) & 1);
    const int e = j >> 1, isv = e >= 16, unit = e & 15;
    return (uint32_t)(unit * 256 + (j & 1) * 32) << 20 | (j < 8 ? j * HALF : SM_RING + ring_hs(j) * HALF) | (TM_KH + isv) << 8 | (j < 8 ? 10 + j : (j - 8) % 10) << 3 | 2
           | (!isv || (DMASK >> unit & 1));
}
__host__ __device__ constexpr int popc(int v) { return v ? (v & 1) + popc(v >> 1) : 0; }
constexpr int NPARK = popc(PARKS);
constexpr int SM_SNAP = SM_RING + ring_hs(12) * HALF, SM_CSP = SM_RING + ring_hs(11) * HALF;
struct Step { int unit, slot, par, next, mma0, nmma; };
struct Sched { uint32_t tile[64][3]; Step st[16]; };
constexpr Sched make_sched() {
    Sched s{};
    for (int j = 0; j < 64; j++) {
        const int e = j >> 1;
        const uint32_t d = load_word(j);
        uint32_t w = (uint32_t)(j < 8 ? 0 : (j - 8) / 10 & 1) << 31 | (e & 15) * 4 << 20 | ((d & 0x3f000) - (j & 1) * HALF) | (d & 0xf8);
        if (e == PUBAT || e == SNAPAT) w |= G_A;
        if (e == HW0 || e == 4) w |= G_B;
        if ((e >= LATEAT && e < LATEAT + 4) || e == HW1) w |= G_C;
        s.tile[j][0] = w;
    }
    for (int j = NI1; j < 69; j++) {
        if (j == 12) continue;
        const int at = j < 12 ? (ETRIG >> (4 * (j - 4)) & 15) : j - 5;
        s.tile[at][1] = load_word(j);
        s.tile[at][2] = j >= PFREE ? 0 : PACE0 + j * PACE / 2 + (j > JP2 ? (j - JP2) * PACE2 : 0);
    }
    int done = 0;
    for (int p = 0; p < 16; p++) {
        Step& c = s.st[p];
        c.unit = (int)(VORD2 >> (4 * p) & 15); c.slot = (int)(VSLOT >> (4 * p) & 15); c.par = p >= 9; c.next = -1;
        c.mma0 = done;
        if (p >= NPARK) { const int avail = p - done + (p >= LAG0); c.nmma = p == 15 ? 16 - done : (avail < NMMA ? avail : NMMA); done += c.nmma; }
    }
    for (int p = 9; p < 16; p++) s.st[VTRIG >> (4 * (p - 9)) & 15].next = p;
    return s;
}
constexpr Sched SCH = make_sched();
__host__ __device__ constexpr int kunit(int o) { return o < 5 ? o + 11 : o == 5 ? 10 : o - 6; }

template <int I> struct IC { static constexpr int value = I; };
template <uint32_t I> struct UC { static constexpr uint32_t value = I; };
template <int A, int B, class F> __device__ __forceinline__ void static_for(F&& f) {
    if constexpr (A < B) { f(IC<A>{}); static_for<A + 1, B>(f); }
}

typedef unsigned long long u64;
constexpr int ACC_PITCH = 352, ACC1_PITCH = 256, ACC_BYTES = 32768;
struct alignas(1024) Scratch {
    unsigned char acc[4 * ACC_BYTES];
    u64 l0[NCTA][384];
    u64 ll[2][NCTA][256];
    alignas(128) unsigned epoch;
    alignas(128) unsigned zflag;
};
__device__ __align__(1024) unsigned char g_scratch[sizeof(Scratch) + ACC_BYTES];

struct Params {
    CUtensorMap tm[9];
    const __nv_bfloat16 *x, *k, *b1, *b2, *w1;
    __nv_bfloat16* out;
    Scratch* g;
    uint4 tile[66];
};

#define TSTAMP(i)
#define TSTAMP2(i)
#define TSTAMPL(i)
#define TDUMP()
#define CSTAMP(i, x)
#define TRACE(i)

__device__ __forceinline__ void mbar_wait(uint32_t bar, uint32_t parity) {
    asm volatile("{\n.reg .pred p;\nLOOP:\nmbarrier.try_wait.parity.shared::cta.b64 p, [%0], %1;\n@!p bra.uni LOOP;\n}" :: "r"(bar), "r"(parity) : "memory");
}
__device__ __forceinline__ bool mbar_test(uint32_t bar, uint32_t parity) {
    uint32_t r;
    asm volatile("{\n.reg .pred p;\nmbarrier.test_wait.parity.shared::cta.b64 p, [%1], %2;\nselp.u32 %0, 1, 0, p;\n}" : "=r"(r) : "r"(bar), "r"(parity) : "memory");
    return __all_sync(~0u, r);
}
__device__ __forceinline__ bool elect() {
    uint32_t r;
    asm volatile("{\n.reg .pred p;\nelect.sync _|p, 0xffffffff;\nselp.u32 %0, 1, 0, p;\n}" : "=r"(r));
    return r != 0;
}
__device__ __forceinline__ void mbar_expect(uint32_t bar, uint32_t bytes) {
    asm volatile("mbarrier.arrive.expect_tx.shared::cta.b64 _, [%0], %1;" :: "r"(bar), "r"(bytes) : "memory");
}
__device__ __forceinline__ uint4 lds128(uint32_t a) {
    uint4 v; asm volatile("ld.shared.v4.u32 {%0,%1,%2,%3}, [%4];" : "=r"(v.x), "=r"(v.y), "=r"(v.z), "=r"(v.w) : "r"(a) : "memory"); return v;
}
__device__ __forceinline__ uint4 ldsm_t(uint32_t a) {
    uint4 v; asm volatile("ldmatrix.sync.aligned.m8n8.x4.trans.shared.b16 {%0,%1,%2,%3}, [%4];" : "=r"(v.x), "=r"(v.y), "=r"(v.z), "=r"(v.w) : "r"(a) : "memory"); return v;
}
__device__ __forceinline__ uint2 lds64(uint32_t a) {
    uint2 v; asm volatile("ld.shared.v2.u32 {%0,%1}, [%2];" : "=r"(v.x), "=r"(v.y) : "r"(a) : "memory"); return v;
}
__device__ __forceinline__ float2 lds64f(uint32_t a) { const uint2 v = lds64(a); return make_float2(__uint_as_float(v.x), __uint_as_float(v.y)); }
__device__ __forceinline__ uint32_t lds32(uint32_t a) {
    uint32_t v; asm volatile("ld.shared.u32 %0, [%1];" : "=r"(v) : "r"(a) : "memory"); return v;
}
__device__ __forceinline__ float ldsf(uint32_t a) { return __uint_as_float(lds32(a)); }
__device__ __forceinline__ void sts32(uint32_t a, uint32_t v) { asm volatile("st.shared.u32 [%0], %1;" :: "r"(a), "r"(v) : "memory"); }
__device__ __forceinline__ void stsf(uint32_t a, float v) { sts32(a, __float_as_uint(v)); }
__device__ __forceinline__ void sts16(uint32_t a, uint32_t v) { asm volatile("st.shared.u16 [%0], %1;" :: "r"(a), "h"((uint16_t)v) : "memory"); }
__device__ __forceinline__ void sts64(uint32_t a, uint32_t x, uint32_t y) { asm volatile("st.shared.v2.u32 [%0], {%1,%2};" :: "r"(a), "r"(x), "r"(y) : "memory"); }
__device__ __forceinline__ void sts64f(uint32_t a, float x, float y) { sts64(a, __float_as_uint(x), __float_as_uint(y)); }
__device__ __forceinline__ void sts128f(uint32_t a, float x, float y, float z, float w) {
    asm volatile("st.shared.v4.f32 [%0], {%1,%2,%3,%4};" :: "r"(a), "f"(x), "f"(y), "f"(z), "f"(w) : "memory");
}
__device__ __forceinline__ void mma(float (&c)[4], const uint4& a, uint32_t b0, uint32_t b1) {
    asm volatile("mma.sync.aligned.m16n8k16.row.col.f32.bf16.bf16.f32 {%0,%1,%2,%3}, {%4,%5,%6,%7}, {%8,%9}, {%0,%1,%2,%3};"
                 : "+f"(c[0]), "+f"(c[1]), "+f"(c[2]), "+f"(c[3]) : "r"(a.x), "r"(a.y), "r"(a.z), "r"(a.w), "r"(b0), "r"(b1));
}
__device__ __forceinline__ u64 ld_rlx(const void* p) {
    u64 a; asm volatile("ld.relaxed.gpu.global.u64 %0, [%1];" : "=l"(a) : "l"(p) : "memory"); return a;
}
__device__ __forceinline__ void ld_rlx2(const void* p, u64& a, u64& b) {
    asm volatile("ld.relaxed.gpu.global.v2.u64 {%0,%1}, [%2];" : "=l"(a), "=l"(b) : "l"(p) : "memory");
}
__device__ __forceinline__ void st_rlx(void* p, u64 a) { asm volatile("st.relaxed.gpu.global.u64 [%0], %1;" :: "l"(p), "l"(a) : "memory"); }
__device__ __forceinline__ u64 ll_pack(float v, uint32_t tag) { return ((u64)tag << 32) | __float_as_uint(v); }
__device__ __forceinline__ float ll_val(u64 w) { return __uint_as_float((uint32_t)w); }
__device__ __forceinline__ uint32_t ll_tag(u64 w) { return (uint32_t)(w >> 32); }
__device__ __forceinline__ float bf_lo(uint32_t u) { return __uint_as_float(u << 16); }
__device__ __forceinline__ float bf_hi(uint32_t u) { return __uint_as_float(u & 0xffff0000u); }
__device__ __forceinline__ uint32_t pack_bf(float lo, float hi) {
    uint32_t r; asm("cvt.rn.bf16x2.f32 %0, %1, %2;" : "=r"(r) : "f"(hi), "f"(lo)); return r;
}
__device__ __forceinline__ float ex2(float v) { float r; asm("ex2.approx.ftz.f32 %0, %1;" : "=f"(r) : "f"(v)); return r; }
__device__ __forceinline__ float rcp(float v) { float r; asm("rcp.approx.ftz.f32 %0, %1;" : "=f"(r) : "f"(v)); return r; }
__device__ __forceinline__ float rsq(float v) { float r; asm("rsqrt.approx.ftz.f32 %0, %1;" : "=f"(r) : "f"(v)); return r; }
__device__ __forceinline__ void bar_sync(int id, int n) { asm volatile("bar.sync %0, %1;" :: "r"(id), "r"(n) : "memory"); }
__device__ __forceinline__ uint32_t clk() { uint32_t c; asm volatile("mov.u32 %0, %clock;" : "=r"(c)); return c; }
__device__ __forceinline__ void sched_fence() { __syncwarp(); while (clk() == 0x9e3779b9u); }
__device__ __forceinline__ uint32_t pin(uint32_t v) { return __shfl_xor_sync(~0u, v, 0); }
__device__ __forceinline__ float shx(float v, int o) { return __shfl_xor_sync(~0u, v, o); }

__device__ __forceinline__ u64 fx_pack(float v, float scale) { return ((u64)__float2ll_rn(v * scale) & ~255ull) | 1ull; }
__device__ __forceinline__ float fx_scale(float meansq) {
    const int e = max(((int)(__float_as_uint(meansq) >> 23) - 127) >> 1, -6);
    return __uint_as_float((uint32_t)(127 + 32 - e) << 23);
}
__device__ __forceinline__ float fx_inv(float scale) { return __uint_as_float((254u << 23) - __float_as_uint(scale)); }
__device__ __forceinline__ uint32_t lo32(u64 w) { uint32_t l; asm("mov.b64 {%0, _}, %1;" : "=r"(l) : "l"(w)); return l; }
__device__ __forceinline__ int hi32(u64 w) { int h; asm("mov.b64 {_, %0}, %1;" : "=r"(h) : "l"(w)); return h; }
__device__ __forceinline__ float fx_val(u64 w) { return (float)hi32(w) * 4294967296.f + (float)lo32(w); }
constexpr float FX2_ONE = 12582912.f;
__device__ __forceinline__ float fx2_scale(float meansq) { return __uint_as_float((uint32_t)(127 + 16 - max(((int)(__float_as_uint(meansq) >> 23) - 127) >> 1, -100)) << 23); }
__device__ __forceinline__ u64 fx2_pack(float a, float b) {
    const uint32_t lo = __float_as_uint(a) * 512u + (1u - 0x4b400000u * 512u);
    return lo | (u64)(__float_as_uint(b) * 16u - 0x4b400000u * 16u + (uint32_t)((int)lo >> 31)) << 32;
}
__device__ __forceinline__ float fx2_lo(u64 w, float inv) { return (float)(int)(__funnelshift_r(lo32(w), hi32(w), 4) & ~31u) * (inv * 0.5f); }
__device__ __forceinline__ float fx2_hi(u64 w, float inv) { return (float)((hi32(w) + 8) & ~15) * inv; }
__device__ __forceinline__ uint32_t fx2_get(u64 w, float inv) {
    return pack_bf((float)(int)__funnelshift_r(lo32(w), hi32(w), 4) * (inv * 0.5f) - inv * 3.f, (float)hi32(w) * inv);
}
__device__ __forceinline__ float fx2_inv(float meansq) { return fx_inv(fx2_scale(meansq)) * 0.0625f; }
__device__ __noinline__ uint32_t fx2_wide(const unsigned char* a, float meansq) {
    __threadfence();
    const u64 w = ld_rlx(a);
    const float inv = fx_inv(fx_scale(meansq));
    return pack_bf(fx2_lo(w, fx2_inv(meansq)) + fx_val(ld_rlx(a + 64)) * inv, fx2_hi(w, fx2_inv(meansq)) + fx_val(ld_rlx(a + 96)) * inv);
}
__device__ __noinline__ uint32_t fx1_wide(const unsigned char* a, float meansq) {
    __threadfence();
    const u64 w = ld_rlx(a);
    const unsigned char* b = a + 64 + (reinterpret_cast<u64>(a) & 31);
    const float inv = fx_inv(fx_scale(meansq)), inv1 = fx2_inv(meansq) * 0.5f;
    return pack_bf((float)(int)(lo32(w) & ~127u) * inv1 + fx_val(ld_rlx(b)) * inv, (float)(hi32(w) & ~127) * inv1 + fx_val(ld_rlx(b + 8)) * inv);
}
__device__ __noinline__ void fx_send(const unsigned char* wide, float v, float meansq, const unsigned char* a, uint32_t flag) {
    asm volatile("red.relaxed.gpu.global.add.u64 [%0], %1;" :: "l"(wide), "l"(fx_pack(v, fx_scale(meansq))) : "memory");
    __threadfence();
    asm volatile("red.relaxed.gpu.global.or.b32 [%0], %1;" :: "l"(a), "r"(flag) : "memory");
}
template <int N, class A, class F> __device__ __forceinline__ void fx2_wait(A a, F look, u64 (&w)[N], uint32_t msqa, float inv, uint32_t (&x)[N]) {
    auto miss = [&]() {
#pragma unroll
        for (int i = 0; i < N; i++) x[i] = fx2_get(w[i], inv);
        return __any_sync(~0u, ((lo32(w[0]) ^ 96) | (lo32(w[N - 1]) ^ 96)) & 0x160);
    };
    if (miss()) {
        int it = 0;
#pragma unroll 1
        do {
            if (__all_sync(~0u, (lo32(w[0]) & lo32(w[N - 1]) & 96) == 96)) {
#pragma unroll
                for (int i = 0; i < N; i++) x[i] = fx2_wide(a(i), ldsf(msqa));
                break;
            }
            look();
        } while (miss() & (++it < SPIN));
    }
}
__device__ __forceinline__ void st_rlx_if(bool p, void* a, u64 v) {
    asm volatile("{\n.reg .pred p;\nsetp.ne.u32 p, %2, 0;\n@p st.relaxed.gpu.global.u64 [%0], %1;\n}" :: "l"(a), "l"(v), "r"((uint32_t)p) : "memory");
}
__device__ __forceinline__ void sts128f(uint32_t a, const float (&v)[4]) { sts128f(a, v[0], v[1], v[2], v[3]); }
__device__ __forceinline__ void bar_arrive(int id, int n) { asm volatile("bar.arrive %0, %1;" :: "r"(id), "r"(n) : "memory"); }
template <class T> __device__ __forceinline__ T* pin(T* p) { return reinterpret_cast<T*>(__shfl_xor_sync(~0u, (u64)p, 0)); }

__device__ __forceinline__ void tma3(uint32_t dst, const CUtensorMap* tm, int c1, int c2, uint32_t bar, uint32_t pol) {
    asm volatile("cp.async.bulk.tensor.3d.shared::cluster.global.mbarrier::complete_tx::bytes.L2::cache_hint [%0], [%1, {%2, %3, %4}], [%5], %6;"
                 :: "r"(dst), "l"(tm), "r"(0), "r"(c1), "r"(c2), "r"(bar), "l"((u64)pol << 32) : "memory");
}
__device__ __forceinline__ void tma_v(uint32_t dst, const CUtensorMap* tm, int line, uint32_t bar) {
    asm volatile("cp.async.bulk.tensor.2d.shared::cluster.global.mbarrier::complete_tx::bytes.L2::cache_hint [%0], [%1, {%2, %3}], [%4], %5;"
                 :: "r"(dst), "l"(tm), "r"(0), "r"(line), "r"(bar), "l"((u64)POL_FIRST << 32) : "memory");
}
__device__ __forceinline__ void tma3_pf(const CUtensorMap* tm, int c1, int c2, uint32_t pol) {
    asm volatile("cp.async.bulk.prefetch.tensor.3d.L2.global.tile.L2::cache_hint [%0, {%1, %2, %3}], %4;"
                 :: "l"(tm), "r"(0), "r"(c1), "r"(c2), "l"((u64)pol << 32) : "memory");
}
__device__ __forceinline__ void issue_half(uint32_t d, uint32_t sb, int rowc, int cta, const CUtensorMap* tm0) {
    const uint32_t bar = sb + SM_CBAR + (d & 0xf8);
    const CUtensorMap* tm = tm0 + ((d >> 8) & 3);
    const bool wo = (d & 0x300) == TM_WO << 8;
    const int c1 = wo ? (cta & 3) + 4 * (d >> 20) : 0, c2 = wo ? (cta >> 2) * DH : rowc + (d >> 20);
    mbar_expect(bar, HALF);
    tma3(sb + (d & 0x3f000), tm, c1, c2, bar, POL_FIRST);
    if (!(d & 1)) tma3_pf(tm + 2, c1, c2, POL_NORMAL);
}
__device__ __forceinline__ uint32_t cnt_inc(uint32_t a, uint32_t last) {
    uint32_t old; asm volatile("atom.relaxed.cta.shared.inc.u32 %0, [%1], %2;" : "=r"(old) : "r"(a), "r"(last) : "memory"); return old;
}
__device__ __forceinline__ void wait_until(uint32_t due) {
#pragma unroll 1
    for (int it = 0; it < 4096; it++) { uint32_t now; asm volatile("mov.u32 %0, %globaltimer_lo;" : "=r"(now)); if ((int)(now - due) >= 0) break; }
}
__device__ __forceinline__ uint32_t bf2_mul(uint32_t a, uint32_t b) { uint32_t r; asm("mul.rn.bf16x2 %0, %1, %2;" : "=r"(r) : "r"(a), "r"(b)); return r; }
__device__ __forceinline__ uint32_t bf2_fma(uint32_t a, uint32_t b, uint32_t c) { uint32_t r; asm("fma.rn.bf16x2 %0, %1, %2, %3;" : "=r"(r) : "r"(a), "r"(b), "r"(c)); return r; }
__device__ __forceinline__ uint32_t bf2_amax(uint32_t a, uint32_t b) { uint32_t r; asm("max.NaN.xorsign.abs.bf16x2 %0, %1, %2;" : "=r"(r) : "r"(a), "r"(b)); return r; }
__device__ __forceinline__ uint4 k_unpack(uint32_t l0, uint32_t l1, uint32_t h, uint32_t m1) {
    const uint32_t ha = h & 0x87878787u, hc = ha * m1 + h, hb = __funnelshift_l(hc, hc, 4);
    return make_uint4(__byte_perm(l0, ha, 0x5140), __byte_perm(l0, ha, 0x7362), __byte_perm(l1, hb, 0x5140), __byte_perm(l1, hb, 0x7362));
}
#define KR4(u, i) "+r"(kr[u][i].x), "+r"(kr[u][i].y), "+r"(kr[u][i].z), "+r"(kr[u][i].w)
#define KR6(u) KR4(u, 0), KR4(u, 1), KR4(u, 2), KR4(u, 3), KR4(u, 4), KR4(u, 5)
__device__ __forceinline__ void k_keep(uint4 (&kr)[8][6], const uint32_t (&c)[18], int e, uint32_t a) {
    asm volatile("{\nKT: .branchtargets K0, K1, K2, K3, K4, K5, K6, K7, K8, K9, K10, K11, K12, K13, K14, K15;\nbrx.idx.uni %210, KT;\n"
                 "K0: mov.b32 %12, %192; mov.b32 %13, %193; mov.b32 %14, %194; mov.b32 %15, %195; mov.b32 %16, %196; mov.b32 %17, %197; mov.b32 %18, %198; mov.b32 %19, %199; mov.b32 %20, %200; mov.b32 %21, %201; mov.b32 %22, %202; mov.b32 %23, %203; mov.b32 %24, %204; mov.b32 %25, %205; mov.b32 %26, %206; mov.b32 %27, %207; mov.b32 %28, %208; mov.b32 %29, %209; bra.uni KE;\n"
                 "K1: mov.b32 %30, %192; mov.b32 %31, %193; mov.b32 %32, %194; mov.b32 %33, %195; mov.b32 %34, %196; mov.b32 %35, %197; mov.b32 %36, %198; mov.b32 %37, %199; mov.b32 %38, %200; mov.b32 %39, %201; mov.b32 %40, %202; mov.b32 %41, %203; mov.b32 %42, %204; mov.b32 %43, %205; mov.b32 %44, %206; mov.b32 %45, %207; mov.b32 %46, %208; mov.b32 %47, %209; bra.uni KE;\n"
                 "K2: mov.b32 %48, %192; mov.b32 %49, %193; mov.b32 %50, %194; mov.b32 %51, %195; mov.b32 %52, %196; mov.b32 %53, %197; mov.b32 %54, %198; mov.b32 %55, %199; mov.b32 %56, %200; mov.b32 %57, %201; mov.b32 %58, %202; mov.b32 %59, %203; mov.b32 %60, %204; mov.b32 %61, %205; mov.b32 %62, %206; mov.b32 %63, %207; mov.b32 %64, %208; mov.b32 %65, %209; bra.uni KE;\n"
                 "K3: mov.b32 %66, %192; mov.b32 %67, %193; mov.b32 %68, %194; mov.b32 %69, %195; mov.b32 %70, %196; mov.b32 %71, %197; mov.b32 %72, %198; mov.b32 %73, %199; mov.b32 %74, %200; mov.b32 %75, %201; mov.b32 %76, %202; mov.b32 %77, %203; mov.b32 %78, %204; mov.b32 %79, %205; mov.b32 %80, %206; mov.b32 %81, %207; mov.b32 %82, %208; mov.b32 %83, %209; bra.uni KE;\n"
                 "K4: mov.b32 %84, %192; mov.b32 %85, %193; mov.b32 %86, %194; mov.b32 %87, %195; mov.b32 %88, %196; mov.b32 %89, %197; mov.b32 %90, %198; mov.b32 %91, %199; mov.b32 %92, %200; mov.b32 %93, %201; mov.b32 %94, %202; mov.b32 %95, %203; mov.b32 %96, %204; mov.b32 %97, %205; mov.b32 %98, %206; mov.b32 %99, %207; mov.b32 %100, %208; mov.b32 %101, %209; bra.uni KE;\n"
                 "K5: mov.b32 %102, %192; mov.b32 %103, %193; mov.b32 %104, %194; mov.b32 %105, %195; mov.b32 %106, %196; mov.b32 %107, %197; mov.b32 %108, %198; mov.b32 %109, %199; mov.b32 %110, %200; mov.b32 %111, %201; mov.b32 %112, %202; mov.b32 %113, %203; mov.b32 %114, %204; mov.b32 %115, %205; mov.b32 %116, %206; mov.b32 %117, %207; mov.b32 %118, %208; mov.b32 %119, %209; bra.uni KE;\n"
                 "K6: mov.b32 %120, %192; mov.b32 %121, %193; mov.b32 %122, %194; mov.b32 %123, %195; mov.b32 %124, %196; mov.b32 %125, %197; mov.b32 %126, %198; mov.b32 %127, %199; mov.b32 %128, %200; mov.b32 %129, %201; mov.b32 %130, %202; mov.b32 %131, %203; mov.b32 %132, %204; mov.b32 %133, %205; mov.b32 %134, %206; mov.b32 %135, %207; mov.b32 %136, %208; mov.b32 %137, %209; bra.uni KE;\n"
                 "K7: mov.b32 %138, %192; mov.b32 %139, %193; mov.b32 %140, %194; mov.b32 %141, %195; mov.b32 %142, %196; mov.b32 %143, %197; mov.b32 %144, %198; mov.b32 %145, %199; mov.b32 %146, %200; mov.b32 %147, %201; mov.b32 %148, %202; mov.b32 %149, %203; mov.b32 %150, %204; mov.b32 %151, %205; mov.b32 %152, %206; mov.b32 %153, %207; mov.b32 %154, %208; mov.b32 %155, %209; bra.uni KE;\n"
                 "K8: mov.b32 %156, %192; mov.b32 %157, %193; mov.b32 %158, %194; mov.b32 %159, %195; mov.b32 %160, %196; mov.b32 %161, %197; mov.b32 %162, %198; mov.b32 %163, %199; mov.b32 %164, %200; mov.b32 %165, %201; mov.b32 %166, %202; mov.b32 %167, %203; mov.b32 %168, %204; mov.b32 %169, %205; mov.b32 %170, %206; mov.b32 %171, %207; mov.b32 %172, %208; mov.b32 %173, %209; bra.uni KE;\n"
                 "K9: mov.b32 %174, %192; mov.b32 %175, %193; mov.b32 %176, %194; mov.b32 %177, %195; mov.b32 %178, %196; mov.b32 %179, %197; mov.b32 %180, %198; mov.b32 %181, %199; mov.b32 %182, %200; mov.b32 %183, %201; mov.b32 %184, %202; mov.b32 %185, %203; mov.b32 %186, %204; mov.b32 %187, %205; mov.b32 %188, %206; mov.b32 %189, %207; mov.b32 %190, %208; mov.b32 %191, %209; bra.uni KE;\n"
                 "K10: st.shared.v2.b32 [%211+75784], {%192, %193}; st.shared.v2.b32 [%211+76288], {%194, %195}; st.shared.v2.b32 [%211+76296], {%196, %197}; mov.b32 %0, %198; mov.b32 %1, %199; mov.b32 %2, %200; mov.b32 %3, %201; mov.b32 %4, %202; mov.b32 %5, %203; mov.b32 %6, %204; mov.b32 %7, %205; mov.b32 %8, %206; mov.b32 %9, %207; mov.b32 %10, %208; mov.b32 %11, %209; bra.uni KE;\n"
                 "K11: st.shared.v2.b32 [%211+0], {%192, %193}; st.shared.v2.b32 [%211+8], {%194, %195}; st.shared.v2.b32 [%211+512], {%196, %197}; st.shared.v2.b32 [%211+520], {%198, %199}; st.shared.v2.b32 [%211+1024], {%200, %201}; st.shared.v2.b32 [%211+1032], {%202, %203}; st.shared.v2.b32 [%211+1536], {%204, %205}; st.shared.v2.b32 [%211+1544], {%206, %207}; st.shared.v2.b32 [%211+2048], {%208, %209}; bra.uni KE;\n"
                 "K12: st.shared.v2.b32 [%211+2056], {%192, %193}; st.shared.v2.b32 [%211+2560], {%194, %195}; st.shared.v2.b32 [%211+2568], {%196, %197}; st.shared.v2.b32 [%211+24576], {%198, %199}; st.shared.v2.b32 [%211+24584], {%200, %201}; st.shared.v2.b32 [%211+25088], {%202, %203}; st.shared.v2.b32 [%211+25096], {%204, %205}; st.shared.v2.b32 [%211+25600], {%206, %207}; st.shared.v2.b32 [%211+25608], {%208, %209}; bra.uni KE;\n"
                 "K13: st.shared.v2.b32 [%211+26112], {%192, %193}; st.shared.v2.b32 [%211+26120], {%194, %195}; st.shared.v2.b32 [%211+26624], {%196, %197}; st.shared.v2.b32 [%211+26632], {%198, %199}; st.shared.v2.b32 [%211+27136], {%200, %201}; st.shared.v2.b32 [%211+27144], {%202, %203}; st.shared.v2.b32 [%211+49152], {%204, %205}; st.shared.v2.b32 [%211+49160], {%206, %207}; st.shared.v2.b32 [%211+49664], {%208, %209}; bra.uni KE;\n"
                 "K14: st.shared.v2.b32 [%211+49672], {%192, %193}; st.shared.v2.b32 [%211+50176], {%194, %195}; st.shared.v2.b32 [%211+50184], {%196, %197}; st.shared.v2.b32 [%211+50688], {%198, %199}; st.shared.v2.b32 [%211+50696], {%200, %201}; st.shared.v2.b32 [%211+51200], {%202, %203}; st.shared.v2.b32 [%211+51208], {%204, %205}; st.shared.v2.b32 [%211+51712], {%206, %207}; st.shared.v2.b32 [%211+51720], {%208, %209}; bra.uni KE;\n"
                 "K15: st.shared.v2.b32 [%211+73728], {%192, %193}; st.shared.v2.b32 [%211+73736], {%194, %195}; st.shared.v2.b32 [%211+74240], {%196, %197}; st.shared.v2.b32 [%211+74248], {%198, %199}; st.shared.v2.b32 [%211+74752], {%200, %201}; st.shared.v2.b32 [%211+74760], {%202, %203}; st.shared.v2.b32 [%211+75264], {%204, %205}; st.shared.v2.b32 [%211+75272], {%206, %207}; st.shared.v2.b32 [%211+75776], {%208, %209}; \nKE:\n}"
                 : KR6(0), KR6(1), KR6(2), KR6(3), KR6(4), KR6(5), KR6(6), KR6(7)
                 : "r"(c[0]), "r"(c[1]), "r"(c[2]), "r"(c[3]), "r"(c[4]), "r"(c[5]), "r"(c[6]), "r"(c[7]), "r"(c[8]), "r"(c[9]), "r"(c[10]), "r"(c[11]), "r"(c[12]), "r"(c[13]), "r"(c[14]), "r"(c[15]), "r"(c[16]), "r"(c[17]), "r"(e), "r"(a) : "memory");
}
__device__ __forceinline__ uint32_t smem_base() { extern __shared__ __align__(1024) unsigned char smem[]; return (uint32_t)__cvta_generic_to_shared(smem); }
__device__ __forceinline__ void k_rare(uint4 v0, uint4 v1, uint4 v2, uint4 v3, uint4 v4, uint4 v5, uint32_t odd, int e, int warp, int lane) {
    const uint32_t sb = smem_base(), g = lane >> 2, t = lane & 3, st = sb + SM_BAR + warp * 96 + 80;
    uint32_t lt; asm volatile("mov.u32 %0, %lanemask_lt;" : "=r"(lt));
    const uint4 v[6] = {v0, v1, v2, v3, v4, v5};
    odd <<= 6;
#pragma unroll
    for (int i = 0; i < 6; i++) if (v[i].x | v[i].y | v[i].z | v[i].w) odd |= 1u << i;
    odd = __reduce_or_sync(~0u, odd);
    uint32_t n = odd >= 64 ? NEXC + 1 : __shfl_sync(~0u, lds32(st), 0);
#pragma unroll 1
    for (; odd && n <= NEXC; odd &= odd - 1) {
        const int i = __ffs(odd) - 1;
#pragma unroll
        for (int k = 1; k < 6; k++) if (i == k) v0 = v[k];
#pragma unroll 1
        for (int k = 0; k < 4; k++, v0.x = v0.y, v0.y = v0.z, v0.z = v0.w) {
            const uint32_t who = __ballot_sync(~0u, v0.x), at = n + __popc(who & lt);
            sts64(v0.x && at < NEXC ? sb + SM_EXC + warp * 128 + at * 8 : st + 8, v0.x, (e * 32 + g * 4) << 16 | (((k & 1) * 4 + t) * 48 + i * 8 + (k >> 1) * 4));
            n += __popc(who);
        }
    }
    const uint32_t bad = lds32(st + 4);
    __syncwarp();
    if (n <= NEXC) sts32(st, n);
    else {
        sts32(st + 4, bad | 1u << e);
        asm volatile("st.shared.u8 [%0], %1;" :: "r"(sb + SM_SC + warp * 128 + g * 16 + (e & 3) * 4 + (e >> 2)), "r"(0) : "memory");
    }
    __syncwarp();
}
template <int K> __device__ __forceinline__ uint32_t& word(uint4& v) { if constexpr (K == 0) return v.x; else if constexpr (K == 1) return v.y; else if constexpr (K == 2) return v.z; else return v.w; }
__device__ __forceinline__ void add_if(bool p, float& d, float a, float b) {
    asm volatile("{\n.reg .pred p;\nsetp.ne.u32 p, %3, 0;\n@p add.f32 %0, %1, %2;\n}" : "+f"(d) : "f"(a), "f"(b), "r"((uint32_t)p));
}
__device__ __forceinline__ float warp_max(float v) {
#pragma unroll
    for (int o = 16; o; o >>= 1) v = fmaxf(v, shx(v, o));
    return v;
}
__device__ __forceinline__ float warp_sum(float v) {
#pragma unroll
    for (int o = 16; o; o >>= 1) v += shx(v, o);
    return v;
}
template <int PITCH> __device__ __forceinline__ void ll_look(const u64* buf, u64 (&w)[4]) {
#pragma unroll
    for (int i = 0; i < 4; i++) w[i] = ld_rlx(buf + i * PITCH);
}
template <int PITCH> __device__ __forceinline__ float ll_gather(const u64* buf, uint32_t tag, u64 (&w)[4]) {
    auto miss = [&]() {
        uint32_t a, b;
        asm("lop3.b32 %0, %1, %2, %3, 0x7e;" : "=r"(a) : "r"(ll_tag(w[0])), "r"(ll_tag(w[1])), "r"(tag));
        asm("lop3.b32 %0, %1, %2, %3, 0x7e;" : "=r"(b) : "r"(ll_tag(w[2])), "r"(ll_tag(w[3])), "r"(tag));
        return __any_sync(~0u, a | b);
    };
    int it = 0;
    goto check;
again:
    ll_look<PITCH>(buf, w);
check:
    if (miss() & (++it < SPIN)) goto again;
    return (ll_val(w[0]) + ll_val(w[1])) + (ll_val(w[2]) + ll_val(w[3]));
}
__device__ __forceinline__ float sum8(uint32_t a, int pitch) {
    float s[8];
#pragma unroll
    for (int w = 0; w < 8; w++) s[w] = ldsf(a + w * pitch);
    return ((s[0] + s[1]) + (s[2] + s[3])) + ((s[4] + s[5]) + (s[6] + s[7]));
}
__device__ __forceinline__ float sum5(float a, float b, float c, float d, float e) { return ((a + b) + (c + d)) + e; }
__device__ __forceinline__ float ln_part(uint2 xp, int lane) {
    const float x0 = bf_lo(xp.x), x1 = bf_hi(xp.x), x2 = bf_lo(xp.y), x3 = bf_hi(xp.y);
    const float s1 = (x0 + x1) + (x2 + x3), s2 = (x0 * x0 + x1 * x1) + (x2 * x2 + x3 * x3);
    return ((lane & 16) ? s2 : s1) + shx((lane & 16) ? s1 : s2, 16);
}
__device__ __forceinline__ float ln_rstd(float mean, float msq) { return rsq(fmaxf(msq - mean * mean, 0.f) + 1e-5f); }
__device__ __forceinline__ float score(const uint4 (&v)[6], const uint4 (&qf)[3]) {
    float d[2][4];
#pragma unroll
    for (int j = 0; j < 2; j++) d[j][0] = d[j][1] = d[j][2] = d[j][3] = 0.f;
#pragma unroll
    for (int i = 0; i < 3; i++) { mma(d[0], v[2 * i], qf[i].x, qf[i].y); mma(d[1], v[2 * i + 1], qf[i].z, qf[i].w); }
    return (d[0][0] + d[0][3]) + (d[1][0] + d[1][3]);
}
__device__ __forceinline__ float k_side(uint32_t sb, uint2 x) {
    const uint32_t qq = lds32(sb + SM_VEC + (x.y & 0xffff));
    return (bf_lo(x.x) * bf_lo(qq) + bf_hi(x.x) * bf_hi(qq)) * 0x1p-64f;
}
__device__ __forceinline__ void k_fix(const __nv_bfloat16* k, uint32_t bad, int warp, int lane) {
    const uint32_t sb = smem_base(), g = lane >> 2, sa = sb + SM_PART + warp * 768 + 256;
    const uint2 x = lds64(sb + SM_EXC + warp * 128 + (lane & 15) * 8);
    if ((int)x.y >= 0x40000000 && lane < 16) asm volatile("red.shared.add.f32 [%0], %1;" :: "r"(sa + ((x.y >> 16) & 511)), "f"(k_side(sb, x)) : "memory");
    __syncwarp();
#pragma unroll 1
    for (bad &= 0xffff; bad; bad &= bad - 1) {
        const int e = __ffs(bad) - 1;
        const __nv_bfloat16* kp = k + (e * 256 + (g >> 1) + 4 * (g & 1)) * DH + (lane & 3) * 8;
        uint4 v[6], qf[3];
#pragma unroll
        for (int i = 0; i < 6; i++) v[i] = *reinterpret_cast<const uint4*>(kp + i * 32);
#pragma unroll
        for (int i = 0; i < 3; i++) qf[i] = lds128(sb + SM_VEC + (lane & 7) * 48 + i * 16);
        stsf(sa + e * 32 + g * 4, score(v, qf) * 0x1p-64f);
    }
    __syncwarp();
}
constexpr float CS = 0.07216878364870322f * 1.4426950408889634f;
__device__ __forceinline__ void head_weight(const u64* a, u64 pm, u64 pl, int layer, int lane) {
    const uint32_t sb = smem_base(), tag = lds32(sb + SM_EPOCH) * 4 + 2 + 2 * layer;
#pragma unroll 1
    for (int it = 0; it < SPIN; it++) {
        if (__all_sync(~0u, ll_tag(pm) == tag && ll_tag(pl) == tag)) break;
        ld_rlx2(a, pm, pl);
    }
    const float f = ex2((ll_val(pm) - warp_max(ll_val(pm))) * CS);
    const float w = f * rcp(warp_sum(f * ll_val(pl)));
    if (lane < 8) stsf(sb + SM_FAC + lane * 4, w);
}
constexpr uint32_t ONES = 0x3f803f80u;

__global__ void __launch_bounds__(NTHR, 1) fused_kernel(const __grid_constant__ Params P) {
    const uint32_t sb = smem_base();
    const int bx = blockIdx.x;
    const int cta0 = bx >= NCTA || CMAP == 0 ? bx : CMAP == 4 ? (((bx >> 1) & 7) + (bx >> 5) * 8) * 4 + ((bx >> 4) & 1) * 2 + (bx & 1)
                   : (((bx >> 1) & 15) + (bx >> 6) * 16) * 4 + ((bx >> 5) & 1) * 2 + (bx & 1);
    if (__all_sync(~0u, threadIdx.x >= NTHR - 32 && bx < NCTA) && elect()) {
        asm volatile("mbarrier.init.shared::cta.b64 [%0], 1;" :: "r"(sb + SM_CBAR + CB_WQ * 8));
        asm volatile("mbarrier.init.shared::cta.b64 [%0], 1;" :: "r"(sb + SM_CBAR + 80));
        asm volatile("fence.mbarrier_init.release.cluster;" ::: "memory");
        mbar_expect(sb + SM_CBAR + CB_WQ * 8, 5 * HALF);
        auto k0 = [&]() {
            mbar_expect(sb + SM_CBAR + 80, HALF);
            tma3(sb, &P.tm[TM_KH], 0, (cta0 >> 2) * SK + (SK - WIN) + (cta0 & 3) * 64, sb + SM_CBAR + 80, POL_FIRST);
        };
        if (K0FIRST) k0();
#pragma unroll 1
        for (int i = 0; i < 5; i++) tma3(sb + SM_WQR + (i == 4 ? 0 : i + 1) * HALF, &P.tm[TM_WQ], (cta0 >> 2) * 3, (cta0 & 3) * 160 + i * 32, sb + SM_CBAR + CB_WQ * 8, POL_FIRST);
        if (!K0FIRST) k0();
    }
    __syncwarp();
    int id = cta0 * NTHR + threadIdx.x, tid, lane, g, t, key, warp, cta, mlp, rowc, roww, j40;
    uint32_t maskA, maskB, barw, subw, prow;
    auto fresh = [&]() {
        const int cw = __shfl_sync(~0u, id >> 5, 0);
        id = pin(id); tid = id & 255; lane = id & 31; g = lane >> 2; t = lane & 3; key = (g >> 1) + 4 * (g & 1);
        const uint32_t m = (g & 1) ? 0xffff0000u : 0x0000ffffu;
        maskA = (g & 2) ? 0u : m; maskB = (g & 2) ? m : 0u;
        warp = cw & 7; cta = cw >> 3;
        mlp = (cta & 3) == 3 ? 96 : (cta >> 2) * 3 + (cta & 3);
        rowc = (cta >> 2) * SK + (SK - WIN) + (cta & 3) * 64; roww = rowc + warp * 8;
        j40 = (cta & 3) * 40;
        barw = sb + SM_BAR + warp * 96; subw = sb + warp * SUB; prow = sb + SM_PART + warp * 768;
    };
    fresh();
    auto fresh_lane = [&]() { id = pin(id); tid = id & 255; lane = id & 31; g = lane >> 2; t = lane & 3; };
    auto pinf = [&](float v) { return __uint_as_float(pin(__float_as_uint(v) | (id >> 16))); };

    if (cta == NCTA) {
        const uint32_t ep = *(volatile unsigned*)&P.g->epoch;
        if (tid == 0) {
#pragma unroll 1
            for (int it = 0; it < SPIN; it++) { if (ll_tag(ld_rlx(&P.g->ll[0][0][192])) == ep * 4 + 2) break; __nanosleep(200); }
        }
        __syncthreads();
#pragma unroll 1
        for (int i = tid >> 6; i < 80; i += 4) {
            const int a = i * ((tid & 16) ? ACC_PITCH : ACC1_PITCH);
            if (!(tid & 8) || (a & 127)) *reinterpret_cast<uint4*>(P.g->acc + ((tid >> 4) & 3) * ACC_BYTES + (a & ~127) + (tid & 15) * 16) = make_uint4(0, 0, 0, 0);
        }
        __threadfence();
        __syncthreads();
        if (tid == 0) asm volatile("st.relaxed.gpu.global.u32 [%0], %1;" :: "l"(&P.g->zflag), "r"(ep + 1) : "memory");
        return;
    }
    TSTAMP(0);
    if (tid == 64) { uint32_t now; asm volatile("mov.u32 %0, %globaltimer_lo;" : "=r"(now)); sts32(sb + SM_T0, now); }

    const CUtensorMap* tmk = reinterpret_cast<const CUtensorMap*>(__shfl_sync(~0u, (u64)&P.tm[0] + (lane >> 5), 0));
    auto c4 = [&]() { return 32 * min(warp, 4) + 16 * (t >> 1) + 2 * g + (t & 1); };
    auto xcol = [&](int i, int tt) { return (i < 2 ? 64 * i + 8 * warp : 128 + 8 * (warp >> 1)) + 2 * tt; };
    uint2 xp;
    uint32_t px[3], small;
    auto issue_first = [&](int j) {
        mbar_expect(sb + SM_CBAR + 80 + j * 8, HALF);
        tma3(sb + j * HALF, tmk + TM_KH, 0, rowc + (j >> 1) * 256 + (j & 1) * 32, sb + SM_CBAR + 80 + j * 8, POL_FIRST);
    };
    if (elect()) {
        if (warp != 2) asm volatile("mbarrier.init.shared::cta.b64 [%0], 1;" :: "r"(sb + SM_CBAR + 64 + warp * 8));
#pragma unroll
        for (int i = 0; i < 9; i++) asm volatile("mbarrier.init.shared::cta.b64 [%0], 1;" :: "r"(barw + i * 8));
        asm volatile("mbarrier.init.shared::cta.b64 [%0], 1;" :: "r"(sb + SM_CBAR + warp * 8));
        asm volatile("mbarrier.init.shared::cta.b64 [%0], 1;" :: "r"(sb + SM_CBAR + 128 + warp * 8));
        if (warp < 3) asm volatile("mbarrier.init.shared::cta.b64 [%0], %1;" :: "r"(sb + SM_CBAR + 192 + warp * 8), "r"(warp == 2 ? 8 : 1));
        sts64(barw + 80, 0, 0);
        asm volatile("fence.mbarrier_init.release.cluster;" ::: "memory");
        asm volatile("prefetch.tensormap [%0];" :: "l"(tmk + warp) : "memory");
    }
    __syncwarp();
    asm volatile("ld.global.nc.v2.u32 {%0,%1}, [%2];" : "=r"(xp.x), "=r"(xp.y) : "l"(P.x + 4 * c4()) : "memory");
#pragma unroll
    for (int i = 0; i < 3; i++) asm volatile("ld.global.nc.u32 %0, [%1];" : "=r"(px[i]) : "l"(P.x + 4 * j40 + xcol(i, t)) : "memory");
    asm volatile("ld.relaxed.gpu.global.u32 %0, [%1];" : "=r"(small) : "l"(lane < 16 ? (const void*)(P.b1 + min(mlp, 95) * 16 + (lane & 14)) : (const void*)&P.g->epoch) : "memory");
    if (tid >= 192 && tid < 192 + NCB) sts32(sb + SM_CNT + (tid - 192) * 8, 0);
    unsigned char* accg = reinterpret_cast<unsigned char*>(__shfl_sync(~0u, (u64)P.g->acc + (lane >> 5), 0));
    auto release = [&](const uint4& tw) {
        uint32_t old;
        __syncwarp();
        asm volatile("atom.relaxed.cta.shared.add.u32 %0, [%1], 1;" : "=r"(old) : "r"(sb + SM_CNT + (tw.x & 0xf8)) : "memory");
        return old;
    };
    auto refill = [&](const uint4& tw, uint32_t old) {
        if (__any_sync(~0u, (old & 127) == 127 && (tw.y & 2))) {
            wait_until(lds32(sb + SM_T0) + tw.z);
            if (elect()) issue_half(tw.y, sb, rowc, cta, tmk);
            __syncwarp();
        }
    };
    __syncthreads();
    auto issue_paced = [&](int j0, int j1) {
        if (warp >= j0 && warp < j1) {
            wait_until(lds32(sb + SM_T0) + PACES + warp * PACE / 2);
            if (elect()) issue_first(warp);
            __syncwarp();
        }
    };

    uint32_t offV0, offV2;
    auto calc_offsets = [&]() {
        offV0 = subw + (6 * t) * 128 + ((g ^ ((6 * t) & 7)) << 4);
        offV2 = subw + (6 * t + 2) * 128 + ((g ^ ((6 * t + 2) & 7)) << 4);
    };
    calc_offsets();

    auto load_v = [&](uint4 (&v)[6], uint32_t so) {
        v[0] = lds128(offV0 + so); v[1] = lds128((offV0 ^ 16) + so + 128); v[2] = lds128(offV2 + so);
        v[3] = lds128((offV2 ^ 16) + so + 128); v[4] = lds128((offV0 ^ 64) + so + 512); v[5] = lds128((offV0 ^ 80) + so + 640);
    };
    auto issue_v = [&](auto I, int dw) {
        constexpr Step c = SCH.st[I.value];
        const uint32_t bar = barw + dw * 96 + c.slot * 8;
        mbar_expect(bar, SUB);
        tma_v(subw + dw * SUB + c.slot * TILE, tmk, roww * 3 + dw * 24 + c.unit * 768, bar);
    };
    auto refill2 = [&](auto I) { __syncwarp(); if (elect()) issue_v(I, 0); };
    uint4 wq0[6], wqh[3], wq1[6];
    auto load_wq1 = [&](int i) { wq1[i] = lds128((i == 2 ? offV2 : i == 3 ? (offV2 ^ 16) + 128 : (offV0 ^ (i * 16)) + i * 128) + SM_WQ + TILE); };
    auto load_wq = [&]() {
        load_v(wq0, SM_WQ);
        const uint32_t so = SM_WQR - ((warp + 1) >> 1) * SUB;
        wqh[0] = lds128(((warp & 1) ? (offV2 ^ 16) + 128 : offV0) + so);
        wqh[1] = lds128(((warp & 1) ? (offV0 ^ 64) + 512 : (offV0 ^ 16) + 128) + so);
        wqh[2] = lds128(((warp & 1) ? (offV0 ^ 80) + 640 : offV2) + so);
#pragma unroll
        for (int i = 0; i < NWQ1; i++) load_wq1(i);
    };
    uint4 kr[8][6];
    const unsigned char* rap;
    u64 rw[2];
    auto look_rw = [&]() { rw[0] = ld_rlx(rap); rw[1] = ld_rlx(rap + 40 * ACC_PITCH); };
    auto q_proj = [&](auto L, uint32_t (&p)[3], uint32_t pst) {
        if (L.value == 0 && g >= 4) p[0] = p[1] = p[2] = ONES;
        float a[3][4], b[3][4];
        const uint32_t dH = __byte_perm(p[2], 0, (warp & 1) ? 0x3232 : 0x1010);
        const uint32_t dA = __byte_perm(p[0], 0, 0x1010), dB = __byte_perm(p[0], 0, 0x3232), dC = __byte_perm(p[1], 0, 0x1010), dD = __byte_perm(p[1], 0, 0x3232);
#pragma unroll
        for (int i = NWQ1; i < 3; i++) load_wq1(i);
#pragma unroll
        for (int j = 0; j < 3; j++) { a[j][0] = a[j][1] = a[j][2] = a[j][3] = 0.f; mma(a[j], wq0[j], dA & maskA, dA & maskB); }
#pragma unroll
        for (int j = 0; j < 3; j++) { b[j][0] = b[j][1] = b[j][2] = b[j][3] = 0.f; mma(b[j], wq0[j + 3], dB & maskA, dB & maskB); }
#pragma unroll
        for (int j = 0; j < 3; j++) mma(a[j], wqh[j], dH & maskA, dH & maskB);
#pragma unroll
        for (int i = 3; i < 6; i++) load_wq1(i);
        if (L.value == 1 && P4AT == 2) refill2(IC<4>{});
#pragma unroll
        for (int j = 0; j < 3; j++) mma(b[j], wq1[j], dC & maskA, dC & maskB);
#pragma unroll
        for (int j = 0; j < 3; j++) mma(a[j], wq1[j + 3], dD & maskA, dD & maskB);
#pragma unroll
        for (int j = 0; j < 3; j++) {
            if (L.value) {
#pragma unroll
                for (int k = 0; k < 2; k++) { a[j][k] += b[j][k]; add_if(t & 2, a[j][k], a[j][k + 2], b[j][k + 2]); }
                sts64f(pst + j * 256, a[j][0], a[j][1]);
            } else sts128f(pst + j * 256, a[j][0] + b[j][0], a[j][1] + b[j][1], a[j][2] + b[j][2], a[j][3] + b[j][3]);
        }
        CSTAMP(23, __float_as_uint(a[2][1]));
        uint32_t tag;
        if (L.value) tag = lds32(sb + SM_EPOCH) * 4 + 3;
        u64* pub = L.value ? &P.g->ll[0][cta][tid] : &P.g->l0[cta][tid];
        if (L.value == 0) asm volatile("fence.proxy.async.shared::cta;" ::: "memory");
        TSTAMPL(21);
        __syncthreads();
        if (!L.value) tag = lds32(sb + SM_EPOCH) * 4 + 1;
#pragma unroll 1
        for (int k = 0; k < 2 - L.value; k++) st_rlx_if(tid < 192, pub + k * 192, ll_pack(sum8(sb + (k ? SM_CSP : SM_PART) + tid * 4, 768), tag));
        TSTAMPL(23);
            CSTAMP(24, tag);
    };
    auto ln_stats = [&]() {
        float ss = ln_part(xp, lane);
        ss += shx(ss, 8); ss += shx(ss, 4); ss += shx(ss, 2); ss += shx(ss, 1);
        stsf(sb + SM_STAT + min(warp, 5) * 8 + (lane >> 4) * 4, ss);
    };
    auto ln_final = [&](float& mean, float& rstd) {
        float2 v[5];
#pragma unroll
        for (int w = 0; w < 5; w++) v[w] = lds64f(sb + SM_STAT + w * 8);
        mean = sum5(v[0].x, v[1].x, v[2].x, v[3].x, v[4].x) * (1.f / D_MODEL);
        const float msq = sum5(v[0].y, v[1].y, v[2].y, v[3].y, v[4].y) * (1.f / D_MODEL);
        rstd = ln_rstd(mean, msq);
        stsf(sb + SM_FXS, msq);
    };
    auto q_addr = [&](int d) { return sb + SM_VEC + (((d >> 1) & 1) * 4 + ((d >> 3) & 3)) * 48 + (d >> 5) * 8 + ((d >> 2) & 1) * 4 + (d & 1) * 2; };
    {
#pragma unroll
        for (int u = 0; u < 8; u++)
#pragma unroll
            for (int i = 0; i < 6; i++) kr[u][i] = lds128(sb + SM_CS + (u * 6 + i) * 16);
        issue_paced(1, NIM);
        ln_stats();
        if (tid == 16) { sts32(sb + SM_EPOCH, small); sts32(sb + SM_M1, ~0u); }
        else if (tid < 16) sts32(sb + SM_B1 + tid * 4, (tid & 1) ? small & 0xffff0000u : small << 16);
        mbar_wait(sb + SM_CBAR + CB_WQ * 8, 0);
        load_wq();
        q_proj(IC<0>{}, px, sb + (t < 2 ? SM_PART : SM_CSP) + warp * 768 + (8 * g + 4 * (t & 1)) * 4);
    }
    {
        uint32_t offQ, offL;
        auto calc_ql = [&]() {
            offQ = pin(sb + SM_VEC + (lane & 7) * 48);
            offL = pin(subw + lane * 16);
        };

        auto issue_w = [&](auto L, int which) {
            const uint32_t bar = sb + SM_CBAR + (CB_W1 + which) * 8;
            if (mlp == 96) asm volatile("mbarrier.arrive.shared::cta.b64 _, [%0];" :: "r"(bar) : "memory");
            else {
                mbar_expect(bar, 20480);
                if (which) {
                    tma3(sb + (L.value ? 3 * TILE : SM_W2), tmk + TM_W2, 0, mlp * 16, bar, POL_FIRST);
                    if (!L.value) tma3_pf(tmk + TM_W2, 0, mlp * 16, POL_NORMAL);
                    if (!L.value) asm volatile("cp.async.bulk.prefetch.L2.global.L2::cache_hint [%0], 20480, %1;" :: "l"(P.w1 + mlp * 10240), "l"((u64)POL_NORMAL << 32) : "memory");
                }
                else asm volatile("cp.async.bulk.tensor.3d.shared::cluster.global.mbarrier::complete_tx::bytes.L2::cache_hint [%0], [%1, {%2, %3, %3}], [%4], %5;"
                                  :: "r"(sb + (L.value ? 2 * TILE : SM_W1)), "l"(tmk + TM_W1), "r"(mlp * 16), "r"(0), "r"(bar), "l"((u64)POL_FIRST << 32) : "memory");
            }
        };
        float acc[3][4];
        auto load_q = [&](uint4 (&qf)[3]) {
#pragma unroll
            for (int i = 0; i < 3; i++) qf[i] = lds128(offQ + i * 16);
        };
        auto softmax = [&](float S0, float S1, float S2, float S3) {
            int mi = __float_as_int(fmaxf(fmaxf(S0, S1), fmaxf(S2, S3)));
            mi = __reduce_max_sync(~0u, mi ^ ((mi >> 31) & 0x7fffffff));
            const float mrun = __int_as_float(mi ^ ((mi >> 31) & 0x7fffffff));
            const float p0 = ex2((S0 - mrun) * CS), p1 = ex2((S1 - mrun) * CS), p2 = ex2((S2 - mrun) * CS), p3 = ex2((S3 - mrun) * CS);
            const uint32_t pa = pack_bf(p0, p1), pb = pack_bf(p2, p3), pw = prow + 256 + (key >> 1) * 80 + t * 4 + (key & 1) * 2;
            sts16(pw, pa); sts16(pw + 16, pa >> 16); sts16(pw + 32, pb); sts16(pw + 48, pb >> 16);
            __syncwarp();
#pragma unroll
            for (int j = 0; j < 3; j++) acc[j][0] = acc[j][1] = acc[j][2] = acc[j][3] = 0.f;
            return make_float2(mrun, (p0 + p1) + (p2 + p3));
        };
        auto pv = [&](const uint4 (&v)[6], uint32_t pp) {
            const uint32_t dA = __byte_perm(pp, 0, 0x1010), dB = __byte_perm(pp, 0, 0x3232);
            mma(acc[0], v[0], dA & maskA, dA & maskB); mma(acc[1], v[1], dA & maskA, dA & maskB); mma(acc[2], v[2], dA & maskA, dA & maskB);
            mma(acc[0], v[3], dB & maskA, dB & maskB); mma(acc[1], v[4], dB & maskA, dB & maskB); mma(acc[2], v[5], dB & maskA, dB & maskB);
        };
        auto sa = [&]() { return prow + 256 + t * 32 + g * 4; };
        auto pass1 = [&]() {
            if (NIM < NI1) issue_paced(NIM, NI1);
            fresh();
            calc_ql();
            __syncthreads();
            sts64(prow + lane * 8, xp.x, xp.y);
            int e = 0;
            const uint4* tab = P.tile + (warp >> 2);
            uint4 tw = tab[0];
            uint32_t ka[3];
#pragma unroll
            for (int j = 0; j < 3; j++) ka[j] = pin(subw + key * 384 + j * 128 + ((t ^ ((3 * key + j) & 7)) << 4));
            auto load_k = [&](uint4 (&v)[6], uint32_t so) {
#pragma unroll
                for (int i = 0; i < 6; i++) v[i] = lds128(((i & 1) ? ka[i >> 1] ^ 64 : ka[i >> 1]) + so);
            };
            const uint32_t s0 = pin(prow + 256 + g * 4), sca = pin(sb + SM_SC + warp * 128 + g * 16);
#pragma unroll 1
            do {
                const uint4 tn = tab[2 * e + 2];
                uint4 v[6], qf[3];
                if (tw.x & (G_A | G_B | G_C)) {
                    if ((tw.x & G_A) && warp == 7 && elect()) {
                        mbar_expect(sb + SM_CBAR + CB_SNAP * 8, HALF);
                        asm volatile("cp.async.bulk.shared::cluster.global.mbarrier::complete_tx::bytes [%0], [%1], 12288, [%2];"
                                     :: "r"(sb + SM_SNAP), "l"(&P.g->l0[cta & ~3][0]), "r"(sb + SM_CBAR + CB_SNAP * 8) : "memory");
                    }
                    if (tw.x & G_B) {
                        if (warp < 6) {
                            mbar_wait(sb + SM_CBAR + CB_SNAP * 8, 0);
                            float qc[2] = {0.f, 0.f}, mean, rstd;
#pragma unroll 1
                            for (int k = 0; k < 2; k++) {
                                u64 qw[4];
#pragma unroll
                                for (int i = 0; i < 4; i++) { const uint2 x = lds64(sb + SM_SNAP + i * 3072 + k * 1536 + tid * 8); qw[i] = x.x | (u64)x.y << 32; }
                                qc[0] = qc[1];
                                qc[1] = ll_gather<384>(&P.g->l0[cta & ~3][k * 192 + tid], lds32(sb + SM_EPOCH) * 4 + 1, qw);
                            }
                            ln_final(mean, rstd);
                            stsf(sb + SM_CS + tid * 4, qc[1]);
                            const float q = (qc[0] - mean * qc[1]) * rstd;
                            sts16(q_addr(tid), pack_bf(q, q));
                        }
                        __syncthreads();
                        if (warp == 7 && elect()) issue_half(UC<load_word(12)>::value, sb, rowc, cta, tmk);
                        TSTAMP(2);
                    }
                    if (tw.x & G_C) {
                        load_k(v, (e - LATEAT) * TILE);
                        load_q(qf);
                        stsf(s0 + (e - LATEAT) * 32, score(v, qf));
                    }
                }
                load_q(qf);
                mbar_wait(sb + SM_CBAR + (tw.x & 0xf8), tw.x >> 31);
                TRACE(e);
                load_k(v, tw.x & 0x3f000);
                const uint32_t old = release(tw);
                const float s = score(v, qf);
                uint32_t m;
                {
                    uint32_t a[6];
#pragma unroll
                    for (int i = 0; i < 6; i++) a[i] = bf2_amax(bf2_amax(v[i].x, v[i].y), bf2_amax(v[i].z, v[i].w));
                    m = bf2_amax(bf2_amax(bf2_amax(a[0], a[1]), bf2_amax(a[2], a[3])), bf2_amax(a[4], a[5]));
                }
                m = bf2_amax(m, m >> 16) & 0x7f80;
                m = max(m, __shfl_xor_sync(~0u, m, 1));
                stsf(s0 + e * 32, s);
                m = max(m, __shfl_xor_sync(~0u, m, 2));
                refill(tw, old);
                const uint32_t b = min(max(m, 15u << 7) - (15u << 7), 126u << 7);
                const uint32_t dn = ((127u << 7) - b) * 0x10001u, up = ((127u << 7 | 0x8000u) + b) * 0x10001u;
                uint32_t c[18], any = m > (141u << 7);
#pragma unroll
                for (int i = 0; i < 6; i++) {
                    const uint32_t y0 = bf2_mul(v[i].x, dn), y1 = bf2_mul(v[i].y, dn), y2 = bf2_mul(v[i].z, dn), y3 = bf2_mul(v[i].w, dn);
                    v[i] = make_uint4(bf2_fma(y0, up, v[i].x), bf2_fma(y1, up, v[i].y), bf2_fma(y2, up, v[i].z), bf2_fma(y3, up, v[i].w));
                    any |= v[i].x | v[i].y;
                    any |= v[i].z | v[i].w;
                    const uint32_t hb = __byte_perm(y2, y3, 0x7531);
                    c[3 * i] = __byte_perm(y0, y1, 0x6420); c[3 * i + 1] = __byte_perm(y2, y3, 0x6420);
                    c[3 * i + 2] = __byte_perm(y0, y1, 0x7531) | __funnelshift_r(hb, hb, 4);
                }
                asm volatile("st.shared.u8 [%0], %1;" :: "r"(sca + (e & 3) * 4 + (e >> 2)), "r"((b >> 7) + 63) : "memory");
                const bool rare = __any_sync(~0u, any);
                k_keep(kr, c, e, offL);
                if (rare) k_rare(v[0], v[1], v[2], v[3], v[4], v[5], m > (141u << 7), e, warp, lane);
                tw = tn;
            } while (++e < 16);
            asm volatile("fence.proxy.async.shared::cta;" ::: "memory");
            __syncwarp();
            TSTAMP(10);
            fresh(); calc_offsets();
            {
                const uint2 st = lds64(barw + 80);
                const uint32_t xa = sb + SM_EXC + warp * 128 + (lane & 15) * 8 + 4;
                uint32_t pos = lds32(xa), lt;
                asm volatile("mov.u32 %0, %lanemask_lt;" : "=r"(lt));
                if (lane >= st.x) pos = 0x80000000u;
                const bool dup = (__match_any_sync(~0u, pos >> 16) & lt) && lane < st.x;
                if (lane < 16) sts32(xa, dup ? pos | 0x40000000u : pos);
                if (__any_sync(~0u, dup)) sts32(barw + 84, st.y | 0x10000u);
                const float2 ml = softmax(ldsf(sa()), ldsf(sa() + 128), ldsf(sa() + 256), ldsf(sa() + 384));
                sts64f(sb + SM_ML + warp * 8, ml.x, warp_sum(ml.y));
            }
            u64 pm = 0, pl = 0;
#pragma unroll 1
            do {
                const uint4 tn = tab[2 * e + 2];
                if (tw.x & (G_A | G_B | G_C)) {
                    if (tw.x & G_A) {
                        if (lane < 24) st_rlx(&P.g->ll[0][cta][warp * 24 + lane], 0ull);
                        else if (lane < 28) st_rlx(&P.g->ll[0][cta][168 + warp * 4 + lane], ll_pack(ldsf(sb + SM_ML + warp * 8 + (lane & 1) * 4), lds32(sb + SM_EPOCH) * 4 + 2));
                    }
                    if (warp == 2) {
                        if (tw.x & G_B) ld_rlx2(&P.g->ll[0][cta ^ (lane >> 3)][192 + (lane & 7) * 4], pm, pl);
                        if (tw.x & G_C) head_weight(&P.g->ll[0][cta ^ (lane >> 3)][192 + (lane & 7) * 4], pm, pl, 0, lane);
                    }
                    __syncwarp();
                }
                const uint32_t pp = lds32(prow + 256 + t * 80 + ((tw.x >> 20) & 255));
                mbar_wait(sb + SM_CBAR + (tw.x & 0xf8), tw.x >> 31);
                TRACE(e);
                uint4 v[6];
                load_v(v, tw.x & 0x3f000);
                refill(tw, release(tw));
                pv(v, pp);
                tw = tn;
            } while (++e < 32);
        };
        uint32_t osa, ora, owa, orow, otag;
        u64* olb;
        float xc;
        auto o_setup = [&](auto L) {
            fresh();
            const int lz = lane, d = warp * 24 + min(lz, 23);
            osa = pin(prow + ((lz >> 2) * 8 + (lz & 1) * 4 + (lz & 2)) * 4);
            ora = pin(sb + SM_PART + d * 4);
            olb = pin(&P.g->ll[L.value][cta & ~3][d]);
            orow = pin((lz & 1) + 2 * (lz & 2) + 2 * (lz >> 4));
            owa = pin(sb + SM_RING + warp * 1536 + orow * 64 + ((((lz >> 2) & 3) ^ (orow >> 1)) << 4));
            otag = lds32(sb + SM_EPOCH) * 4 + 2 + 2 * L.value;
            uint32_t x; asm volatile("ld.shared.u16 %0, [%1];" : "=r"(x) : "r"(prow + ((cta & 1) * 16 + (lz >> 3) * 4 + (cta & 2) + ((lz >> 2) & 1)) * 8 + (lz & 3) * 2) : "memory");
            xc = bf_lo(x) * (1.f / 32);
        };
        auto wo_at = [&](auto A) {
            constexpr uint32_t x = WOP ^ A.value * 0x11111;
            if constexpr (A.value > 0 && ((x - 0x11111) & ~x & 0x88888) != 0) {
                if ((WOP >> (4 * warp) & 15) == A.value) {
                    mbar_wait(sb + SM_CBAR + CB_REL * 8, 0);
                    if (elect()) {
                        const uint32_t bar = sb + SM_CBAR + (CB_WO + warp) * 8;
                        mbar_expect(bar, HALF);
                        tma3(sb + SM_RING + (warp + (warp < 2 ? 3 : -2)) * HALF, tmk + TM_WO, (cta & 3) + 4 * warp, (cta >> 2) * DH, bar, POL_FIRST);
                    }
                    __syncwarp();
                }
            }
        };
        static_assert(ring_hs(64) == 3, "wo");
        auto pass2 = [&]() {
            constexpr IC<1> L{};
            if (P4AT == 0) refill2(IC<4>{});
            if (P2LATE == 1 && warp >= 4) refill2(IC<2>{});
            uint4 tb[8][3];
            auto load_tb = [&](auto I) {
#pragma unroll
                for (int i = 0; i < 3; i++) tb[I.value][i] = lds128(offL + (I.value >> 1) * TILE + ((I.value & 1) * 3 + i) * 512);
            };
            const u64* qb = &P.g->ll[0][cta & ~3][min(tid, 191)];
            {
                uint32_t x[2];
                fx2_wait<2>([&](int i) { return rap + i * 40 * ACC_PITCH; }, look_rw, rw, sb + SM_MSQ, ldsf(sb + SM_MSQ + 4), x);
                xp = make_uint2(x[0], x[1]);
                CSTAMP(25, xp.y);
            }
            ln_stats();
            u64 qw[4];
            ll_look<256>(qb, qw);
            const float cs = ldsf(sb + SM_CS + min(tid, 191) * 4);
            const uint32_t qtag = lds32(sb + SM_EPOCH) * 4 + 3, qa = pin(q_addr(min(tid, 191)));
            fresh_lane();
            offQ = sb + SM_VEC + (lane & 7) * 48; offL = subw + lane * 16;
            __syncthreads();
            auto vwait = [&](auto I) { mbar_wait(barw + IC<SCH.st[I.value].slot>::value * 8, IC<SCH.st[I.value].par>::value); };
            bool ok;
            uint32_t m1, m1n;
            {
                float mean, rstd;
                ln_final(mean, rstd);
                const float sq = shx(rstd * 0x1p64f, 0), q0 = shx(-mean * cs * sq, 0);
                CSTAMP(26, __float_as_uint(q0));
                static_for<0, NPRE>(load_tb);
                if (P4AT == 1) refill2(IC<4>{});
                if (S0EARLY) refill2(IC<5>{});
                m1n = m1 = lds32(sb + SM_M1);
                sts64(prow + lane * 8, xp.x, xp.y);
                sts128f(prow + 256 + lane * 16, 0.f, 0.f, 0.f, 0.f);
                const float q = ll_gather<256>(qb, qtag, qw) * sq + q0;
                sts16(qa, pack_bf(q, q));
                TSTAMPL(24);
                CSTAMP(27, __float_as_uint(q));
            }
            if (!S0EARLY) refill2(IC<5>{});
            if (P2LATE == 2 && warp >= 4) refill2(IC<2>{});
            if (P4AT == 3) refill2(IC<4>{});
            if (NOWIN & 1) { if (warp < 6) refill2(IC<0>{}); if (warp >= 5) refill2(IC<3>{}); }
            if (NOWIN & 2) { if (warp >= 6) refill2(IC<1>{}); if (warp < 4) refill2(IC<2>{}); }
            if (NOWIN & 4) { if (warp >= 6) refill2(IC<0>{}); if (warp < 6) refill2(IC<1>{}); }
            if (NOWIN & 8) { if (warp < 5) refill2(IC<3>{}); if (warp >= 4) refill2(IC<2>{}); }
            __syncthreads();
            uint4 qf[3];
            load_q(qf);
            CSTAMP(28, qf[0].x);
            float S[4], d[2][4];
            auto vload = [&](auto I) {
                constexpr int p = I.value;
                constexpr Step c = SCH.st[p];
                load_v(kr[p & 7], c.slot * TILE);
                if constexpr (c.next >= 0) refill2(IC<c.next>{});
                if constexpr (p == 11) { __syncwarp(); if (elect()) asm volatile("mbarrier.arrive.shared::cta.b64 _, [%0];" :: "r"(sb + SM_CBAR + CB_REL * 8) : "memory"); }
            };
            static_for<0, 96>([&](auto F) {
                constexpr int f = F.value, i = f % 6, u = kunit(f / 6), w = 3 * f % 12;
                uint4 (&src)[3] = *reinterpret_cast<uint4 (*)[3]>(f < 32 ? &tb[f / 4 & 7][0] : &kr[(f / 8 + 4) & 7][(f / 4 & 1) * 3]);
                const uint4 a = k_unpack(word<w % 4>(src[w / 4]), word<(w + 1) % 4>(src[(w + 1) / 4]), word<(w + 2) % 4>(src[(w + 2) / 4]), m1);
                if constexpr (f < 32 ? f % 4 == M1AT : f % 8 == M1P) m1 = m1n;
                if constexpr (f % 4 == 3 && f / 4 + NPRE < 8) {
                    load_tb(IC<f / 4 + NPRE>{});
                    if constexpr ((f / 4 + NPRE) & 1) { refill2(IC<5 + (f / 4 + NPRE) / 2>{}); m1n = lds32(sb + SM_M1); }
                }
                if constexpr (i < 2) d[i][0] = d[i][1] = d[i][2] = d[i][3] = 0.f;
                mma(d[i & 1], a, (i & 1) ? qf[i / 2].z : qf[i / 2].x, (i & 1) ? qf[i / 2].w : qf[i / 2].y);
                if constexpr (i == 5) {
                    if constexpr (u == 11 || ((u & 3) == 0 && u != 8)) S[u >> 2] = (d[0][0] + d[0][3]) + (d[1][0] + d[1][3]);
                    else add_if(t == (u & 3), S[u >> 2], d[0][0] + d[0][3], d[1][0] + d[1][3]);
                    if constexpr (f < 64) S[u >> 2] = shx(S[u >> 2], 0);
                }
                if constexpr (f == 31) { fresh(); calc_offsets(); ok = mbar_test(barw + IC<SCH.st[0].slot>::value * 8, 0); }
                if constexpr (f == 48) {
                    const uint2 x = lds64(sb + SM_EXC + warp * 128 + (lane & 15) * 8);
                    const float c = k_side(sb, x);
                    if (x.y < 0x40000000u) stsf(prow + 256 + (x.y >> 16), c);
                }
                if constexpr (f >= 32 && f % 8 == 7) {
                    if constexpr (PARKS >> (f / 8 - 4) & 1) {
                        constexpr int p = popc(PARKS & ((1 << (f / 8 - 4)) - 1));
                        if (!ok) vwait(IC<p>{});
                        vload(IC<p>{});
                        m1n = lds32(sb + SM_M1);
                        ok = mbar_test(barw + IC<SCH.st[p + 1].slot>::value * 8, IC<SCH.st[p + 1].par>::value);
                    }
                }
            });
            uint32_t bad = lds32(barw + 84);
            const uint32_t sc = lds32(sb + SM_SC + tid * 4);
            __syncwarp();
            if (bad) k_fix(P.k + (size_t)roww * DH, bad, warp, lane);
            TSTAMP(30);
            CSTAMP(29, __float_as_uint(S[2]));
            const float2 ml = softmax(S[0] * __uint_as_float((sc & 255) << 23) + ldsf(sa()), S[1] * __uint_as_float((sc & 0xff00) << 15) + ldsf(sa() + 128),
                                      S[2] * __uint_as_float((sc & 0xff0000) << 7) + ldsf(sa() + 256), S[3] * __uint_as_float((sc >> 24) << 23) + ldsf(sa() + 384));
            uint4 pq[4];
#pragma unroll
            for (int j = 0; j < 4; j++) pq[j] = lds128(prow + 256 + t * 80 + j * 16);
            TSTAMP(1);
            CSTAMP(30, pq[3].w);
            if (!ok) vwait(IC<NPARK>{});
            float ac2[3][4];
#pragma unroll
            for (int j = 0; j < 3; j++) ac2[j][0] = ac2[j][1] = ac2[j][2] = ac2[j][3] = 0.f;
            const uint32_t sl = (g & 1) ? 0x1044 : 0x4410, sh = (g & 1) ? 0x3244 : 0x4432;
            const uint32_t sA0 = (g & 2) ? 0x4444 : sl, sA1 = (g & 2) ? sl : 0x4444, sB0 = (g & 2) ? 0x4444 : sh, sB1 = (g & 2) ? sh : 0x4444;
            u64 pm = 0, pl = 0;
            static_for<NPARK, 16>([&](auto I) {
                constexpr int p = I.value;
                static_assert(p - SCH.st[p].mma0 < 8, "buffer in use");
                vload(I);
                if constexpr (p < 15) ok = mbar_test(barw + IC<SCH.st[p + 1].slot>::value * 8, IC<SCH.st[p + 1].par>::value);
                static_for<SCH.st[p].mma0, SCH.st[p].mma0 + SCH.st[p].nmma>([&](auto J) {
                    constexpr int u = SCH.st[J.value].unit;
                    const uint32_t pp = word<u & 3>(pq[u >> 2]), a0 = __byte_perm(pp, 0, sA0), a1 = __byte_perm(pp, 0, sA1), b0 = __byte_perm(pp, 0, sB0), b1 = __byte_perm(pp, 0, sB1);
#pragma unroll
                    for (int j = 0; j < 3; j++) mma(acc[j], kr[J.value & 7][j], a0, a1);
#pragma unroll
                    for (int j = 0; j < 3; j++) mma(ac2[j], kr[J.value & 7][j + 3], b0, b1);
                });
                if constexpr (p == NPARK) {
                    const float l = warp_sum(ml.y);
                    if (lane < 28) st_rlx(&P.g->ll[1][cta][lane < 24 ? warp * 24 + lane : 168 + warp * 4 + lane], lane < 24 ? 0ull : ll_pack((lane & 1) ? l : ml.x, lds32(sb + SM_EPOCH) * 4 + 4));
                }
                if constexpr (p == HWAT) { if (warp == 6) ld_rlx2(&P.g->ll[1][cta ^ (lane >> 3)][192 + (lane & 7) * 4], pm, pl); }
                if constexpr (p == 13) o_setup(L);
                if constexpr (p == HWAT + 2) { if (warp == 6) head_weight(&P.g->ll[1][cta ^ (lane >> 3)][192 + (lane & 7) * 4], pm, pl, 1, lane); }
                wo_at(IC<p - 10>{});
                if constexpr (p < 15) { if (!ok) mbar_wait(barw + IC<SCH.st[p + 1].slot>::value * 8, IC<SCH.st[p + 1].par>::value); TRACE(33 + p); }
            });
#pragma unroll
            for (int j = 0; j < 3; j++)
#pragma unroll
                for (int k = 0; k < 2; k++) { acc[j][k] += ac2[j][k]; add_if(t & 2, acc[j][k], acc[j][k + 2], ac2[j][k + 2]); }
        };

        const unsigned char* ap;
        uint32_t hpa, hsa, hst, w2a, la;
        uint2 b2v;
        float b1v, cs1;
        auto mlp_global = [&](auto L) {
            const int cz = c4();
            ap = accg + 2 * L.value * ACC_BYTES + (cz >> 1) * ACC1_PITCH + (cz & 1) * 16;
            if (L.value) ap = pin(ap);
            rap = pin(accg + (2 * L.value + 1) * ACC_BYTES + (cz >> 2) * ACC_PITCH + (cz & 3) * 8);
            asm volatile("ld.global.nc.v2.u32 {%0,%1}, [%2];" : "=r"(b2v.x), "=r"(b2v.y) : "l"(P.b2 + 4 * cz));
        };
        auto mlp_shared = [&](auto L) {
            const int lz = lane;
            hpa = pin(sb + SM_PART + warp * 256 + ((lz & 2) * 4 + (lz >> 2)) * 16 + (L.value ? 0 : (lz & 1) * 4));
            hsa = pin(sb + SM_PART + (lz & 15) * 16); hst = pin(sb + SM_PART + (lz & 15) * 16 + warp * 256 + 8 + (lz >> 4) * 4);
            w2a = pin(sb + (L.value ? 3 * TILE : SM_W2) + ((lz & 3) * 10 + 2 * warp) * 128 + (((lz >> 2) ^ ((2 * lz + 2 * warp) & 6)) << 4));
            la = sb + (L.value ? 2 * TILE : SM_W1) + warp * 4096 + (lz & 4) * 512 + (lz & 2) * 64 + (lz & 1) * 32 + (lz >> 4) * 64 + ((((lz >> 3) ^ (lz >> 1)) & 1) << 4);
            b1v = ldsf(sb + SM_B1 + (lz & 15) * 4);
            if (L.value) { la = pin(la); cs1 = ldsf(sb + SM_ML + (lz & 15) * 4); }
            else fresh();
        };
        uint32_t pa;
        unsigned char* rop;
        uint32_t wpa;
        float sc1;
        auto sum_setup = [&](auto L) {
            const int lz = lane, word = warp * 128 + (cta & 3) * 32 + lz;
            wpa = pin(sb + SM_RING + warp * 1536 + ((((lz >> 2) * 8 + (lz & 1) * 4) * 4) ^ ((((lz >> 1) ^ (lz >> 4)) & 1) ? 256 + 64 : 0)));
            sc1 = pinf(fx2_scale(ldsf(sb + SM_FXS)) * 0.25f);
            pa = pin(sb + SM_RING + warp * 256 + ((lz * 4) ^ ((warp & 1) * 64)));
            rop = pin(accg + 2 * L.value * ACC_BYTES + (word >> 3) * ACC1_PITCH + (word & 7) * 4);
        };
        auto out_proj = [&](auto L) {
            TSTAMP2(3);
            CSTAMP(0, __float_as_uint(acc[2][1]));
            __syncwarp();
#pragma unroll
            for (int j = 0; j < 3; j++) {
                if (L.value == 0 && (t & 2)) { acc[j][0] = acc[j][2]; acc[j][1] = acc[j][3]; }
                sts64f(osa + 256 * j, acc[j][0], acc[j][1]);
            }
            __syncthreads();
            {
                float s[8];
#pragma unroll
                for (int w = 0; w < 8; w++) s[w] = ldsf(ora + w * 768);
                const uint4 fa = lds128(sb + SM_FAC), fb = lds128(sb + SM_FAC + 16);
            CSTAMP(1, __float_as_uint(s[0]));
                const float own = ((s[0] * __uint_as_float(fa.x) + s[1] * __uint_as_float(fa.y)) + (s[2] * __uint_as_float(fa.z) + s[3] * __uint_as_float(fa.w))) +
                                  ((s[4] * __uint_as_float(fb.x) + s[5] * __uint_as_float(fb.y)) + (s[6] * __uint_as_float(fb.z) + s[7] * __uint_as_float(fb.w)));
                st_rlx_if(lane < 24, olb + (cta & 3) * 256, ll_pack(own, otag));
            CSTAMP(2, __float_as_uint(own));
            }
            TSTAMPL(29);
            if (L.value) wo_at(IC<6>{});
            if (L.value == 0 && warp == 7) {
#pragma unroll 1
                for (int it = 0; it < SPIN; it++) {
                    uint32_t v; asm volatile("ld.acquire.gpu.global.u32 %0, [%1];" : "=r"(v) : "l"(&P.g->zflag) : "memory");
                    if (__all_sync(~0u, v == (otag >> 2) + 1)) break;
                }
            }
            constexpr int NW = L.value ? NWO1 : 3;
            uint4 v[5][3];
            u64 ow[4];
            auto read_wo = [&](auto J) {
#pragma unroll
                for (int p = 0; p < 3; p++) v[J.value][p] = lds128(((J.value & 1) ? owa ^ 144 : owa) + ring_hs(64 + J.value) * HALF + p * 512);
            };
            static_for<0, NW>([&](auto J) {
                if (L.value && J.value == 0) { sum_setup(L); maskA = pin(maskA); maskB = pin(maskB); }
                if ((L.value ? OPOLL1 : OPOLL) == J.value) { ll_look<256>(olb, ow); if (L.value) { mlp_shared(L); mlp_global(L); } }
                mbar_wait(sb + SM_CBAR + (CB_WO + J.value) * 8, L.value);
                read_wo(J);
                if (L.value == 0 && W1AT0 == J.value + 1) {
                    __syncwarp();
                    if (elect() && cnt_inc(sb + SM_CNT + CB_W1 * 8, 7) == 7) issue_w(L, 0);
                    __syncwarp();
                }
                if (L.value == 1 && (W1AT1 == J.value + 1 || W2AT1 == J.value + 1)) {
                    if (warp == 7 && elect()) { if (W1AT1 == J.value + 1) issue_w(L, 0); if (W2AT1 == J.value + 1) issue_w(L, 1); }
                    __syncwarp();
                }
            });
            sched_fence();
            const float o = ll_gather<256>(olb, otag, ow);
            CSTAMP(3, __float_as_uint(o));
            TSTAMP2(4);
            bool ok = true;
            if constexpr (NW < 5) ok = mbar_test(sb + SM_CBAR + (CB_WO + 4) * 8, L.value);
            if constexpr (NW < 4) ok &= mbar_test(sb + SM_CBAR + (CB_WO + 3) * 8, L.value);
            const uint32_t od = pack_bf(o, o);
            uint32_t oa[3], ob[3];
#pragma unroll
            for (int p = 0; p < 3; p++) { const uint32_t op = __shfl_sync(~0u, od, 8 * p + orow); oa[p] = op & maskA; ob[p] = op & maskB; }
            CSTAMP(4, oa[2]);
            float y[5][4];
#pragma unroll
            for (int j = 0; j < 5; j++) y[j][0] = y[j][1] = y[j][2] = y[j][3] = 0.f;
            auto rest = [&]() {
                if (!ok) static_for<NW, 5>([&](auto J) { mbar_wait(sb + SM_CBAR + (CB_WO + J.value) * 8, L.value); });
                static_for<NW, 5>(read_wo);
                __syncwarp();
            };
            if (L.value) rest();
#pragma unroll
            for (int p = 0; p < 3; p++)
#pragma unroll
                for (int j = 0; j < NW; j++) mma(y[j], v[j][p], oa[p], ob[p]);
            if (!L.value) { rest(); sum_setup(L); }
#pragma unroll
            for (int p = 0; p < 3; p++)
#pragma unroll
                for (int j = NW; j < 5; j++) mma(y[j], v[j][p], oa[p], ob[p]);
            CSTAMP(5, __float_as_uint(y[4][3]));
#pragma unroll
            for (int j = 0; j < 5; j += 2) {
                if (j < 4 && (t >> 1) != (g >> 2)) { y[j][0] = y[j + 1][0]; y[j][1] = y[j + 1][1]; y[j][2] = y[j + 1][2]; y[j][3] = y[j + 1][3]; }
                sts128f(wpa + j * 256, y[j]);
            }
            TSTAMP2(5);
        };
        u64 yw[2];
        bool wide;
        float msq = 0.f, yf[4] = {};
        auto mlp_part = [&](auto L) {
            bar_sync(0, 256);
            CSTAMP(6, __float_as_uint(sc1));
            const float s = (sum8(pa, 1536) + xc) + sum8(pa + 128, 1536), sm = s * sc1 + FX2_ONE;
            CSTAMP(7, __float_as_uint(s));
            const bool wide1 = !(fabsf(sm - FX2_ONE) < FX1LIM);
            asm volatile("red.relaxed.gpu.global.add.u32 [%0], %1;" :: "l"(rop), "r"(wide1 ? 0u : __float_as_uint(sm) * 128u + (1u - 0x4b400000u * 128u)) : "memory");
            const uint32_t c0 = clk();
            TSTAMP2(6);
            if (L.value == 0) bar_arrive(2, 256);
            if (wide1) {
                fx_send(rop + 64 + (lane & 7) * 4, s, ldsf(sb + SM_FXS), rop, 64);
                asm volatile("red.relaxed.gpu.global.add.u32 [%0], 1;" :: "l"(rop) : "memory");
            }
            __syncwarp();
            if (L.value == 1 && mlp == 96) { TDUMP(); asm volatile("exit;"); }
            uint4 wf[8], w2r[8];
            uint4 w;
            auto look = [&]() { asm volatile("ld.relaxed.gpu.global.v4.u32 {%0,%1,%2,%3}, [%4];" : "=r"(w.x), "=r"(w.y), "=r"(w.z), "=r"(w.w) : "l"(ap) : "memory"); };
            auto read_w1 = [&]() {
#pragma unroll
                for (int j = 0; j < 8; j++) wf[j] = ldsm_t(la + j * 256);
            };
            auto read_w2 = [&]() {
#pragma unroll
                for (int i = 0; i < 8; i++) w2r[i] = lds128(((i & 1) ? (w2a ^ 16) + 128 : w2a) + (i >> 1) * 5120);
            };
            const float inv = pinf(fx_inv(sc1) * (1.f / 128)), off = L.value ? pinf(fx_inv(sc1) * -0.25f) : inv * -32.f;
            if (L.value == 0) { fresh(); mlp_global(L); }
            mbar_wait(sb + SM_CBAR + CB_W1 * 8, L.value);
            if (L.value == 1) {
                if (W2PRE == 1) mbar_wait(sb + SM_CBAR + CB_W2 * 8, 1);
                read_w1();
                if (W2PRE == 1) read_w2();
            }
            while (clk() - c0 < AR1D);
            look();
            if (L.value == 0) { mlp_shared(L); read_w1(); bar_arrive(3, 256); }
            else if (W2PRE == 2) { mbar_wait(sb + SM_CBAR + CB_W2 * 8, 1); read_w2(); }
            TSTAMPL(28);
            {
                sched_fence();
                auto miss = [&]() {
                    xp = make_uint2(pack_bf((float)(int)w.x * inv + off, (float)(int)w.y * inv + off), pack_bf((float)(int)w.z * inv + off, (float)(int)w.w * inv + off));
                    uint32_t a, b;
                    asm("lop3.b32 %0, %1, %2, 32, 0x7e;" : "=r"(a) : "r"(w.x), "r"(w.y));
                    asm("lop3.b32 %0, %1, %2, 32, 0x7e;" : "=r"(b) : "r"(w.z), "r"(w.w));
                    return __any_sync(~0u, (a | b) & 96);
                };
                if (miss()) {
                    int it = 0;
#pragma unroll 1
                    do {
                        if (!__any_sync(~0u, ~(w.x & w.y & w.z & w.w) & 32)) { xp.x = fx1_wide(ap, ldsf(sb + SM_FXS)); xp.y = fx1_wide(ap + 8, ldsf(sb + SM_FXS)); break; }
                        look();
                    } while (miss() & (++it < SPIN));
                }
                CSTAMP(8, w.w);
            }
            TSTAMP2(7);
            CSTAMP(9, xp.y);
            {
                bool ok = true;
                if (L.value == 0 || !W2PRE) ok = mbar_test(sb + SM_CBAR + CB_W2 * 8, L.value);
                const bool ev = L.value || !(g & 1), od = L.value || (g & 1);
                const uint32_t e0 = ev ? xp.x : ONES, e1 = ev ? xp.y : ONES, o0 = od ? xp.x : ONES, o1 = od ? xp.y : ONES;
                float d[8][4];
#pragma unroll
                for (int j = 0; j < 8; j++) { d[j][0] = d[j][1] = d[j][2] = d[j][3] = 0.f; mma(d[j], wf[j], (j & 1) ? o0 : e0, (j & 1) ? o1 : e1); }
                float ss = ln_part(xp, lane);
                ss += shx(ss, 8); ss += shx(ss, 4);
                float r[4], dd;
#pragma unroll
                for (int k = 0; k < 4; k += 1 + L.value) r[k] = d[0][k] + d[1][k ^ 1];
#pragma unroll
                for (int j = 1; j < 4; j++)
#pragma unroll
                    for (int k = 0; k < 4; k += 1 + L.value) add_if(t == j, r[k], d[2 * j][k], d[2 * j + 1][k ^ 1]);
                CSTAMP(10, __float_as_uint(r[2]));
                if (L.value) {
                    dd = ((t & 2) ? r[2] : r[0]) + shx((t & 2) ? r[0] : r[2], 2);
                    ss += shx(ss, 2);
                    dd += shx(dd, 1);
                } else {
                    const float a = ((t & 1) ? r[1] : r[0]) + shx((t & 1) ? r[0] : r[1], 1), b = ((t & 1) ? r[3] : r[2]) + shx((t & 1) ? r[2] : r[3], 1);
                    ss += shx(ss, 2);
                    dd = ((t & 2) ? b : a) + shx((t & 2) ? a : b, 2);
                }
                ss += shx(ss, 1);
                stsf(hpa, dd);
                stsf(hst, ss);
                CSTAMP(11, __float_as_uint(dd + ss));
                if (!ok) mbar_wait(sb + SM_CBAR + CB_W2 * 8, L.value);
            }
            TSTAMPL(25);
            bar_sync(1, 160);
            uint4 hp[5];
#pragma unroll
            for (int w = 0; w < 5; w++) hp[w] = lds128(hsa + w * 256);
            CSTAMP(12, hp[0].x);
            auto hs = [&](auto K) { return sum5(__uint_as_float(word<K.value>(hp[0])), __uint_as_float(word<K.value>(hp[1])), __uint_as_float(word<K.value>(hp[2])),
                                                __uint_as_float(word<K.value>(hp[3])), __uint_as_float(word<K.value>(hp[4]))); };
            const float mean = hs(IC<2>{}) * (1.f / D_MODEL);
            msq = hs(IC<3>{}) * (1.f / D_MODEL);
            if (L.value == 0) cs1 = hs(IC<1>{});
            float hv = hs(IC<0>{}) - mean * cs1;
            CSTAMP(13, __float_as_uint(hv));
            const float sc2 = fx2_scale(msq), lim = fx_inv(sc2) * FX2LIM;
            if (L.value == 0 || !W2PRE) read_w2();
            if (L.value == 0) {
                bar_arrive(4, 256);
                wide = false;
                if (mlp == 96) return;
            }
            hv = hv * ln_rstd(mean, msq) + b1v;
            CSTAMP(14, __float_as_uint(hv));
            hv = hv * rcp(1.f + ex2(hv * (-2.302208198f - 0.1029432397f * hv * hv)));
            const uint32_t hd = pack_bf(hv, hv);
            CSTAMP(15, hd);
            TSTAMPL(27);
            float ym[4][4];
#pragma unroll
            for (int i = 0; i < 2; i++) {
                ym[i][0] = ym[i][1] = ym[i][2] = ym[i][3] = 0.f;
                const float f = mlp < 64 ? 1.f / 64 : 0.f;
                ym[i + 2][0] = (bf_lo(xp.x) + bf_lo(b2v.x)) * f; ym[i + 2][1] = (bf_hi(xp.x) + bf_hi(b2v.x)) * f;
                ym[i + 2][2] = (bf_lo(xp.y) + bf_lo(b2v.y)) * f; ym[i + 2][3] = (bf_hi(xp.y) + bf_hi(b2v.y)) * f;
            }
#pragma unroll
            for (int i = 0; i < 4; i++) {
                const uint32_t hh = __shfl_sync(~0u, hd, 4 * i + t);
                mma(ym[(i & 1) * 2], w2r[2 * i], hh & maskA, hh & maskB);
                mma(ym[(i & 1) * 2 + 1], w2r[2 * i + 1], hh & maskA, hh & maskB);
            }
#pragma unroll
            for (int k = 0; k < 4; k++) { yf[k] = ym[0][k] + ym[2][k]; add_if(t & 2, yf[k], ym[1][k], ym[3][k]); }
            CSTAMP(16, __float_as_uint(yf[3]));
            yw[0] = fx2_pack(yf[0] * sc2 + FX2_ONE, yf[1] * sc2 + FX2_ONE); yw[1] = fx2_pack(yf[2] * sc2 + FX2_ONE, yf[3] * sc2 + FX2_ONE);
            wide = !(fmaxf(fmaxf(fabsf(yf[0]), fabsf(yf[1])), fmaxf(fabsf(yf[2]), fabsf(yf[3]))) < lim);
            if (wide) yw[0] = yw[1] = 0;
            if (L.value == 0) {
#pragma unroll
                for (int k = 0; k < 2; k++) asm volatile("red.relaxed.gpu.global.add.u64 [%0], %1;" :: "l"(rap + k * 40 * ACC_PITCH), "l"(yw[k]) : "memory");
            }
        };
        auto send_wide = [&]() {
#pragma unroll 1
            for (int k = 0; k < 4; k++, yf[0] = yf[1], yf[1] = yf[2], yf[2] = yf[3]) {
                const unsigned char* a = rap + (k >> 1) * 40 * ACC_PITCH;
                fx_send(a + 64 + (k & 1) * 32, yf[0], msq, a, 256);
            }
            yw[0] = yw[1] = 1;
        };

        pass1();
        o_setup(IC<0>{});
        out_proj(IC<0>{});
        uint32_t c0;
        if (warp < 5) {
            mlp_part(IC<0>{});
            c0 = clk() + (mlp == 96 ? PCD : 0);
            stsf(sb + SM_ML + (lane & 15) * 4, cs1);
            TSTAMP(8);
            if (__any_sync(~0u, wide)) {
                if (wide) {
                    send_wide();
#pragma unroll
                    for (int k = 0; k < 2; k++) asm volatile("red.relaxed.gpu.global.add.u64 [%0], 1;" :: "l"(rap + k * 40 * ACC_PITCH) : "memory");
                }
                __syncwarp();
            }
            fresh(); calc_offsets();
            load_wq();
        } else {
            bar_sync(0, 256);
            if (warp == 5 && elect()) {
                asm volatile("fence.proxy.async.shared::cta;" ::: "memory");
                if (W1AT0 == 4) issue_w(IC<0>{}, 0);
                issue_w(IC<0>{}, 1);
            }
            __syncwarp();
            fresh(); calc_offsets();
            load_wq();
#pragma unroll 1
            for (int ph = 0; ph < 3; ph++) {
                bar_sync(ph + 2, 256);
                c0 = clk();
                if (ph == 2) {
                    msq = sum5(ldsf(sb + SM_PART + 12), ldsf(sb + SM_PART + 268), ldsf(sb + SM_PART + 524), ldsf(sb + SM_PART + 780), ldsf(sb + SM_PART + 1036)) * (1.f / D_MODEL);
                    bar_arrive(5, 256);
                }
                if (!(NOWIN >> ph & 1) && elect()) {
                    asm volatile("fence.proxy.async.shared::cta;" ::: "memory");
                    const uint32_t gap = ph == 0 ? WG1 : ph == 1 ? WG2 : WG3;
                    uint32_t c1 = c0 + (ph == 0 ? WD1 : ph == 1 ? WD2 : 0) + (warp - 5) * gap;
#pragma unroll 1
                    for (int k = warp + (ph == 0 ? -5 : ph == 1 ? 9 : 1); k < (ph == 0 ? 9 : ph == 1 ? 20 : 14); k += 3, c1 += 3 * gap) {
                        const int i = ph == 0 && k >= 6 ? k + 23 : k;
                        const uint32_t bar = sb + SM_BAR + (i & 7) * 96 + 32 + (i & 24);
                        while ((int)(clk() - c1) < 0);
                        mbar_expect(bar, SUB);
                        tma_v(sb + SM_RING + i * SUB, tmk,
                              rowc * 3 + (i & 7) * 24 + ((UC<SCH.st[0].unit | SCH.st[1].unit << 8 | SCH.st[2].unit << 16 | SCH.st[3].unit << 24>::value >> (i & 24)) & 15) * 768, bar);
                    }
                }
                __syncwarp();
            }
            c0 += PCD;
        }
        {
            constexpr IC<1> L{};
            fresh();
            const int col = xcol(g & 3, t), cw = j40 + (col >> 2);
            const unsigned char* xa = pin(accg + ACC_BYTES + ((cw >> 2) + (col & 2) * 20) * ACC_PITCH + (cw & 3) * 8);
            const uint32_t pst = pin(prow + (g * 8 + (t & 1) * 4 + (t & 2)) * 4);
            const float inv = pinf(fx2_inv(msq));
            sts64f(sb + SM_MSQ, msq, inv);
            rap = pin(accg + ACC_BYTES + (c4() >> 2) * ACC_PITCH + (c4() & 3) * 8);
            fresh();
            maskA = pin(maskA); maskB = pin(maskB);
            u64 w[1];
            uint32_t x1[1], x2[3];
            auto look = [&]() { w[0] = ld_rlx(xa); };
            if (warp < 5) {
                bar_sync(5, 256);
                if (DPRE) { while ((int)(clk() - c0) < WD4 + warp * WG4); if (warp < DPRE) refill2(IC<3>{}); }
            }
            while ((int)(clk() - c0) < ARDELAY);
            look();
            if (DPOST) while ((int)(clk() - c0) < ARDELAY + DPOST);
            if (warp < 5 && !(NOWIN & 8) && elect()) {
                if (warp >= DPRE) issue_v(IC<3>{}, 0);
                if (warp < 4 && !P2LATE) issue_v(IC<2>{}, 4);
            }
            __syncwarp();
            fx2_wait<1>([&](int) { return xa; }, look, w, sb + SM_MSQ, inv, x1);
            if (warp < 5) look_rw(); else rw[0] = rw[1] = 96;
#pragma unroll
            for (int i = 0; i < 3; i++) x2[i] = __shfl_sync(~0u, x1[0], 4 * i + t);
            TSTAMP(9);
            CSTAMP(22, x2[2]);
            q_proj(L, x2, pst);
            pass2();
            out_proj(L);
            if (warp >= 5) {
                bar_arrive(0, 256);
                if ((W1AT1 == 6 || W2AT1 == 6) && warp == 5 && elect()) { if (W1AT1 == 6) issue_w(L, 0); if (W2AT1 == 6) issue_w(L, 1); }
                TDUMP();
                return;
            }
            mlp_part(L);
            u64 old[2];
            auto add = [&]() {
#pragma unroll
                for (int k = 0; k < 2; k++) asm volatile("atom.relaxed.gpu.global.add.u64 %0, [%1], %2;" : "=l"(old[k]) : "l"(rap + k * 40 * ACC_PITCH), "l"(yw[k]) : "memory");
            };
            add();
            uint32_t* op = pin(reinterpret_cast<uint32_t*>(P.out) + 2 * c4());
            const float inv2 = pinf(fx2_inv(msq));
            if (wide) { send_wide(); add(); }
            TSTAMP(18);
            CSTAMP(17, hi32(yw[1]));
            __syncwarp();
            CSTAMP(18, lo32(old[0]) ^ lo32(old[1]));
#pragma unroll
            for (int k = 0; k < 2; k++) {
                yw[k] += old[k];
                asm volatile("{\n.reg .pred p;\nsetp.eq.u32 p, %2, 96;\n@p st.global.u32 [%0], %1;\n}"
                             :: "l"(op + k), "r"(fx2_get(yw[k], inv2)), "r"(lo32(yw[k]) & 511) : "memory");
            }
            if ((lo32(yw[0]) & 255) == 96 && tid == 0) P.g->epoch = lds32(sb + SM_EPOCH) + 1;
#pragma unroll
            for (int k = 0; k < 2; k++) if ((lo32(yw[k]) & 511) == 256 + 96) op[k] = fx2_wide(rap + k * 40 * ACC_PITCH, msq);
            TSTAMP(19);
            CSTAMP(19, lo32(yw[1]));
            TDUMP();
        }
    }
}

typedef CUresult (*EncodeFn)(CUtensorMap*, CUtensorMapDataType, cuuint32_t, void*, const cuuint64_t*, const cuuint64_t*, const cuuint32_t*,
                             const cuuint32_t*, CUtensorMapInterleave, CUtensorMapSwizzle, CUtensorMapL2promotion, CUtensorMapFloatOOBfill);

}

extern "C" void kernel_launch(void* const* d_in, const int* in_sizes, int n_in, void* d_out, int out_size) {
    (void)in_sizes; (void)n_in; (void)out_size;
    static EncodeFn enc = nullptr;
    static void* scratch = nullptr;
    if (!enc) {
        void* fn = nullptr;
        cudaDriverEntryPointQueryResult qr;
        cudaGetDriverEntryPoint("cuTensorMapEncodeTiled", &fn, cudaEnableDefault, &qr);
        enc = (EncodeFn)fn;
        cudaGetSymbolAddress(&scratch, g_scratch);
        cudaFuncSetAttribute(fused_kernel, cudaFuncAttributeMaxDynamicSharedMemorySize, SM_TOTAL);
    }
    Params P = {};
    auto map3 = [&](int m, int in, cuuint64_t d0, cuuint64_t d1, cuuint64_t d2, cuuint64_t s1, cuuint64_t s2, cuuint32_t b0, cuuint32_t b1, cuuint32_t b2,
                    CUtensorMapSwizzle sw, int promo) {
        const cuuint64_t dim[3] = {d0, d1, d2}, str[2] = {s1, s2};
        const cuuint32_t box[3] = {b0, b1, b2}, ones[3] = {1, 1, 1};
        enc(&P.tm[m], CU_TENSOR_MAP_DATA_TYPE_BFLOAT16, d2 ? 3 : 2, d_in[in], dim, str, box, ones, CU_TENSOR_MAP_INTERLEAVE_NONE, sw, (CUtensorMapL2promotion)promo,
            CU_TENSOR_MAP_FLOAT_OOB_FILL_NONE);
    };
    map3(TM_KH, 1, 64, 3, NHEAD * SK, 128, DH * 2, 64, 3, 32, CU_TENSOR_MAP_SWIZZLE_128B, PROMOK);
    map3(TM_VH, 2, 64, 3, NHEAD * SK, 128, DH * 2, 64, 3, 32, CU_TENSOR_MAP_SWIZZLE_128B, PROMOK);
    map3(TM_VP, 2, 64, 3, NHEAD * SK, 128, DH * 2, PFW, 3, 32, CU_TENSOR_MAP_SWIZZLE_NONE, 0);
    map3(TM_V, 2, 64, NHEAD * SK * 3, 0, 128, 0, 64, 24, 0, CU_TENSOR_MAP_SWIZZLE_128B, PROMOV);
    map3(TM_WO, 4, 32, 20, NHEAD * DH, 64, D_MODEL * 2, 32, 1, DH, CU_TENSOR_MAP_SWIZZLE_64B, PROMOW);
    map3(TM_WOP, 4, 32, 20, NHEAD * DH, 64, D_MODEL * 2, PFW, 1, DH, CU_TENSOR_MAP_SWIZZLE_NONE, 0);
    map3(TM_WQ, 3, 64, NHEAD * 3, D_MODEL, 128, NHEAD * DH * 2, 64, 3, 32, CU_TENSOR_MAP_SWIZZLE_128B, PROMOQ);
    map3(TM_W1, 6, DFF, 128, 5, DFF * 2, DFF * 256, 16, 128, 5, CU_TENSOR_MAP_SWIZZLE_32B, PROMO1);
    map3(TM_W2, 8, 64, 10, DFF, 128, D_MODEL * 2, 64, 10, 16, CU_TENSOR_MAP_SWIZZLE_128B, PROMO2);
    P.x = (const __nv_bfloat16*)d_in[0];
    P.k = (const __nv_bfloat16*)d_in[1];
    P.b1 = (const __nv_bfloat16*)d_in[7];
    P.b2 = (const __nv_bfloat16*)d_in[9];
    P.w1 = (const __nv_bfloat16*)d_in[6];
    P.out = (__nv_bfloat16*)d_out;
    P.g = (Scratch*)(((uintptr_t)scratch + ACC_BYTES - 1) & ~(uintptr_t)(ACC_BYTES - 1));
    for (int i = 0; i < 64; i++) P.tile[i] = make_uint4(SCH.tile[i][0], SCH.tile[i][1], SCH.tile[i][2], 0);
    fused_kernel<<<NCTA + 1, NTHR, SM_TOTAL, cudaStreamPerThread>>>(P);
}
```

```cpp
#include <cuda_runtime.h>
#include <cuda_bf16.h>
#include <cuda.h>
#include <stdint.h>

namespace {

constexpr int D_MODEL = 640, NHEAD = 32, SK = 32768, DH = 192, WIN = 4096, DFF = 1536;
constexpr int NCTA = 128, NTHR = 256;
constexpr int TILE = 64 * DH * 2;
constexpr int HALF = TILE / 2;
constexpr int SUB = 8 * DH * 2;
constexpr int SM_RING = 4 * TILE;
constexpr int SM_W2 = SM_RING + 20480, SM_W1 = SM_W2 + 20480;
constexpr int SM_WQR = 6 * TILE + HALF, SM_WQ = 7 * TILE;
constexpr int SM_PART = 9 * TILE;
constexpr int SM_EXC = SM_PART + 6144;
constexpr int SM_SC = SM_EXC + 1024;
constexpr int SM_BAR = SM_SC + 1024;
constexpr int SM_VEC = SM_BAR + 768;
constexpr int SM_CS = SM_VEC + 384;
constexpr int SM_FAC = SM_CS + 768;
constexpr int SM_ML = SM_FAC + 32;
constexpr int SM_B1 = SM_ML + 64;
constexpr int SM_STAT = SM_B1 + 64;
constexpr int NCB = 28;
constexpr int CB_WO = 18, CB_W1 = 23, CB_W2 = 24, CB_SNAP = 25, CB_REL = 26, CB_WQ = 27;
constexpr int SM_CBAR = SM_STAT + 48;
constexpr int SM_CNT = SM_CBAR + NCB * 8;
constexpr int SM_EPOCH = SM_CNT + NCB * 8;
constexpr int SM_FXS = SM_EPOCH + 4;
constexpr int SM_T0 = SM_FXS + 4;
constexpr int SM_M1 = SM_T0 + 4;
constexpr int SM_MSQ = SM_M1 + 4;
constexpr int SM_TS = SM_MSQ + 8;
constexpr int SM_TOTAL = 232448;
static_assert(SM_TS + 320 <= SM_TOTAL, "smem");
constexpr int NEXC = 16;

constexpr int SPIN = 1 << 20;
enum { TM_V = 0, TM_KH = 1, TM_VH = 2, TM_WO = 3, TM_VP = 4, TM_WOP = 5, TM_W1 = 6, TM_W2 = 7, TM_WQ = 8 };
constexpr uint32_t POL_NORMAL = 0x16F00000u, POL_FIRST = 0x12F00000u;

#define PACE 980
#define PACE0 1500
#define PACES 1300
#define NIM 4
#define NI1 6
#define ETRIG 0x54321000
#define PFREE 66
#define SNAPAT 1
#define LATEAT 5
#define PUBAT 28
#define HW0 30
#define HW1 31
#define AR1D 250
#define ARDELAY 650
#define DPOST 200
#define PCD 350
#define WD1 100
#define WG1 140
#define WG2 120
#define WG3 65
#define VORD2 0x7685943a2b1cd0efull
#define VSLOT 0x1087654321087654ull
#define VTRIG 0xba73210
#define PARKS 0xa5
#define NPRE 2
#define M1AT 1
#define M1P 3
#define LAG0 12
#define NMMA 2
#define HWAT 12
#define WOP 0x44433
#define NWO1 4
#define FX1LIM 524288.f
#define FX2LIM 524288.f

constexpr uint32_t G_A = 1u << 28, G_B = 1u << 29, G_C = 1u << 30;
__host__ __device__ constexpr int ring_hs(int j) { return (j + 4) % 5; }
__host__ __device__ constexpr uint32_t load_word(int j) {
    if (j >= 64) return (uint32_t)(j - 64) << 20 | (SM_RING + ring_hs(j) * HALF) | TM_WO << 8 | (CB_WO + j - 64) << 3 | 2;
    const int e = j >> 1, isv = e >= 16, unit = e & 15;
    return (uint32_t)(unit * 256 + (j & 1) * 32) << 20 | (j < 8 ? j * HALF : SM_RING + ring_hs(j) * HALF) | (TM_KH + isv) << 8 | (j < 8 ? 10 + j : (j - 8) % 10) << 3 | 2 | !isv;
}
__host__ __device__ constexpr int popc(int v) { return v ? (v & 1) + popc(v >> 1) : 0; }
constexpr int NPARK = popc(PARKS);
constexpr int SM_SNAP = SM_RING + ring_hs(12) * HALF, SM_CSP = SM_RING + ring_hs(11) * HALF;
struct Step { int unit, slot, par, next, mma0, nmma; };
struct Sched { uint32_t tile[64][3]; Step st[16]; };
constexpr Sched make_sched() {
    Sched s{};
    for (int j = 0; j < 64; j++) {
        const int e = j >> 1;
        const uint32_t d = load_word(j);
        uint32_t w = (uint32_t)(j < 8 ? 0 : (j - 8) / 10 & 1) << 31 | (e & 15) * 4 << 20 | ((d & 0x3f000) - (j & 1) * HALF) | (d & 0xf8);
        if (e == PUBAT || e == SNAPAT) w |= G_A;
        if (e == HW0 || e == 4) w |= G_B;
        if ((e >= LATEAT && e < LATEAT + 4) || e == HW1) w |= G_C;
        s.tile[j][0] = w;
    }
    for (int j = NI1; j < 69; j++) {
        if (j == 12) continue;
        const int at = j < 12 ? (ETRIG >> (4 * (j - 4)) & 15) : j - 5;
        s.tile[at][1] = load_word(j);
        s.tile[at][2] = j >= PFREE ? 0 : PACE0 + j * PACE / 2;
    }
    int done = 0;
    for (int p = 0; p < 16; p++) {
        Step& c = s.st[p];
        c.unit = (int)(VORD2 >> (4 * p) & 15); c.slot = (int)(VSLOT >> (4 * p) & 15); c.par = p >= 9; c.next = -1;
        c.mma0 = done;
        if (p >= NPARK) { const int avail = p - done + (p >= LAG0); c.nmma = p == 15 ? 16 - done : (avail < NMMA ? avail : NMMA); done += c.nmma; }
    }
    for (int p = 9; p < 16; p++) s.st[VTRIG >> (4 * (p - 9)) & 15].next = p;
    return s;
}
constexpr Sched SCH = make_sched();
__host__ __device__ constexpr int kunit(int o) { return o < 5 ? o + 11 : o == 5 ? 10 : o - 6; }

template <int I> struct IC { static constexpr int value = I; };
template <uint32_t I> struct UC { static constexpr uint32_t value = I; };
template <int A, int B, class F> __device__ __forceinline__ void static_for(F&& f) {
    if constexpr (A < B) { f(IC<A>{}); static_for<A + 1, B>(f); }
}

typedef unsigned long long u64;
constexpr int ACC_PITCH = 352, ACC1_PITCH = 256, ACC_BYTES = 32768;
struct alignas(1024) Scratch {
    unsigned char acc[4 * ACC_BYTES];
    u64 l0[NCTA][384];
    u64 ll[NCTA][256];
    alignas(128) unsigned epoch;
    alignas(128) unsigned zflag;
};
__device__ __align__(1024) unsigned char g_scratch[sizeof(Scratch) + ACC_BYTES];

struct Params {
    CUtensorMap tm[9];
    const __nv_bfloat16 *x, *k, *b1, *b2, *w1;
    __nv_bfloat16* out;
    Scratch* g;
    uint4 tile[66];
};

#define TSTAMP(i)
#define TSTAMP2(i)
#define TSTAMPL(i)
#define TDUMP()
#define CSTAMP(i, x)
#define TRACE(i)

__device__ __forceinline__ void mbar_wait(uint32_t bar, uint32_t parity) {
    asm volatile("{\n.reg .pred p;\nLOOP:\nmbarrier.try_wait.parity.shared::cta.b64 p, [%0], %1;\n@!p bra.uni LOOP;\n}" :: "r"(bar), "r"(parity) : "memory");
}
__device__ __forceinline__ bool mbar_test(uint32_t bar, uint32_t parity) {
    uint32_t r;
    asm volatile("{\n.reg .pred p;\nmbarrier.test_wait.parity.shared::cta.b64 p, [%1], %2;\nselp.u32 %0, 1, 0, p;\n}" : "=r"(r) : "r"(bar), "r"(parity) : "memory");
    return __all_sync(~0u, r);
}
__device__ __forceinline__ bool elect() {
    uint32_t r;
    asm volatile("{\n.reg .pred p;\nelect.sync _|p, 0xffffffff;\nselp.u32 %0, 1, 0, p;\n}" : "=r"(r));
    return r != 0;
}
__device__ __forceinline__ void mbar_expect(uint32_t bar, uint32_t bytes) {
    asm volatile("mbarrier.arrive.expect_tx.shared::cta.b64 _, [%0], %1;" :: "r"(bar), "r"(bytes) : "memory");
}
__device__ __forceinline__ uint4 lds128(uint32_t a) {
    uint4 v; asm volatile("ld.shared.v4.u32 {%0,%1,%2,%3}, [%4];" : "=r"(v.x), "=r"(v.y), "=r"(v.z), "=r"(v.w) : "r"(a) : "memory"); return v;
}
__device__ __forceinline__ uint4 ldsm_t(uint32_t a) {
    uint4 v; asm volatile("ldmatrix.sync.aligned.m8n8.x4.trans.shared.b16 {%0,%1,%2,%3}, [%4];" : "=r"(v.x), "=r"(v.y), "=r"(v.z), "=r"(v.w) : "r"(a) : "memory"); return v;
}
__device__ __forceinline__ uint2 lds64(uint32_t a) {
    uint2 v; asm volatile("ld.shared.v2.u32 {%0,%1}, [%2];" : "=r"(v.x), "=r"(v.y) : "r"(a) : "memory"); return v;
}
__device__ __forceinline__ float2 lds64f(uint32_t a) { const uint2 v = lds64(a); return make_float2(__uint_as_float(v.x), __uint_as_float(v.y)); }
__device__ __forceinline__ uint32_t lds32(uint32_t a) {
    uint32_t v; asm volatile("ld.shared.u32 %0, [%1];" : "=r"(v) : "r"(a) : "memory"); return v;
}
__device__ __forceinline__ float ldsf(uint32_t a) { return __uint_as_float(lds32(a)); }
__device__ __forceinline__ void sts32(uint32_t a, uint32_t v) { asm volatile("st.shared.u32 [%0], %1;" :: "r"(a), "r"(v) : "memory"); }
__device__ __forceinline__ void stsf(uint32_t a, float v) { sts32(a, __float_as_uint(v)); }
__device__ __forceinline__ void sts16(uint32_t a, uint32_t v) { asm volatile("st.shared.u16 [%0], %1;" :: "r"(a), "h"((uint16_t)v) : "memory"); }
__device__ __forceinline__ void sts64(uint32_t a, uint32_t x, uint32_t y) { asm volatile("st.shared.v2.u32 [%0], {%1,%2};" :: "r"(a), "r"(x), "r"(y) : "memory"); }
__device__ __forceinline__ void sts64f(uint32_t a, float x, float y) { sts64(a, __float_as_uint(x), __float_as_uint(y)); }
__device__ __forceinline__ void sts128f(uint32_t a, float x, float y, float z, float w) {
    asm volatile("st.shared.v4.f32 [%0], {%1,%2,%3,%4};" :: "r"(a), "f"(x), "f"(y), "f"(z), "f"(w) : "memory");
}
__device__ __forceinline__ void mma(float (&c)[4], const uint4& a, uint32_t b0, uint32_t b1) {
    asm volatile("mma.sync.aligned.m16n8k16.row.col.f32.bf16.bf16.f32 {%0,%1,%2,%3}, {%4,%5,%6,%7}, {%8,%9}, {%0,%1,%2,%3};"
                 : "+f"(c[0]), "+f"(c[1]), "+f"(c[2]), "+f"(c[3]) : "r"(a.x), "r"(a.y), "r"(a.z), "r"(a.w), "r"(b0), "r"(b1));
}
__device__ __forceinline__ u64 ld_rlx(const void* p) {
    u64 a; asm volatile("ld.relaxed.gpu.global.u64 %0, [%1];" : "=l"(a) : "l"(p) : "memory"); return a;
}
__device__ __forceinline__ void ld_rlx2(const void* p, u64& a, u64& b) {
    asm volatile("ld.relaxed.gpu.global.v2.u64 {%0,%1}, [%2];" : "=l"(a), "=l"(b) : "l"(p) : "memory");
}
__device__ __forceinline__ void st_rlx(void* p, u64 a) { asm volatile("st.relaxed.gpu.global.u64 [%0], %1;" :: "l"(p), "l"(a) : "memory"); }
__device__ __forceinline__ u64 ll_pack(float v, uint32_t tag) { return ((u64)tag << 32) | __float_as_uint(v); }
__device__ __forceinline__ float ll_val(u64 w) { return __uint_as_float((uint32_t)w); }
__device__ __forceinline__ uint32_t ll_tag(u64 w) { return (uint32_t)(w >> 32); }
__device__ __forceinline__ float bf_lo(uint32_t u) { return __uint_as_float(u << 16); }
__device__ __forceinline__ float bf_hi(uint32_t u) { return __uint_as_float(u & 0xffff0000u); }
__device__ __forceinline__ uint32_t pack_bf(float lo, float hi) {
    uint32_t r; asm("cvt.rn.bf16x2.f32 %0, %1, %2;" : "=r"(r) : "f"(hi), "f"(lo)); return r;
}
__device__ __forceinline__ float ex2(float v) { float r; asm("ex2.approx.ftz.f32 %0, %1;" : "=f"(r) : "f"(v)); return r; }
__device__ __forceinline__ float rcp(float v) { float r; asm("rcp.approx.ftz.f32 %0, %1;" : "=f"(r) : "f"(v)); return r; }
__device__ __forceinline__ float rsq(float v) { float r; asm("rsqrt.approx.ftz.f32 %0, %1;" : "=f"(r) : "f"(v)); return r; }
__device__ __forceinline__ void bar_sync(int id, int n) { asm volatile("bar.sync %0, %1;" :: "r"(id), "r"(n) : "memory"); }
__device__ __forceinline__ uint32_t clk() { uint32_t c; asm volatile("mov.u32 %0, %clock;" : "=r"(c)); return c; }
__device__ __forceinline__ void sched_fence() { __syncwarp(); while (clk() == 0x9e3779b9u); }
__device__ __forceinline__ uint32_t pin(uint32_t v) { return __shfl_xor_sync(~0u, v, 0); }
__device__ __forceinline__ float shx(float v, int o) { return __shfl_xor_sync(~0u, v, o); }

__device__ __forceinline__ u64 fx_pack(float v, float scale) { return ((u64)__float2ll_rn(v * scale) & ~255ull) | 1ull; }
__device__ __forceinline__ float fx_scale(float meansq) {
    const int e = max(((int)(__float_as_uint(meansq) >> 23) - 127) >> 1, -6);
    return __uint_as_float((uint32_t)(127 + 32 - e) << 23);
}
__device__ __forceinline__ float fx_inv(float scale) { return __uint_as_float((254u << 23) - __float_as_uint(scale)); }
__device__ __forceinline__ uint32_t lo32(u64 w) { uint32_t l; asm("mov.b64 {%0, _}, %1;" : "=r"(l) : "l"(w)); return l; }
__device__ __forceinline__ int hi32(u64 w) { int h; asm("mov.b64 {_, %0}, %1;" : "=r"(h) : "l"(w)); return h; }
__device__ __forceinline__ float fx_val(u64 w) { return (float)hi32(w) * 4294967296.f + (float)lo32(w); }
constexpr float FX2_ONE = 12582912.f;
__device__ __forceinline__ float fx2_scale(float meansq) { return __uint_as_float((uint32_t)(127 + 16 - max(((int)(__float_as_uint(meansq) >> 23) - 127) >> 1, -100)) << 23); }
__device__ __forceinline__ u64 fx2_pack(float a, float b) {
    const uint32_t lo = __float_as_uint(a) * 512u + (1u - 0x4b400000u * 512u);
    return lo | (u64)(__float_as_uint(b) * 16u - 0x4b400000u * 16u + (uint32_t)((int)lo >> 31)) << 32;
}
__device__ __forceinline__ float fx2_lo(u64 w, float inv) { return (float)(int)(__funnelshift_r(lo32(w), hi32(w), 4) & ~31u) * (inv * 0.5f); }
__device__ __forceinline__ float fx2_hi(u64 w, float inv) { return (float)((hi32(w) + 8) & ~15) * inv; }
__device__ __forceinline__ uint32_t fx2_get(u64 w, float inv) {
    return pack_bf((float)(int)__funnelshift_r(lo32(w), hi32(w), 4) * (inv * 0.5f) - inv * 3.f, (float)hi32(w) * inv);
}
__device__ __forceinline__ float fx2_inv(float meansq) { return fx_inv(fx2_scale(meansq)) * 0.0625f; }
__device__ __noinline__ uint32_t fx2_wide(const unsigned char* a, float meansq) {
    __threadfence();
    const u64 w = ld_rlx(a);
    const float inv = fx_inv(fx_scale(meansq));
    return pack_bf(fx2_lo(w, fx2_inv(meansq)) + fx_val(ld_rlx(a + 64)) * inv, fx2_hi(w, fx2_inv(meansq)) + fx_val(ld_rlx(a + 96)) * inv);
}
__device__ __noinline__ uint32_t fx1_wide(const unsigned char* a, float meansq) {
    __threadfence();
    const u64 w = ld_rlx(a);
    const unsigned char* b = a + 64 + (reinterpret_cast<u64>(a) & 31);
    const float inv = fx_inv(fx_scale(meansq)), inv1 = fx2_inv(meansq) * 0.5f;
    return pack_bf((float)(int)(lo32(w) & ~127u) * inv1 + fx_val(ld_rlx(b)) * inv, (float)(hi32(w) & ~127) * inv1 + fx_val(ld_rlx(b + 8)) * inv);
}
__device__ __noinline__ void fx_send(const unsigned char* wide, float v, float meansq, const unsigned char* a, uint32_t flag) {
    asm volatile("red.relaxed.gpu.global.add.u64 [%0], %1;" :: "l"(wide), "l"(fx_pack(v, fx_scale(meansq))) : "memory");
    __threadfence();
    asm volatile("red.relaxed.gpu.global.or.b32 [%0], %1;" :: "l"(a), "r"(flag) : "memory");
}
template <int N, class A, class F> __device__ __forceinline__ void fx2_wait(A a, F look, u64 (&w)[N], uint32_t msqa, float inv, uint32_t (&x)[N]) {
    auto miss = [&]() {
#pragma unroll
        for (int i = 0; i < N; i++) x[i] = fx2_get(w[i], inv);
        return __any_sync(~0u, ((lo32(w[0]) ^ 96) | (lo32(w[N - 1]) ^ 96)) & 0x160);
    };
    if (miss()) {
        int it = 0;
#pragma unroll 1
        do {
            if (__all_sync(~0u, (lo32(w[0]) & lo32(w[N - 1]) & 96) == 96)) {
#pragma unroll
                for (int i = 0; i < N; i++) x[i] = fx2_wide(a(i), ldsf(msqa));
                break;
            }
            look();
        } while (miss() & (++it < SPIN));
    }
}
__device__ __forceinline__ void st_rlx_if(bool p, void* a, u64 v) {
    asm volatile("{\n.reg .pred p;\nsetp.ne.u32 p, %2, 0;\n@p st.relaxed.gpu.global.u64 [%0], %1;\n}" :: "l"(a), "l"(v), "r"((uint32_t)p) : "memory");
}
__device__ __forceinline__ void sts128f(uint32_t a, const float (&v)[4]) { sts128f(a, v[0], v[1], v[2], v[3]); }
__device__ __forceinline__ void bar_arrive(int id, int n) { asm volatile("bar.arrive %0, %1;" :: "r"(id), "r"(n) : "memory"); }
template <class T> __device__ __forceinline__ T* pin(T* p) { return reinterpret_cast<T*>(__shfl_xor_sync(~0u, (u64)p, 0)); }

__device__ __forceinline__ void tma3(uint32_t dst, const CUtensorMap* tm, int c1, int c2, uint32_t bar, uint32_t pol) {
    asm volatile("cp.async.bulk.tensor.3d.shared::cluster.global.mbarrier::complete_tx::bytes.L2::cache_hint [%0], [%1, {%2, %3, %4}], [%5], %6;"
                 :: "r"(dst), "l"(tm), "r"(0), "r"(c1), "r"(c2), "r"(bar), "l"((u64)pol << 32) : "memory");
}
__device__ __forceinline__ void tma_v(uint32_t dst, const CUtensorMap* tm, int line, uint32_t bar) {
    asm volatile("cp.async.bulk.tensor.2d.shared::cluster.global.mbarrier::complete_tx::bytes.L2::cache_hint [%0], [%1, {%2, %3}], [%4], %5;"
                 :: "r"(dst), "l"(tm), "r"(0), "r"(line), "r"(bar), "l"((u64)POL_FIRST << 32) : "memory");
}
__device__ __forceinline__ void tma3_pf(const CUtensorMap* tm, int c1, int c2, uint32_t pol) {
    asm volatile("cp.async.bulk.prefetch.tensor.3d.L2.global.tile.L2::cache_hint [%0, {%1, %2, %3}], %4;"
                 :: "l"(tm), "r"(0), "r"(c1), "r"(c2), "l"((u64)pol << 32) : "memory");
}
__device__ __forceinline__ void issue_half(uint32_t d, uint32_t sb, int rowc, int cta, const CUtensorMap* tm0) {
    const uint32_t bar = sb + SM_CBAR + (d & 0xf8);
    const CUtensorMap* tm = tm0 + ((d >> 8) & 3);
    const bool wo = (d & 0x300) == TM_WO << 8;
    const int c1 = wo ? (cta & 3) + 4 * (d >> 20) : 0, c2 = wo ? (cta >> 2) * DH : rowc + (d >> 20);
    mbar_expect(bar, HALF);
    tma3(sb + (d & 0x3f000), tm, c1, c2, bar, POL_FIRST);
    if (!(d & 1)) tma3_pf(tm + 2, c1, c2, POL_NORMAL);
}
__device__ __forceinline__ uint32_t cnt_inc(uint32_t a, uint32_t last) {
    uint32_t old; asm volatile("atom.relaxed.cta.shared.inc.u32 %0, [%1], %2;" : "=r"(old) : "r"(a), "r"(last) : "memory"); return old;
}
__device__ __forceinline__ void wait_until(uint32_t due) {
#pragma unroll 1
    for (int it = 0; it < 4096; it++) { uint32_t now; asm volatile("mov.u32 %0, %globaltimer_lo;" : "=r"(now)); if ((int)(now - due) >= 0) break; }
}
__device__ __forceinline__ uint32_t bf2_mul(uint32_t a, uint32_t b) { uint32_t r; asm("mul.rn.bf16x2 %0, %1, %2;" : "=r"(r) : "r"(a), "r"(b)); return r; }
__device__ __forceinline__ uint32_t bf2_fma(uint32_t a, uint32_t b, uint32_t c) { uint32_t r; asm("fma.rn.bf16x2 %0, %1, %2, %3;" : "=r"(r) : "r"(a), "r"(b), "r"(c)); return r; }
__device__ __forceinline__ uint32_t bf2_amax(uint32_t a, uint32_t b) { uint32_t r; asm("max.NaN.xorsign.abs.bf16x2 %0, %1, %2;" : "=r"(r) : "r"(a), "r"(b)); return r; }
__device__ __forceinline__ uint4 k_unpack(uint32_t l0, uint32_t l1, uint32_t h, uint32_t m1) {
    const uint32_t ha = h & 0x87878787u, hc = ha * m1 + h, hb = __funnelshift_l(hc, hc, 4);
    return make_uint4(__byte_perm(l0, ha, 0x5140), __byte_perm(l0, ha, 0x7362), __byte_perm(l1, hb, 0x5140), __byte_perm(l1, hb, 0x7362));
}
#define KR4(u, i) "+r"(kr[u][i].x), "+r"(kr[u][i].y), "+r"(kr[u][i].z), "+r"(kr[u][i].w)
#define KR6(u) KR4(u, 0), KR4(u, 1), KR4(u, 2), KR4(u, 3), KR4(u, 4), KR4(u, 5)
__device__ __forceinline__ void k_keep(uint4 (&kr)[8][6], const uint32_t (&c)[18], int e, uint32_t a) {
    asm volatile("{\nKT: .branchtargets K0, K1, K2, K3, K4, K5, K6, K7, K8, K9, K10, K11, K12, K13, K14, K15;\nbrx.idx.uni %210, KT;\n"
                 "K0: mov.b32 %12, %192; mov.b32 %13, %193; mov.b32 %14, %194; mov.b32 %15, %195; mov.b32 %16, %196; mov.b32 %17, %197; mov.b32 %18, %198; mov.b32 %19, %199; mov.b32 %20, %200; mov.b32 %21, %201; mov.b32 %22, %202; mov.b32 %23, %203; mov.b32 %24, %204; mov.b32 %25, %205; mov.b32 %26, %206; mov.b32 %27, %207; mov.b32 %28, %208; mov.b32 %29, %209; bra.uni KE;\n"
                 "K1: mov.b32 %30, %192; mov.b32 %31, %193; mov.b32 %32, %194; mov.b32 %33, %195; mov.b32 %34, %196; mov.b32 %35, %197; mov.b32 %36, %198; mov.b32 %37, %199; mov.b32 %38, %200; mov.b32 %39, %201; mov.b32 %40, %202; mov.b32 %41, %203; mov.b32 %42, %204; mov.b32 %43, %205; mov.b32 %44, %206; mov.b32 %45, %207; mov.b32 %46, %208; mov.b32 %47, %209; bra.uni KE;\n"
                 "K2: mov.b32 %48, %192; mov.b32 %49, %193; mov.b32 %50, %194; mov.b32 %51, %195; mov.b32 %52, %196; mov.b32 %53, %197; mov.b32 %54, %198; mov.b32 %55, %199; mov.b32 %56, %200; mov.b32 %57, %201; mov.b32 %58, %202; mov.b32 %59, %203; mov.b32 %60, %204; mov.b32 %61, %205; mov.b32 %62, %206; mov.b32 %63, %207; mov.b32 %64, %208; mov.b32 %65, %209; bra.uni KE;\n"
                 "K3: mov.b32 %66, %192; mov.b32 %67, %193; mov.b32 %68, %194; mov.b32 %69, %195; mov.b32 %70, %196; mov.b32 %71, %197; mov.b32 %72, %198; mov.b32 %73, %199; mov.b32 %74, %200; mov.b32 %75, %201; mov.b32 %76, %202; mov.b32 %77, %203; mov.b32 %78, %204; mov.b32 %79, %205; mov.b32 %80, %206; mov.b32 %81, %207; mov.b32 %82, %208; mov.b32 %83, %209; bra.uni KE;\n"
                 "K4: mov.b32 %84, %192; mov.b32 %85, %193; mov.b32 %86, %194; mov.b32 %87, %195; mov.b32 %88, %196; mov.b32 %89, %197; mov.b32 %90, %198; mov.b32 %91, %199; mov.b32 %92, %200; mov.b32 %93, %201; mov.b32 %94, %202; mov.b32 %95, %203; mov.b32 %96, %204; mov.b32 %97, %205; mov.b32 %98, %206; mov.b32 %99, %207; mov.b32 %100, %208; mov.b32 %101, %209; bra.uni KE;\n"
                 "K5: mov.b32 %102, %192; mov.b32 %103, %193; mov.b32 %104, %194; mov.b32 %105, %195; mov.b32 %106, %196; mov.b32 %107, %197; mov.b32 %108, %198; mov.b32 %109, %199; mov.b32 %110, %200; mov.b32 %111, %201; mov.b32 %112, %202; mov.b32 %113, %203; mov.b32 %114, %204; mov.b32 %115, %205; mov.b32 %116, %206; mov.b32 %117, %207; mov.b32 %118, %208; mov.b32 %119, %209; bra.uni KE;\n"
                 "K6: mov.b32 %120, %192; mov.b32 %121, %193; mov.b32 %122, %194; mov.b32 %123, %195; mov.b32 %124, %196; mov.b32 %125, %197; mov.b32 %126, %198; mov.b32 %127, %199; mov.b32 %128, %200; mov.b32 %129, %201; mov.b32 %130, %202; mov.b32 %131, %203; mov.b32 %132, %204; mov.b32 %133, %205; mov.b32 %134, %206; mov.b32 %135, %207; mov.b32 %136, %208; mov.b32 %137, %209; bra.uni KE;\n"
                 "K7: mov.b32 %138, %192; mov.b32 %139, %193; mov.b32 %140, %194; mov.b32 %141, %195; mov.b32 %142, %196; mov.b32 %143, %197; mov.b32 %144, %198; mov.b32 %145, %199; mov.b32 %146, %200; mov.b32 %147, %201; mov.b32 %148, %202; mov.b32 %149, %203; mov.b32 %150, %204; mov.b32 %151, %205; mov.b32 %152, %206; mov.b32 %153, %207; mov.b32 %154, %208; mov.b32 %155, %209; bra.uni KE;\n"
                 "K8: mov.b32 %156, %192; mov.b32 %157, %193; mov.b32 %158, %194; mov.b32 %159, %195; mov.b32 %160, %196; mov.b32 %161, %197; mov.b32 %162, %198; mov.b32 %163, %199; mov.b32 %164, %200; mov.b32 %165, %201; mov.b32 %166, %202; mov.b32 %167, %203; mov.b32 %168, %204; mov.b32 %169, %205; mov.b32 %170, %206; mov.b32 %171, %207; mov.b32 %172, %208; mov.b32 %173, %209; bra.uni KE;\n"
                 "K9: mov.b32 %174, %192; mov.b32 %175, %193; mov.b32 %176, %194; mov.b32 %177, %195; mov.b32 %178, %196; mov.b32 %179, %197; mov.b32 %180, %198; mov.b32 %181, %199; mov.b32 %182, %200; mov.b32 %183, %201; mov.b32 %184, %202; mov.b32 %185, %203; mov.b32 %186, %204; mov.b32 %187, %205; mov.b32 %188, %206; mov.b32 %189, %207; mov.b32 %190, %208; mov.b32 %191, %209; bra.uni KE;\n"
                 "K10: st.shared.v2.b32 [%211+75784], {%192, %193}; st.shared.v2.b32 [%211+76288], {%194, %195}; st.shared.v2.b32 [%211+76296], {%196, %197}; mov.b32 %0, %198; mov.b32 %1, %199; mov.b32 %2, %200; mov.b32 %3, %201; mov.b32 %4, %202; mov.b32 %5, %203; mov.b32 %6, %204; mov.b32 %7, %205; mov.b32 %8, %206; mov.b32 %9, %207; mov.b32 %10, %208; mov.b32 %11, %209; bra.uni KE;\n"
                 "K11: st.shared.v2.b32 [%211+0], {%192, %193}; st.shared.v2.b32 [%211+8], {%194, %195}; st.shared.v2.b32 [%211+512], {%196, %197}; st.shared.v2.b32 [%211+520], {%198, %199}; st.shared.v2.b32 [%211+1024], {%200, %201}; st.shared.v2.b32 [%211+1032], {%202, %203}; st.shared.v2.b32 [%211+1536], {%204, %205}; st.shared.v2.b32 [%211+1544], {%206, %207}; st.shared.v2.b32 [%211+2048], {%208, %209}; bra.uni KE;\n"
                 "K12: st.shared.v2.b32 [%211+2056], {%192, %193}; st.shared.v2.b32 [%211+2560], {%194, %195}; st.shared.v2.b32 [%211+2568], {%196, %197}; st.shared.v2.b32 [%211+24576], {%198, %199}; st.shared.v2.b32 [%211+24584], {%200, %201}; st.shared.v2.b32 [%211+25088], {%202, %203}; st.shared.v2.b32 [%211+25096], {%204, %205}; st.shared.v2.b32 [%211+25600], {%206, %207}; st.shared.v2.b32 [%211+25608], {%208, %209}; bra.uni KE;\n"
                 "K13: st.shared.v2.b32 [%211+26112], {%192, %193}; st.shared.v2.b32 [%211+26120], {%194, %195}; st.shared.v2.b32 [%211+26624], {%196, %197}; st.shared.v2.b32 [%211+26632], {%198, %199}; st.shared.v2.b32 [%211+27136], {%200, %201}; st.shared.v2.b32 [%211+27144], {%202, %203}; st.shared.v2.b32 [%211+49152], {%204, %205}; st.shared.v2.b32 [%211+49160], {%206, %207}; st.shared.v2.b32 [%211+49664], {%208, %209}; bra.uni KE;\n"
                 "K14: st.shared.v2.b32 [%211+49672], {%192, %193}; st.shared.v2.b32 [%211+50176], {%194, %195}; st.shared.v2.b32 [%211+50184], {%196, %197}; st.shared.v2.b32 [%211+50688], {%198, %199}; st.shared.v2.b32 [%211+50696], {%200, %201}; st.shared.v2.b32 [%211+51200], {%202, %203}; st.shared.v2.b32 [%211+51208], {%204, %205}; st.shared.v2.b32 [%211+51712], {%206, %207}; st.shared.v2.b32 [%211+51720], {%208, %209}; bra.uni KE;\n"
                 "K15: st.shared.v2.b32 [%211+73728], {%192, %193}; st.shared.v2.b32 [%211+73736], {%194, %195}; st.shared.v2.b32 [%211+74240], {%196, %197}; st.shared.v2.b32 [%211+74248], {%198, %199}; st.shared.v2.b32 [%211+74752], {%200, %201}; st.shared.v2.b32 [%211+74760], {%202, %203}; st.shared.v2.b32 [%211+75264], {%204, %205}; st.shared.v2.b32 [%211+75272], {%206, %207}; st.shared.v2.b32 [%211+75776], {%208, %209}; \nKE:\n}"
                 : KR6(0), KR6(1), KR6(2), KR6(3), KR6(4), KR6(5), KR6(6), KR6(7)
                 : "r"(c[0]), "r"(c[1]), "r"(c[2]), "r"(c[3]), "r"(c[4]), "r"(c[5]), "r"(c[6]), "r"(c[7]), "r"(c[8]), "r"(c[9]), "r"(c[10]), "r"(c[11]), "r"(c[12]), "r"(c[13]), "r"(c[14]), "r"(c[15]), "r"(c[16]), "r"(c[17]), "r"(e), "r"(a) : "memory");
}
__device__ __forceinline__ uint32_t smem_base() { extern __shared__ __align__(1024) unsigned char smem[]; return (uint32_t)__cvta_generic_to_shared(smem); }
__device__ __forceinline__ void k_rare(uint4 v0, uint4 v1, uint4 v2, uint4 v3, uint4 v4, uint4 v5, uint32_t odd, int e, int warp, int lane) {
    const uint32_t sb = smem_base(), g = lane >> 2, t = lane & 3, st = sb + SM_BAR + warp * 96 + 80;
    uint32_t lt; asm volatile("mov.u32 %0, %lanemask_lt;" : "=r"(lt));
    const uint4 v[6] = {v0, v1, v2, v3, v4, v5};
    odd <<= 6;
#pragma unroll
    for (int i = 0; i < 6; i++) if (v[i].x | v[i].y | v[i].z | v[i].w) odd |= 1u << i;
    odd = __reduce_or_sync(~0u, odd);
    uint32_t n = odd >= 64 ? NEXC + 1 : __shfl_sync(~0u, lds32(st), 0);
#pragma unroll 1
    for (; odd && n <= NEXC; odd &= odd - 1) {
        const int i = __ffs(odd) - 1;
#pragma unroll
        for (int k = 1; k < 6; k++) if (i == k) v0 = v[k];
#pragma unroll 1
        for (int k = 0; k < 4; k++, v0.x = v0.y, v0.y = v0.z, v0.z = v0.w) {
            const uint32_t who = __ballot_sync(~0u, v0.x), at = n + __popc(who & lt);
            sts64(v0.x && at < NEXC ? sb + SM_EXC + warp * 128 + at * 8 : st + 8, v0.x, (e * 32 + g * 4) << 16 | (((k & 1) * 4 + t) * 48 + i * 8 + (k >> 1) * 4));
            n += __popc(who);
        }
    }
    const uint32_t bad = lds32(st + 4);
    __syncwarp();
    if (n <= NEXC) sts32(st, n);
    else {
        sts32(st + 4, bad | 1u << e);
        asm volatile("st.shared.u8 [%0], %1;" :: "r"(sb + SM_SC + warp * 128 + g * 16 + (e & 3) * 4 + (e >> 2)), "r"(0) : "memory");
    }
    __syncwarp();
}
template <int K> __device__ __forceinline__ uint32_t& word(uint4& v) { if constexpr (K == 0) return v.x; else if constexpr (K == 1) return v.y; else if constexpr (K == 2) return v.z; else return v.w; }
__device__ __forceinline__ void add_if(bool p, float& d, float a, float b) {
    asm volatile("{\n.reg .pred p;\nsetp.ne.u32 p, %3, 0;\n@p add.f32 %0, %1, %2;\n}" : "+f"(d) : "f"(a), "f"(b), "r"((uint32_t)p));
}
__device__ __forceinline__ float warp_max(float v) {
#pragma unroll
    for (int o = 16; o; o >>= 1) v = fmaxf(v, shx(v, o));
    return v;
}
__device__ __forceinline__ float warp_sum(float v) {
#pragma unroll
    for (int o = 16; o; o >>= 1) v += shx(v, o);
    return v;
}
template <int PITCH> __device__ __forceinline__ void ll_look(const u64* buf, u64 (&w)[4]) {
#pragma unroll
    for (int i = 0; i < 4; i++) w[i] = ld_rlx(buf + i * PITCH);
}
template <int PITCH> __device__ __forceinline__ float ll_gather(const u64* buf, uint32_t tag, u64 (&w)[4]) {
    auto miss = [&]() {
        uint32_t a, b;
        asm("lop3.b32 %0, %1, %2, %3, 0x7e;" : "=r"(a) : "r"(ll_tag(w[0])), "r"(ll_tag(w[1])), "r"(tag));
        asm("lop3.b32 %0, %1, %2, %3, 0x7e;" : "=r"(b) : "r"(ll_tag(w[2])), "r"(ll_tag(w[3])), "r"(tag));
        return __any_sync(~0u, a | b);
    };
    int it = 0;
    goto check;
again:
    ll_look<PITCH>(buf, w);
check:
    if (miss() & (++it < SPIN)) goto again;
    return (ll_val(w[0]) + ll_val(w[1])) + (ll_val(w[2]) + ll_val(w[3]));
}
__device__ __forceinline__ float sum8(uint32_t a, int pitch) {
    float s[8];
#pragma unroll
    for (int w = 0; w < 8; w++) s[w] = ldsf(a + w * pitch);
    return ((s[0] + s[1]) + (s[2] + s[3])) + ((s[4] + s[5]) + (s[6] + s[7]));
}
__device__ __forceinline__ float sum5(float a, float b, float c, float d, float e) { return ((a + b) + (c + d)) + e; }
__device__ __forceinline__ float ln_part(uint2 xp, int lane) {
    const float x0 = bf_lo(xp.x), x1 = bf_hi(xp.x), x2 = bf_lo(xp.y), x3 = bf_hi(xp.y);
    const float s1 = (x0 + x1) + (x2 + x3), s2 = (x0 * x0 + x1 * x1) + (x2 * x2 + x3 * x3);
    return ((lane & 16) ? s2 : s1) + shx((lane & 16) ? s1 : s2, 16);
}
__device__ __forceinline__ float ln_rstd(float mean, float msq) { return rsq(fmaxf(msq - mean * mean, 0.f) + 1e-5f); }
__device__ __forceinline__ float score(const uint4 (&v)[6], const uint4 (&qf)[3]) {
    float d[2][4];
#pragma unroll
    for (int j = 0; j < 2; j++) d[j][0] = d[j][1] = d[j][2] = d[j][3] = 0.f;
#pragma unroll
    for (int i = 0; i < 3; i++) { mma(d[0], v[2 * i], qf[i].x, qf[i].y); mma(d[1], v[2 * i + 1], qf[i].z, qf[i].w); }
    return (d[0][0] + d[0][3]) + (d[1][0] + d[1][3]);
}
__device__ __forceinline__ float k_side(uint32_t sb, uint2 x) {
    const uint32_t qq = lds32(sb + SM_VEC + (x.y & 0xffff));
    return (bf_lo(x.x) * bf_lo(qq) + bf_hi(x.x) * bf_hi(qq)) * 0x1p-64f;
}
__device__ __forceinline__ void k_fix(const __nv_bfloat16* k, uint32_t bad, int warp, int lane) {
    const uint32_t sb = smem_base(), g = lane >> 2, sa = sb + SM_PART + warp * 768 + 256;
    const uint2 x = lds64(sb + SM_EXC + warp * 128 + (lane & 15) * 8);
    if ((int)x.y >= 0x40000000 && lane < 16) asm volatile("red.shared.add.f32 [%0], %1;" :: "r"(sa + ((x.y >> 16) & 511)), "f"(k_side(sb, x)) : "memory");
    __syncwarp();
#pragma unroll 1
    for (bad &= 0xffff; bad; bad &= bad - 1) {
        const int e = __ffs(bad) - 1;
        const __nv_bfloat16* kp = k + (e * 256 + (g >> 1) + 4 * (g & 1)) * DH + (lane & 3) * 8;
        uint4 v[6], qf[3];
#pragma unroll
        for (int i = 0; i < 6; i++) v[i] = *reinterpret_cast<const uint4*>(kp + i * 32);
#pragma unroll
        for (int i = 0; i < 3; i++) qf[i] = lds128(sb + SM_VEC + (lane & 7) * 48 + i * 16);
        stsf(sa + e * 32 + g * 4, score(v, qf) * 0x1p-64f);
    }
    __syncwarp();
}
constexpr float CS = 0.07216878364870322f * 1.4426950408889634f;
__device__ __forceinline__ void head_weight(const u64* a, u64 pm, u64 pl, int layer, int lane) {
    const uint32_t sb = smem_base(), tag = lds32(sb + SM_EPOCH) * 4 + 2 + 2 * layer;
#pragma unroll 1
    for (int it = 0; it < SPIN; it++) {
        if (__all_sync(~0u, ll_tag(pm) == tag && ll_tag(pl) == tag)) break;
        ld_rlx2(a, pm, pl);
    }
    const float f = ex2((ll_val(pm) - warp_max(ll_val(pm))) * CS);
    const float w = f * rcp(warp_sum(f * ll_val(pl)));
    if (lane < 8) stsf(sb + SM_FAC + lane * 4, w);
}
constexpr uint32_t ONES = 0x3f803f80u;

__global__ void __launch_bounds__(NTHR, 1) fused_kernel(const __grid_constant__ Params P) {
    const uint32_t sb = smem_base();
    const int bx = blockIdx.x;
    if (__all_sync(~0u, threadIdx.x >= NTHR - 32 && bx < NCTA) && elect()) {
        asm volatile("mbarrier.init.shared::cta.b64 [%0], 1;" :: "r"(sb + SM_CBAR + CB_WQ * 8));
        asm volatile("mbarrier.init.shared::cta.b64 [%0], 1;" :: "r"(sb + SM_CBAR + 80));
        asm volatile("fence.mbarrier_init.release.cluster;" ::: "memory");
        mbar_expect(sb + SM_CBAR + CB_WQ * 8, 5 * HALF);
        mbar_expect(sb + SM_CBAR + 80, HALF);
        tma3(sb, &P.tm[TM_KH], 0, (bx >> 2) * SK + (SK - WIN) + (bx & 3) * 64, sb + SM_CBAR + 80, POL_FIRST);
#pragma unroll 1
        for (int i = 0; i < 5; i++) tma3(sb + SM_WQR + (i == 4 ? 0 : i + 1) * HALF, &P.tm[TM_WQ], (bx >> 2) * 3, (bx & 3) * 160 + i * 32, sb + SM_CBAR + CB_WQ * 8, POL_FIRST);
    }
    __syncwarp();
    int id = bx * NTHR + threadIdx.x, tid, lane, g, t, key, warp, cta, mlp, rowc, roww, j40;
    uint32_t maskA, maskB, barw, subw, prow;
    auto fresh = [&]() {
        const int cw = __shfl_sync(~0u, id >> 5, 0);
        id = pin(id); tid = id & 255; lane = id & 31; g = lane >> 2; t = lane & 3; key = (g >> 1) + 4 * (g & 1);
        const uint32_t m = (g & 1) ? 0xffff0000u : 0x0000ffffu;
        maskA = (g & 2) ? 0u : m; maskB = (g & 2) ? m : 0u;
        warp = cw & 7; cta = cw >> 3;
        mlp = (cta & 3) == 3 ? 96 : (cta >> 2) * 3 + (cta & 3);
        rowc = (cta >> 2) * SK + (SK - WIN) + (cta & 3) * 64; roww = rowc + warp * 8;
        j40 = (cta & 3) * 40;
        barw = sb + SM_BAR + warp * 96; subw = sb + warp * SUB; prow = sb + SM_PART + warp * 768;
    };
    fresh();
    auto fresh_lane = [&]() { id = pin(id); tid = id & 255; lane = id & 31; g = lane >> 2; t = lane & 3; };
    auto pinf = [&](float v) { return __uint_as_float(pin(__float_as_uint(v) | (id >> 16))); };

    if (cta == NCTA) {
        const uint32_t ep = *(volatile unsigned*)&P.g->epoch;
        if (tid == 0) {
#pragma unroll 1
            for (int it = 0; it < SPIN; it++) { if (ll_tag(ld_rlx(&P.g->ll[0][192])) == ep * 4 + 2) break; __nanosleep(200); }
        }
        __syncthreads();
#pragma unroll 1
        for (int i = tid >> 6; i < 80; i += 4) {
            const int a = i * ((tid & 16) ? ACC_PITCH : ACC1_PITCH);
            if (!(tid & 8) || (a & 127)) *reinterpret_cast<uint4*>(P.g->acc + ((tid >> 4) & 3) * ACC_BYTES + (a & ~127) + (tid & 15) * 16) = make_uint4(0, 0, 0, 0);
        }
        __threadfence();
        __syncthreads();
        if (tid == 0) asm volatile("st.relaxed.gpu.global.u32 [%0], %1;" :: "l"(&P.g->zflag), "r"(ep + 1) : "memory");
        return;
    }
    TSTAMP(0);
    if (tid == 64) { uint32_t now; asm volatile("mov.u32 %0, %globaltimer_lo;" : "=r"(now)); sts32(sb + SM_T0, now); }

    const CUtensorMap* tmk = reinterpret_cast<const CUtensorMap*>(__shfl_sync(~0u, (u64)&P.tm[0] + (lane >> 5), 0));
    auto c4 = [&]() { return 32 * min(warp, 4) + 16 * (t >> 1) + 2 * g + (t & 1); };
    auto xcol = [&](int i, int tt) { return (i < 2 ? 64 * i + 8 * warp : 128 + 8 * (warp >> 1)) + 2 * tt; };
    uint2 xp;
    uint32_t px[3], small;
    auto issue_first = [&](int j) {
        mbar_expect(sb + SM_CBAR + 80 + j * 8, HALF);
        tma3(sb + j * HALF, tmk + TM_KH, 0, rowc + (j >> 1) * 256 + (j & 1) * 32, sb + SM_CBAR + 80 + j * 8, POL_FIRST);
    };
    if (elect()) {
        if (warp != 2) asm volatile("mbarrier.init.shared::cta.b64 [%0], 1;" :: "r"(sb + SM_CBAR + 64 + warp * 8));
#pragma unroll
        for (int i = 0; i < 9; i++) asm volatile("mbarrier.init.shared::cta.b64 [%0], 1;" :: "r"(barw + i * 8));
        asm volatile("mbarrier.init.shared::cta.b64 [%0], 1;" :: "r"(sb + SM_CBAR + warp * 8));
        asm volatile("mbarrier.init.shared::cta.b64 [%0], 1;" :: "r"(sb + SM_CBAR + 128 + warp * 8));
        if (warp < 3) asm volatile("mbarrier.init.shared::cta.b64 [%0], %1;" :: "r"(sb + SM_CBAR + 192 + warp * 8), "r"(warp == 2 ? 8 : 1));
        sts64(barw + 80, 0, 0);
        asm volatile("fence.mbarrier_init.release.cluster;" ::: "memory");
        asm volatile("prefetch.tensormap [%0];" :: "l"(tmk + warp) : "memory");
    }
    __syncwarp();
    asm volatile("ld.global.nc.v2.u32 {%0,%1}, [%2];" : "=r"(xp.x), "=r"(xp.y) : "l"(P.x + 4 * c4()) : "memory");
#pragma unroll
    for (int i = 0; i < 3; i++) asm volatile("ld.global.nc.u32 %0, [%1];" : "=r"(px[i]) : "l"(P.x + 4 * j40 + xcol(i, t)) : "memory");
    asm volatile("ld.relaxed.gpu.global.u32 %0, [%1];" : "=r"(small) : "l"(lane < 16 ? (const void*)(P.b1 + min(mlp, 95) * 16 + (lane & 14)) : (const void*)&P.g->epoch) : "memory");
    if (tid >= 192 && tid < 192 + NCB) sts32(sb + SM_CNT + (tid - 192) * 8, 0);
    unsigned char* accg = reinterpret_cast<unsigned char*>(__shfl_sync(~0u, (u64)P.g->acc + (lane >> 5), 0));
    auto release = [&](const uint4& tw) {
        uint32_t old;
        __syncwarp();
        asm volatile("atom.relaxed.cta.shared.add.u32 %0, [%1], 1;" : "=r"(old) : "r"(sb + SM_CNT + (tw.x & 0xf8)) : "memory");
        return old;
    };
    auto refill = [&](const uint4& tw, uint32_t old) {
        if (__any_sync(~0u, (old & 127) == 127 && (tw.y & 2))) {
            wait_until(lds32(sb + SM_T0) + tw.z);
            if (elect()) issue_half(tw.y, sb, rowc, cta, tmk);
            __syncwarp();
        }
    };
    __syncthreads();
    auto issue_paced = [&](int j0, int j1) {
        if (warp >= j0 && warp < j1) {
            wait_until(lds32(sb + SM_T0) + PACES + warp * PACE / 2);
            if (elect()) issue_first(warp);
            __syncwarp();
        }
    };

    uint32_t offV0, offV2;
    auto calc_offsets = [&]() {
        offV0 = subw + (6 * t) * 128 + ((g ^ ((6 * t) & 7)) << 4);
        offV2 = subw + (6 * t + 2) * 128 + ((g ^ ((6 * t + 2) & 7)) << 4);
    };
    calc_offsets();

    auto load_v = [&](uint4 (&v)[6], uint32_t so) {
        v[0] = lds128(offV0 + so); v[1] = lds128((offV0 ^ 16) + so + 128); v[2] = lds128(offV2 + so);
        v[3] = lds128((offV2 ^ 16) + so + 128); v[4] = lds128((offV0 ^ 64) + so + 512); v[5] = lds128((offV0 ^ 80) + so + 640);
    };
    auto issue_v = [&](auto I, int dw) {
        constexpr Step c = SCH.st[I.value];
        const uint32_t bar = barw + dw * 96 + c.slot * 8;
        mbar_expect(bar, SUB);
        tma_v(subw + dw * SUB + c.slot * TILE, tmk, roww * 3 + dw * 24 + c.unit * 768, bar);
    };
    auto refill2 = [&](auto I) { __syncwarp(); if (elect()) issue_v(I, 0); };
    uint4 wq0[6], wqh[3], wq1[6];
    auto load_wq1 = [&](int i) { wq1[i] = lds128((i == 2 ? offV2 : i == 3 ? (offV2 ^ 16) + 128 : (offV0 ^ (i * 16)) + i * 128) + SM_WQ + TILE); };
    auto load_wq = [&]() {
        load_v(wq0, SM_WQ);
        const uint32_t so = SM_WQR - ((warp + 1) >> 1) * SUB;
        wqh[0] = lds128(((warp & 1) ? (offV2 ^ 16) + 128 : offV0) + so);
        wqh[1] = lds128(((warp & 1) ? (offV0 ^ 64) + 512 : (offV0 ^ 16) + 128) + so);
        wqh[2] = lds128(((warp & 1) ? (offV0 ^ 80) + 640 : offV2) + so);
    };
    uint4 kr[8][6];
    const unsigned char* rap;
    u64 rw[2];
    auto look_rw = [&]() { rw[0] = ld_rlx(rap); rw[1] = ld_rlx(rap + 40 * ACC_PITCH); };
    auto q_proj = [&](auto L, uint32_t (&p)[3], uint32_t pst) {
        if (L.value == 0 && g >= 4) p[0] = p[1] = p[2] = ONES;
        float a[3][4], b[3][4];
        const uint32_t dH = __byte_perm(p[2], 0, (warp & 1) ? 0x3232 : 0x1010);
        const uint32_t dA = __byte_perm(p[0], 0, 0x1010), dB = __byte_perm(p[0], 0, 0x3232), dC = __byte_perm(p[1], 0, 0x1010), dD = __byte_perm(p[1], 0, 0x3232);
#pragma unroll
        for (int i = 0; i < 3; i++) load_wq1(i);
#pragma unroll
        for (int j = 0; j < 3; j++) { a[j][0] = a[j][1] = a[j][2] = a[j][3] = 0.f; mma(a[j], wq0[j], dA & maskA, dA & maskB); }
#pragma unroll
        for (int j = 0; j < 3; j++) { b[j][0] = b[j][1] = b[j][2] = b[j][3] = 0.f; mma(b[j], wq0[j + 3], dB & maskA, dB & maskB); }
#pragma unroll
        for (int j = 0; j < 3; j++) mma(a[j], wqh[j], dH & maskA, dH & maskB);
#pragma unroll
        for (int i = 3; i < 6; i++) load_wq1(i);
#pragma unroll
        for (int j = 0; j < 3; j++) mma(b[j], wq1[j], dC & maskA, dC & maskB);
#pragma unroll
        for (int j = 0; j < 3; j++) mma(a[j], wq1[j + 3], dD & maskA, dD & maskB);
#pragma unroll
        for (int j = 0; j < 3; j++) {
            if (L.value) {
#pragma unroll
                for (int k = 0; k < 2; k++) { a[j][k] += b[j][k]; add_if(t & 2, a[j][k], a[j][k + 2], b[j][k + 2]); }
                sts64f(pst + j * 256, a[j][0], a[j][1]);
            } else sts128f(pst + j * 256, a[j][0] + b[j][0], a[j][1] + b[j][1], a[j][2] + b[j][2], a[j][3] + b[j][3]);
        }
        CSTAMP(23, __float_as_uint(a[2][1]));
        uint32_t tag;
        if (L.value) tag = lds32(sb + SM_EPOCH) * 4 + 3;
        u64* pub = L.value ? &P.g->ll[cta][tid] : &P.g->l0[cta][tid];
        if (L.value == 0) asm volatile("fence.proxy.async.shared::cta;" ::: "memory");
        TSTAMPL(21);
        __syncthreads();
        if (!L.value) tag = lds32(sb + SM_EPOCH) * 4 + 1;
#pragma unroll 1
        for (int k = 0; k < 2 - L.value; k++) st_rlx_if(tid < 192, pub + k * 192, ll_pack(sum8(sb + (k ? SM_CSP : SM_PART) + tid * 4, 768), tag));
        TSTAMPL(23);
            CSTAMP(24, tag);
    };
    auto ln_stats = [&]() {
        float ss = ln_part(xp, lane);
        ss += shx(ss, 8); ss += shx(ss, 4); ss += shx(ss, 2); ss += shx(ss, 1);
        stsf(sb + SM_STAT + min(warp, 5) * 8 + (lane >> 4) * 4, ss);
    };
    auto ln_final = [&](float& mean, float& rstd) {
        float2 v[5];
#pragma unroll
        for (int w = 0; w < 5; w++) v[w] = lds64f(sb + SM_STAT + w * 8);
        mean = sum5(v[0].x, v[1].x, v[2].x, v[3].x, v[4].x) * (1.f / D_MODEL);
        const float msq = sum5(v[0].y, v[1].y, v[2].y, v[3].y, v[4].y) * (1.f / D_MODEL);
        rstd = ln_rstd(mean, msq);
        stsf(sb + SM_FXS, msq);
    };
    auto q_addr = [&](int d) { return sb + SM_VEC + (((d >> 1) & 1) * 4 + ((d >> 3) & 3)) * 48 + (d >> 5) * 8 + ((d >> 2) & 1) * 4 + (d & 1) * 2; };
    {
#pragma unroll
        for (int u = 0; u < 8; u++)
#pragma unroll
            for (int i = 0; i < 6; i++) kr[u][i] = lds128(sb + SM_CS + (u * 6 + i) * 16);
        issue_paced(1, NIM);
        ln_stats();
        if (tid == 16) { sts32(sb + SM_EPOCH, small); sts32(sb + SM_M1, ~0u); }
        else if (tid < 16) sts32(sb + SM_B1 + tid * 4, (tid & 1) ? small & 0xffff0000u : small << 16);
        mbar_wait(sb + SM_CBAR + CB_WQ * 8, 0);
        load_wq();
        q_proj(IC<0>{}, px, sb + (t < 2 ? SM_PART : SM_CSP) + warp * 768 + (8 * g + 4 * (t & 1)) * 4);
    }
    {
        uint32_t offQ, offL;
        auto calc_ql = [&]() {
            offQ = pin(sb + SM_VEC + (lane & 7) * 48);
            offL = pin(subw + lane * 16);
        };

        auto issue_w = [&](auto L, int which) {
            const uint32_t bar = sb + SM_CBAR + (CB_W1 + which) * 8;
            if (mlp == 96) asm volatile("mbarrier.arrive.shared::cta.b64 _, [%0];" :: "r"(bar) : "memory");
            else {
                mbar_expect(bar, 20480);
                if (which) {
                    tma3(sb + (L.value ? 3 * TILE : SM_W2), tmk + TM_W2, 0, mlp * 16, bar, POL_FIRST);
                    if (!L.value) tma3_pf(tmk + TM_W2, 0, mlp * 16, POL_NORMAL);
                    if (!L.value) asm volatile("cp.async.bulk.prefetch.L2.global.L2::cache_hint [%0], 20480, %1;" :: "l"(P.w1 + mlp * 10240), "l"((u64)POL_NORMAL << 32) : "memory");
                }
                else asm volatile("cp.async.bulk.tensor.3d.shared::cluster.global.mbarrier::complete_tx::bytes.L2::cache_hint [%0], [%1, {%2, %3, %3}], [%4], %5;"
                                  :: "r"(sb + (L.value ? 2 * TILE : SM_W1)), "l"(tmk + TM_W1), "r"(mlp * 16), "r"(0), "r"(bar), "l"((u64)POL_FIRST << 32) : "memory");
            }
        };
        float acc[3][4];
        auto load_q = [&](uint4 (&qf)[3]) {
#pragma unroll
            for (int i = 0; i < 3; i++) qf[i] = lds128(offQ + i * 16);
        };
        auto softmax = [&](float S0, float S1, float S2, float S3) {
            int mi = __float_as_int(fmaxf(fmaxf(S0, S1), fmaxf(S2, S3)));
            mi = __reduce_max_sync(~0u, mi ^ ((mi >> 31) & 0x7fffffff));
            const float mrun = __int_as_float(mi ^ ((mi >> 31) & 0x7fffffff));
            const float p0 = ex2((S0 - mrun) * CS), p1 = ex2((S1 - mrun) * CS), p2 = ex2((S2 - mrun) * CS), p3 = ex2((S3 - mrun) * CS);
            const uint32_t pa = pack_bf(p0, p1), pb = pack_bf(p2, p3), pw = prow + 256 + (key >> 1) * 80 + t * 4 + (key & 1) * 2;
            sts16(pw, pa); sts16(pw + 16, pa >> 16); sts16(pw + 32, pb); sts16(pw + 48, pb >> 16);
            __syncwarp();
#pragma unroll
            for (int j = 0; j < 3; j++) acc[j][0] = acc[j][1] = acc[j][2] = acc[j][3] = 0.f;
            return make_float2(mrun, (p0 + p1) + (p2 + p3));
        };
        auto pv = [&](const uint4 (&v)[6], uint32_t pp) {
            const uint32_t dA = __byte_perm(pp, 0, 0x1010), dB = __byte_perm(pp, 0, 0x3232);
            mma(acc[0], v[0], dA & maskA, dA & maskB); mma(acc[1], v[1], dA & maskA, dA & maskB); mma(acc[2], v[2], dA & maskA, dA & maskB);
            mma(acc[0], v[3], dB & maskA, dB & maskB); mma(acc[1], v[4], dB & maskA, dB & maskB); mma(acc[2], v[5], dB & maskA, dB & maskB);
        };
        auto sa = [&]() { return prow + 256 + t * 32 + g * 4; };
        auto pass1 = [&]() {
            issue_paced(NIM, NI1);
            fresh();
            calc_ql();
            __syncthreads();
            sts64(prow + lane * 8, xp.x, xp.y);
            int e = 0;
            const uint4* tab = P.tile + (warp >> 2);
            uint4 tw = tab[0];
            uint32_t ka[3];
#pragma unroll
            for (int j = 0; j < 3; j++) ka[j] = pin(subw + key * 384 + j * 128 + ((t ^ ((3 * key + j) & 7)) << 4));
            auto load_k = [&](uint4 (&v)[6], uint32_t so) {
#pragma unroll
                for (int i = 0; i < 6; i++) v[i] = lds128(((i & 1) ? ka[i >> 1] ^ 64 : ka[i >> 1]) + so);
            };
            const uint32_t s0 = pin(prow + 256 + g * 4), sca = pin(sb + SM_SC + warp * 128 + g * 16);
#pragma unroll 1
            do {
                const uint4 tn = tab[2 * e + 2];
                uint4 v[6], qf[3];
                if (tw.x & (G_A | G_B | G_C)) {
                    if ((tw.x & G_A) && warp == 7 && elect()) {
                        mbar_expect(sb + SM_CBAR + CB_SNAP * 8, HALF);
                        asm volatile("cp.async.bulk.shared::cluster.global.mbarrier::complete_tx::bytes [%0], [%1], 12288, [%2];"
                                     :: "r"(sb + SM_SNAP), "l"(&P.g->l0[cta & ~3][0]), "r"(sb + SM_CBAR + CB_SNAP * 8) : "memory");
                    }
                    if (tw.x & G_B) {
                        if (warp < 6) {
                            mbar_wait(sb + SM_CBAR + CB_SNAP * 8, 0);
                            float qc[2] = {0.f, 0.f}, mean, rstd;
#pragma unroll 1
                            for (int k = 0; k < 2; k++) {
                                u64 qw[4];
#pragma unroll
                                for (int i = 0; i < 4; i++) { const uint2 x = lds64(sb + SM_SNAP + i * 3072 + k * 1536 + tid * 8); qw[i] = x.x | (u64)x.y << 32; }
                                qc[0] = qc[1];
                                qc[1] = ll_gather<384>(&P.g->l0[cta & ~3][k * 192 + tid], lds32(sb + SM_EPOCH) * 4 + 1, qw);
                            }
                            ln_final(mean, rstd);
                            stsf(sb + SM_CS + tid * 4, qc[1]);
                            const float q = (qc[0] - mean * qc[1]) * rstd;
                            sts16(q_addr(tid), pack_bf(q, q));
                        }
                        __syncthreads();
                        if (warp == 7 && elect()) issue_half(UC<load_word(12)>::value, sb, rowc, cta, tmk);
                        TSTAMP(2);
                    }
                    if (tw.x & G_C) {
                        load_k(v, (e - LATEAT) * TILE);
                        load_q(qf);
                        stsf(s0 + (e - LATEAT) * 32, score(v, qf));
                    }
                }
                load_q(qf);
                mbar_wait(sb + SM_CBAR + (tw.x & 0xf8), tw.x >> 31);
                TRACE(e);
                load_k(v, tw.x & 0x3f000);
                const uint32_t old = release(tw);
                const float s = score(v, qf);
                uint32_t m;
                {
                    uint32_t a[6];
#pragma unroll
                    for (int i = 0; i < 6; i++) a[i] = bf2_amax(bf2_amax(v[i].x, v[i].y), bf2_amax(v[i].z, v[i].w));
                    m = bf2_amax(bf2_amax(bf2_amax(a[0], a[1]), bf2_amax(a[2], a[3])), bf2_amax(a[4], a[5]));
                }
                m = bf2_amax(m, m >> 16) & 0x7f80;
                m = max(m, __shfl_xor_sync(~0u, m, 1));
                stsf(s0 + e * 32, s);
                m = max(m, __shfl_xor_sync(~0u, m, 2));
                refill(tw, old);
                const uint32_t b = min(max(m, 15u << 7) - (15u << 7), 126u << 7);
                const uint32_t dn = ((127u << 7) - b) * 0x10001u, up = ((127u << 7 | 0x8000u) + b) * 0x10001u;
                uint32_t c[18], any = m > (141u << 7);
#pragma unroll
                for (int i = 0; i < 6; i++) {
                    const uint32_t y0 = bf2_mul(v[i].x, dn), y1 = bf2_mul(v[i].y, dn), y2 = bf2_mul(v[i].z, dn), y3 = bf2_mul(v[i].w, dn);
                    v[i] = make_uint4(bf2_fma(y0, up, v[i].x), bf2_fma(y1, up, v[i].y), bf2_fma(y2, up, v[i].z), bf2_fma(y3, up, v[i].w));
                    any |= v[i].x | v[i].y;
                    any |= v[i].z | v[i].w;
                    const uint32_t hb = __byte_perm(y2, y3, 0x7531);
                    c[3 * i] = __byte_perm(y0, y1, 0x6420); c[3 * i + 1] = __byte_perm(y2, y3, 0x6420);
                    c[3 * i + 2] = __byte_perm(y0, y1, 0x7531) | __funnelshift_r(hb, hb, 4);
                }
                asm volatile("st.shared.u8 [%0], %1;" :: "r"(sca + (e & 3) * 4 + (e >> 2)), "r"((b >> 7) + 63) : "memory");
                const bool rare = __any_sync(~0u, any);
                k_keep(kr, c, e, offL);
                if (rare) k_rare(v[0], v[1], v[2], v[3], v[4], v[5], m > (141u << 7), e, warp, lane);
                tw = tn;
            } while (++e < 16);
            asm volatile("fence.proxy.async.shared::cta;" ::: "memory");
            __syncwarp();
            TSTAMP(10);
            fresh(); calc_offsets();
            {
                const uint2 st = lds64(barw + 80);
                const uint32_t xa = sb + SM_EXC + warp * 128 + (lane & 15) * 8 + 4;
                uint32_t pos = lds32(xa), lt;
                asm volatile("mov.u32 %0, %lanemask_lt;" : "=r"(lt));
                if (lane >= st.x) pos = 0x80000000u;
                const bool dup = (__match_any_sync(~0u, pos >> 16) & lt) && lane < st.x;
                if (lane < 16) sts32(xa, dup ? pos | 0x40000000u : pos);
                if (__any_sync(~0u, dup)) sts32(barw + 84, st.y | 0x10000u);
                const float2 ml = softmax(ldsf(sa()), ldsf(sa() + 128), ldsf(sa() + 256), ldsf(sa() + 384));
                sts64f(sb + SM_ML + warp * 8, ml.x, warp_sum(ml.y));
            }
            u64 pm = 0, pl = 0;
#pragma unroll 1
            do {
                const uint4 tn = tab[2 * e + 2];
                if (tw.x & (G_A | G_B | G_C)) {
                    if (tw.x & G_A) {
                        if (lane < 24) st_rlx(&P.g->ll[cta][warp * 24 + lane], 0ull);
                        else if (lane < 28) st_rlx(&P.g->ll[cta][168 + warp * 4 + lane], ll_pack(ldsf(sb + SM_ML + warp * 8 + (lane & 1) * 4), lds32(sb + SM_EPOCH) * 4 + 2));
                    }
                    if (warp == 2) {
                        if (tw.x & G_B) ld_rlx2(&P.g->ll[cta ^ (lane >> 3)][192 + (lane & 7) * 4], pm, pl);
                        if (tw.x & G_C) head_weight(&P.g->ll[cta ^ (lane >> 3)][192 + (lane & 7) * 4], pm, pl, 0, lane);
                    }
                    __syncwarp();
                }
                const uint32_t pp = lds32(prow + 256 + t * 80 + ((tw.x >> 20) & 255));
                mbar_wait(sb + SM_CBAR + (tw.x & 0xf8), tw.x >> 31);
                TRACE(e);
                uint4 v[6];
                load_v(v, tw.x & 0x3f000);
                refill(tw, release(tw));
                pv(v, pp);
                tw = tn;
            } while (++e < 32);
        };
        uint32_t osa, ora, owa, orow, otag;
        u64* olb;
        float xc;
        auto o_setup = [&](auto L) {
            fresh();
            const int lz = lane, d = warp * 24 + min(lz, 23);
            osa = pin(prow + ((lz >> 2) * 8 + (lz & 1) * 4 + (lz & 2)) * 4);
            ora = pin(sb + SM_PART + d * 4);
            olb = pin(&P.g->ll[cta & ~3][d]);
            orow = pin((lz & 1) + 2 * (lz & 2) + 2 * (lz >> 4));
            owa = pin(sb + SM_RING + warp * 1536 + orow * 64 + ((((lz >> 2) & 3) ^ (orow >> 1)) << 4));
            otag = lds32(sb + SM_EPOCH) * 4 + 2 + 2 * L.value;
            uint32_t x; asm volatile("ld.shared.u16 %0, [%1];" : "=r"(x) : "r"(prow + ((cta & 1) * 16 + (lz >> 3) * 4 + (cta & 2) + ((lz >> 2) & 1)) * 8 + (lz & 3) * 2) : "memory");
            xc = bf_lo(x) * (1.f / 32);
        };
        auto wo_at = [&](auto A) {
            constexpr uint32_t x = WOP ^ A.value * 0x11111;
            if constexpr (A.value > 0 && ((x - 0x11111) & ~x & 0x88888) != 0) {
                if ((WOP >> (4 * warp) & 15) == A.value) {
                    mbar_wait(sb + SM_CBAR + CB_REL * 8, 0);
                    if (elect()) {
                        const uint32_t bar = sb + SM_CBAR + (CB_WO + warp) * 8;
                        mbar_expect(bar, HALF);
                        tma3(sb + SM_RING + (warp + (warp < 2 ? 3 : -2)) * HALF, tmk + TM_WO, (cta & 3) + 4 * warp, (cta >> 2) * DH, bar, POL_FIRST);
                    }
                    __syncwarp();
                }
            }
        };
        static_assert(ring_hs(64) == 3, "wo");
        auto pass2 = [&]() {
            constexpr IC<1> L{};
            refill2(IC<4>{});
            uint4 tb[8][3];
            auto load_tb = [&](auto I) {
#pragma unroll
                for (int i = 0; i < 3; i++) tb[I.value][i] = lds128(offL + (I.value >> 1) * TILE + ((I.value & 1) * 3 + i) * 512);
            };
            const u64* qb = &P.g->ll[cta & ~3][min(tid, 191)];
            {
                uint32_t x[2];
                fx2_wait<2>([&](int i) { return rap + i * 40 * ACC_PITCH; }, look_rw, rw, sb + SM_MSQ, ldsf(sb + SM_MSQ + 4), x);
                xp = make_uint2(x[0], x[1]);
                CSTAMP(25, xp.y);
            }
            ln_stats();
            u64 qw[4];
            ll_look<256>(qb, qw);
            const float cs = ldsf(sb + SM_CS + min(tid, 191) * 4);
            const uint32_t qtag = lds32(sb + SM_EPOCH) * 4 + 3, qa = pin(q_addr(min(tid, 191)));
            fresh_lane();
            offQ = sb + SM_VEC + (lane & 7) * 48; offL = subw + lane * 16;
            __syncthreads();
            auto vwait = [&](auto I) { mbar_wait(barw + IC<SCH.st[I.value].slot>::value * 8, IC<SCH.st[I.value].par>::value); };
            bool ok;
            uint32_t m1, m1n;
            {
                float mean, rstd;
                ln_final(mean, rstd);
                const float sq = shx(rstd * 0x1p64f, 0), q0 = shx(-mean * cs * sq, 0);
                CSTAMP(26, __float_as_uint(q0));
                static_for<0, NPRE>(load_tb);
                refill2(IC<5>{});
                m1n = m1 = lds32(sb + SM_M1);
                sts64(prow + lane * 8, xp.x, xp.y);
                sts128f(prow + 256 + lane * 16, 0.f, 0.f, 0.f, 0.f);
                const float q = ll_gather<256>(qb, qtag, qw) * sq + q0;
                sts16(qa, pack_bf(q, q));
                TSTAMPL(24);
                CSTAMP(27, __float_as_uint(q));
            }
            __syncthreads();
            uint4 qf[3];
            load_q(qf);
            CSTAMP(28, qf[0].x);
            float S[4], d[2][4];
            auto vload = [&](auto I) {
                constexpr int p = I.value;
                constexpr Step c = SCH.st[p];
                load_v(kr[p & 7], c.slot * TILE);
                if constexpr (c.next >= 0) refill2(IC<c.next>{});
                if constexpr (p == 11) { __syncwarp(); if (elect()) asm volatile("mbarrier.arrive.shared::cta.b64 _, [%0];" :: "r"(sb + SM_CBAR + CB_REL * 8) : "memory"); }
            };
            static_for<0, 96>([&](auto F) {
                constexpr int f = F.value, i = f % 6, u = kunit(f / 6), w = 3 * f % 12;
                uint4 (&src)[3] = *reinterpret_cast<uint4 (*)[3]>(f < 32 ? &tb[f / 4 & 7][0] : &kr[(f / 8 + 4) & 7][(f / 4 & 1) * 3]);
                const uint4 a = k_unpack(word<w % 4>(src[w / 4]), word<(w + 1) % 4>(src[(w + 1) / 4]), word<(w + 2) % 4>(src[(w + 2) / 4]), m1);
                if constexpr (f < 32 ? f % 4 == M1AT : f % 8 == M1P) m1 = m1n;
                if constexpr (f % 4 == 3 && f / 4 + NPRE < 8) {
                    load_tb(IC<f / 4 + NPRE>{});
                    if constexpr ((f / 4 + NPRE) & 1) { refill2(IC<5 + (f / 4 + NPRE) / 2>{}); m1n = lds32(sb + SM_M1); }
                }
                if constexpr (i < 2) d[i][0] = d[i][1] = d[i][2] = d[i][3] = 0.f;
                mma(d[i & 1], a, (i & 1) ? qf[i / 2].z : qf[i / 2].x, (i & 1) ? qf[i / 2].w : qf[i / 2].y);
                if constexpr (i == 5) {
                    if constexpr (u == 11 || ((u & 3) == 0 && u != 8)) S[u >> 2] = (d[0][0] + d[0][3]) + (d[1][0] + d[1][3]);
                    else add_if(t == (u & 3), S[u >> 2], d[0][0] + d[0][3], d[1][0] + d[1][3]);
                    if constexpr (f < 64) S[u >> 2] = shx(S[u >> 2], 0);
                }
                if constexpr (f == 31) { fresh(); calc_offsets(); ok = mbar_test(barw + IC<SCH.st[0].slot>::value * 8, 0); }
                if constexpr (f == 48) {
                    const uint2 x = lds64(sb + SM_EXC + warp * 128 + (lane & 15) * 8);
                    const float c = k_side(sb, x);
                    if (x.y < 0x40000000u) stsf(prow + 256 + (x.y >> 16), c);
                }
                if constexpr (f >= 32 && f % 8 == 7) {
                    if constexpr (PARKS >> (f / 8 - 4) & 1) {
                        constexpr int p = popc(PARKS & ((1 << (f / 8 - 4)) - 1));
                        if (!ok) vwait(IC<p>{});
                        vload(IC<p>{});
                        m1n = lds32(sb + SM_M1);
                        ok = mbar_test(barw + IC<SCH.st[p + 1].slot>::value * 8, IC<SCH.st[p + 1].par>::value);
                    }
                }
            });
            uint32_t bad = lds32(barw + 84);
            const uint32_t sc = lds32(sb + SM_SC + tid * 4);
            __syncwarp();
            if (bad) k_fix(P.k + (size_t)roww * DH, bad, warp, lane);
            TSTAMP(30);
            CSTAMP(29, __float_as_uint(S[2]));
            const float2 ml = softmax(S[0] * __uint_as_float((sc & 255) << 23) + ldsf(sa()), S[1] * __uint_as_float((sc & 0xff00) << 15) + ldsf(sa() + 128),
                                      S[2] * __uint_as_float((sc & 0xff0000) << 7) + ldsf(sa() + 256), S[3] * __uint_as_float((sc >> 24) << 23) + ldsf(sa() + 384));
            uint4 pq[4];
#pragma unroll
            for (int j = 0; j < 4; j++) pq[j] = lds128(prow + 256 + t * 80 + j * 16);
            TSTAMP(1);
            CSTAMP(30, pq[3].w);
            if (!ok) vwait(IC<NPARK>{});
            float ac2[3][4];
#pragma unroll
            for (int j = 0; j < 3; j++) ac2[j][0] = ac2[j][1] = ac2[j][2] = ac2[j][3] = 0.f;
            const uint32_t sl = (g & 1) ? 0x1044 : 0x4410, sh = (g & 1) ? 0x3244 : 0x4432;
            const uint32_t sA0 = (g & 2) ? 0x4444 : sl, sA1 = (g & 2) ? sl : 0x4444, sB0 = (g & 2) ? 0x4444 : sh, sB1 = (g & 2) ? sh : 0x4444;
            u64 pm = 0, pl = 0;
            static_for<NPARK, 16>([&](auto I) {
                constexpr int p = I.value;
                static_assert(p - SCH.st[p].mma0 < 8, "buffer in use");
                vload(I);
                if constexpr (p < 15) ok = mbar_test(barw + IC<SCH.st[p + 1].slot>::value * 8, IC<SCH.st[p + 1].par>::value);
                static_for<SCH.st[p].mma0, SCH.st[p].mma0 + SCH.st[p].nmma>([&](auto J) {
                    constexpr int u = SCH.st[J.value].unit;
                    const uint32_t pp = word<u & 3>(pq[u >> 2]), a0 = __byte_perm(pp, 0, sA0), a1 = __byte_perm(pp, 0, sA1), b0 = __byte_perm(pp, 0, sB0), b1 = __byte_perm(pp, 0, sB1);
#pragma unroll
                    for (int j = 0; j < 3; j++) mma(acc[j], kr[J.value & 7][j], a0, a1);
#pragma unroll
                    for (int j = 0; j < 3; j++) mma(ac2[j], kr[J.value & 7][j + 3], b0, b1);
                });
                if constexpr (p == NPARK) {
                    const float l = warp_sum(ml.y);
                    st_rlx_if(lane < 4, &P.g->ll[cta][192 + warp * 4 + lane], ll_pack((lane & 1) ? l : ml.x, lds32(sb + SM_EPOCH) * 4 + 4));
                }
                if constexpr (p == HWAT) { if (warp == 6) ld_rlx2(&P.g->ll[cta ^ (lane >> 3)][192 + (lane & 7) * 4], pm, pl); }
                if constexpr (p == 13) o_setup(L);
                if constexpr (p == HWAT + 2) { if (warp == 6) head_weight(&P.g->ll[cta ^ (lane >> 3)][192 + (lane & 7) * 4], pm, pl, 1, lane); }
                wo_at(IC<p - 10>{});
                if constexpr (p < 15) { if (!ok) mbar_wait(barw + IC<SCH.st[p + 1].slot>::value * 8, IC<SCH.st[p + 1].par>::value); TRACE(33 + p); }
            });
#pragma unroll
            for (int j = 0; j < 3; j++)
#pragma unroll
                for (int k = 0; k < 2; k++) { acc[j][k] += ac2[j][k]; add_if(t & 2, acc[j][k], acc[j][k + 2], ac2[j][k + 2]); }
        };

        const unsigned char* ap;
        uint32_t hpa, hsa, hst, w2a, la;
        uint2 b2v;
        float b1v, cs1;
        auto mlp_global = [&](auto L) {
            const int cz = c4();
            ap = accg + 2 * L.value * ACC_BYTES + (cz >> 1) * ACC1_PITCH + (cz & 1) * 16;
            if (L.value) ap = pin(ap);
            rap = pin(accg + (2 * L.value + 1) * ACC_BYTES + (cz >> 2) * ACC_PITCH + (cz & 3) * 8);
            asm volatile("ld.global.nc.v2.u32 {%0,%1}, [%2];" : "=r"(b2v.x), "=r"(b2v.y) : "l"(P.b2 + 4 * cz));
        };
        auto mlp_shared = [&](auto L) {
            const int lz = lane;
            hpa = pin(sb + SM_PART + warp * 256 + ((lz & 2) * 4 + (lz >> 2)) * 16 + (L.value ? 0 : (lz & 1) * 4));
            hsa = pin(sb + SM_PART + (lz & 15) * 16); hst = pin(sb + SM_PART + (lz & 15) * 16 + warp * 256 + 8 + (lz >> 4) * 4);
            w2a = pin(sb + (L.value ? 3 * TILE : SM_W2) + ((lz & 3) * 10 + 2 * warp) * 128 + (((lz >> 2) ^ ((2 * lz + 2 * warp) & 6)) << 4));
            la = sb + (L.value ? 2 * TILE : SM_W1) + warp * 4096 + (lz & 4) * 512 + (lz & 2) * 64 + (lz & 1) * 32 + (lz >> 4) * 64 + ((((lz >> 3) ^ (lz >> 1)) & 1) << 4);
            b1v = ldsf(sb + SM_B1 + (lz & 15) * 4);
            if (L.value) { la = pin(la); cs1 = ldsf(sb + SM_ML + (lz & 15) * 4); }
            else fresh();
        };
        uint32_t pa;
        unsigned char* rop;
        uint32_t wpa;
        float sc1;
        auto sum_setup = [&](auto L) {
            const int lz = lane, word = warp * 128 + (cta & 3) * 32 + lz;
            wpa = pin(sb + SM_RING + warp * 1536 + ((((lz >> 2) * 8 + (lz & 1) * 4) * 4) ^ ((((lz >> 1) ^ (lz >> 4)) & 1) ? 256 + 64 : 0)));
            sc1 = pinf(fx2_scale(ldsf(sb + SM_FXS)) * 0.25f);
            pa = pin(sb + SM_RING + warp * 256 + ((lz * 4) ^ ((warp & 1) * 64)));
            rop = pin(accg + 2 * L.value * ACC_BYTES + (word >> 3) * ACC1_PITCH + (word & 7) * 4);
        };
        auto out_proj = [&](auto L) {
            TSTAMP2(3);
            CSTAMP(0, __float_as_uint(acc[2][1]));
            __syncwarp();
#pragma unroll
            for (int j = 0; j < 3; j++) {
                if (L.value == 0 && (t & 2)) { acc[j][0] = acc[j][2]; acc[j][1] = acc[j][3]; }
                sts64f(osa + 256 * j, acc[j][0], acc[j][1]);
            }
            __syncthreads();
            {
                float s[8];
#pragma unroll
                for (int w = 0; w < 8; w++) s[w] = ldsf(ora + w * 768);
                const uint4 fa = lds128(sb + SM_FAC), fb = lds128(sb + SM_FAC + 16);
            CSTAMP(1, __float_as_uint(s[0]));
                const float own = ((s[0] * __uint_as_float(fa.x) + s[1] * __uint_as_float(fa.y)) + (s[2] * __uint_as_float(fa.z) + s[3] * __uint_as_float(fa.w))) +
                                  ((s[4] * __uint_as_float(fb.x) + s[5] * __uint_as_float(fb.y)) + (s[6] * __uint_as_float(fb.z) + s[7] * __uint_as_float(fb.w)));
                st_rlx_if(lane < 24, olb + (cta & 3) * 256, ll_pack(own, otag));
            CSTAMP(2, __float_as_uint(own));
            }
            TSTAMPL(29);
            if (L.value) wo_at(IC<6>{});
            if (L.value == 0 && warp == 7) {
#pragma unroll 1
                for (int it = 0; it < SPIN; it++) {
                    uint32_t v; asm volatile("ld.acquire.gpu.global.u32 %0, [%1];" : "=r"(v) : "l"(&P.g->zflag) : "memory");
                    if (__all_sync(~0u, v == (otag >> 2) + 1)) break;
                }
            }
            constexpr int NW = L.value ? NWO1 : 3;
            uint4 v[5][3];
            u64 ow[4];
            auto read_wo = [&](auto J) {
#pragma unroll
                for (int p = 0; p < 3; p++) v[J.value][p] = lds128(((J.value & 1) ? owa ^ 144 : owa) + ring_hs(64 + J.value) * HALF + p * 512);
            };
            static_for<0, NW>([&](auto J) {
                if (L.value && J.value == 0) { sum_setup(L); maskA = pin(maskA); maskB = pin(maskB); }
                if (J.value == 2) { ll_look<256>(olb, ow); if (L.value) { mlp_shared(L); mlp_global(L); } }
                mbar_wait(sb + SM_CBAR + (CB_WO + J.value) * 8, L.value);
                read_wo(J);
                if (L.value == 0 && J.value == 2) {
                    __syncwarp();
                    if (elect() && cnt_inc(sb + SM_CNT + CB_W1 * 8, 7) == 7) issue_w(L, 0);
                    __syncwarp();
                }
                if (L.value == 1 && J.value == 2) {
                    if (warp == 7 && elect()) issue_w(L, 0);
                    __syncwarp();
                }
            });
            sched_fence();
            const float o = ll_gather<256>(olb, otag, ow);
            CSTAMP(3, __float_as_uint(o));
            TSTAMP2(4);
            bool ok = true;
            if constexpr (NW < 5) ok = mbar_test(sb + SM_CBAR + (CB_WO + 4) * 8, L.value);
            if constexpr (NW < 4) ok &= mbar_test(sb + SM_CBAR + (CB_WO + 3) * 8, L.value);
            const uint32_t od = pack_bf(o, o);
            uint32_t oa[3], ob[3];
#pragma unroll
            for (int p = 0; p < 3; p++) { const uint32_t op = __shfl_sync(~0u, od, 8 * p + orow); oa[p] = op & maskA; ob[p] = op & maskB; }
            CSTAMP(4, oa[2]);
            float y[5][4];
#pragma unroll
            for (int j = 0; j < 5; j++) y[j][0] = y[j][1] = y[j][2] = y[j][3] = 0.f;
            auto rest = [&]() {
                if (!ok) static_for<NW, 5>([&](auto J) { mbar_wait(sb + SM_CBAR + (CB_WO + J.value) * 8, L.value); });
                static_for<NW, 5>(read_wo);
                __syncwarp();
            };
            if (L.value) rest();
#pragma unroll
            for (int p = 0; p < 3; p++)
#pragma unroll
                for (int j = 0; j < NW; j++) mma(y[j], v[j][p], oa[p], ob[p]);
            if (!L.value) { rest(); sum_setup(L); }
#pragma unroll
            for (int p = 0; p < 3; p++)
#pragma unroll
                for (int j = NW; j < 5; j++) mma(y[j], v[j][p], oa[p], ob[p]);
            CSTAMP(5, __float_as_uint(y[4][3]));
#pragma unroll
            for (int j = 0; j < 5; j += 2) {
                if (j < 4 && (t >> 1) != (g >> 2)) { y[j][0] = y[j + 1][0]; y[j][1] = y[j + 1][1]; y[j][2] = y[j + 1][2]; y[j][3] = y[j + 1][3]; }
                sts128f(wpa + j * 256, y[j]);
            }
            TSTAMP2(5);
        };
        u64 yw[2];
        bool wide;
        float msq = 0.f, yf[4] = {};
        auto mlp_part = [&](auto L) {
            bar_sync(0, 256);
            CSTAMP(6, __float_as_uint(sc1));
            const float s = (sum8(pa, 1536) + xc) + sum8(pa + 128, 1536), sm = s * sc1 + FX2_ONE;
            CSTAMP(7, __float_as_uint(s));
            const bool wide1 = !(fabsf(sm - FX2_ONE) < FX1LIM);
            asm volatile("red.relaxed.gpu.global.add.u32 [%0], %1;" :: "l"(rop), "r"(wide1 ? 0u : __float_as_uint(sm) * 128u + (1u - 0x4b400000u * 128u)) : "memory");
            const uint32_t c0 = clk();
            TSTAMP2(6);
            if (L.value == 0) bar_arrive(2, 256);
            if (wide1) {
                fx_send(rop + 64 + (lane & 7) * 4, s, ldsf(sb + SM_FXS), rop, 64);
                asm volatile("red.relaxed.gpu.global.add.u32 [%0], 1;" :: "l"(rop) : "memory");
            }
            __syncwarp();
            if (L.value == 1 && mlp == 96) { TDUMP(); asm volatile("exit;"); }
            uint4 wf[8], w2r[8];
            uint4 w;
            auto look = [&]() { asm volatile("ld.relaxed.gpu.global.v4.u32 {%0,%1,%2,%3}, [%4];" : "=r"(w.x), "=r"(w.y), "=r"(w.z), "=r"(w.w) : "l"(ap) : "memory"); };
            auto read_w1 = [&]() {
#pragma unroll
                for (int j = 0; j < 8; j++) wf[j] = ldsm_t(la + j * 256);
            };
            auto read_w2 = [&]() {
#pragma unroll
                for (int i = 0; i < 8; i++) w2r[i] = lds128(((i & 1) ? (w2a ^ 16) + 128 : w2a) + (i >> 1) * 5120);
            };
            const float inv = pinf(fx_inv(sc1) * (1.f / 128)), off = L.value ? pinf(fx_inv(sc1) * -0.25f) : inv * -32.f;
            if (L.value == 0) { fresh(); mlp_global(L); }
            mbar_wait(sb + SM_CBAR + CB_W1 * 8, L.value);
            if (L.value == 1) read_w1();
            while (clk() - c0 < AR1D);
            look();
            if (L.value == 0) { mlp_shared(L); read_w1(); bar_arrive(3, 256); }
            else { mbar_wait(sb + SM_CBAR + CB_W2 * 8, 1); read_w2(); }
            TSTAMPL(28);
            {
                sched_fence();
                auto miss = [&]() {
                    xp = make_uint2(pack_bf((float)(int)w.x * inv + off, (float)(int)w.y * inv + off), pack_bf((float)(int)w.z * inv + off, (float)(int)w.w * inv + off));
                    uint32_t a, b;
                    asm("lop3.b32 %0, %1, %2, 32, 0x7e;" : "=r"(a) : "r"(w.x), "r"(w.y));
                    asm("lop3.b32 %0, %1, %2, 32, 0x7e;" : "=r"(b) : "r"(w.z), "r"(w.w));
                    return __any_sync(~0u, (a | b) & 96);
                };
                if (miss()) {
                    int it = 0;
#pragma unroll 1
                    do {
                        if (!__any_sync(~0u, ~(w.x & w.y & w.z & w.w) & 32)) { xp.x = fx1_wide(ap, ldsf(sb + SM_FXS)); xp.y = fx1_wide(ap + 8, ldsf(sb + SM_FXS)); break; }
                        look();
                    } while (miss() & (++it < SPIN));
                }
                CSTAMP(8, w.w);
            }
            TSTAMP2(7);
            CSTAMP(9, xp.y);
            {
                bool ok = true;
                if (L.value == 0) ok = mbar_test(sb + SM_CBAR + CB_W2 * 8, 0);
                const bool ev = L.value || !(g & 1), od = L.value || (g & 1);
                const uint32_t e0 = ev ? xp.x : ONES, e1 = ev ? xp.y : ONES, o0 = od ? xp.x : ONES, o1 = od ? xp.y : ONES;
                float d[8][4];
#pragma unroll
                for (int j = 0; j < 8; j++) { d[j][0] = d[j][1] = d[j][2] = d[j][3] = 0.f; mma(d[j], wf[j], (j & 1) ? o0 : e0, (j & 1) ? o1 : e1); }
                float ss = ln_part(xp, lane);
                ss += shx(ss, 8); ss += shx(ss, 4);
                float r[4], dd;
#pragma unroll
                for (int k = 0; k < 4; k += 1 + L.value) r[k] = d[0][k] + d[1][k ^ 1];
#pragma unroll
                for (int j = 1; j < 4; j++)
#pragma unroll
                    for (int k = 0; k < 4; k += 1 + L.value) add_if(t == j, r[k], d[2 * j][k], d[2 * j + 1][k ^ 1]);
                CSTAMP(10, __float_as_uint(r[2]));
                if (L.value) {
                    dd = ((t & 2) ? r[2] : r[0]) + shx((t & 2) ? r[0] : r[2], 2);
                    ss += shx(ss, 2);
                    dd += shx(dd, 1);
                } else {
                    const float a = ((t & 1) ? r[1] : r[0]) + shx((t & 1) ? r[0] : r[1], 1), b = ((t & 1) ? r[3] : r[2]) + shx((t & 1) ? r[2] : r[3], 1);
                    ss += shx(ss, 2);
                    dd = ((t & 2) ? b : a) + shx((t & 2) ? a : b, 2);
                }
                ss += shx(ss, 1);
                stsf(hpa, dd);
                stsf(hst, ss);
                CSTAMP(11, __float_as_uint(dd + ss));
                if (!ok) mbar_wait(sb + SM_CBAR + CB_W2 * 8, L.value);
            }
            TSTAMPL(25);
            bar_sync(1, 160);
            uint4 hp[5];
#pragma unroll
            for (int w = 0; w < 5; w++) hp[w] = lds128(hsa + w * 256);
            CSTAMP(12, hp[0].x);
            auto hs = [&](auto K) { return sum5(__uint_as_float(word<K.value>(hp[0])), __uint_as_float(word<K.value>(hp[1])), __uint_as_float(word<K.value>(hp[2])),
                                                __uint_as_float(word<K.value>(hp[3])), __uint_as_float(word<K.value>(hp[4]))); };
            const float mean = hs(IC<2>{}) * (1.f / D_MODEL);
            msq = hs(IC<3>{}) * (1.f / D_MODEL);
            if (L.value == 0) cs1 = hs(IC<1>{});
            float hv = hs(IC<0>{}) - mean * cs1;
            CSTAMP(13, __float_as_uint(hv));
            const float sc2 = fx2_scale(msq), lim = fx_inv(sc2) * FX2LIM;
            if (L.value == 0) {
                read_w2();
                bar_arrive(4, 256);
                wide = false;
                if (mlp == 96) return;
            }
            hv = hv * ln_rstd(mean, msq) + b1v;
            CSTAMP(14, __float_as_uint(hv));
            hv = hv * rcp(1.f + ex2(hv * (-2.302208198f - 0.1029432397f * hv * hv)));
            const uint32_t hd = pack_bf(hv, hv);
            CSTAMP(15, hd);
            TSTAMPL(27);
            float ym[4][4];
#pragma unroll
            for (int i = 0; i < 2; i++) {
                ym[i][0] = ym[i][1] = ym[i][2] = ym[i][3] = 0.f;
                const float f = mlp < 64 ? 1.f / 64 : 0.f;
                ym[i + 2][0] = (bf_lo(xp.x) + bf_lo(b2v.x)) * f; ym[i + 2][1] = (bf_hi(xp.x) + bf_hi(b2v.x)) * f;
                ym[i + 2][2] = (bf_lo(xp.y) + bf_lo(b2v.y)) * f; ym[i + 2][3] = (bf_hi(xp.y) + bf_hi(b2v.y)) * f;
            }
#pragma unroll
            for (int i = 0; i < 4; i++) {
                const uint32_t hh = __shfl_sync(~0u, hd, 4 * i + t);
                mma(ym[(i & 1) * 2], w2r[2 * i], hh & maskA, hh & maskB);
                mma(ym[(i & 1) * 2 + 1], w2r[2 * i + 1], hh & maskA, hh & maskB);
            }
#pragma unroll
            for (int k = 0; k < 4; k++) { yf[k] = ym[0][k] + ym[2][k]; add_if(t & 2, yf[k], ym[1][k], ym[3][k]); }
            CSTAMP(16, __float_as_uint(yf[3]));
            yw[0] = fx2_pack(yf[0] * sc2 + FX2_ONE, yf[1] * sc2 + FX2_ONE); yw[1] = fx2_pack(yf[2] * sc2 + FX2_ONE, yf[3] * sc2 + FX2_ONE);
            wide = !(fmaxf(fmaxf(fabsf(yf[0]), fabsf(yf[1])), fmaxf(fabsf(yf[2]), fabsf(yf[3]))) < lim);
            if (wide) yw[0] = yw[1] = 0;
            if (L.value == 0) {
#pragma unroll
                for (int k = 0; k < 2; k++) asm volatile("red.relaxed.gpu.global.add.u64 [%0], %1;" :: "l"(rap + k * 40 * ACC_PITCH), "l"(yw[k]) : "memory");
            }
        };
        auto send_wide = [&]() {
#pragma unroll 1
            for (int k = 0; k < 4; k++, yf[0] = yf[1], yf[1] = yf[2], yf[2] = yf[3]) {
                const unsigned char* a = rap + (k >> 1) * 40 * ACC_PITCH;
                fx_send(a + 64 + (k & 1) * 32, yf[0], msq, a, 256);
            }
            yw[0] = yw[1] = 1;
        };

        pass1();
        o_setup(IC<0>{});
        out_proj(IC<0>{});
        uint32_t c0;
        if (warp < 5) {
            mlp_part(IC<0>{});
            c0 = clk() + (mlp == 96 ? PCD : 0);
            stsf(sb + SM_ML + (lane & 15) * 4, cs1);
            TSTAMP(8);
            if (__any_sync(~0u, wide)) {
                if (wide) {
                    send_wide();
#pragma unroll
                    for (int k = 0; k < 2; k++) asm volatile("red.relaxed.gpu.global.add.u64 [%0], 1;" :: "l"(rap + k * 40 * ACC_PITCH) : "memory");
                }
                __syncwarp();
            }
            fresh(); calc_offsets();
            load_wq();
        } else {
            bar_sync(0, 256);
            if (warp == 5 && elect()) {
                asm volatile("fence.proxy.async.shared::cta;" ::: "memory");
                issue_w(IC<0>{}, 1);
            }
            __syncwarp();
            fresh(); calc_offsets();
            load_wq();
#pragma unroll 1
            for (int ph = 0; ph < 3; ph++) {
                bar_sync(ph + 2, 256);
                c0 = clk();
                if (ph == 2) {
                    msq = sum5(ldsf(sb + SM_PART + 12), ldsf(sb + SM_PART + 268), ldsf(sb + SM_PART + 524), ldsf(sb + SM_PART + 780), ldsf(sb + SM_PART + 1036)) * (1.f / D_MODEL);
                    bar_arrive(5, 256);
                }
                if (elect()) {
                    asm volatile("fence.proxy.async.shared::cta;" ::: "memory");
                    const uint32_t gap = ph == 0 ? WG1 : ph == 1 ? WG2 : WG3;
                    uint32_t c1 = c0 + (ph == 0 ? WD1 : 0) + (warp - 5) * gap;
#pragma unroll 1
                    for (int k = warp + (ph == 0 ? -5 : ph == 1 ? 9 : 1); k < (ph == 0 ? 9 : ph == 1 ? 20 : 14); k += 3, c1 += 3 * gap) {
                        const int i = ph == 0 && k >= 6 ? k + 23 : k;
                        const uint32_t bar = sb + SM_BAR + (i & 7) * 96 + 32 + (i & 24);
                        while ((int)(clk() - c1) < 0);
                        mbar_expect(bar, SUB);
                        tma_v(sb + SM_RING + i * SUB, tmk,
                              rowc * 3 + (i & 7) * 24 + ((UC<SCH.st[0].unit | SCH.st[1].unit << 8 | SCH.st[2].unit << 16 | SCH.st[3].unit << 24>::value >> (i & 24)) & 15) * 768, bar);
                    }
                }
                __syncwarp();
            }
            c0 += PCD;
        }
        {
            constexpr IC<1> L{};
            fresh();
            const int col = xcol(g & 3, t), cw = j40 + (col >> 2);
            const unsigned char* xa = pin(accg + ACC_BYTES + ((cw >> 2) + (col & 2) * 20) * ACC_PITCH + (cw & 3) * 8);
            const uint32_t pst = pin(prow + (g * 8 + (t & 1) * 4 + (t & 2)) * 4);
            const float inv = pinf(fx2_inv(msq));
            sts64f(sb + SM_MSQ, msq, inv);
            rap = pin(accg + ACC_BYTES + (c4() >> 2) * ACC_PITCH + (c4() & 3) * 8);
            fresh();
            maskA = pin(maskA); maskB = pin(maskB);
            u64 w[1];
            uint32_t x1[1], x2[3];
            auto look = [&]() { w[0] = ld_rlx(xa); };
            if (warp < 5) bar_sync(5, 256);
            while ((int)(clk() - c0) < ARDELAY);
            look();
            while ((int)(clk() - c0) < ARDELAY + DPOST);
            if (warp < 5 && elect()) {
                issue_v(IC<3>{}, 0);
                if (warp < 4) issue_v(IC<2>{}, 4);
            }
            __syncwarp();
            fx2_wait<1>([&](int) { return xa; }, look, w, sb + SM_MSQ, inv, x1);
            if (warp < 5) look_rw(); else rw[0] = rw[1] = 96;
#pragma unroll
            for (int i = 0; i < 3; i++) x2[i] = __shfl_sync(~0u, x1[0], 4 * i + t);
            TSTAMP(9);
            CSTAMP(22, x2[2]);
            q_proj(L, x2, pst);
            pass2();
            out_proj(L);
            if (warp >= 5) {
                bar_arrive(0, 256);
                if (warp == 5 && elect()) issue_w(L, 1);
                TDUMP();
                return;
            }
            mlp_part(L);
            u64 old[2];
            auto add = [&]() {
#pragma unroll
                for (int k = 0; k < 2; k++) asm volatile("atom.relaxed.gpu.global.add.u64 %0, [%1], %2;" : "=l"(old[k]) : "l"(rap + k * 40 * ACC_PITCH), "l"(yw[k]) : "memory");
            };
            add();
            uint32_t* op = pin(reinterpret_cast<uint32_t*>(P.out) + 2 * c4());
            const float inv2 = pinf(fx2_inv(msq));
            if (wide) { send_wide(); add(); }
            TSTAMP(18);
            CSTAMP(17, hi32(yw[1]));
            __syncwarp();
            CSTAMP(18, lo32(old[0]) ^ lo32(old[1]));
#pragma unroll
            for (int k = 0; k < 2; k++) {
                yw[k] += old[k];
                asm volatile("{\n.reg .pred p;\nsetp.eq.u32 p, %2, 96;\n@p st.global.u32 [%0], %1;\n}"
                             :: "l"(op + k), "r"(fx2_get(yw[k], inv2)), "r"(lo32(yw[k]) & 511) : "memory");
            }
            if ((lo32(yw[0]) & 255) == 96 && tid == 0) P.g->epoch = lds32(sb + SM_EPOCH) + 1;
#pragma unroll
            for (int k = 0; k < 2; k++) if ((lo32(yw[k]) & 511) == 256 + 96) op[k] = fx2_wide(rap + k * 40 * ACC_PITCH, msq);
            TSTAMP(19);
            CSTAMP(19, lo32(yw[1]));
            TDUMP();
        }
    }
}

typedef CUresult (*EncodeFn)(CUtensorMap*, CUtensorMapDataType, cuuint32_t, void*, const cuuint64_t*, const cuuint64_t*, const cuuint32_t*,
                             const cuuint32_t*, CUtensorMapInterleave, CUtensorMapSwizzle, CUtensorMapL2promotion, CUtensorMapFloatOOBfill);

}

extern "C" void kernel_launch(void* const* d_in, const int* in_sizes, int n_in, void* d_out, int out_size) {
    (void)in_sizes; (void)n_in; (void)out_size;
    static EncodeFn enc = nullptr;
    static void* scratch = nullptr;
    if (!enc) {
        void* fn = nullptr;
        cudaDriverEntryPointQueryResult qr;
        cudaGetDriverEntryPoint("cuTensorMapEncodeTiled", &fn, cudaEnableDefault, &qr);
        enc = (EncodeFn)fn;
        cudaGetSymbolAddress(&scratch, g_scratch);
        cudaFuncSetAttribute(fused_kernel, cudaFuncAttributeMaxDynamicSharedMemorySize, SM_TOTAL);
    }
    Params P = {};
    auto map3 = [&](int m, int in, cuuint64_t d0, cuuint64_t d1, cuuint64_t d2, cuuint64_t s1, cuuint64_t s2, cuuint32_t b0, cuuint32_t b1, cuuint32_t b2,
                    CUtensorMapSwizzle sw, int promo) {
        const cuuint64_t dim[3] = {d0, d1, d2}, str[2] = {s1, s2};
        const cuuint32_t box[3] = {b0, b1, b2}, ones[3] = {1, 1, 1};
        enc(&P.tm[m], CU_TENSOR_MAP_DATA_TYPE_BFLOAT16, d2 ? 3 : 2, d_in[in], dim, str, box, ones, CU_TENSOR_MAP_INTERLEAVE_NONE, sw, (CUtensorMapL2promotion)promo,
            CU_TENSOR_MAP_FLOAT_OOB_FILL_NONE);
    };
    map3(TM_KH, 1, 64, 3, NHEAD * SK, 128, DH * 2, 64, 3, 32, CU_TENSOR_MAP_SWIZZLE_128B, 0);
    map3(TM_VH, 2, 64, 3, NHEAD * SK, 128, DH * 2, 64, 3, 32, CU_TENSOR_MAP_SWIZZLE_128B, 0);
    map3(TM_VP, 2, 64, 3, NHEAD * SK, 128, DH * 2, 8, 3, 32, CU_TENSOR_MAP_SWIZZLE_NONE, 0);
    map3(TM_V, 2, 64, NHEAD * SK * 3, 0, 128, 0, 64, 24, 0, CU_TENSOR_MAP_SWIZZLE_128B, 0);
    map3(TM_WO, 4, 32, 20, NHEAD * DH, 64, D_MODEL * 2, 32, 1, DH, CU_TENSOR_MAP_SWIZZLE_64B, 2);
    map3(TM_WOP, 4, 32, 20, NHEAD * DH, 64, D_MODEL * 2, 8, 1, DH, CU_TENSOR_MAP_SWIZZLE_NONE, 0);
    map3(TM_WQ, 3, 64, NHEAD * 3, D_MODEL, 128, NHEAD * DH * 2, 64, 3, 32, CU_TENSOR_MAP_SWIZZLE_128B, 0);
    map3(TM_W1, 6, DFF, 128, 5, DFF * 2, DFF * 256, 16, 128, 5, CU_TENSOR_MAP_SWIZZLE_32B, 2);
    map3(TM_W2, 8, 64, 10, DFF, 128, D_MODEL * 2, 64, 10, 16, CU_TENSOR_MAP_SWIZZLE_128B, 0);
    P.x = (const __nv_bfloat16*)d_in[0];
    P.k = (const __nv_bfloat16*)d_in[1];
    P.b1 = (const __nv_bfloat16*)d_in[7];
    P.b2 = (const __nv_bfloat16*)d_in[9];
    P.w1 = (const __nv_bfloat16*)d_in[6];
    P.out = (__nv_bfloat16*)d_out;
    P.g = (Scratch*)(((uintptr_t)scratch + ACC_BYTES - 1) & ~(uintptr_t)(ACC_BYTES - 1));
    for (int i = 0; i < 64; i++) P.tile[i] = make_uint4(SCH.tile[i][0], SCH.tile[i][1], SCH.tile[i][2], 0);
    fused_kernel<<<NCTA + 1, NTHR, SM_TOTAL, cudaStreamPerThread>>>(P);
}
```

```cpp
#include <cuda_runtime.h>
#include <cuda_bf16.h>
#include <cuda.h>
#include <stdint.h>

namespace {

constexpr int D_MODEL = 640, NHEAD = 32, SK = 32768, DH = 192, WIN = 4096, DFF = 1536;
constexpr int NCTA = 128, NTHR = 256;
constexpr int TILE = 64 * DH * 2;
constexpr int HALF = TILE / 2;
constexpr int SUB = 8 * DH * 2;
constexpr int SM_RING = 4 * TILE;
constexpr int SM_W2 = SM_RING + 20480, SM_W1 = SM_W2 + 20480;
constexpr int SM_WQR = 6 * TILE + HALF, SM_WQ = 7 * TILE;
constexpr int SM_PART = 9 * TILE;
constexpr int SM_EXC = SM_PART + 6144;
constexpr int SM_SC = SM_EXC + 1024;
constexpr int SM_BAR = SM_SC + 1024;
constexpr int SM_VEC = SM_BAR + 768;
constexpr int SM_CS = SM_VEC + 384;
constexpr int SM_FAC = SM_CS + 768;
constexpr int SM_ML = SM_FAC + 32;
constexpr int SM_B1 = SM_ML + 64;
constexpr int SM_STAT = SM_B1 + 64;
constexpr int NCB = 28;
constexpr int CB_WO = 18, CB_W1 = 23, CB_W2 = 24, CB_SNAP = 25, CB_REL = 26, CB_WQ = 27;
constexpr int SM_CBAR = SM_STAT + 48;
constexpr int SM_CNT = SM_CBAR + NCB * 8;
constexpr int SM_ZERO = SM_CNT + NCB * 8;
constexpr int SM_EPOCH = SM_ZERO + 64;
constexpr int SM_FXS = SM_EPOCH + 4;
constexpr int SM_T0 = SM_FXS + 4;
constexpr int SM_M1 = SM_T0 + 4;
constexpr int SM_MSQ = SM_M1 + 4;
constexpr int SM_TS = SM_MSQ + 8;
constexpr int SM_TOTAL = 232448;
static_assert(SM_TS + 320 <= SM_TOTAL && SM_ZERO % 16 == 0, "smem");
constexpr int NEXC = 16;

constexpr int SPIN = 1 << 20;
enum { TM_V = 0, TM_KH = 1, TM_VH = 2, TM_WO = 3, TM_VP = 4, TM_WOP = 5, TM_W1 = 6, TM_W2 = 7, TM_WQ = 8 };
constexpr uint32_t POL_NORMAL = 0x16F00000u, POL_FIRST = 0x12F00000u;

#define PACE 980
#define PACE0 1500
#define PACES 1300
#define NIM 4
#define NI1 6
#define ETRIG 0x54321000
#define PFREE 66
#define SNAPAT 1
#define LATEAT 5
#define PUBAT 28
#define HW0 30
#define HW1 31
#define AR1D 250
#define ARDELAY 650
#define DPOST 200
#define PCD 350
#define WD1 100
#define WG1 140
#define WG2 120
#define WG3 65
#define VORD2 0x7685943a2b1cd0efull
#define VSLOT 0x1087654321087654ull
#define VTRIG 0xba73210
#define PARKS 0xa5
#define NPRE 2
#define M1AT 1
#define M1P 3
#define LAG0 12
#define NMMA 2
#define HWAT 12
#define WOP 0x44433
#define NWO1 4
#define FX1LIM 524288.f
#define FX2LIM 524288.f

constexpr uint32_t G_A = 1u << 28, G_B = 1u << 29, G_C = 1u << 30;
__host__ __device__ constexpr int ring_hs(int j) { return (j + 4) % 5; }
__host__ __device__ constexpr uint32_t load_word(int j) {
    if (j >= 64) return (uint32_t)(j - 64) << 20 | (SM_RING + ring_hs(j) * HALF) | TM_WO << 8 | (CB_WO + j - 64) << 3 | 2;
    const int e = j >> 1, isv = e >= 16, unit = e & 15;
    return (uint32_t)(unit * 256 + (j & 1) * 32) << 20 | (j < 8 ? j * HALF : SM_RING + ring_hs(j) * HALF) | (TM_KH + isv) << 8 | (j < 8 ? 10 + j : (j - 8) % 10) << 3 | 2 | !isv;
}
__host__ __device__ constexpr int popc(int v) { return v ? (v & 1) + popc(v >> 1) : 0; }
constexpr int NPARK = popc(PARKS);
constexpr int SM_SNAP = SM_RING + ring_hs(12) * HALF, SM_CSP = SM_RING + ring_hs(11) * HALF;
struct Step { int unit, slot, par, next, mma0, nmma; };
struct Sched { uint32_t tile[64][3]; Step st[16]; };
constexpr Sched make_sched() {
    Sched s{};
    for (int j = 0; j < 64; j++) {
        const int e = j >> 1;
        const uint32_t d = load_word(j);
        uint32_t w = (uint32_t)(j < 8 ? 0 : (j - 8) / 10 & 1) << 31 | (e & 15) * 4 << 20 | ((d & 0x3f000) - (j & 1) * HALF) | (d & 0xf8);
        if (e == PUBAT || e == SNAPAT) w |= G_A;
        if (e == HW0 || e == 4) w |= G_B;
        if ((e >= LATEAT && e < LATEAT + 4) || e == HW1) w |= G_C;
        s.tile[j][0] = w;
    }
    for (int j = NI1; j < 69; j++) {
        if (j == 12) continue;
        const int at = j < 12 ? (ETRIG >> (4 * (j - 4)) & 15) : j - 5;
        s.tile[at][1] = load_word(j);
        s.tile[at][2] = j >= PFREE ? 0 : PACE0 + j * PACE / 2;
    }
    int done = 0;
    for (int p = 0; p < 16; p++) {
        Step& c = s.st[p];
        c.unit = (int)(VORD2 >> (4 * p) & 15); c.slot = (int)(VSLOT >> (4 * p) & 15); c.par = p >= 9; c.next = -1;
        c.mma0 = done;
        if (p >= NPARK) { const int avail = p - done + (p >= LAG0); c.nmma = p == 15 ? 16 - done : (avail < NMMA ? avail : NMMA); done += c.nmma; }
    }
    for (int p = 9; p < 16; p++) s.st[VTRIG >> (4 * (p - 9)) & 15].next = p;
    return s;
}
constexpr Sched SCH = make_sched();
__host__ __device__ constexpr int kunit(int o) { return o < 5 ? o + 11 : o == 5 ? 10 : o - 6; }

template <int I> struct IC { static constexpr int value = I; };
template <uint32_t I> struct UC { static constexpr uint32_t value = I; };
template <int A, int B, class F> __device__ __forceinline__ void static_for(F&& f) {
    if constexpr (A < B) { f(IC<A>{}); static_for<A + 1, B>(f); }
}

typedef unsigned long long u64;
constexpr int ACC_PITCH = 352, ACC1_PITCH = 256, ACC_BYTES = 32768;
struct alignas(1024) Scratch {
    unsigned char acc[4 * ACC_BYTES];
    u64 l0[NCTA][384];
    u64 ll[NCTA][256];
    alignas(128) unsigned epoch;
    alignas(128) unsigned zeroed;
};
__device__ __align__(1024) unsigned char g_scratch[sizeof(Scratch) + ACC_BYTES];

struct Params {
    CUtensorMap tm[9];
    const __nv_bfloat16 *x, *k, *b1, *b2, *w1;
    __nv_bfloat16* out;
    Scratch* g;
    uint4 tile[66];
};

#define TSTAMP(i)
#define TSTAMP2(i)
#define TSTAMPL(i)
#define TDUMP()
#define CSTAMP(i, x)
#define TRACE(i)

__device__ __forceinline__ void mbar_wait(uint32_t bar, uint32_t parity) {
    asm volatile("{\n.reg .pred p;\nLOOP:\nmbarrier.try_wait.parity.shared::cta.b64 p, [%0], %1;\n@!p bra.uni LOOP;\n}" :: "r"(bar), "r"(parity) : "memory");
}
__device__ __forceinline__ bool mbar_test(uint32_t bar, uint32_t parity) {
    uint32_t r;
    asm volatile("{\n.reg .pred p;\nmbarrier.test_wait.parity.shared::cta.b64 p, [%1], %2;\nselp.u32 %0, 1, 0, p;\n}" : "=r"(r) : "r"(bar), "r"(parity) : "memory");
    return __all_sync(~0u, r);
}
__device__ __forceinline__ bool elect() {
    uint32_t r;
    asm volatile("{\n.reg .pred p;\nelect.sync _|p, 0xffffffff;\nselp.u32 %0, 1, 0, p;\n}" : "=r"(r));
    return r != 0;
}
__device__ __forceinline__ void mbar_expect(uint32_t bar, uint32_t bytes) {
    asm volatile("mbarrier.arrive.expect_tx.shared::cta.b64 _, [%0], %1;" :: "r"(bar), "r"(bytes) : "memory");
}
__device__ __forceinline__ uint4 lds128(uint32_t a) {
    uint4 v; asm volatile("ld.shared.v4.u32 {%0,%1,%2,%3}, [%4];" : "=r"(v.x), "=r"(v.y), "=r"(v.z), "=r"(v.w) : "r"(a) : "memory"); return v;
}
__device__ __forceinline__ uint4 ldsm_t(uint32_t a) {
    uint4 v; asm volatile("ldmatrix.sync.aligned.m8n8.x4.trans.shared.b16 {%0,%1,%2,%3}, [%4];" : "=r"(v.x), "=r"(v.y), "=r"(v.z), "=r"(v.w) : "r"(a) : "memory"); return v;
}
__device__ __forceinline__ uint2 lds64(uint32_t a) {
    uint2 v; asm volatile("ld.shared.v2.u32 {%0,%1}, [%2];" : "=r"(v.x), "=r"(v.y) : "r"(a) : "memory"); return v;
}
__device__ __forceinline__ float2 lds64f(uint32_t a) { const uint2 v = lds64(a); return make_float2(__uint_as_float(v.x), __uint_as_float(v.y)); }
__device__ __forceinline__ uint32_t lds32(uint32_t a) {
    uint32_t v; asm volatile("ld.shared.u32 %0, [%1];" : "=r"(v) : "r"(a) : "memory"); return v;
}
__device__ __forceinline__ float ldsf(uint32_t a) { return __uint_as_float(lds32(a)); }
__device__ __forceinline__ void sts32(uint32_t a, uint32_t v) { asm volatile("st.shared.u32 [%0], %1;" :: "r"(a), "r"(v) : "memory"); }
__device__ __forceinline__ void stsf(uint32_t a, float v) { sts32(a, __float_as_uint(v)); }
__device__ __forceinline__ void sts16(uint32_t a, uint32_t v) { asm volatile("st.shared.u16 [%0], %1;" :: "r"(a), "h"((uint16_t)v) : "memory"); }
__device__ __forceinline__ void sts64(uint32_t a, uint32_t x, uint32_t y) { asm volatile("st.shared.v2.u32 [%0], {%1,%2};" :: "r"(a), "r"(x), "r"(y) : "memory"); }
__device__ __forceinline__ void sts64f(uint32_t a, float x, float y) { sts64(a, __float_as_uint(x), __float_as_uint(y)); }
__device__ __forceinline__ void sts128f(uint32_t a, float x, float y, float z, float w) {
    asm volatile("st.shared.v4.f32 [%0], {%1,%2,%3,%4};" :: "r"(a), "f"(x), "f"(y), "f"(z), "f"(w) : "memory");
}
__device__ __forceinline__ void mma(float (&c)[4], const uint4& a, uint32_t b0, uint32_t b1) {
    asm volatile("mma.sync.aligned.m16n8k16.row.col.f32.bf16.bf16.f32 {%0,%1,%2,%3}, {%4,%5,%6,%7}, {%8,%9}, {%0,%1,%2,%3};"
                 : "+f"(c[0]), "+f"(c[1]), "+f"(c[2]), "+f"(c[3]) : "r"(a.x), "r"(a.y), "r"(a.z), "r"(a.w), "r"(b0), "r"(b1));
}
__device__ __forceinline__ u64 ld_rlx(const void* p) {
    u64 a; asm volatile("ld.relaxed.gpu.global.u64 %0, [%1];" : "=l"(a) : "l"(p) : "memory"); return a;
}
__device__ __forceinline__ void ld_rlx2(const void* p, u64& a, u64& b) {
    asm volatile("ld.relaxed.gpu.global.v2.u64 {%0,%1}, [%2];" : "=l"(a), "=l"(b) : "l"(p) : "memory");
}
__device__ __forceinline__ void st_rlx(void* p, u64 a) { asm volatile("st.relaxed.gpu.global.u64 [%0], %1;" :: "l"(p), "l"(a) : "memory"); }
__device__ __forceinline__ u64 ll_pack(float v, uint32_t tag) { return ((u64)tag << 32) | __float_as_uint(v); }
__device__ __forceinline__ float ll_val(u64 w) { return __uint_as_float((uint32_t)w); }
__device__ __forceinline__ uint32_t ll_tag(u64 w) { return (uint32_t)(w >> 32); }
__device__ __forceinline__ float bf_lo(uint32_t u) { return __uint_as_float(u << 16); }
__device__ __forceinline__ float bf_hi(uint32_t u) { return __uint_as_float(u & 0xffff0000u); }
__device__ __forceinline__ uint32_t pack_bf(float lo, float hi) {
    uint32_t r; asm("cvt.rn.bf16x2.f32 %0, %1, %2;" : "=r"(r) : "f"(hi), "f"(lo)); return r;
}
__device__ __forceinline__ float ex2(float v) { float r; asm("ex2.approx.ftz.f32 %0, %1;" : "=f"(r) : "f"(v)); return r; }
__device__ __forceinline__ float rcp(float v) { float r; asm("rcp.approx.ftz.f32 %0, %1;" : "=f"(r) : "f"(v)); return r; }
__device__ __forceinline__ float rsq(float v) { float r; asm("rsqrt.approx.ftz.f32 %0, %1;" : "=f"(r) : "f"(v)); return r; }
__device__ __forceinline__ void bar_sync(int id, int n) { asm volatile("bar.sync %0, %1;" :: "r"(id), "r"(n) : "memory"); }
__device__ __forceinline__ uint32_t clk() { uint32_t c; asm volatile("mov.u32 %0, %clock;" : "=r"(c)); return c; }
__device__ __forceinline__ void sched_fence() { __syncwarp(); while (clk() == 0x9e3779b9u); }
__device__ __forceinline__ uint32_t pin(uint32_t v) { return __shfl_xor_sync(~0u, v, 0); }
__device__ __forceinline__ float shx(float v, int o) { return __shfl_xor_sync(~0u, v, o); }

__device__ __forceinline__ u64 fx_pack(float v, float scale) { return ((u64)__float2ll_rn(v * scale) & ~255ull) | 1ull; }
__device__ __forceinline__ float fx_scale(float meansq) {
    const int e = max(((int)(__float_as_uint(meansq) >> 23) - 127) >> 1, -6);
    return __uint_as_float((uint32_t)(127 + 32 - e) << 23);
}
__device__ __forceinline__ float fx_inv(float scale) { return __uint_as_float((254u << 23) - __float_as_uint(scale)); }
__device__ __forceinline__ uint32_t lo32(u64 w) { uint32_t l; asm("mov.b64 {%0, _}, %1;" : "=r"(l) : "l"(w)); return l; }
__device__ __forceinline__ int hi32(u64 w) { int h; asm("mov.b64 {_, %0}, %1;" : "=r"(h) : "l"(w)); return h; }
__device__ __forceinline__ float fx_val(u64 w) { return (float)hi32(w) * 4294967296.f + (float)lo32(w); }
constexpr float FX2_ONE = 12582912.f;
__device__ __forceinline__ float fx2_scale(float meansq) { return __uint_as_float((uint32_t)(127 + 16 - max(((int)(__float_as_uint(meansq) >> 23) - 127) >> 1, -100)) << 23); }
__device__ __forceinline__ u64 fx2_pack(float a, float b) {
    const uint32_t lo = __float_as_uint(a) * 512u + (1u - 0x4b400000u * 512u);
    return lo | (u64)(__float_as_uint(b) * 16u - 0x4b400000u * 16u + (uint32_t)((int)lo >> 31)) << 32;
}
__device__ __forceinline__ float fx2_lo(u64 w, float inv) { return (float)(int)(__funnelshift_r(lo32(w), hi32(w), 4) & ~31u) * (inv * 0.5f); }
__device__ __forceinline__ float fx2_hi(u64 w, float inv) { return (float)((hi32(w) + 8) & ~15) * inv; }
__device__ __forceinline__ uint32_t fx2_get(u64 w, float inv) {
    return pack_bf((float)(int)__funnelshift_r(lo32(w), hi32(w), 4) * (inv * 0.5f) - inv * 3.f, (float)hi32(w) * inv);
}
__device__ __forceinline__ float fx2_inv(float meansq) { return fx_inv(fx2_scale(meansq)) * 0.0625f; }
__device__ __noinline__ uint32_t fx2_wide(const unsigned char* a, float meansq) {
    __threadfence();
    const u64 w = ld_rlx(a);
    const float inv = fx_inv(fx_scale(meansq));
    return pack_bf(fx2_lo(w, fx2_inv(meansq)) + fx_val(ld_rlx(a + 64)) * inv, fx2_hi(w, fx2_inv(meansq)) + fx_val(ld_rlx(a + 96)) * inv);
}
__device__ __noinline__ uint32_t fx1_wide(const unsigned char* a, float meansq) {
    __threadfence();
    const u64 w = ld_rlx(a);
    const unsigned char* b = a + 64 + (reinterpret_cast<u64>(a) & 31);
    const float inv = fx_inv(fx_scale(meansq)), inv1 = fx2_inv(meansq) * 0.5f;
    return pack_bf((float)(int)(lo32(w) & ~127u) * inv1 + fx_val(ld_rlx(b)) * inv, (float)(hi32(w) & ~127) * inv1 + fx_val(ld_rlx(b + 8)) * inv);
}
__device__ __noinline__ void fx_send(const unsigned char* wide, float v, float meansq, const unsigned char* a, uint32_t flag) {
    asm volatile("red.relaxed.gpu.global.add.u64 [%0], %1;" :: "l"(wide), "l"(fx_pack(v, fx_scale(meansq))) : "memory");
    __threadfence();
    asm volatile("red.relaxed.gpu.global.or.b32 [%0], %1;" :: "l"(a), "r"(flag) : "memory");
}
template <int N, class A, class F> __device__ __forceinline__ void fx2_wait(A a, F look, u64 (&w)[N], uint32_t msqa, float inv, uint32_t (&x)[N]) {
    auto miss = [&]() {
#pragma unroll
        for (int i = 0; i < N; i++) x[i] = fx2_get(w[i], inv);
        return __any_sync(~0u, ((lo32(w[0]) ^ 96) | (lo32(w[N - 1]) ^ 96)) & 0x160);
    };
    if (miss()) {
        int it = 0;
#pragma unroll 1
        do {
            if (__all_sync(~0u, (lo32(w[0]) & lo32(w[N - 1]) & 96) == 96)) {
#pragma unroll
                for (int i = 0; i < N; i++) x[i] = fx2_wide(a(i), ldsf(msqa));
                break;
            }
            look();
        } while (miss() & (++it < SPIN));
    }
}
__device__ __forceinline__ void st_rlx_if(bool p, void* a, u64 v) {
    asm volatile("{\n.reg .pred p;\nsetp.ne.u32 p, %2, 0;\n@p st.relaxed.gpu.global.u64 [%0], %1;\n}" :: "l"(a), "l"(v), "r"((uint32_t)p) : "memory");
}
__device__ __forceinline__ void sts128f(uint32_t a, const float (&v)[4]) { sts128f(a, v[0], v[1], v[2], v[3]); }
__device__ __forceinline__ void bar_arrive(int id, int n) { asm volatile("bar.arrive %0, %1;" :: "r"(id), "r"(n) : "memory"); }
template <class T> __device__ __forceinline__ T* pin(T* p) { return reinterpret_cast<T*>(__shfl_xor_sync(~0u, (u64)p, 0)); }

__device__ __forceinline__ void tma3(uint32_t dst, const CUtensorMap* tm, int c1, int c2, uint32_t bar, uint32_t pol) {
    asm volatile("cp.async.bulk.tensor.3d.shared::cluster.global.mbarrier::complete_tx::bytes.L2::cache_hint [%0], [%1, {%2, %3, %4}], [%5], %6;"
                 :: "r"(dst), "l"(tm), "r"(0), "r"(c1), "r"(c2), "r"(bar), "l"((u64)pol << 32) : "memory");
}
__device__ __forceinline__ void tma_v(uint32_t dst, const CUtensorMap* tm, int line, uint32_t bar) {
    asm volatile("cp.async.bulk.tensor.2d.shared::cluster.global.mbarrier::complete_tx::bytes.L2::cache_hint [%0], [%1, {%2, %3}], [%4], %5;"
                 :: "r"(dst), "l"(tm), "r"(0), "r"(line), "r"(bar), "l"((u64)POL_FIRST << 32) : "memory");
}
__device__ __forceinline__ void tma3_pf(const CUtensorMap* tm, int c1, int c2, uint32_t pol) {
    asm volatile("cp.async.bulk.prefetch.tensor.3d.L2.global.tile.L2::cache_hint [%0, {%1, %2, %3}], %4;"
                 :: "l"(tm), "r"(0), "r"(c1), "r"(c2), "l"((u64)pol << 32) : "memory");
}
__device__ __forceinline__ void issue_half(uint32_t d, uint32_t sb, int rowc, int cta, const CUtensorMap* tm0) {
    const uint32_t bar = sb + SM_CBAR + (d & 0xf8);
    const CUtensorMap* tm = tm0 + ((d >> 8) & 3);
    const bool wo = (d & 0x300) == TM_WO << 8;
    const int c1 = wo ? (cta & 3) + 4 * (d >> 20) : 0, c2 = wo ? (cta >> 2) * DH : rowc + (d >> 20);
    mbar_expect(bar, HALF);
    tma3(sb + (d & 0x3f000), tm, c1, c2, bar, POL_FIRST);
    if (!(d & 1)) tma3_pf(tm + 2, c1, c2, POL_NORMAL);
}
__device__ __forceinline__ uint32_t cnt_inc(uint32_t a, uint32_t last) {
    uint32_t old; asm volatile("atom.relaxed.cta.shared.inc.u32 %0, [%1], %2;" : "=r"(old) : "r"(a), "r"(last) : "memory"); return old;
}
__device__ __forceinline__ void wait_until(uint32_t due) {
#pragma unroll 1
    for (int it = 0; it < 4096; it++) { uint32_t now; asm volatile("mov.u32 %0, %globaltimer_lo;" : "=r"(now)); if ((int)(now - due) >= 0) break; }
}
__device__ __forceinline__ uint32_t bf2_mul(uint32_t a, uint32_t b) { uint32_t r; asm("mul.rn.bf16x2 %0, %1, %2;" : "=r"(r) : "r"(a), "r"(b)); return r; }
__device__ __forceinline__ uint32_t bf2_fma(uint32_t a, uint32_t b, uint32_t c) { uint32_t r; asm("fma.rn.bf16x2 %0, %1, %2, %3;" : "=r"(r) : "r"(a), "r"(b), "r"(c)); return r; }
__device__ __forceinline__ uint32_t bf2_amax(uint32_t a, uint32_t b) { uint32_t r; asm("max.NaN.xorsign.abs.bf16x2 %0, %1, %2;" : "=r"(r) : "r"(a), "r"(b)); return r; }
__device__ __forceinline__ uint4 k_unpack(uint32_t l0, uint32_t l1, uint32_t h, uint32_t m1) {
    const uint32_t ha = h & 0x87878787u, hc = ha * m1 + h, hb = __funnelshift_l(hc, hc, 4);
    return make_uint4(__byte_perm(l0, ha, 0x5140), __byte_perm(l0, ha, 0x7362), __byte_perm(l1, hb, 0x5140), __byte_perm(l1, hb, 0x7362));
}
#define KR4(u, i) "+r"(kr[u][i].x), "+r"(kr[u][i].y), "+r"(kr[u][i].z), "+r"(kr[u][i].w)
#define KR6(u) KR4(u, 0), KR4(u, 1), KR4(u, 2), KR4(u, 3), KR4(u, 4), KR4(u, 5)
__device__ __forceinline__ void k_keep(uint4 (&kr)[8][6], const uint32_t (&c)[18], int e, uint32_t a) {
    asm volatile("{\nKT: .branchtargets K0, K1, K2, K3, K4, K5, K6, K7, K8, K9, K10, K11, K12, K13, K14, K15;\nbrx.idx.uni %210, KT;\n"
                 "K0: mov.b32 %12, %192; mov.b32 %13, %193; mov.b32 %14, %194; mov.b32 %15, %195; mov.b32 %16, %196; mov.b32 %17, %197; mov.b32 %18, %198; mov.b32 %19, %199; mov.b32 %20, %200; mov.b32 %21, %201; mov.b32 %22, %202; mov.b32 %23, %203; mov.b32 %24, %204; mov.b32 %25, %205; mov.b32 %26, %206; mov.b32 %27, %207; mov.b32 %28, %208; mov.b32 %29, %209; bra.uni KE;\n"
                 "K1: mov.b32 %30, %192; mov.b32 %31, %193; mov.b32 %32, %194; mov.b32 %33, %195; mov.b32 %34, %196; mov.b32 %35, %197; mov.b32 %36, %198; mov.b32 %37, %199; mov.b32 %38, %200; mov.b32 %39, %201; mov.b32 %40, %202; mov.b32 %41, %203; mov.b32 %42, %204; mov.b32 %43, %205; mov.b32 %44, %206; mov.b32 %45, %207; mov.b32 %46, %208; mov.b32 %47, %209; bra.uni KE;\n"
                 "K2: mov.b32 %48, %192; mov.b32 %49, %193; mov.b32 %50, %194; mov.b32 %51, %195; mov.b32 %52, %196; mov.b32 %53, %197; mov.b32 %54, %198; mov.b32 %55, %199; mov.b32 %56, %200; mov.b32 %57, %201; mov.b32 %58, %202; mov.b32 %59, %203; mov.b32 %60, %204; mov.b32 %61, %205; mov.b32 %62, %206; mov.b32 %63, %207; mov.b32 %64, %208; mov.b32 %65, %209; bra.uni KE;\n"
                 "K3: mov.b32 %66, %192; mov.b32 %67, %193; mov.b32 %68, %194; mov.b32 %69, %195; mov.b32 %70, %196; mov.b32 %71, %197; mov.b32 %72, %198; mov.b32 %73, %199; mov.b32 %74, %200; mov.b32 %75, %201; mov.b32 %76, %202; mov.b32 %77, %203; mov.b32 %78, %204; mov.b32 %79, %205; mov.b32 %80, %206; mov.b32 %81, %207; mov.b32 %82, %208; mov.b32 %83, %209; bra.uni KE;\n"
                 "K4: mov.b32 %84, %192; mov.b32 %85, %193; mov.b32 %86, %194; mov.b32 %87, %195; mov.b32 %88, %196; mov.b32 %89, %197; mov.b32 %90, %198; mov.b32 %91, %199; mov.b32 %92, %200; mov.b32 %93, %201; mov.b32 %94, %202; mov.b32 %95, %203; mov.b32 %96, %204; mov.b32 %97, %205; mov.b32 %98, %206; mov.b32 %99, %207; mov.b32 %100, %208; mov.b32 %101, %209; bra.uni KE;\n"
                 "K5: mov.b32 %102, %192; mov.b32 %103, %193; mov.b32 %104, %194; mov.b32 %105, %195; mov.b32 %106, %196; mov.b32 %107, %197; mov.b32 %108, %198; mov.b32 %109, %199; mov.b32 %110, %200; mov.b32 %111, %201; mov.b32 %112, %202; mov.b32 %113, %203; mov.b32 %114, %204; mov.b32 %115, %205; mov.b32 %116, %206; mov.b32 %117, %207; mov.b32 %118, %208; mov.b32 %119, %209; bra.uni KE;\n"
                 "K6: mov.b32 %120, %192; mov.b32 %121, %193; mov.b32 %122, %194; mov.b32 %123, %195; mov.b32 %124, %196; mov.b32 %125, %197; mov.b32 %126, %198; mov.b32 %127, %199; mov.b32 %128, %200; mov.b32 %129, %201; mov.b32 %130, %202; mov.b32 %131, %203; mov.b32 %132, %204; mov.b32 %133, %205; mov.b32 %134, %206; mov.b32 %135, %207; mov.b32 %136, %208; mov.b32 %137, %209; bra.uni KE;\n"
                 "K7: mov.b32 %138, %192; mov.b32 %139, %193; mov.b32 %140, %194; mov.b32 %141, %195; mov.b32 %142, %196; mov.b32 %143, %197; mov.b32 %144, %198; mov.b32 %145, %199; mov.b32 %146, %200; mov.b32 %147, %201; mov.b32 %148, %202; mov.b32 %149, %203; mov.b32 %150, %204; mov.b32 %151, %205; mov.b32 %152, %206; mov.b32 %153, %207; mov.b32 %154, %208; mov.b32 %155, %209; bra.uni KE;\n"
                 "K8: mov.b32 %156, %192; mov.b32 %157, %193; mov.b32 %158, %194; mov.b32 %159, %195; mov.b32 %160, %196; mov.b32 %161, %197; mov.b32 %162, %198; mov.b32 %163, %199; mov.b32 %164, %200; mov.b32 %165, %201; mov.b32 %166, %202; mov.b32 %167, %203; mov.b32 %168, %204; mov.b32 %169, %205; mov.b32 %170, %206; mov.b32 %171, %207; mov.b32 %172, %208; mov.b32 %173, %209; bra.uni KE;\n"
                 "K9: mov.b32 %174, %192; mov.b32 %175, %193; mov.b32 %176, %194; mov.b32 %177, %195; mov.b32 %178, %196; mov.b32 %179, %197; mov.b32 %180, %198; mov.b32 %181, %199; mov.b32 %182, %200; mov.b32 %183, %201; mov.b32 %184, %202; mov.b32 %185, %203; mov.b32 %186, %204; mov.b32 %187, %205; mov.b32 %188, %206; mov.b32 %189, %207; mov.b32 %190, %208; mov.b32 %191, %209; bra.uni KE;\n"
                 "K10: st.shared.v2.b32 [%211+75784], {%192, %193}; st.shared.v2.b32 [%211+76288], {%194, %195}; st.shared.v2.b32 [%211+76296], {%196, %197}; mov.b32 %0, %198; mov.b32 %1, %199; mov.b32 %2, %200; mov.b32 %3, %201; mov.b32 %4, %202; mov.b32 %5, %203; mov.b32 %6, %204; mov.b32 %7, %205; mov.b32 %8, %206; mov.b32 %9, %207; mov.b32 %10, %208; mov.b32 %11, %209; bra.uni KE;\n"
                 "K11: st.shared.v2.b32 [%211+0], {%192, %193}; st.shared.v2.b32 [%211+8], {%194, %195}; st.shared.v2.b32 [%211+512], {%196, %197}; st.shared.v2.b32 [%211+520], {%198, %199}; st.shared.v2.b32 [%211+1024], {%200, %201}; st.shared.v2.b32 [%211+1032], {%202, %203}; st.shared.v2.b32 [%211+1536], {%204, %205}; st.shared.v2.b32 [%211+1544], {%206, %207}; st.shared.v2.b32 [%211+2048], {%208, %209}; bra.uni KE;\n"
                 "K12: st.shared.v2.b32 [%211+2056], {%192, %193}; st.shared.v2.b32 [%211+2560], {%194, %195}; st.shared.v2.b32 [%211+2568], {%196, %197}; st.shared.v2.b32 [%211+24576], {%198, %199}; st.shared.v2.b32 [%211+24584], {%200, %201}; st.shared.v2.b32 [%211+25088], {%202, %203}; st.shared.v2.b32 [%211+25096], {%204, %205}; st.shared.v2.b32 [%211+25600], {%206, %207}; st.shared.v2.b32 [%211+25608], {%208, %209}; bra.uni KE;\n"
                 "K13: st.shared.v2.b32 [%211+26112], {%192, %193}; st.shared.v2.b32 [%211+26120], {%194, %195}; st.shared.v2.b32 [%211+26624], {%196, %197}; st.shared.v2.b32 [%211+26632], {%198, %199}; st.shared.v2.b32 [%211+27136], {%200, %201}; st.shared.v2.b32 [%211+27144], {%202, %203}; st.shared.v2.b32 [%211+49152], {%204, %205}; st.shared.v2.b32 [%211+49160], {%206, %207}; st.shared.v2.b32 [%211+49664], {%208, %209}; bra.uni KE;\n"
                 "K14: st.shared.v2.b32 [%211+49672], {%192, %193}; st.shared.v2.b32 [%211+50176], {%194, %195}; st.shared.v2.b32 [%211+50184], {%196, %197}; st.shared.v2.b32 [%211+50688], {%198, %199}; st.shared.v2.b32 [%211+50696], {%200, %201}; st.shared.v2.b32 [%211+51200], {%202, %203}; st.shared.v2.b32 [%211+51208], {%204, %205}; st.shared.v2.b32 [%211+51712], {%206, %207}; st.shared.v2.b32 [%211+51720], {%208, %209}; bra.uni KE;\n"
                 "K15: st.shared.v2.b32 [%211+73728], {%192, %193}; st.shared.v2.b32 [%211+73736], {%194, %195}; st.shared.v2.b32 [%211+74240], {%196, %197}; st.shared.v2.b32 [%211+74248], {%198, %199}; st.shared.v2.b32 [%211+74752], {%200, %201}; st.shared.v2.b32 [%211+74760], {%202, %203}; st.shared.v2.b32 [%211+75264], {%204, %205}; st.shared.v2.b32 [%211+75272], {%206, %207}; st.shared.v2.b32 [%211+75776], {%208, %209}; \nKE:\n}"
                 : KR6(0), KR6(1), KR6(2), KR6(3), KR6(4), KR6(5), KR6(6), KR6(7)
                 : "r"(c[0]), "r"(c[1]), "r"(c[2]), "r"(c[3]), "r"(c[4]), "r"(c[5]), "r"(c[6]), "r"(c[7]), "r"(c[8]), "r"(c[9]), "r"(c[10]), "r"(c[11]), "r"(c[12]), "r"(c[13]), "r"(c[14]), "r"(c[15]), "r"(c[16]), "r"(c[17]), "r"(e), "r"(a) : "memory");
}
__device__ __forceinline__ uint32_t smem_base() { extern __shared__ __align__(1024) unsigned char smem[]; return (uint32_t)__cvta_generic_to_shared(smem); }
__device__ __forceinline__ void k_rare(uint4 v0, uint4 v1, uint4 v2, uint4 v3, uint4 v4, uint4 v5, uint32_t odd, int e, int warp, int lane) {
    const uint32_t sb = smem_base(), g = lane >> 2, t = lane & 3, st = sb + SM_BAR + warp * 96 + 80;
    uint32_t lt; asm volatile("mov.u32 %0, %lanemask_lt;" : "=r"(lt));
    const uint4 v[6] = {v0, v1, v2, v3, v4, v5};
    odd <<= 6;
#pragma unroll
    for (int i = 0; i < 6; i++) if (v[i].x | v[i].y | v[i].z | v[i].w) odd |= 1u << i;
    odd = __reduce_or_sync(~0u, odd);
    uint32_t n = odd >= 64 ? NEXC + 1 : __shfl_sync(~0u, lds32(st), 0);
#pragma unroll 1
    for (; odd && n <= NEXC; odd &= odd - 1) {
        const int i = __ffs(odd) - 1;
#pragma unroll
        for (int k = 1; k < 6; k++) if (i == k) v0 = v[k];
#pragma unroll 1
        for (int k = 0; k < 4; k++, v0.x = v0.y, v0.y = v0.z, v0.z = v0.w) {
            const uint32_t who = __ballot_sync(~0u, v0.x), at = n + __popc(who & lt);
            sts64(v0.x && at < NEXC ? sb + SM_EXC + warp * 128 + at * 8 : st + 8, v0.x, (e * 32 + g * 4) << 16 | (((k & 1) * 4 + t) * 48 + i * 8 + (k >> 1) * 4));
            n += __popc(who);
        }
    }
    const uint32_t bad = lds32(st + 4);
    __syncwarp();
    if (n <= NEXC) sts32(st, n);
    else {
        sts32(st + 4, bad | 1u << e);
        asm volatile("st.shared.u8 [%0], %1;" :: "r"(sb + SM_SC + warp * 128 + g * 16 + (e & 3) * 4 + (e >> 2)), "r"(0) : "memory");
    }
    __syncwarp();
}
template <int K> __device__ __forceinline__ uint32_t& word(uint4& v) { if constexpr (K == 0) return v.x; else if constexpr (K == 1) return v.y; else if constexpr (K == 2) return v.z; else return v.w; }
__device__ __forceinline__ void add_if(bool p, float& d, float a, float b) {
    asm volatile("{\n.reg .pred p;\nsetp.ne.u32 p, %3, 0;\n@p add.f32 %0, %1, %2;\n}" : "+f"(d) : "f"(a), "f"(b), "r"((uint32_t)p));
}
__device__ __forceinline__ float warp_max(float v) {
#pragma unroll
    for (int o = 16; o; o >>= 1) v = fmaxf(v, shx(v, o));
    return v;
}
__device__ __forceinline__ float warp_sum(float v) {
#pragma unroll
    for (int o = 16; o; o >>= 1) v += shx(v, o);
    return v;
}
template <int PITCH> __device__ __forceinline__ void ll_look(const u64* buf, u64 (&w)[4]) {
#pragma unroll
    for (int i = 0; i < 4; i++) w[i] = ld_rlx(buf + i * PITCH);
}
template <int PITCH> __device__ __forceinline__ float ll_gather(const u64* buf, uint32_t tag, u64 (&w)[4]) {
    auto miss = [&]() {
        uint32_t a, b;
        asm("lop3.b32 %0, %1, %2, %3, 0x7e;" : "=r"(a) : "r"(ll_tag(w[0])), "r"(ll_tag(w[1])), "r"(tag));
        asm("lop3.b32 %0, %1, %2, %3, 0x7e;" : "=r"(b) : "r"(ll_tag(w[2])), "r"(ll_tag(w[3])), "r"(tag));
        return __any_sync(~0u, a | b);
    };
    int it = 0;
    goto check;
again:
    ll_look<PITCH>(buf, w);
check:
    if (miss() & (++it < SPIN)) goto again;
    return (ll_val(w[0]) + ll_val(w[1])) + (ll_val(w[2]) + ll_val(w[3]));
}
__device__ __forceinline__ float sum8(uint32_t a, int pitch) {
    float s[8];
#pragma unroll
    for (int w = 0; w < 8; w++) s[w] = ldsf(a + w * pitch);
    return ((s[0] + s[1]) + (s[2] + s[3])) + ((s[4] + s[5]) + (s[6] + s[7]));
}
__device__ __forceinline__ float sum5(float a, float b, float c, float d, float e) { return ((a + b) + (c + d)) + e; }
__device__ __forceinline__ float ln_part(uint2 xp, int lane) {
    const float x0 = bf_lo(xp.x), x1 = bf_hi(xp.x), x2 = bf_lo(xp.y), x3 = bf_hi(xp.y);
    const float s1 = (x0 + x1) + (x2 + x3), s2 = (x0 * x0 + x1 * x1) + (x2 * x2 + x3 * x3);
    return ((lane & 16) ? s2 : s1) + shx((lane & 16) ? s1 : s2, 16);
}
__device__ __forceinline__ float ln_rstd(float mean, float msq) { return rsq(fmaxf(msq - mean * mean, 0.f) + 1e-5f); }
__device__ __forceinline__ float score(const uint4 (&v)[6], const uint4 (&qf)[3]) {
    float d[2][4];
#pragma unroll
    for (int j = 0; j < 2; j++) d[j][0] = d[j][1] = d[j][2] = d[j][3] = 0.f;
#pragma unroll
    for (int i = 0; i < 3; i++) { mma(d[0], v[2 * i], qf[i].x, qf[i].y); mma(d[1], v[2 * i + 1], qf[i].z, qf[i].w); }
    return (d[0][0] + d[0][3]) + (d[1][0] + d[1][3]);
}
__device__ __forceinline__ float k_side(uint32_t sb, uint2 x) {
    const uint32_t qq = lds32(sb + SM_VEC + (x.y & 0xffff));
    return (bf_lo(x.x) * bf_lo(qq) + bf_hi(x.x) * bf_hi(qq)) * 0x1p-64f;
}
__device__ __forceinline__ void k_fix(const __nv_bfloat16* k, uint32_t bad, int warp, int lane) {
    const uint32_t sb = smem_base(), g = lane >> 2, sa = sb + SM_PART + warp * 768 + 256;
    const uint2 x = lds64(sb + SM_EXC + warp * 128 + (lane & 15) * 8);
    if ((int)x.y >= 0x40000000 && lane < 16) asm volatile("red.shared.add.f32 [%0], %1;" :: "r"(sa + ((x.y >> 16) & 511)), "f"(k_side(sb, x)) : "memory");
    __syncwarp();
#pragma unroll 1
    for (bad &= 0xffff; bad; bad &= bad - 1) {
        const int e = __ffs(bad) - 1;
        const __nv_bfloat16* kp = k + (e * 256 + (g >> 1) + 4 * (g & 1)) * DH + (lane & 3) * 8;
        uint4 v[6], qf[3];
#pragma unroll
        for (int i = 0; i < 6; i++) v[i] = *reinterpret_cast<const uint4*>(kp + i * 32);
#pragma unroll
        for (int i = 0; i < 3; i++) qf[i] = lds128(sb + SM_VEC + (lane & 7) * 48 + i * 16);
        stsf(sa + e * 32 + g * 4, score(v, qf) * 0x1p-64f);
    }
    __syncwarp();
}
constexpr float CS = 0.07216878364870322f * 1.4426950408889634f;
__device__ __forceinline__ void head_weight(const u64* a, u64 pm, u64 pl, int layer, int lane) {
    const uint32_t sb = smem_base(), tag = lds32(sb + SM_EPOCH) * 4 + 2 + 2 * layer;
#pragma unroll 1
    for (int it = 0; it < SPIN; it++) {
        if (__all_sync(~0u, ll_tag(pm) == tag && ll_tag(pl) == tag)) break;
        ld_rlx2(a, pm, pl);
    }
    const float f = ex2((ll_val(pm) - warp_max(ll_val(pm))) * CS);
    const float w = f * rcp(warp_sum(f * ll_val(pl)));
    if (lane < 8) stsf(sb + SM_FAC + lane * 4, w);
}
constexpr uint32_t ONES = 0x3f803f80u;

__global__ void __launch_bounds__(NTHR, 1) fused_kernel(const __grid_constant__ Params P) {
    const uint32_t sb = smem_base();
    const int bx = blockIdx.x;
    if (__all_sync(~0u, threadIdx.x >= NTHR - 32) && elect()) {
        asm volatile("mbarrier.init.shared::cta.b64 [%0], 1;" :: "r"(sb + SM_CBAR + CB_WQ * 8));
        asm volatile("mbarrier.init.shared::cta.b64 [%0], 1;" :: "r"(sb + SM_CBAR + 80));
        asm volatile("fence.mbarrier_init.release.cluster;" ::: "memory");
        mbar_expect(sb + SM_CBAR + CB_WQ * 8, 5 * HALF);
        mbar_expect(sb + SM_CBAR + 80, HALF);
        tma3(sb, &P.tm[TM_KH], 0, (bx >> 2) * SK + (SK - WIN) + (bx & 3) * 64, sb + SM_CBAR + 80, POL_FIRST);
#pragma unroll 1
        for (int i = 0; i < 5; i++) tma3(sb + SM_WQR + (i == 4 ? 0 : i + 1) * HALF, &P.tm[TM_WQ], (bx >> 2) * 3, (bx & 3) * 160 + i * 32, sb + SM_CBAR + CB_WQ * 8, POL_FIRST);
    }
    __syncwarp();
    int id = bx * NTHR + threadIdx.x, tid, lane, g, t, key, warp, cta, mlp, rowc, roww, j40;
    uint32_t maskA, maskB, barw, subw, prow;
    auto fresh = [&]() {
        const int cw = __shfl_sync(~0u, id >> 5, 0);
        id = pin(id); tid = id & 255; lane = id & 31; g = lane >> 2; t = lane & 3; key = (g >> 1) + 4 * (g & 1);
        const uint32_t m = (g & 1) ? 0xffff0000u : 0x0000ffffu;
        maskA = (g & 2) ? 0u : m; maskB = (g & 2) ? m : 0u;
        warp = cw & 7; cta = cw >> 3;
        mlp = (cta & 3) == 3 ? 96 : (cta >> 2) * 3 + (cta & 3);
        rowc = (cta >> 2) * SK + (SK - WIN) + (cta & 3) * 64; roww = rowc + warp * 8;
        j40 = (cta & 3) * 40;
        barw = sb + SM_BAR + warp * 96; subw = sb + warp * SUB; prow = sb + SM_PART + warp * 768;
    };
    fresh();
    auto fresh_lane = [&]() { id = pin(id); tid = id & 255; lane = id & 31; g = lane >> 2; t = lane & 3; };
    auto pinf = [&](float v) { return __uint_as_float(pin(__float_as_uint(v) | (id >> 16))); };

    TSTAMP(0);
    if (tid == 64) { uint32_t now; asm volatile("mov.u32 %0, %globaltimer_lo;" : "=r"(now)); sts32(sb + SM_T0, now); }

    const CUtensorMap* tmk = reinterpret_cast<const CUtensorMap*>(__shfl_sync(~0u, (u64)&P.tm[0] + (lane >> 5), 0));
    auto c4 = [&]() { return 32 * min(warp, 4) + 16 * (t >> 1) + 2 * g + (t & 1); };
    auto xcol = [&](int i, int tt) { return (i < 2 ? 64 * i + 8 * warp : 128 + 8 * (warp >> 1)) + 2 * tt; };
    uint2 xp;
    uint32_t px[3], small;
    auto issue_first = [&](int j) {
        mbar_expect(sb + SM_CBAR + 80 + j * 8, HALF);
        tma3(sb + j * HALF, tmk + TM_KH, 0, rowc + (j >> 1) * 256 + (j & 1) * 32, sb + SM_CBAR + 80 + j * 8, POL_FIRST);
    };
    if (elect()) {
        if (warp != 2) asm volatile("mbarrier.init.shared::cta.b64 [%0], 1;" :: "r"(sb + SM_CBAR + 64 + warp * 8));
#pragma unroll
        for (int i = 0; i < 9; i++) asm volatile("mbarrier.init.shared::cta.b64 [%0], 1;" :: "r"(barw + i * 8));
        asm volatile("mbarrier.init.shared::cta.b64 [%0], 1;" :: "r"(sb + SM_CBAR + warp * 8));
        asm volatile("mbarrier.init.shared::cta.b64 [%0], 1;" :: "r"(sb + SM_CBAR + 128 + warp * 8));
        if (warp < 3) asm volatile("mbarrier.init.shared::cta.b64 [%0], %1;" :: "r"(sb + SM_CBAR + 192 + warp * 8), "r"(warp == 2 ? 8 : 1));
        sts64(barw + 80, 0, 0);
        asm volatile("fence.mbarrier_init.release.cluster;" ::: "memory");
        asm volatile("prefetch.tensormap [%0];" :: "l"(tmk + warp) : "memory");
    }
    __syncwarp();
    asm volatile("ld.global.nc.v2.u32 {%0,%1}, [%2];" : "=r"(xp.x), "=r"(xp.y) : "l"(P.x + 4 * c4()) : "memory");
#pragma unroll
    for (int i = 0; i < 3; i++) asm volatile("ld.global.nc.u32 %0, [%1];" : "=r"(px[i]) : "l"(P.x + 4 * j40 + xcol(i, t)) : "memory");
    asm volatile("ld.relaxed.gpu.global.u32 %0, [%1];" : "=r"(small) : "l"(lane < 16 ? (const void*)(P.b1 + min(mlp, 95) * 16 + (lane & 14)) : (const void*)&P.g->epoch) : "memory");
    if (tid < NCB + 8) sts64(sb + SM_CNT + tid * 8, 0, 0);
    unsigned char* accg = reinterpret_cast<unsigned char*>(__shfl_sync(~0u, (u64)P.g->acc + (lane >> 5), 0));
    auto release = [&](const uint4& tw) {
        uint32_t old;
        __syncwarp();
        asm volatile("atom.relaxed.cta.shared.add.u32 %0, [%1], 1;" : "=r"(old) : "r"(sb + SM_CNT + (tw.x & 0xf8)) : "memory");
        return old;
    };
    auto refill = [&](const uint4& tw, uint32_t old) {
        if (__any_sync(~0u, (old & 127) == 127 && (tw.y & 2))) {
            wait_until(lds32(sb + SM_T0) + tw.z);
            if (elect()) issue_half(tw.y, sb, rowc, cta, tmk);
            __syncwarp();
        }
    };
    __syncthreads();
    auto issue_paced = [&](int j0, int j1) {
        if (warp >= j0 && warp < j1) {
            wait_until(lds32(sb + SM_T0) + PACES + warp * PACE / 2);
            if (elect()) issue_first(warp);
            __syncwarp();
        }
    };

    uint32_t offV0, offV2;
    auto calc_offsets = [&]() {
        offV0 = subw + (6 * t) * 128 + ((g ^ ((6 * t) & 7)) << 4);
        offV2 = subw + (6 * t + 2) * 128 + ((g ^ ((6 * t + 2) & 7)) << 4);
    };
    calc_offsets();

    auto load_v = [&](uint4 (&v)[6], uint32_t so) {
        v[0] = lds128(offV0 + so); v[1] = lds128((offV0 ^ 16) + so + 128); v[2] = lds128(offV2 + so);
        v[3] = lds128((offV2 ^ 16) + so + 128); v[4] = lds128((offV0 ^ 64) + so + 512); v[5] = lds128((offV0 ^ 80) + so + 640);
    };
    auto issue_v = [&](auto I, int dw) {
        constexpr Step c = SCH.st[I.value];
        const uint32_t bar = barw + dw * 96 + c.slot * 8;
        mbar_expect(bar, SUB);
        tma_v(subw + dw * SUB + c.slot * TILE, tmk, roww * 3 + dw * 24 + c.unit * 768, bar);
    };
    auto refill2 = [&](auto I) { __syncwarp(); if (elect()) issue_v(I, 0); };
    uint4 wq0[6], wqh[3], wq1[6];
    auto load_wq1 = [&](int i) { wq1[i] = lds128((i == 2 ? offV2 : i == 3 ? (offV2 ^ 16) + 128 : (offV0 ^ (i * 16)) + i * 128) + SM_WQ + TILE); };
    auto load_wq = [&]() {
        load_v(wq0, SM_WQ);
        const uint32_t so = SM_WQR - ((warp + 1) >> 1) * SUB;
        wqh[0] = lds128(((warp & 1) ? (offV2 ^ 16) + 128 : offV0) + so);
        wqh[1] = lds128(((warp & 1) ? (offV0 ^ 64) + 512 : (offV0 ^ 16) + 128) + so);
        wqh[2] = lds128(((warp & 1) ? (offV0 ^ 80) + 640 : offV2) + so);
    };
    uint4 kr[8][6];
    const unsigned char* rap;
    u64 rw[2];
    auto look_rw = [&]() { rw[0] = ld_rlx(rap); rw[1] = ld_rlx(rap + 40 * ACC_PITCH); };
    auto q_proj = [&](auto L, uint32_t (&p)[3], uint32_t pst) {
        if (L.value == 0 && g >= 4) p[0] = p[1] = p[2] = ONES;
        float a[3][4], b[3][4];
        const uint32_t dH = __byte_perm(p[2], 0, (warp & 1) ? 0x3232 : 0x1010);
        const uint32_t dA = __byte_perm(p[0], 0, 0x1010), dB = __byte_perm(p[0], 0, 0x3232), dC = __byte_perm(p[1], 0, 0x1010), dD = __byte_perm(p[1], 0, 0x3232);
#pragma unroll
        for (int i = 0; i < 3; i++) load_wq1(i);
#pragma unroll
        for (int j = 0; j < 3; j++) { a[j][0] = a[j][1] = a[j][2] = a[j][3] = 0.f; mma(a[j], wq0[j], dA & maskA, dA & maskB); }
#pragma unroll
        for (int j = 0; j < 3; j++) { b[j][0] = b[j][1] = b[j][2] = b[j][3] = 0.f; mma(b[j], wq0[j + 3], dB & maskA, dB & maskB); }
#pragma unroll
        for (int j = 0; j < 3; j++) mma(a[j], wqh[j], dH & maskA, dH & maskB);
#pragma unroll
        for (int i = 3; i < 6; i++) load_wq1(i);
#pragma unroll
        for (int j = 0; j < 3; j++) mma(b[j], wq1[j], dC & maskA, dC & maskB);
#pragma unroll
        for (int j = 0; j < 3; j++) mma(a[j], wq1[j + 3], dD & maskA, dD & maskB);
#pragma unroll
        for (int j = 0; j < 3; j++) {
            if (L.value) {
#pragma unroll
                for (int k = 0; k < 2; k++) { a[j][k] += b[j][k]; add_if(t & 2, a[j][k], a[j][k + 2], b[j][k + 2]); }
                sts64f(pst + j * 256, a[j][0], a[j][1]);
            } else sts128f(pst + j * 256, a[j][0] + b[j][0], a[j][1] + b[j][1], a[j][2] + b[j][2], a[j][3] + b[j][3]);
        }
        CSTAMP(23, __float_as_uint(a[2][1]));
        uint32_t tag;
        if (L.value) tag = lds32(sb + SM_EPOCH) * 4 + 3;
        u64* pub = L.value ? &P.g->ll[cta][tid] : &P.g->l0[cta][tid];
        if (L.value == 0) asm volatile("fence.proxy.async.shared::cta;" ::: "memory");
        TSTAMPL(21);
        __syncthreads();
        if (!L.value) tag = lds32(sb + SM_EPOCH) * 4 + 1;
#pragma unroll 1
        for (int k = 0; k < 2 - L.value; k++) st_rlx_if(tid < 192, pub + k * 192, ll_pack(sum8(sb + (k ? SM_CSP : SM_PART) + tid * 4, 768), tag));
        TSTAMPL(23);
            CSTAMP(24, tag);
    };
    auto ln_stats = [&]() {
        float ss = ln_part(xp, lane);
        ss += shx(ss, 8); ss += shx(ss, 4); ss += shx(ss, 2); ss += shx(ss, 1);
        stsf(sb + SM_STAT + min(warp, 5) * 8 + (lane >> 4) * 4, ss);
    };
    auto ln_final = [&](float& mean, float& rstd) {
        float2 v[5];
#pragma unroll
        for (int w = 0; w < 5; w++) v[w] = lds64f(sb + SM_STAT + w * 8);
        mean = sum5(v[0].x, v[1].x, v[2].x, v[3].x, v[4].x) * (1.f / D_MODEL);
        const float msq = sum5(v[0].y, v[1].y, v[2].y, v[3].y, v[4].y) * (1.f / D_MODEL);
        rstd = ln_rstd(mean, msq);
        stsf(sb + SM_FXS, msq);
    };
    auto q_addr = [&](int d) { return sb + SM_VEC + (((d >> 1) & 1) * 4 + ((d >> 3) & 3)) * 48 + (d >> 5) * 8 + ((d >> 2) & 1) * 4 + (d & 1) * 2; };
    {
#pragma unroll
        for (int u = 0; u < 8; u++)
#pragma unroll
            for (int i = 0; i < 6; i++) kr[u][i] = lds128(sb + SM_CS + (u * 6 + i) * 16);
        issue_paced(1, NIM);
        ln_stats();
        if (tid == 16) { sts32(sb + SM_EPOCH, small); sts32(sb + SM_M1, ~0u); }
        else if (tid < 16) sts32(sb + SM_B1 + tid * 4, (tid & 1) ? small & 0xffff0000u : small << 16);
        mbar_wait(sb + SM_CBAR + CB_WQ * 8, 0);
        load_wq();
        q_proj(IC<0>{}, px, sb + (t < 2 ? SM_PART : SM_CSP) + warp * 768 + (8 * g + 4 * (t & 1)) * 4);
    }
    {
        uint32_t offQ, offL;
        auto calc_ql = [&]() {
            offQ = pin(sb + SM_VEC + (lane & 7) * 48);
            offL = pin(subw + lane * 16);
        };

        auto issue_w = [&](auto L, int which) {
            const uint32_t bar = sb + SM_CBAR + (CB_W1 + which) * 8;
            if (mlp == 96) asm volatile("mbarrier.arrive.shared::cta.b64 _, [%0];" :: "r"(bar) : "memory");
            else {
                mbar_expect(bar, 20480);
                if (which) {
                    tma3(sb + (L.value ? 3 * TILE : SM_W2), tmk + TM_W2, 0, mlp * 16, bar, POL_FIRST);
                    if (!L.value) tma3_pf(tmk + TM_W2, 0, mlp * 16, POL_NORMAL);
                    if (!L.value) asm volatile("cp.async.bulk.prefetch.L2.global.L2::cache_hint [%0], 20480, %1;" :: "l"(P.w1 + mlp * 10240), "l"((u64)POL_NORMAL << 32) : "memory");
                }
                else asm volatile("cp.async.bulk.tensor.3d.shared::cluster.global.mbarrier::complete_tx::bytes.L2::cache_hint [%0], [%1, {%2, %3, %3}], [%4], %5;"
                                  :: "r"(sb + (L.value ? 2 * TILE : SM_W1)), "l"(tmk + TM_W1), "r"(mlp * 16), "r"(0), "r"(bar), "l"((u64)POL_FIRST << 32) : "memory");
            }
        };
        float acc[3][4];
        auto load_q = [&](uint4 (&qf)[3]) {
#pragma unroll
            for (int i = 0; i < 3; i++) qf[i] = lds128(offQ + i * 16);
        };
        auto softmax = [&](float S0, float S1, float S2, float S3) {
            int mi = __float_as_int(fmaxf(fmaxf(S0, S1), fmaxf(S2, S3)));
            mi = __reduce_max_sync(~0u, mi ^ ((mi >> 31) & 0x7fffffff));
            const float mrun = __int_as_float(mi ^ ((mi >> 31) & 0x7fffffff));
            const float p0 = ex2((S0 - mrun) * CS), p1 = ex2((S1 - mrun) * CS), p2 = ex2((S2 - mrun) * CS), p3 = ex2((S3 - mrun) * CS);
            const uint32_t pa = pack_bf(p0, p1), pb = pack_bf(p2, p3), pw = prow + 256 + (key >> 1) * 80 + t * 4 + (key & 1) * 2;
            sts16(pw, pa); sts16(pw + 16, pa >> 16); sts16(pw + 32, pb); sts16(pw + 48, pb >> 16);
            __syncwarp();
#pragma unroll
            for (int j = 0; j < 3; j++) acc[j][0] = acc[j][1] = acc[j][2] = acc[j][3] = 0.f;
            return make_float2(mrun, (p0 + p1) + (p2 + p3));
        };
        auto pv = [&](const uint4 (&v)[6], uint32_t pp) {
            const uint32_t dA = __byte_perm(pp, 0, 0x1010), dB = __byte_perm(pp, 0, 0x3232);
            mma(acc[0], v[0], dA & maskA, dA & maskB); mma(acc[1], v[1], dA & maskA, dA & maskB); mma(acc[2], v[2], dA & maskA, dA & maskB);
            mma(acc[0], v[3], dB & maskA, dB & maskB); mma(acc[1], v[4], dB & maskA, dB & maskB); mma(acc[2], v[5], dB & maskA, dB & maskB);
        };
        auto sa = [&]() { return prow + 256 + t * 32 + g * 4; };
        auto pass1 = [&]() {
            issue_paced(NIM, NI1);
            fresh();
            calc_ql();
            __syncthreads();
            sts64(prow + lane * 8, xp.x, xp.y);
            int e = 0;
            const uint4* tab = P.tile + (warp >> 2);
            uint4 tw = tab[0];
            uint32_t ka[3];
#pragma unroll
            for (int j = 0; j < 3; j++) ka[j] = pin(subw + key * 384 + j * 128 + ((t ^ ((3 * key + j) & 7)) << 4));
            auto load_k = [&](uint4 (&v)[6], uint32_t so) {
#pragma unroll
                for (int i = 0; i < 6; i++) v[i] = lds128(((i & 1) ? ka[i >> 1] ^ 64 : ka[i >> 1]) + so);
            };
            const uint32_t s0 = pin(prow + 256 + g * 4), sca = pin(sb + SM_SC + warp * 128 + g * 16);
#pragma unroll 1
            do {
                const uint4 tn = tab[2 * e + 2];
                uint4 v[6], qf[3];
                if (tw.x & (G_A | G_B | G_C)) {
                    if ((tw.x & G_A) && warp == 7 && elect()) {
                        mbar_expect(sb + SM_CBAR + CB_SNAP * 8, HALF);
                        asm volatile("cp.async.bulk.shared::cluster.global.mbarrier::complete_tx::bytes [%0], [%1], 12288, [%2];"
                                     :: "r"(sb + SM_SNAP), "l"(&P.g->l0[cta & ~3][0]), "r"(sb + SM_CBAR + CB_SNAP * 8) : "memory");
                    }
                    if (tw.x & G_B) {
                        if (warp < 6) {
                            mbar_wait(sb + SM_CBAR + CB_SNAP * 8, 0);
                            float qc[2] = {0.f, 0.f}, mean, rstd;
#pragma unroll 1
                            for (int k = 0; k < 2; k++) {
                                u64 qw[4];
#pragma unroll
                                for (int i = 0; i < 4; i++) { const uint2 x = lds64(sb + SM_SNAP + i * 3072 + k * 1536 + tid * 8); qw[i] = x.x | (u64)x.y << 32; }
                                qc[0] = qc[1];
                                qc[1] = ll_gather<384>(&P.g->l0[cta & ~3][k * 192 + tid], lds32(sb + SM_EPOCH) * 4 + 1, qw);
                            }
                            ln_final(mean, rstd);
                            stsf(sb + SM_CS + tid * 4, qc[1]);
                            const float q = (qc[0] - mean * qc[1]) * rstd;
                            sts16(q_addr(tid), pack_bf(q, q));
                        }
                        __syncthreads();
                        if (warp == 7 && elect()) issue_half(UC<load_word(12)>::value, sb, rowc, cta, tmk);
                        TSTAMP(2);
                    }
                    if (tw.x & G_C) {
                        load_k(v, (e - LATEAT) * TILE);
                        load_q(qf);
                        stsf(s0 + (e - LATEAT) * 32, score(v, qf));
                    }
                }
                load_q(qf);
                mbar_wait(sb + SM_CBAR + (tw.x & 0xf8), tw.x >> 31);
                TRACE(e);
                load_k(v, tw.x & 0x3f000);
                const uint32_t old = release(tw);
                const float s = score(v, qf);
                uint32_t m;
                {
                    uint32_t a[6];
#pragma unroll
                    for (int i = 0; i < 6; i++) a[i] = bf2_amax(bf2_amax(v[i].x, v[i].y), bf2_amax(v[i].z, v[i].w));
                    m = bf2_amax(bf2_amax(bf2_amax(a[0], a[1]), bf2_amax(a[2], a[3])), bf2_amax(a[4], a[5]));
                }
                m = bf2_amax(m, m >> 16) & 0x7f80;
                m = max(m, __shfl_xor_sync(~0u, m, 1));
                stsf(s0 + e * 32, s);
                m = max(m, __shfl_xor_sync(~0u, m, 2));
                refill(tw, old);
                const uint32_t b = min(max(m, 15u << 7) - (15u << 7), 126u << 7);
                const uint32_t dn = ((127u << 7) - b) * 0x10001u, up = ((127u << 7 | 0x8000u) + b) * 0x10001u;
                uint32_t c[18], any = m > (141u << 7);
#pragma unroll
                for (int i = 0; i < 6; i++) {
                    const uint32_t y0 = bf2_mul(v[i].x, dn), y1 = bf2_mul(v[i].y, dn), y2 = bf2_mul(v[i].z, dn), y3 = bf2_mul(v[i].w, dn);
                    v[i] = make_uint4(bf2_fma(y0, up, v[i].x), bf2_fma(y1, up, v[i].y), bf2_fma(y2, up, v[i].z), bf2_fma(y3, up, v[i].w));
                    any |= v[i].x | v[i].y;
                    any |= v[i].z | v[i].w;
                    const uint32_t hb = __byte_perm(y2, y3, 0x7531);
                    c[3 * i] = __byte_perm(y0, y1, 0x6420); c[3 * i + 1] = __byte_perm(y2, y3, 0x6420);
                    c[3 * i + 2] = __byte_perm(y0, y1, 0x7531) | __funnelshift_r(hb, hb, 4);
                }
                asm volatile("st.shared.u8 [%0], %1;" :: "r"(sca + (e & 3) * 4 + (e >> 2)), "r"((b >> 7) + 63) : "memory");
                const bool rare = __any_sync(~0u, any);
                k_keep(kr, c, e, offL);
                if (rare) k_rare(v[0], v[1], v[2], v[3], v[4], v[5], m > (141u << 7), e, warp, lane);
                tw = tn;
            } while (++e < 16);
            asm volatile("fence.proxy.async.shared::cta;" ::: "memory");
            __syncwarp();
            TSTAMP(10);
            fresh(); calc_offsets();
            offV0 = pin(offV0); offV2 = pin(offV2);
            {
                const uint2 st = lds64(barw + 80);
                const uint32_t xa = sb + SM_EXC + warp * 128 + (lane & 15) * 8 + 4;
                uint32_t pos = lds32(xa), lt;
                asm volatile("mov.u32 %0, %lanemask_lt;" : "=r"(lt));
                if (lane >= st.x) pos = 0x80000000u;
                const bool dup = (__match_any_sync(~0u, pos >> 16) & lt) && lane < st.x;
                if (lane < 16) sts32(xa, dup ? pos | 0x40000000u : pos);
                if (__any_sync(~0u, dup)) sts32(barw + 84, st.y | 0x10000u);
                const float2 ml = softmax(ldsf(sa()), ldsf(sa() + 128), ldsf(sa() + 256), ldsf(sa() + 384));
                sts64f(sb + SM_ML + warp * 8, ml.x, warp_sum(ml.y));
            }
            u64 pm = 0, pl = 0;
#pragma unroll 1
            do {
                const uint4 tn = tab[2 * e + 2];
                if (tw.x & (G_A | G_B | G_C)) {
                    if (tw.x & G_A) {
                        if (lane < 24) st_rlx(&P.g->ll[cta][warp * 24 + lane], 0ull);
                        else if (lane < 28) st_rlx(&P.g->ll[cta][168 + warp * 4 + lane], ll_pack(ldsf(sb + SM_ML + warp * 8 + (lane & 1) * 4), lds32(sb + SM_EPOCH) * 4 + 2));
                    }
                    if (warp == 0 && cta < 80 && elect()) {
                        if (tw.x & G_A) {
#pragma unroll 1
                            for (int k = 0; k < 12; k++) {
                                const int r = k < 4 ? k & 2 : (k >> 1 & 2) + 1;
                                asm volatile("cp.async.bulk.global.shared::cta.bulk_group [%0], [%1], 64;"
                                             :: "l"(P.g->acc + r * ACC_BYTES + (k < 4 ? cta * ACC1_PITCH + (k & 1) * 64 : (cta * ACC_PITCH & ~127) + (k & 3) * 64)), "r"(sb + SM_ZERO) : "memory");
                            }
                            asm volatile("cp.async.bulk.commit_group;" ::: "memory");
                        }
                        if (tw.x & G_B) asm volatile("cp.async.bulk.wait_group 0;\nred.relaxed.gpu.global.add.u32 [%0], 1;" :: "l"(&P.g->zeroed) : "memory");
                    }
                    if (warp == 2) {
                        if (tw.x & G_B) ld_rlx2(&P.g->ll[cta ^ (lane >> 3)][192 + (lane & 7) * 4], pm, pl);
                        if (tw.x & G_C) head_weight(&P.g->ll[cta ^ (lane >> 3)][192 + (lane & 7) * 4], pm, pl, 0, lane);
                    }
                    __syncwarp();
                }
                const uint32_t pp = lds32(prow + 256 + t * 80 + ((tw.x >> 20) & 255));
                mbar_wait(sb + SM_CBAR + (tw.x & 0xf8), tw.x >> 31);
                TRACE(e);
                uint4 v[6];
                load_v(v, tw.x & 0x3f000);
                refill(tw, release(tw));
                pv(v, pp);
                tw = tn;
            } while (++e < 32);
        };
        uint32_t osa, ora, owa, orow, otag;
        u64* olb;
        float xc;
        auto o_setup = [&](auto L) {
            fresh();
            const int lz = lane, d = warp * 24 + min(lz, 23);
            osa = pin(prow + ((lz >> 2) * 8 + (lz & 1) * 4 + (lz & 2)) * 4);
            ora = pin(sb + SM_PART + d * 4);
            olb = pin(&P.g->ll[cta & ~3][d]);
            orow = pin((lz & 1) + 2 * (lz & 2) + 2 * (lz >> 4));
            owa = pin(sb + SM_RING + warp * 1536 + orow * 64 + ((((lz >> 2) & 3) ^ (orow >> 1)) << 4));
            otag = lds32(sb + SM_EPOCH) * 4 + 2 + 2 * L.value;
            uint32_t x; asm volatile("ld.shared.u16 %0, [%1];" : "=r"(x) : "r"(prow + ((cta & 1) * 16 + (lz >> 3) * 4 + (cta & 2) + ((lz >> 2) & 1)) * 8 + (lz & 3) * 2) : "memory");
            xc = bf_lo(x) * (1.f / 32);
        };
        auto wo_at = [&](auto A) {
            constexpr uint32_t x = WOP ^ A.value * 0x11111;
            if constexpr (A.value > 0 && ((x - 0x11111) & ~x & 0x88888) != 0) {
                if ((WOP >> (4 * warp) & 15) == A.value) {
                    mbar_wait(sb + SM_CBAR + CB_REL * 8, 0);
                    if (elect()) {
                        const uint32_t bar = sb + SM_CBAR + (CB_WO + warp) * 8;
                        mbar_expect(bar, HALF);
                        tma3(sb + SM_RING + (warp + (warp < 2 ? 3 : -2)) * HALF, tmk + TM_WO, (cta & 3) + 4 * warp, (cta >> 2) * DH, bar, POL_FIRST);
                    }
                    __syncwarp();
                }
            }
        };
        static_assert(ring_hs(64) == 3, "wo");
        auto pass2 = [&]() {
            constexpr IC<1> L{};
            refill2(IC<4>{});
            uint4 tb[8][3];
            auto load_tb = [&](auto I) {
#pragma unroll
                for (int i = 0; i < 3; i++) tb[I.value][i] = lds128(offL + (I.value >> 1) * TILE + ((I.value & 1) * 3 + i) * 512);
            };
            const u64* qb = &P.g->ll[cta & ~3][min(tid, 191)];
            {
                uint32_t x[2];
                fx2_wait<2>([&](int i) { return rap + i * 40 * ACC_PITCH; }, look_rw, rw, sb + SM_MSQ, ldsf(sb + SM_MSQ + 4), x);
                xp = make_uint2(x[0], x[1]);
                CSTAMP(25, xp.y);
            }
            ln_stats();
            u64 qw[4];
            ll_look<256>(qb, qw);
            const float cs = ldsf(sb + SM_CS + min(tid, 191) * 4);
            const uint32_t qtag = lds32(sb + SM_EPOCH) * 4 + 3, qa = pin(q_addr(min(tid, 191)));
            fresh_lane();
            offQ = sb + SM_VEC + (lane & 7) * 48; offL = subw + lane * 16;
            __syncthreads();
            auto vwait = [&](auto I) { mbar_wait(barw + IC<SCH.st[I.value].slot>::value * 8, IC<SCH.st[I.value].par>::value); };
            bool ok;
            uint32_t m1, m1n;
            {
                float mean, rstd;
                ln_final(mean, rstd);
                const float sq = shx(rstd * 0x1p64f, 0), q0 = shx(-mean * cs * sq, 0);
                CSTAMP(26, __float_as_uint(q0));
                static_for<0, NPRE>(load_tb);
                refill2(IC<5>{});
                m1n = m1 = lds32(sb + SM_M1);
                sts64(prow + lane * 8, xp.x, xp.y);
                sts128f(prow + 256 + lane * 16, 0.f, 0.f, 0.f, 0.f);
                const float q = ll_gather<256>(qb, qtag, qw) * sq + q0;
                sts16(qa, pack_bf(q, q));
                TSTAMPL(24);
                CSTAMP(27, __float_as_uint(q));
            }
            __syncthreads();
            uint4 qf[3];
            load_q(qf);
            CSTAMP(28, qf[0].x);
            float S[4], d[2][4];
            auto vload = [&](auto I) {
                constexpr int p = I.value;
                constexpr Step c = SCH.st[p];
                load_v(kr[p & 7], c.slot * TILE);
                if constexpr (c.next >= 0) refill2(IC<c.next>{});
                if constexpr (p == 11) { __syncwarp(); if (elect()) asm volatile("mbarrier.arrive.shared::cta.b64 _, [%0];" :: "r"(sb + SM_CBAR + CB_REL * 8) : "memory"); }
            };
            static_for<0, 96>([&](auto F) {
                constexpr int f = F.value, i = f % 6, u = kunit(f / 6), w = 3 * f % 12;
                uint4 (&src)[3] = *reinterpret_cast<uint4 (*)[3]>(f < 32 ? &tb[f / 4 & 7][0] : &kr[(f / 8 + 4) & 7][(f / 4 & 1) * 3]);
                const uint4 a = k_unpack(word<w % 4>(src[w / 4]), word<(w + 1) % 4>(src[(w + 1) / 4]), word<(w + 2) % 4>(src[(w + 2) / 4]), m1);
                if constexpr (f < 32 ? f % 4 == M1AT : f % 8 == M1P) m1 = m1n;
                if constexpr (f % 4 == 3 && f / 4 + NPRE < 8) {
                    load_tb(IC<f / 4 + NPRE>{});
                    if constexpr ((f / 4 + NPRE) & 1) { refill2(IC<5 + (f / 4 + NPRE) / 2>{}); m1n = lds32(sb + SM_M1); }
                }
                if constexpr (i < 2) d[i][0] = d[i][1] = d[i][2] = d[i][3] = 0.f;
                mma(d[i & 1], a, (i & 1) ? qf[i / 2].z : qf[i / 2].x, (i & 1) ? qf[i / 2].w : qf[i / 2].y);
                if constexpr (i == 5) {
                    if constexpr (u == 11 || ((u & 3) == 0 && u != 8)) S[u >> 2] = (d[0][0] + d[0][3]) + (d[1][0] + d[1][3]);
                    else add_if(t == (u & 3), S[u >> 2], d[0][0] + d[0][3], d[1][0] + d[1][3]);
                    if constexpr (f < 64) S[u >> 2] = shx(S[u >> 2], 0);
                }
                if constexpr (f == 31) { fresh(); calc_offsets(); ok = mbar_test(barw + IC<SCH.st[0].slot>::value * 8, 0); }
                if constexpr (f == 48) {
                    const uint2 x = lds64(sb + SM_EXC + warp * 128 + (lane & 15) * 8);
                    const float c = k_side(sb, x);
                    if (x.y < 0x40000000u) stsf(prow + 256 + (x.y >> 16), c);
                }
                if constexpr (f >= 32 && f % 8 == 7) {
                    if constexpr (PARKS >> (f / 8 - 4) & 1) {
                        constexpr int p = popc(PARKS & ((1 << (f / 8 - 4)) - 1));
                        if (!ok) vwait(IC<p>{});
                        vload(IC<p>{});
                        m1n = lds32(sb + SM_M1);
                        ok = mbar_test(barw + IC<SCH.st[p + 1].slot>::value * 8, IC<SCH.st[p + 1].par>::value);
                    }
                }
            });
            uint32_t bad = lds32(barw + 84);
            const uint32_t sc = lds32(sb + SM_SC + tid * 4);
            __syncwarp();
            if (bad) k_fix(P.k + (size_t)roww * DH, bad, warp, lane);
            TSTAMP(30);
            CSTAMP(29, __float_as_uint(S[2]));
            const float2 ml = softmax(S[0] * __uint_as_float((sc & 255) << 23) + ldsf(sa()), S[1] * __uint_as_float((sc & 0xff00) << 15) + ldsf(sa() + 128),
                                      S[2] * __uint_as_float((sc & 0xff0000) << 7) + ldsf(sa() + 256), S[3] * __uint_as_float((sc >> 24) << 23) + ldsf(sa() + 384));
            uint4 pq[4];
#pragma unroll
            for (int j = 0; j < 4; j++) pq[j] = lds128(prow + 256 + t * 80 + j * 16);
            TSTAMP(1);
            CSTAMP(30, pq[3].w);
            if (!ok) vwait(IC<NPARK>{});
            float ac2[3][4];
#pragma unroll
            for (int j = 0; j < 3; j++) ac2[j][0] = ac2[j][1] = ac2[j][2] = ac2[j][3] = 0.f;
            const uint32_t sl = (g & 1) ? 0x1044 : 0x4410, sh = (g & 1) ? 0x3244 : 0x4432;
            const uint32_t sA0 = (g & 2) ? 0x4444 : sl, sA1 = (g & 2) ? sl : 0x4444, sB0 = (g & 2) ? 0x4444 : sh, sB1 = (g & 2) ? sh : 0x4444;
            u64 pm = 0, pl = 0;
            static_for<NPARK, 16>([&](auto I) {
                constexpr int p = I.value;
                static_assert(p - SCH.st[p].mma0 < 8, "buffer in use");
                vload(I);
                if constexpr (p < 15) ok = mbar_test(barw + IC<SCH.st[p + 1].slot>::value * 8, IC<SCH.st[p + 1].par>::value);
                static_for<SCH.st[p].mma0, SCH.st[p].mma0 + SCH.st[p].nmma>([&](auto J) {
                    constexpr int u = SCH.st[J.value].unit;
                    const uint32_t pp = word<u & 3>(pq[u >> 2]), a0 = __byte_perm(pp, 0, sA0), a1 = __byte_perm(pp, 0, sA1), b0 = __byte_perm(pp, 0, sB0), b1 = __byte_perm(pp, 0, sB1);
#pragma unroll
                    for (int j = 0; j < 3; j++) mma(acc[j], kr[J.value & 7][j], a0, a1);
#pragma unroll
                    for (int j = 0; j < 3; j++) mma(ac2[j], kr[J.value & 7][j + 3], b0, b1);
                });
                if constexpr (p == NPARK) {
                    const float l = warp_sum(ml.y);
                    st_rlx_if(lane < 4, &P.g->ll[cta][192 + warp * 4 + lane], ll_pack((lane & 1) ? l : ml.x, lds32(sb + SM_EPOCH) * 4 + 4));
                }
                if constexpr (p == HWAT) { if (warp == 6) ld_rlx2(&P.g->ll[cta ^ (lane >> 3)][192 + (lane & 7) * 4], pm, pl); }
                if constexpr (p == 13) o_setup(L);
                if constexpr (p == HWAT + 2) { if (warp == 6) head_weight(&P.g->ll[cta ^ (lane >> 3)][192 + (lane & 7) * 4], pm, pl, 1, lane); }
                wo_at(IC<p - 10>{});
                if constexpr (p < 15) { if (!ok) mbar_wait(barw + IC<SCH.st[p + 1].slot>::value * 8, IC<SCH.st[p + 1].par>::value); TRACE(33 + p); }
            });
#pragma unroll
            for (int j = 0; j < 3; j++)
#pragma unroll
                for (int k = 0; k < 2; k++) { acc[j][k] += ac2[j][k]; add_if(t & 2, acc[j][k], acc[j][k + 2], ac2[j][k + 2]); }
        };

        const unsigned char* ap;
        uint32_t hpa, hsa, hst, w2a, la;
        uint2 b2v;
        float b1v, cs1;
        auto mlp_global = [&](auto L) {
            const int cz = c4();
            ap = accg + 2 * L.value * ACC_BYTES + (cz >> 1) * ACC1_PITCH + (cz & 1) * 16;
            if (L.value) ap = pin(ap);
            rap = pin(accg + (2 * L.value + 1) * ACC_BYTES + (cz >> 2) * ACC_PITCH + (cz & 3) * 8);
            asm volatile("ld.global.nc.v2.u32 {%0,%1}, [%2];" : "=r"(b2v.x), "=r"(b2v.y) : "l"(P.b2 + 4 * cz));
        };
        auto mlp_shared = [&](auto L) {
            const int lz = lane;
            hpa = pin(sb + SM_PART + warp * 256 + ((lz & 2) * 4 + (lz >> 2)) * 16 + (L.value ? 0 : (lz & 1) * 4));
            hsa = pin(sb + SM_PART + (lz & 15) * 16); hst = pin(sb + SM_PART + (lz & 15) * 16 + warp * 256 + 8 + (lz >> 4) * 4);
            w2a = pin(sb + (L.value ? 3 * TILE : SM_W2) + ((lz & 3) * 10 + 2 * warp) * 128 + (((lz >> 2) ^ ((2 * lz + 2 * warp) & 6)) << 4));
            la = sb + (L.value ? 2 * TILE : SM_W1) + warp * 4096 + (lz & 4) * 512 + (lz & 2) * 64 + (lz & 1) * 32 + (lz >> 4) * 64 + ((((lz >> 3) ^ (lz >> 1)) & 1) << 4);
            b1v = ldsf(sb + SM_B1 + (lz & 15) * 4);
            if (L.value) { la = pin(la); cs1 = ldsf(sb + SM_ML + (lz & 15) * 4); }
            else fresh();
        };
        uint32_t pa;
        unsigned char* rop;
        uint32_t wpa;
        float sc1;
        auto sum_setup = [&](auto L) {
            const int lz = lane, word = warp * 128 + (cta & 3) * 32 + lz;
            wpa = pin(sb + SM_RING + warp * 1536 + ((((lz >> 2) * 8 + (lz & 1) * 4) * 4) ^ ((((lz >> 1) ^ (lz >> 4)) & 1) ? 256 + 64 : 0)));
            sc1 = pinf(fx2_scale(ldsf(sb + SM_FXS)) * 0.25f);
            pa = pin(sb + SM_RING + warp * 256 + ((lz * 4) ^ ((warp & 1) * 64)));
            rop = pin(accg + 2 * L.value * ACC_BYTES + (word >> 3) * ACC1_PITCH + (word & 7) * 4);
        };
        auto out_proj = [&](auto L) {
            TSTAMP2(3);
            CSTAMP(0, __float_as_uint(acc[2][1]));
            __syncwarp();
#pragma unroll
            for (int j = 0; j < 3; j++) {
                if (L.value == 0 && (t & 2)) { acc[j][0] = acc[j][2]; acc[j][1] = acc[j][3]; }
                sts64f(osa + 256 * j, acc[j][0], acc[j][1]);
            }
            __syncthreads();
            {
                float s[8];
#pragma unroll
                for (int w = 0; w < 8; w++) s[w] = ldsf(ora + w * 768);
                const uint4 fa = lds128(sb + SM_FAC), fb = lds128(sb + SM_FAC + 16);
            CSTAMP(1, __float_as_uint(s[0]));
                const float own = ((s[0] * __uint_as_float(fa.x) + s[1] * __uint_as_float(fa.y)) + (s[2] * __uint_as_float(fa.z) + s[3] * __uint_as_float(fa.w))) +
                                  ((s[4] * __uint_as_float(fb.x) + s[5] * __uint_as_float(fb.y)) + (s[6] * __uint_as_float(fb.z) + s[7] * __uint_as_float(fb.w)));
                st_rlx_if(lane < 24, olb + (cta & 3) * 256, ll_pack(own, otag));
            CSTAMP(2, __float_as_uint(own));
            }
            TSTAMPL(29);
            if (L.value == 0) fresh();
            if (L.value) wo_at(IC<6>{});
            if (L.value == 0 && warp == 7) {
#pragma unroll 1
                for (int it = 0; it < SPIN; it++) {
                    uint32_t v; asm volatile("ld.acquire.gpu.global.u32 %0, [%1];" : "=r"(v) : "l"(&P.g->zeroed) : "memory");
                    if (__all_sync(~0u, v == (lds32(sb + SM_EPOCH) + 1) * 80)) break;
                }
            }
            constexpr int NW = L.value ? NWO1 : 3;
            uint4 v[5][3];
            u64 ow[4];
            auto read_wo = [&](auto J) {
#pragma unroll
                for (int p = 0; p < 3; p++) v[J.value][p] = lds128(((J.value & 1) ? owa ^ 144 : owa) + ring_hs(64 + J.value) * HALF + p * 512);
            };
            static_for<0, NW>([&](auto J) {
                if (L.value && J.value == 0) { sum_setup(L); maskA = pin(maskA); maskB = pin(maskB); }
                if (J.value == 2) { ll_look<256>(olb, ow); if (L.value) { mlp_shared(L); mlp_global(L); } }
                mbar_wait(sb + SM_CBAR + (CB_WO + J.value) * 8, L.value);
                read_wo(J);
                if (L.value == 0 && J.value == 2) {
                    __syncwarp();
                    if (elect() && cnt_inc(sb + SM_CNT + CB_W1 * 8, 7) == 7) issue_w(L, 0);
                    __syncwarp();
                }
                if (L.value == 1 && J.value == 2) {
                    if (warp == 7 && elect()) issue_w(L, 0);
                    __syncwarp();
                }
            });
            sched_fence();
            const float o = ll_gather<256>(olb, otag, ow);
            CSTAMP(3, __float_as_uint(o));
            TSTAMP2(4);
            bool ok = true;
            if constexpr (NW < 5) ok = mbar_test(sb + SM_CBAR + (CB_WO + 4) * 8, L.value);
            if constexpr (NW < 4) ok &= mbar_test(sb + SM_CBAR + (CB_WO + 3) * 8, L.value);
            const uint32_t od = pack_bf(o, o);
            uint32_t oa[3], ob[3];
#pragma unroll
            for (int p = 0; p < 3; p++) { const uint32_t op = __shfl_sync(~0u, od, 8 * p + orow); oa[p] = op & maskA; ob[p] = op & maskB; }
            CSTAMP(4, oa[2]);
            float y[5][4];
#pragma unroll
            for (int j = 0; j < 5; j++) y[j][0] = y[j][1] = y[j][2] = y[j][3] = 0.f;
            auto rest = [&]() {
                if (!ok) static_for<NW, 5>([&](auto J) { mbar_wait(sb + SM_CBAR + (CB_WO + J.value) * 8, L.value); });
                static_for<NW, 5>(read_wo);
                __syncwarp();
            };
            if (L.value) rest();
#pragma unroll
            for (int p = 0; p < 3; p++)
#pragma unroll
                for (int j = 0; j < NW; j++) mma(y[j], v[j][p], oa[p], ob[p]);
            if (!L.value) { rest(); sum_setup(L); }
#pragma unroll
            for (int p = 0; p < 3; p++)
#pragma unroll
                for (int j = NW; j < 5; j++) mma(y[j], v[j][p], oa[p], ob[p]);
            CSTAMP(5, __float_as_uint(y[4][3]));
#pragma unroll
            for (int j = 0; j < 5; j += 2) {
                if (j < 4 && (t >> 1) != (g >> 2)) { y[j][0] = y[j + 1][0]; y[j][1] = y[j + 1][1]; y[j][2] = y[j + 1][2]; y[j][3] = y[j + 1][3]; }
                sts128f(wpa + j * 256, y[j]);
            }
            TSTAMP2(5);
        };
        u64 yw[2];
        bool wide;
        float msq = 0.f, yf[4] = {};
        auto mlp_part = [&](auto L) {
            bar_sync(0, 256);
            CSTAMP(6, __float_as_uint(sc1));
            const float s = (sum8(pa, 1536) + xc) + sum8(pa + 128, 1536), sm = s * sc1 + FX2_ONE;
            CSTAMP(7, __float_as_uint(s));
            const bool wide1 = !(fabsf(sm - FX2_ONE) < FX1LIM);
            asm volatile("red.relaxed.gpu.global.add.u32 [%0], %1;" :: "l"(rop), "r"(wide1 ? 0u : __float_as_uint(sm) * 128u + (1u - 0x4b400000u * 128u)) : "memory");
            const uint32_t c0 = clk();
            TSTAMP2(6);
            if (L.value == 0) bar_arrive(2, 256);
            if (wide1) {
                fx_send(rop + 64 + (lane & 7) * 4, s, ldsf(sb + SM_FXS), rop, 64);
                asm volatile("red.relaxed.gpu.global.add.u32 [%0], 1;" :: "l"(rop) : "memory");
            }
            __syncwarp();
            if (L.value == 1 && mlp == 96) { TDUMP(); asm volatile("exit;"); }
            uint4 wf[8], w2r[8];
            uint4 w;
            auto look = [&]() { asm volatile("ld.relaxed.gpu.global.v4.u32 {%0,%1,%2,%3}, [%4];" : "=r"(w.x), "=r"(w.y), "=r"(w.z), "=r"(w.w) : "l"(ap) : "memory"); };
            auto read_w1 = [&]() {
#pragma unroll
                for (int j = 0; j < 8; j++) wf[j] = ldsm_t(la + j * 256);
            };
            auto read_w2 = [&]() {
#pragma unroll
                for (int i = 0; i < 8; i++) w2r[i] = lds128(((i & 1) ? (w2a ^ 16) + 128 : w2a) + (i >> 1) * 5120);
            };
            const float inv = pinf(fx_inv(sc1) * (1.f / 128)), off = L.value ? pinf(fx_inv(sc1) * -0.25f) : inv * -32.f;
            if (L.value == 0) { fresh(); mlp_global(L); }
            mbar_wait(sb + SM_CBAR + CB_W1 * 8, L.value);
            if (L.value == 1) read_w1();
            while (clk() - c0 < AR1D);
            look();
            if (L.value == 0) { mlp_shared(L); read_w1(); bar_arrive(3, 256); }
            else { mbar_wait(sb + SM_CBAR + CB_W2 * 8, 1); read_w2(); }
            TSTAMPL(28);
            {
                sched_fence();
                auto miss = [&]() {
                    xp = make_uint2(pack_bf((float)(int)w.x * inv + off, (float)(int)w.y * inv + off), pack_bf((float)(int)w.z * inv + off, (float)(int)w.w * inv + off));
                    uint32_t a, b;
                    asm("lop3.b32 %0, %1, %2, 32, 0x7e;" : "=r"(a) : "r"(w.x), "r"(w.y));
                    asm("lop3.b32 %0, %1, %2, 32, 0x7e;" : "=r"(b) : "r"(w.z), "r"(w.w));
                    return __any_sync(~0u, (a | b) & 96);
                };
                if (miss()) {
                    int it = 0;
#pragma unroll 1
                    do {
                        if (!__any_sync(~0u, ~(w.x & w.y & w.z & w.w) & 32)) { xp.x = fx1_wide(ap, ldsf(sb + SM_FXS)); xp.y = fx1_wide(ap + 8, ldsf(sb + SM_FXS)); break; }
                        look();
                    } while (miss() & (++it < SPIN));
                }
                CSTAMP(8, w.w);
            }
            TSTAMP2(7);
            CSTAMP(9, xp.y);
            {
                bool ok = true;
                if (L.value == 0) ok = mbar_test(sb + SM_CBAR + CB_W2 * 8, 0);
                const bool ev = L.value || !(g & 1), od = L.value || (g & 1);
                const uint32_t e0 = ev ? xp.x : ONES, e1 = ev ? xp.y : ONES, o0 = od ? xp.x : ONES, o1 = od ? xp.y : ONES;
                float d[8][4];
#pragma unroll
                for (int j = 0; j < 8; j++) { d[j][0] = d[j][1] = d[j][2] = d[j][3] = 0.f; mma(d[j], wf[j], (j & 1) ? o0 : e0, (j & 1) ? o1 : e1); }
                float ss = ln_part(xp, lane);
                ss += shx(ss, 8); ss += shx(ss, 4);
                float r[4], dd;
#pragma unroll
                for (int k = 0; k < 4; k += 1 + L.value) r[k] = d[0][k] + d[1][k ^ 1];
#pragma unroll
                for (int j = 1; j < 4; j++)
#pragma unroll
                    for (int k = 0; k < 4; k += 1 + L.value) add_if(t == j, r[k], d[2 * j][k], d[2 * j + 1][k ^ 1]);
                CSTAMP(10, __float_as_uint(r[2]));
                if (L.value) {
                    dd = ((t & 2) ? r[2] : r[0]) + shx((t & 2) ? r[0] : r[2], 2);
                    ss += shx(ss, 2);
                    dd += shx(dd, 1);
                } else {
                    const float a = ((t & 1) ? r[1] : r[0]) + shx((t & 1) ? r[0] : r[1], 1), b = ((t & 1) ? r[3] : r[2]) + shx((t & 1) ? r[2] : r[3], 1);
                    ss += shx(ss, 2);
                    dd = ((t & 2) ? b : a) + shx((t & 2) ? a : b, 2);
                }
                ss += shx(ss, 1);
                stsf(hpa, dd);
                stsf(hst, ss);
                CSTAMP(11, __float_as_uint(dd + ss));
                if (!ok) mbar_wait(sb + SM_CBAR + CB_W2 * 8, L.value);
            }
            TSTAMPL(25);
            bar_sync(1, 160);
            uint4 hp[5];
#pragma unroll
            for (int w = 0; w < 5; w++) hp[w] = lds128(hsa + w * 256);
            CSTAMP(12, hp[0].x);
            auto hs = [&](auto K) { return sum5(__uint_as_float(word<K.value>(hp[0])), __uint_as_float(word<K.value>(hp[1])), __uint_as_float(word<K.value>(hp[2])),
                                                __uint_as_float(word<K.value>(hp[3])), __uint_as_float(word<K.value>(hp[4]))); };
            const float mean = hs(IC<2>{}) * (1.f / D_MODEL);
            msq = hs(IC<3>{}) * (1.f / D_MODEL);
            if (L.value == 0) cs1 = hs(IC<1>{});
            float hv = hs(IC<0>{}) - mean * cs1;
            CSTAMP(13, __float_as_uint(hv));
            const float sc2 = fx2_scale(msq), lim = fx_inv(sc2) * FX2LIM;
            if (L.value == 0) {
                read_w2();
                bar_arrive(4, 256);
                wide = false;
                if (mlp == 96) return;
            }
            hv = hv * ln_rstd(mean, msq) + b1v;
            CSTAMP(14, __float_as_uint(hv));
            hv = hv * rcp(1.f + ex2(hv * (-2.302208198f - 0.1029432397f * hv * hv)));
            const uint32_t hd = pack_bf(hv, hv);
            CSTAMP(15, hd);
            TSTAMPL(27);
            float ym[4][4];
#pragma unroll
            for (int i = 0; i < 2; i++) {
                ym[i][0] = ym[i][1] = ym[i][2] = ym[i][3] = 0.f;
                const float f = mlp < 64 ? 1.f / 64 : 0.f;
                ym[i + 2][0] = (bf_lo(xp.x) + bf_lo(b2v.x)) * f; ym[i + 2][1] = (bf_hi(xp.x) + bf_hi(b2v.x)) * f;
                ym[i + 2][2] = (bf_lo(xp.y) + bf_lo(b2v.y)) * f; ym[i + 2][3] = (bf_hi(xp.y) + bf_hi(b2v.y)) * f;
            }
#pragma unroll
            for (int i = 0; i < 4; i++) {
                const uint32_t hh = __shfl_sync(~0u, hd, 4 * i + t);
                mma(ym[(i & 1) * 2], w2r[2 * i], hh & maskA, hh & maskB);
                mma(ym[(i & 1) * 2 + 1], w2r[2 * i + 1], hh & maskA, hh & maskB);
            }
#pragma unroll
            for (int k = 0; k < 4; k++) { yf[k] = ym[0][k] + ym[2][k]; add_if(t & 2, yf[k], ym[1][k], ym[3][k]); }
            CSTAMP(16, __float_as_uint(yf[3]));
            yw[0] = fx2_pack(yf[0] * sc2 + FX2_ONE, yf[1] * sc2 + FX2_ONE); yw[1] = fx2_pack(yf[2] * sc2 + FX2_ONE, yf[3] * sc2 + FX2_ONE);
            wide = !(fmaxf(fmaxf(fabsf(yf[0]), fabsf(yf[1])), fmaxf(fabsf(yf[2]), fabsf(yf[3]))) < lim);
            if (wide) yw[0] = yw[1] = 0;
            if (L.value == 0) {
#pragma unroll
                for (int k = 0; k < 2; k++) asm volatile("red.relaxed.gpu.global.add.u64 [%0], %1;" :: "l"(rap + k * 40 * ACC_PITCH), "l"(yw[k]) : "memory");
            }
        };
        auto send_wide = [&]() {
#pragma unroll 1
            for (int k = 0; k < 4; k++, yf[0] = yf[1], yf[1] = yf[2], yf[2] = yf[3]) {
                const unsigned char* a = rap + (k >> 1) * 40 * ACC_PITCH;
                fx_send(a + 64 + (k & 1) * 32, yf[0], msq, a, 256);
            }
            yw[0] = yw[1] = 1;
        };

        pass1();
        o_setup(IC<0>{});
        out_proj(IC<0>{});
        uint32_t c0;
        if (warp < 5) {
            mlp_part(IC<0>{});
            c0 = clk() + (mlp == 96 ? PCD : 0);
            stsf(sb + SM_ML + (lane & 15) * 4, cs1);
            TSTAMP(8);
            if (__any_sync(~0u, wide)) {
                if (wide) {
                    send_wide();
#pragma unroll
                    for (int k = 0; k < 2; k++) asm volatile("red.relaxed.gpu.global.add.u64 [%0], 1;" :: "l"(rap + k * 40 * ACC_PITCH) : "memory");
                }
                __syncwarp();
            }
            fresh(); calc_offsets();
            load_wq();
        } else {
            bar_sync(0, 256);
            if (warp == 5 && elect()) {
                asm volatile("fence.proxy.async.shared::cta;" ::: "memory");
                issue_w(IC<0>{}, 1);
            }
            __syncwarp();
            fresh(); calc_offsets();
            load_wq();
#pragma unroll 1
            for (int ph = 0; ph < 3; ph++) {
                bar_sync(ph + 2, 256);
                c0 = clk();
                if (ph == 2) {
                    msq = sum5(ldsf(sb + SM_PART + 12), ldsf(sb + SM_PART + 268), ldsf(sb + SM_PART + 524), ldsf(sb + SM_PART + 780), ldsf(sb + SM_PART + 1036)) * (1.f / D_MODEL);
                    bar_arrive(5, 256);
                }
                if (elect()) {
                    asm volatile("fence.proxy.async.shared::cta;" ::: "memory");
                    const uint32_t gap = ph == 0 ? WG1 : ph == 1 ? WG2 : WG3;
                    uint32_t c1 = c0 + (ph == 0 ? WD1 : 0) + (warp - 5) * gap;
#pragma unroll 1
                    for (int k = warp + (ph == 0 ? -5 : ph == 1 ? 9 : 1); k < (ph == 0 ? 9 : ph == 1 ? 20 : 14); k += 3, c1 += 3 * gap) {
                        const int i = ph == 0 && k >= 6 ? k + 23 : k;
                        const uint32_t bar = sb + SM_BAR + (i & 7) * 96 + 32 + (i & 24);
                        while ((int)(clk() - c1) < 0);
                        mbar_expect(bar, SUB);
                        tma_v(sb + SM_RING + i * SUB, tmk,
                              rowc * 3 + (i & 7) * 24 + ((UC<SCH.st[0].unit | SCH.st[1].unit << 8 | SCH.st[2].unit << 16 | SCH.st[3].unit << 24>::value >> (i & 24)) & 15) * 768, bar);
                    }
                }
                __syncwarp();
            }
            c0 += PCD;
        }
        {
            constexpr IC<1> L{};
            fresh();
            const int col = xcol(g & 3, t), cw = j40 + (col >> 2);
            const unsigned char* xa = pin(accg + ACC_BYTES + ((cw >> 2) + (col & 2) * 20) * ACC_PITCH + (cw & 3) * 8);
            const uint32_t pst = pin(prow + (g * 8 + (t & 1) * 4 + (t & 2)) * 4);
            const float inv = pinf(fx2_inv(msq));
            sts64f(sb + SM_MSQ, msq, inv);
            rap = pin(accg + ACC_BYTES + (c4() >> 2) * ACC_PITCH + (c4() & 3) * 8);
            fresh();
            maskA = pin(maskA); maskB = pin(maskB);
            u64 w[1];
            uint32_t x1[1], x2[3];
            auto look = [&]() { w[0] = ld_rlx(xa); };
            if (warp < 5) bar_sync(5, 256);
            while ((int)(clk() - c0) < ARDELAY);
            look();
            while ((int)(clk() - c0) < ARDELAY + DPOST);
            if (warp < 5 && elect()) {
                issue_v(IC<3>{}, 0);
                if (warp < 4) issue_v(IC<2>{}, 4);
            }
            __syncwarp();
            fx2_wait<1>([&](int) { return xa; }, look, w, sb + SM_MSQ, inv, x1);
            if (warp < 5) look_rw(); else rw[0] = rw[1] = 96;
#pragma unroll
            for (int i = 0; i < 3; i++) x2[i] = __shfl_sync(~0u, x1[0], 4 * i + t);
            TSTAMP(9);
            CSTAMP(22, x2[2]);
            q_proj(L, x2, pst);
            pass2();
            out_proj(L);
            if (warp >= 5) {
                bar_arrive(0, 256);
                if (warp == 5 && elect()) issue_w(L, 1);
                TDUMP();
                return;
            }
            mlp_part(L);
            u64 old[2];
            auto add = [&]() {
#pragma unroll
                for (int k = 0; k < 2; k++) asm volatile("atom.relaxed.gpu.global.add.u64 %0, [%1], %2;" : "=l"(old[k]) : "l"(rap + k * 40 * ACC_PITCH), "l"(yw[k]) : "memory");
            };
            add();
            uint32_t* op = pin(reinterpret_cast<uint32_t*>(P.out) + 2 * c4());
            const float inv2 = pinf(fx2_inv(msq));
            if (wide) { send_wide(); add(); }
            TSTAMP(18);
            CSTAMP(17, hi32(yw[1]));
            __syncwarp();
            CSTAMP(18, lo32(old[0]) ^ lo32(old[1]));
#pragma unroll
            for (int k = 0; k < 2; k++) {
                yw[k] += old[k];
                asm volatile("{\n.reg .pred p;\nsetp.eq.u32 p, %2, 96;\n@p st.global.u32 [%0], %1;\n}"
                             :: "l"(op + k), "r"(fx2_get(yw[k], inv2)), "r"(lo32(yw[k]) & 511) : "memory");
            }
            if ((lo32(yw[0]) & 255) == 96 && tid == 0) P.g->epoch = lds32(sb + SM_EPOCH) + 1;
#pragma unroll
            for (int k = 0; k < 2; k++) if ((lo32(yw[k]) & 511) == 256 + 96) op[k] = fx2_wide(rap + k * 40 * ACC_PITCH, msq);
            TSTAMP(19);
            CSTAMP(19, lo32(yw[1]));
            TDUMP();
        }
    }
}

typedef CUresult (*EncodeFn)(CUtensorMap*, CUtensorMapDataType, cuuint32_t, void*, const cuuint64_t*, const cuuint64_t*, const cuuint32_t*,
                             const cuuint32_t*, CUtensorMapInterleave, CUtensorMapSwizzle, CUtensorMapL2promotion, CUtensorMapFloatOOBfill);

}

extern "C" void kernel_launch(void* const* d_in, const int* in_sizes, int n_in, void* d_out, int out_size) {
    (void)in_sizes; (void)n_in; (void)out_size;
    static EncodeFn enc = nullptr;
    static void* scratch = nullptr;
    if (!enc) {
        void* fn = nullptr;
        cudaDriverEntryPointQueryResult qr;
        cudaGetDriverEntryPoint("cuTensorMapEncodeTiled", &fn, cudaEnableDefault, &qr);
        enc = (EncodeFn)fn;
        cudaGetSymbolAddress(&scratch, g_scratch);
        cudaFuncSetAttribute(fused_kernel, cudaFuncAttributeMaxDynamicSharedMemorySize, SM_TOTAL);
    }
    Params P = {};
    auto map3 = [&](int m, int in, cuuint64_t d0, cuuint64_t d1, cuuint64_t d2, cuuint64_t s1, cuuint64_t s2, cuuint32_t b0, cuuint32_t b1, cuuint32_t b2,
                    CUtensorMapSwizzle sw, int promo) {
        const cuuint64_t dim[3] = {d0, d1, d2}, str[2] = {s1, s2};
        const cuuint32_t box[3] = {b0, b1, b2}, ones[3] = {1, 1, 1};
        enc(&P.tm[m], CU_TENSOR_MAP_DATA_TYPE_BFLOAT16, d2 ? 3 : 2, d_in[in], dim, str, box, ones, CU_TENSOR_MAP_INTERLEAVE_NONE, sw, (CUtensorMapL2promotion)promo,
            CU_TENSOR_MAP_FLOAT_OOB_FILL_NONE);
    };
    map3(TM_KH, 1, 64, 3, NHEAD * SK, 128, DH * 2, 64, 3, 32, CU_TENSOR_MAP_SWIZZLE_128B, 0);
    map3(TM_VH, 2, 64, 3, NHEAD * SK, 128, DH * 2, 64, 3, 32, CU_TENSOR_MAP_SWIZZLE_128B, 0);
    map3(TM_VP, 2, 64, 3, NHEAD * SK, 128, DH * 2, 8, 3, 32, CU_TENSOR_MAP_SWIZZLE_NONE, 0);
    map3(TM_V, 2, 64, NHEAD * SK * 3, 0, 128, 0, 64, 24, 0, CU_TENSOR_MAP_SWIZZLE_128B, 0);
    map3(TM_WO, 4, 32, 20, NHEAD * DH, 64, D_MODEL * 2, 32, 1, DH, CU_TENSOR_MAP_SWIZZLE_64B, 2);
    map3(TM_WOP, 4, 32, 20, NHEAD * DH, 64, D_MODEL * 2, 8, 1, DH, CU_TENSOR_MAP_SWIZZLE_NONE, 0);
    map3(TM_WQ, 3, 64, NHEAD * 3, D_MODEL, 128, NHEAD * DH * 2, 64, 3, 32, CU_TENSOR_MAP_SWIZZLE_128B, 0);
    map3(TM_W1, 6, DFF, 128, 5, DFF * 2, DFF * 256, 16, 128, 5, CU_TENSOR_MAP_SWIZZLE_32B, 2);
    map3(TM_W2, 8, 64, 10, DFF, 128, D_MODEL * 2, 64, 10, 16, CU_TENSOR_MAP_SWIZZLE_128B, 0);
    P.x = (const __nv_bfloat16*)d_in[0];
    P.k = (const __nv_bfloat16*)d_in[1];
    P.b1 = (const __nv_bfloat16*)d_in[7];
    P.b2 = (const __nv_bfloat16*)d_in[9];
    P.w1 = (const __nv_bfloat16*)d_in[6];
    P.out = (__nv_bfloat16*)d_out;
    P.g = (Scratch*)(((uintptr_t)scratch + ACC_BYTES - 1) & ~(uintptr_t)(ACC_BYTES - 1));
    for (int i = 0; i < 64; i++) P.tile[i] = make_uint4(SCH.tile[i][0], SCH.tile[i][1], SCH.tile[i][2], 0);
    fused_kernel<<<NCTA, NTHR, SM_TOTAL, cudaStreamPerThread>>>(P);
}
```

```cpp
#include <cuda_runtime.h>
#include <cuda_bf16.h>
#include <cuda.h>
#include <stdint.h>

namespace {

constexpr int D_MODEL = 640, NHEAD = 32, SK = 32768, DH = 192, WIN = 4096, DFF = 1536;
constexpr int NCTA = 128, NTHR = 256;
constexpr int TILE = 64 * DH * 2;
constexpr int HALF = TILE / 2;
constexpr int SUB = 8 * DH * 2;
constexpr int SM_RING = 4 * TILE;
constexpr int SM_W2 = SM_RING + 20480, SM_W1 = SM_W2 + 20480;
constexpr int SM_WQR = 6 * TILE + HALF, SM_WQ = 7 * TILE;
constexpr int SM_PART = 9 * TILE;
constexpr int SM_EXC = SM_PART + 6144;
constexpr int SM_SC = SM_EXC + 1024;
constexpr int SM_BAR = SM_SC + 1024;
constexpr int SM_VEC = SM_BAR + 768;
constexpr int SM_CS = SM_VEC + 384;
constexpr int SM_FAC = SM_CS + 768;
constexpr int SM_ML = SM_FAC + 32;
constexpr int SM_B1 = SM_ML + 64;
constexpr int SM_STAT = SM_B1 + 64;
constexpr int NCB = 28;
constexpr int CB_WO = 18, CB_W1 = 23, CB_W2 = 24, CB_SNAP = 25, CB_REL = 26, CB_WQ = 27;
constexpr int SM_CBAR = SM_STAT + 48;
constexpr int SM_CNT = SM_CBAR + NCB * 8;
constexpr int SM_ZERO = SM_CNT + NCB * 8;
constexpr int SM_EPOCH = SM_ZERO + 64;
constexpr int SM_FXS = SM_EPOCH + 4;
constexpr int SM_T0 = SM_FXS + 4;
constexpr int SM_M1 = SM_T0 + 4;
constexpr int SM_MSQ = SM_M1 + 4;
constexpr int SM_TS = SM_MSQ + 8;
constexpr int SM_TOTAL = 232448;
static_assert(SM_TS + 320 <= SM_TOTAL && SM_ZERO % 16 == 0, "smem");
constexpr int NEXC = 16;

constexpr int SPIN = 1 << 20;
enum { TM_V = 0, TM_KH = 1, TM_VH = 2, TM_WO = 3, TM_VP = 4, TM_WOP = 5, TM_W1 = 6, TM_W2 = 7, TM_WQ = 8 };
constexpr uint32_t POL_NORMAL = 0x16F00000u, POL_FIRST = 0x12F00000u;

#define PACE 980
#define PACE0 1500
#define PACES 1300
#define NIM 4
#define NI1 6
#define ETRIG 0x54321000
#define PFREE 66
#define SNAPAT 1
#define LATEAT 5
#define PUBAT 28
#define HW0 30
#define HW1 31
#define AR1D 250
#define ARDELAY 650
#define DPOST 200
#define PCD 350
#define WD1 100
#define WG1 140
#define WG2 120
#define WG3 65
#define VORD2 0x7685943a2b1cd0efull
#define VSLOT 0x1087654321087654ull
#define VTRIG 0xba73210
#define PARKS 0xa5
#define RF0 1
#define RF1 2
#define M1D 1
#define LAG0 12
#define NMMA 2
#define HWAT 12
#define WOP 0x44433
#define NWO1 4
#define FX1LIM 524288.f
#define FX2LIM 524288.f

constexpr uint32_t G_A = 1u << 28, G_B = 1u << 29, G_C = 1u << 30;
__host__ __device__ constexpr int ring_hs(int j) { return (j + 4) % 5; }
__host__ __device__ constexpr uint32_t load_word(int j) {
    if (j >= 64) return (uint32_t)(j - 64) << 20 | (SM_RING + ring_hs(j) * HALF) | TM_WO << 8 | (CB_WO + j - 64) << 3 | 2;
    const int e = j >> 1, isv = e >= 16, unit = e & 15;
    return (uint32_t)(unit * 256 + (j & 1) * 32) << 20 | (j < 8 ? j * HALF : SM_RING + ring_hs(j) * HALF) | (TM_KH + isv) << 8 | (j < 8 ? 10 + j : (j - 8) % 10) << 3 | 2 | !isv;
}
__host__ __device__ constexpr int popc(int v) { return v ? (v & 1) + popc(v >> 1) : 0; }
constexpr int NPARK = popc(PARKS), NPRE = 2;
constexpr int SM_SNAP = SM_RING + ring_hs(12) * HALF, SM_CSP = SM_RING + ring_hs(11) * HALF;
struct Step { int unit, slot, par, next, mma0, nmma; };
struct Sched { uint32_t tile[64][3]; Step st[16]; };
constexpr Sched make_sched() {
    Sched s{};
    for (int j = 0; j < 64; j++) {
        const int e = j >> 1;
        const uint32_t d = load_word(j);
        uint32_t w = (uint32_t)(j < 8 ? 0 : (j - 8) / 10 & 1) << 31 | (e & 15) * 4 << 20 | ((d & 0x3f000) - (j & 1) * HALF) | (d & 0xf8);
        if (e == PUBAT || e == SNAPAT) w |= G_A;
        if (e == HW0 || e == 4) w |= G_B;
        if ((e >= LATEAT && e < LATEAT + 4) || e == HW1) w |= G_C;
        s.tile[j][0] = w;
    }
    for (int j = NI1; j < 69; j++) {
        if (j == 12) continue;
        const int at = j < 12 ? (ETRIG >> (4 * (j - 4)) & 15) : j - 5;
        s.tile[at][1] = load_word(j);
        s.tile[at][2] = j >= PFREE ? 0 : PACE0 + j * PACE / 2;
    }
    int done = 0;
    for (int p = 0; p < 16; p++) {
        Step& c = s.st[p];
        c.unit = (int)(VORD2 >> (4 * p) & 15); c.slot = (int)(VSLOT >> (4 * p) & 15); c.par = p >= 9; c.next = -1;
        c.mma0 = done;
        if (p >= NPARK) { const int avail = p - done + (p >= LAG0); c.nmma = p == 15 ? 16 - done : (avail < NMMA ? avail : NMMA); done += c.nmma; }
    }
    for (int p = 9; p < 16; p++) s.st[VTRIG >> (4 * (p - 9)) & 15].next = p;
    return s;
}
constexpr Sched SCH = make_sched();
__host__ __device__ constexpr int kunit(int o) { return o < 5 ? o + 11 : o == 5 ? 10 : o - 6; }

template <int I> struct IC { static constexpr int value = I; };
template <uint32_t I> struct UC { static constexpr uint32_t value = I; };
template <int A, int B, class F> __device__ __forceinline__ void static_for(F&& f) {
    if constexpr (A < B) { f(IC<A>{}); static_for<A + 1, B>(f); }
}

typedef unsigned long long u64;
constexpr int ACC_PITCH = 352, ACC1_PITCH = 256, ACC_BYTES = 32768;
struct alignas(1024) Scratch {
    unsigned char acc[4 * ACC_BYTES];
    u64 l0[NCTA][384];
    u64 ll[NCTA][256];
    alignas(128) unsigned epoch;
    alignas(128) unsigned zeroed;
};
__device__ __align__(1024) unsigned char g_scratch[sizeof(Scratch) + ACC_BYTES];

struct Params {
    CUtensorMap tm[9];
    const __nv_bfloat16 *x, *k, *b1, *b2, *w1;
    __nv_bfloat16* out;
    Scratch* g;
    uint4 tile[66];
};

#define TSTAMP(i)
#define TSTAMP2(i)
#define TSTAMPL(i)
#define TDUMP()
#define CSTAMP(i, x)
#define TRACE(i)

__device__ __forceinline__ void mbar_wait(uint32_t bar, uint32_t parity) {
    asm volatile("{\n.reg .pred p;\nLOOP:\nmbarrier.try_wait.parity.shared::cta.b64 p, [%0], %1;\n@!p bra.uni LOOP;\n}" :: "r"(bar), "r"(parity) : "memory");
}
__device__ __forceinline__ bool mbar_test(uint32_t bar, uint32_t parity) {
    uint32_t r;
    asm volatile("{\n.reg .pred p;\nmbarrier.test_wait.parity.shared::cta.b64 p, [%1], %2;\nselp.u32 %0, 1, 0, p;\n}" : "=r"(r) : "r"(bar), "r"(parity) : "memory");
    return __all_sync(~0u, r);
}
__device__ __forceinline__ bool elect() {
    uint32_t r;
    asm volatile("{\n.reg .pred p;\nelect.sync _|p, 0xffffffff;\nselp.u32 %0, 1, 0, p;\n}" : "=r"(r));
    return r != 0;
}
__device__ __forceinline__ void mbar_expect(uint32_t bar, uint32_t bytes) {
    asm volatile("mbarrier.arrive.expect_tx.shared::cta.b64 _, [%0], %1;" :: "r"(bar), "r"(bytes) : "memory");
}
__device__ __forceinline__ uint4 lds128(uint32_t a) {
    uint4 v; asm volatile("ld.shared.v4.u32 {%0,%1,%2,%3}, [%4];" : "=r"(v.x), "=r"(v.y), "=r"(v.z), "=r"(v.w) : "r"(a) : "memory"); return v;
}
__device__ __forceinline__ uint4 ldsm_t(uint32_t a) {
    uint4 v; asm volatile("ldmatrix.sync.aligned.m8n8.x4.trans.shared.b16 {%0,%1,%2,%3}, [%4];" : "=r"(v.x), "=r"(v.y), "=r"(v.z), "=r"(v.w) : "r"(a) : "memory"); return v;
}
__device__ __forceinline__ uint2 lds64(uint32_t a) {
    uint2 v; asm volatile("ld.shared.v2.u32 {%0,%1}, [%2];" : "=r"(v.x), "=r"(v.y) : "r"(a) : "memory"); return v;
}
__device__ __forceinline__ float2 lds64f(uint32_t a) { const uint2 v = lds64(a); return make_float2(__uint_as_float(v.x), __uint_as_float(v.y)); }
__device__ __forceinline__ uint32_t lds32(uint32_t a) {
    uint32_t v; asm volatile("ld.shared.u32 %0, [%1];" : "=r"(v) : "r"(a) : "memory"); return v;
}
__device__ __forceinline__ float ldsf(uint32_t a) { return __uint_as_float(lds32(a)); }
__device__ __forceinline__ void sts32(uint32_t a, uint32_t v) { asm volatile("st.shared.u32 [%0], %1;" :: "r"(a), "r"(v) : "memory"); }
__device__ __forceinline__ void stsf(uint32_t a, float v) { sts32(a, __float_as_uint(v)); }
__device__ __forceinline__ void sts16(uint32_t a, uint32_t v) { asm volatile("st.shared.u16 [%0], %1;" :: "r"(a), "h"((uint16_t)v) : "memory"); }
__device__ __forceinline__ void sts64(uint32_t a, uint32_t x, uint32_t y) { asm volatile("st.shared.v2.u32 [%0], {%1,%2};" :: "r"(a), "r"(x), "r"(y) : "memory"); }
__device__ __forceinline__ void sts64f(uint32_t a, float x, float y) { sts64(a, __float_as_uint(x), __float_as_uint(y)); }
__device__ __forceinline__ void sts128f(uint32_t a, float x, float y, float z, float w) {
    asm volatile("st.shared.v4.f32 [%0], {%1,%2,%3,%4};" :: "r"(a), "f"(x), "f"(y), "f"(z), "f"(w) : "memory");
}
__device__ __forceinline__ void mma(float (&c)[4], const uint4& a, uint32_t b0, uint32_t b1) {
    asm volatile("mma.sync.aligned.m16n8k16.row.col.f32.bf16.bf16.f32 {%0,%1,%2,%3}, {%4,%5,%6,%7}, {%8,%9}, {%0,%1,%2,%3};"
                 : "+f"(c[0]), "+f"(c[1]), "+f"(c[2]), "+f"(c[3]) : "r"(a.x), "r"(a.y), "r"(a.z), "r"(a.w), "r"(b0), "r"(b1));
}
__device__ __forceinline__ u64 ld_rlx(const void* p) {
    u64 a; asm volatile("ld.relaxed.gpu.global.u64 %0, [%1];" : "=l"(a) : "l"(p) : "memory"); return a;
}
__device__ __forceinline__ void ld_rlx2(const void* p, u64& a, u64& b) {
    asm volatile("ld.relaxed.gpu.global.v2.u64 {%0,%1}, [%2];" : "=l"(a), "=l"(b) : "l"(p) : "memory");
}
__device__ __forceinline__ void st_rlx(void* p, u64 a) { asm volatile("st.relaxed.gpu.global.u64 [%0], %1;" :: "l"(p), "l"(a) : "memory"); }
__device__ __forceinline__ u64 ll_pack(float v, uint32_t tag) { return ((u64)tag << 32) | __float_as_uint(v); }
__device__ __forceinline__ float ll_val(u64 w) { return __uint_as_float((uint32_t)w); }
__device__ __forceinline__ uint32_t ll_tag(u64 w) { return (uint32_t)(w >> 32); }
__device__ __forceinline__ float bf_lo(uint32_t u) { return __uint_as_float(u << 16); }
__device__ __forceinline__ float bf_hi(uint32_t u) { return __uint_as_float(u & 0xffff0000u); }
__device__ __forceinline__ uint32_t pack_bf(float lo, float hi) {
    uint32_t r; asm("cvt.rn.bf16x2.f32 %0, %1, %2;" : "=r"(r) : "f"(hi), "f"(lo)); return r;
}
__device__ __forceinline__ float ex2(float v) { float r; asm("ex2.approx.ftz.f32 %0, %1;" : "=f"(r) : "f"(v)); return r; }
__device__ __forceinline__ float rcp(float v) { float r; asm("rcp.approx.ftz.f32 %0, %1;" : "=f"(r) : "f"(v)); return r; }
__device__ __forceinline__ float rsq(float v) { float r; asm("rsqrt.approx.ftz.f32 %0, %1;" : "=f"(r) : "f"(v)); return r; }
__device__ __forceinline__ void bar_sync(int id, int n) { asm volatile("bar.sync %0, %1;" :: "r"(id), "r"(n) : "memory"); }
__device__ __forceinline__ uint32_t clk() { uint32_t c; asm volatile("mov.u32 %0, %clock;" : "=r"(c)); return c; }
__device__ __forceinline__ void sched_fence() { __syncwarp(); while (clk() == 0x9e3779b9u); }
__device__ __forceinline__ uint32_t pin(uint32_t v) { return __shfl_xor_sync(~0u, v, 0); }
__device__ __forceinline__ float shx(float v, int o) { return __shfl_xor_sync(~0u, v, o); }

__device__ __forceinline__ u64 fx_pack(float v, float scale) { return ((u64)__float2ll_rn(v * scale) & ~255ull) | 1ull; }
__device__ __forceinline__ float fx_scale(float meansq) {
    const int e = max(((int)(__float_as_uint(meansq) >> 23) - 127) >> 1, -6);
    return __uint_as_float((uint32_t)(127 + 32 - e) << 23);
}
__device__ __forceinline__ float fx_inv(float scale) { return __uint_as_float((254u << 23) - __float_as_uint(scale)); }
__device__ __forceinline__ uint32_t lo32(u64 w) { uint32_t l; asm("mov.b64 {%0, _}, %1;" : "=r"(l) : "l"(w)); return l; }
__device__ __forceinline__ int hi32(u64 w) { int h; asm("mov.b64 {_, %0}, %1;" : "=r"(h) : "l"(w)); return h; }
__device__ __forceinline__ float fx_val(u64 w) { return (float)hi32(w) * 4294967296.f + (float)lo32(w); }
constexpr float FX2_ONE = 12582912.f;
__device__ __forceinline__ float fx2_scale(float meansq) { return __uint_as_float((uint32_t)(127 + 16 - max(((int)(__float_as_uint(meansq) >> 23) - 127) >> 1, -100)) << 23); }
__device__ __forceinline__ u64 fx2_pack(float a, float b) {
    const uint32_t lo = __float_as_uint(a) * 512u + (1u - 0x4b400000u * 512u);
    return lo | (u64)(__float_as_uint(b) * 16u - 0x4b400000u * 16u + (uint32_t)((int)lo >> 31)) << 32;
}
__device__ __forceinline__ float fx2_lo(u64 w, float inv) { return (float)(int)(__funnelshift_r(lo32(w), hi32(w), 4) & ~31u) * (inv * 0.5f); }
__device__ __forceinline__ float fx2_hi(u64 w, float inv) { return (float)((hi32(w) + 8) & ~15) * inv; }
__device__ __forceinline__ uint32_t fx2_get(u64 w, float inv) {
    return pack_bf((float)(int)__funnelshift_r(lo32(w), hi32(w), 4) * (inv * 0.5f) - inv * 3.f, (float)hi32(w) * inv);
}
__device__ __forceinline__ float fx2_inv(float meansq) { return fx_inv(fx2_scale(meansq)) * 0.0625f; }
__device__ __noinline__ uint32_t fx2_wide(const unsigned char* a, float meansq) {
    __threadfence();
    const u64 w = ld_rlx(a);
    const float inv = fx_inv(fx_scale(meansq));
    return pack_bf(fx2_lo(w, fx2_inv(meansq)) + fx_val(ld_rlx(a + 64)) * inv, fx2_hi(w, fx2_inv(meansq)) + fx_val(ld_rlx(a + 96)) * inv);
}
__device__ __noinline__ uint32_t fx1_wide(const unsigned char* a, float meansq) {
    __threadfence();
    const u64 w = ld_rlx(a);
    const unsigned char* b = a + 64 + (reinterpret_cast<u64>(a) & 31);
    const float inv = fx_inv(fx_scale(meansq)), inv1 = fx2_inv(meansq) * 0.5f;
    return pack_bf((float)(int)(lo32(w) & ~127u) * inv1 + fx_val(ld_rlx(b)) * inv, (float)(hi32(w) & ~127) * inv1 + fx_val(ld_rlx(b + 8)) * inv);
}
__device__ __noinline__ void fx_send(const unsigned char* wide, float v, float meansq, const unsigned char* a, uint32_t flag) {
    asm volatile("red.relaxed.gpu.global.add.u64 [%0], %1;" :: "l"(wide), "l"(fx_pack(v, fx_scale(meansq))) : "memory");
    __threadfence();
    asm volatile("red.relaxed.gpu.global.or.b32 [%0], %1;" :: "l"(a), "r"(flag) : "memory");
}
template <int N, class A, class F> __device__ __forceinline__ void fx2_wait(A a, F look, u64 (&w)[N], uint32_t msqa, float inv, uint32_t (&x)[N]) {
    auto miss = [&]() {
#pragma unroll
        for (int i = 0; i < N; i++) x[i] = fx2_get(w[i], inv);
        return __any_sync(~0u, ((lo32(w[0]) ^ 96) | (lo32(w[N - 1]) ^ 96)) & 0x160);
    };
    if (miss()) {
        int it = 0;
#pragma unroll 1
        do {
            if (__all_sync(~0u, (lo32(w[0]) & lo32(w[N - 1]) & 96) == 96)) {
#pragma unroll
                for (int i = 0; i < N; i++) x[i] = fx2_wide(a(i), ldsf(msqa));
                break;
            }
            look();
        } while (miss() & (++it < SPIN));
    }
}
__device__ __forceinline__ void st_rlx_if(bool p, void* a, u64 v) {
    asm volatile("{\n.reg .pred p;\nsetp.ne.u32 p, %2, 0;\n@p st.relaxed.gpu.global.u64 [%0], %1;\n}" :: "l"(a), "l"(v), "r"((uint32_t)p) : "memory");
}
__device__ __forceinline__ void sts128f(uint32_t a, const float (&v)[4]) { sts128f(a, v[0], v[1], v[2], v[3]); }
__device__ __forceinline__ void bar_arrive(int id, int n) { asm volatile("bar.arrive %0, %1;" :: "r"(id), "r"(n) : "memory"); }
template <class T> __device__ __forceinline__ T* pin(T* p) { return reinterpret_cast<T*>(__shfl_xor_sync(~0u, (u64)p, 0)); }

__device__ __forceinline__ void tma3(uint32_t dst, const CUtensorMap* tm, int c1, int c2, uint32_t bar, uint32_t pol) {
    asm volatile("cp.async.bulk.tensor.3d.shared::cluster.global.mbarrier::complete_tx::bytes.L2::cache_hint [%0], [%1, {%2, %3, %4}], [%5], %6;"
                 :: "r"(dst), "l"(tm), "r"(0), "r"(c1), "r"(c2), "r"(bar), "l"((u64)pol << 32) : "memory");
}
__device__ __forceinline__ void tma_v(uint32_t dst, const CUtensorMap* tm, int line, uint32_t bar) {
    asm volatile("cp.async.bulk.tensor.2d.shared::cluster.global.mbarrier::complete_tx::bytes.L2::cache_hint [%0], [%1, {%2, %3}], [%4], %5;"
                 :: "r"(dst), "l"(tm), "r"(0), "r"(line), "r"(bar), "l"((u64)POL_FIRST << 32) : "memory");
}
__device__ __forceinline__ void tma3_pf(const CUtensorMap* tm, int c1, int c2, uint32_t pol) {
    asm volatile("cp.async.bulk.prefetch.tensor.3d.L2.global.tile.L2::cache_hint [%0, {%1, %2, %3}], %4;"
                 :: "l"(tm), "r"(0), "r"(c1), "r"(c2), "l"((u64)pol << 32) : "memory");
}
__device__ __forceinline__ void issue_half(uint32_t d, uint32_t sb, int rowc, int cta, const CUtensorMap* tm0) {
    const uint32_t bar = sb + SM_CBAR + (d & 0xf8);
    const CUtensorMap* tm = tm0 + ((d >> 8) & 3);
    const bool wo = (d & 0x300) == TM_WO << 8;
    const int c1 = wo ? (cta & 3) + 4 * (d >> 20) : 0, c2 = wo ? (cta >> 2) * DH : rowc + (d >> 20);
    mbar_expect(bar, HALF);
    tma3(sb + (d & 0x3f000), tm, c1, c2, bar, POL_FIRST);
    if (!(d & 1)) tma3_pf(tm + 2, c1, c2, POL_NORMAL);
}
__device__ __forceinline__ uint32_t cnt_inc(uint32_t a, uint32_t last) {
    uint32_t old; asm volatile("atom.relaxed.cta.shared.inc.u32 %0, [%1], %2;" : "=r"(old) : "r"(a), "r"(last) : "memory"); return old;
}
__device__ __forceinline__ void wait_until(uint32_t due) {
#pragma unroll 1
    for (int it = 0; it < 4096; it++) { uint32_t now; asm volatile("mov.u32 %0, %globaltimer_lo;" : "=r"(now)); if ((int)(now - due) >= 0) break; }
}
__device__ __forceinline__ uint32_t bf2_mul(uint32_t a, uint32_t b) { uint32_t r; asm("mul.rn.bf16x2 %0, %1, %2;" : "=r"(r) : "r"(a), "r"(b)); return r; }
__device__ __forceinline__ uint32_t bf2_fma(uint32_t a, uint32_t b, uint32_t c) { uint32_t r; asm("fma.rn.bf16x2 %0, %1, %2, %3;" : "=r"(r) : "r"(a), "r"(b), "r"(c)); return r; }
__device__ __forceinline__ uint32_t bf2_amax(uint32_t a, uint32_t b) { uint32_t r; asm("max.NaN.xorsign.abs.bf16x2 %0, %1, %2;" : "=r"(r) : "r"(a), "r"(b)); return r; }
__device__ __forceinline__ uint4 k_unpack(uint32_t l0, uint32_t l1, uint32_t h, uint32_t m1) {
    const uint32_t ha = h & 0x87878787u, hc = ha * m1 + h, hb = __funnelshift_l(hc, hc, 4);
    return make_uint4(__byte_perm(l0, ha, 0x5140), __byte_perm(l0, ha, 0x7362), __byte_perm(l1, hb, 0x5140), __byte_perm(l1, hb, 0x7362));
}
#define KR4(u, i) "+r"(kr[u][i].x), "+r"(kr[u][i].y), "+r"(kr[u][i].z), "+r"(kr[u][i].w)
#define KR6(u) KR4(u, 0), KR4(u, 1), KR4(u, 2), KR4(u, 3), KR4(u, 4), KR4(u, 5)
__device__ __forceinline__ void k_keep(uint4 (&kr)[8][6], const uint32_t (&c)[18], int e, uint32_t a) {
    asm volatile("{\nKT: .branchtargets K0, K1, K2, K3, K4, K5, K6, K7, K8, K9, K10, K11, K12, K13, K14, K15;\nbrx.idx.uni %210, KT;\n"
                 "K0: mov.b32 %12, %192; mov.b32 %13, %193; mov.b32 %14, %194; mov.b32 %15, %195; mov.b32 %16, %196; mov.b32 %17, %197; mov.b32 %18, %198; mov.b32 %19, %199; mov.b32 %20, %200; mov.b32 %21, %201; mov.b32 %22, %202; mov.b32 %23, %203; mov.b32 %24, %204; mov.b32 %25, %205; mov.b32 %26, %206; mov.b32 %27, %207; mov.b32 %28, %208; mov.b32 %29, %209; bra.uni KE;\n"
                 "K1: mov.b32 %30, %192; mov.b32 %31, %193; mov.b32 %32, %194; mov.b32 %33, %195; mov.b32 %34, %196; mov.b32 %35, %197; mov.b32 %36, %198; mov.b32 %37, %199; mov.b32 %38, %200; mov.b32 %39, %201; mov.b32 %40, %202; mov.b32 %41, %203; mov.b32 %42, %204; mov.b32 %43, %205; mov.b32 %44, %206; mov.b32 %45, %207; mov.b32 %46, %208; mov.b32 %47, %209; bra.uni KE;\n"
                 "K2: mov.b32 %48, %192; mov.b32 %49, %193; mov.b32 %50, %194; mov.b32 %51, %195; mov.b32 %52, %196; mov.b32 %53, %197; mov.b32 %54, %198; mov.b32 %55, %199; mov.b32 %56, %200; mov.b32 %57, %201; mov.b32 %58, %202; mov.b32 %59, %203; mov.b32 %60, %204; mov.b32 %61, %205; mov.b32 %62, %206; mov.b32 %63, %207; mov.b32 %64, %208; mov.b32 %65, %209; bra.uni KE;\n"
                 "K3: mov.b32 %66, %192; mov.b32 %67, %193; mov.b32 %68, %194; mov.b32 %69, %195; mov.b32 %70, %196; mov.b32 %71, %197; mov.b32 %72, %198; mov.b32 %73, %199; mov.b32 %74, %200; mov.b32 %75, %201; mov.b32 %76, %202; mov.b32 %77, %203; mov.b32 %78, %204; mov.b32 %79, %205; mov.b32 %80, %206; mov.b32 %81, %207; mov.b32 %82, %208; mov.b32 %83, %209; bra.uni KE;\n"
                 "K4: mov.b32 %84, %192; mov.b32 %85, %193; mov.b32 %86, %194; mov.b32 %87, %195; mov.b32 %88, %196; mov.b32 %89, %197; mov.b32 %90, %198; mov.b32 %91, %199; mov.b32 %92, %200; mov.b32 %93, %201; mov.b32 %94, %202; mov.b32 %95, %203; mov.b32 %96, %204; mov.b32 %97, %205; mov.b32 %98, %206; mov.b32 %99, %207; mov.b32 %100, %208; mov.b32 %101, %209; bra.uni KE;\n"
                 "K5: mov.b32 %102, %192; mov.b32 %103, %193; mov.b32 %104, %194; mov.b32 %105, %195; mov.b32 %106, %196; mov.b32 %107, %197; mov.b32 %108, %198; mov.b32 %109, %199; mov.b32 %110, %200; mov.b32 %111, %201; mov.b32 %112, %202; mov.b32 %113, %203; mov.b32 %114, %204; mov.b32 %115, %205; mov.b32 %116, %206; mov.b32 %117, %207; mov.b32 %118, %208; mov.b32 %119, %209; bra.uni KE;\n"
                 "K6: mov.b32 %120, %192; mov.b32 %121, %193; mov.b32 %122, %194; mov.b32 %123, %195; mov.b32 %124, %196; mov.b32 %125, %197; mov.b32 %126, %198; mov.b32 %127, %199; mov.b32 %128, %200; mov.b32 %129, %201; mov.b32 %130, %202; mov.b32 %131, %203; mov.b32 %132, %204; mov.b32 %133, %205; mov.b32 %134, %206; mov.b32 %135, %207; mov.b32 %136, %208; mov.b32 %137, %209; bra.uni KE;\n"
                 "K7: mov.b32 %138, %192; mov.b32 %139, %193; mov.b32 %140, %194; mov.b32 %141, %195; mov.b32 %142, %196; mov.b32 %143, %197; mov.b32 %144, %198; mov.b32 %145, %199; mov.b32 %146, %200; mov.b32 %147, %201; mov.b32 %148, %202; mov.b32 %149, %203; mov.b32 %150, %204; mov.b32 %151, %205; mov.b32 %152, %206; mov.b32 %153, %207; mov.b32 %154, %208; mov.b32 %155, %209; bra.uni KE;\n"
                 "K8: mov.b32 %156, %192; mov.b32 %157, %193; mov.b32 %158, %194; mov.b32 %159, %195; mov.b32 %160, %196; mov.b32 %161, %197; mov.b32 %162, %198; mov.b32 %163, %199; mov.b32 %164, %200; mov.b32 %165, %201; mov.b32 %166, %202; mov.b32 %167, %203; mov.b32 %168, %204; mov.b32 %169, %205; mov.b32 %170, %206; mov.b32 %171, %207; mov.b32 %172, %208; mov.b32 %173, %209; bra.uni KE;\n"
                 "K9: mov.b32 %174, %192; mov.b32 %175, %193; mov.b32 %176, %194; mov.b32 %177, %195; mov.b32 %178, %196; mov.b32 %179, %197; mov.b32 %180, %198; mov.b32 %181, %199; mov.b32 %182, %200; mov.b32 %183, %201; mov.b32 %184, %202; mov.b32 %185, %203; mov.b32 %186, %204; mov.b32 %187, %205; mov.b32 %188, %206; mov.b32 %189, %207; mov.b32 %190, %208; mov.b32 %191, %209; bra.uni KE;\n"
                 "K10: st.shared.v2.b32 [%211+75784], {%192, %193}; st.shared.v2.b32 [%211+76288], {%194, %195}; st.shared.v2.b32 [%211+76296], {%196, %197}; mov.b32 %0, %198; mov.b32 %1, %199; mov.b32 %2, %200; mov.b32 %3, %201; mov.b32 %4, %202; mov.b32 %5, %203; mov.b32 %6, %204; mov.b32 %7, %205; mov.b32 %8, %206; mov.b32 %9, %207; mov.b32 %10, %208; mov.b32 %11, %209; bra.uni KE;\n"
                 "K11: st.shared.v2.b32 [%211+0], {%192, %193}; st.shared.v2.b32 [%211+8], {%194, %195}; st.shared.v2.b32 [%211+512], {%196, %197}; st.shared.v2.b32 [%211+520], {%198, %199}; st.shared.v2.b32 [%211+1024], {%200, %201}; st.shared.v2.b32 [%211+1032], {%202, %203}; st.shared.v2.b32 [%211+1536], {%204, %205}; st.shared.v2.b32 [%211+1544], {%206, %207}; st.shared.v2.b32 [%211+2048], {%208, %209}; bra.uni KE;\n"
                 "K12: st.shared.v2.b32 [%211+2056], {%192, %193}; st.shared.v2.b32 [%211+2560], {%194, %195}; st.shared.v2.b32 [%211+2568], {%196, %197}; st.shared.v2.b32 [%211+24576], {%198, %199}; st.shared.v2.b32 [%211+24584], {%200, %201}; st.shared.v2.b32 [%211+25088], {%202, %203}; st.shared.v2.b32 [%211+25096], {%204, %205}; st.shared.v2.b32 [%211+25600], {%206, %207}; st.shared.v2.b32 [%211+25608], {%208, %209}; bra.uni KE;\n"
                 "K13: st.shared.v2.b32 [%211+26112], {%192, %193}; st.shared.v2.b32 [%211+26120], {%194, %195}; st.shared.v2.b32 [%211+26624], {%196, %197}; st.shared.v2.b32 [%211+26632], {%198, %199}; st.shared.v2.b32 [%211+27136], {%200, %201}; st.shared.v2.b32 [%211+27144], {%202, %203}; st.shared.v2.b32 [%211+49152], {%204, %205}; st.shared.v2.b32 [%211+49160], {%206, %207}; st.shared.v2.b32 [%211+49664], {%208, %209}; bra.uni KE;\n"
                 "K14: st.shared.v2.b32 [%211+49672], {%192, %193}; st.shared.v2.b32 [%211+50176], {%194, %195}; st.shared.v2.b32 [%211+50184], {%196, %197}; st.shared.v2.b32 [%211+50688], {%198, %199}; st.shared.v2.b32 [%211+50696], {%200, %201}; st.shared.v2.b32 [%211+51200], {%202, %203}; st.shared.v2.b32 [%211+51208], {%204, %205}; st.shared.v2.b32 [%211+51712], {%206, %207}; st.shared.v2.b32 [%211+51720], {%208, %209}; bra.uni KE;\n"
                 "K15: st.shared.v2.b32 [%211+73728], {%192, %193}; st.shared.v2.b32 [%211+73736], {%194, %195}; st.shared.v2.b32 [%211+74240], {%196, %197}; st.shared.v2.b32 [%211+74248], {%198, %199}; st.shared.v2.b32 [%211+74752], {%200, %201}; st.shared.v2.b32 [%211+74760], {%202, %203}; st.shared.v2.b32 [%211+75264], {%204, %205}; st.shared.v2.b32 [%211+75272], {%206, %207}; st.shared.v2.b32 [%211+75776], {%208, %209}; \nKE:\n}"
                 : KR6(0), KR6(1), KR6(2), KR6(3), KR6(4), KR6(5), KR6(6), KR6(7)
                 : "r"(c[0]), "r"(c[1]), "r"(c[2]), "r"(c[3]), "r"(c[4]), "r"(c[5]), "r"(c[6]), "r"(c[7]), "r"(c[8]), "r"(c[9]), "r"(c[10]), "r"(c[11]), "r"(c[12]), "r"(c[13]), "r"(c[14]), "r"(c[15]), "r"(c[16]), "r"(c[17]), "r"(e), "r"(a) : "memory");
}
__device__ __forceinline__ uint32_t smem_base() { extern __shared__ __align__(1024) unsigned char smem[]; return (uint32_t)__cvta_generic_to_shared(smem); }
__device__ __forceinline__ void k_rare(uint4 v0, uint4 v1, uint4 v2, uint4 v3, uint4 v4, uint4 v5, uint32_t odd, int e, int warp, int lane) {
    const uint32_t sb = smem_base(), g = lane >> 2, t = lane & 3, st = sb + SM_BAR + warp * 96 + 80;
    uint32_t lt; asm volatile("mov.u32 %0, %lanemask_lt;" : "=r"(lt));
    const uint4 v[6] = {v0, v1, v2, v3, v4, v5};
    odd <<= 6;
#pragma unroll
    for (int i = 0; i < 6; i++) if (v[i].x | v[i].y | v[i].z | v[i].w) odd |= 1u << i;
    odd = __reduce_or_sync(~0u, odd);
    uint32_t n = odd >= 64 ? NEXC + 1 : __shfl_sync(~0u, lds32(st), 0);
#pragma unroll 1
    for (; odd && n <= NEXC; odd &= odd - 1) {
        const int i = __ffs(odd) - 1;
#pragma unroll
        for (int k = 1; k < 6; k++) if (i == k) v0 = v[k];
#pragma unroll 1
        for (int k = 0; k < 4; k++, v0.x = v0.y, v0.y = v0.z, v0.z = v0.w) {
            const uint32_t who = __ballot_sync(~0u, v0.x), at = n + __popc(who & lt);
            sts64(v0.x && at < NEXC ? sb + SM_EXC + warp * 128 + at * 8 : st + 8, v0.x, (e * 32 + g * 4) << 16 | (((k & 1) * 4 + t) * 48 + i * 8 + (k >> 1) * 4));
            n += __popc(who);
        }
    }
    const uint32_t bad = lds32(st + 4);
    __syncwarp();
    if (n <= NEXC) sts32(st, n);
    else {
        sts32(st + 4, bad | 1u << e);
        asm volatile("st.shared.u8 [%0], %1;" :: "r"(sb + SM_SC + warp * 128 + g * 16 + (e & 3) * 4 + (e >> 2)), "r"(0) : "memory");
    }
    __syncwarp();
}
template <int K> __device__ __forceinline__ uint32_t& word(uint4& v) { if constexpr (K == 0) return v.x; else if constexpr (K == 1) return v.y; else if constexpr (K == 2) return v.z; else return v.w; }
__device__ __forceinline__ void add_if(bool p, float& d, float a, float b) {
    asm volatile("{\n.reg .pred p;\nsetp.ne.u32 p, %3, 0;\n@p add.f32 %0, %1, %2;\n}" : "+f"(d) : "f"(a), "f"(b), "r"((uint32_t)p));
}
__device__ __forceinline__ float warp_max(float v) {
#pragma unroll
    for (int o = 16; o; o >>= 1) v = fmaxf(v, shx(v, o));
    return v;
}
__device__ __forceinline__ float warp_sum(float v) {
#pragma unroll
    for (int o = 16; o; o >>= 1) v += shx(v, o);
    return v;
}
template <int PITCH> __device__ __forceinline__ void ll_look(const u64* buf, u64 (&w)[4]) {
#pragma unroll
    for (int i = 0; i < 4; i++) w[i] = ld_rlx(buf + i * PITCH);
}
template <int PITCH> __device__ __forceinline__ float ll_gather(const u64* buf, uint32_t tag, u64 (&w)[4]) {
    auto miss = [&]() {
        uint32_t a, b;
        asm("lop3.b32 %0, %1, %2, %3, 0x7e;" : "=r"(a) : "r"(ll_tag(w[0])), "r"(ll_tag(w[1])), "r"(tag));
        asm("lop3.b32 %0, %1, %2, %3, 0x7e;" : "=r"(b) : "r"(ll_tag(w[2])), "r"(ll_tag(w[3])), "r"(tag));
        return __any_sync(~0u, a | b);
    };
    int it = 0;
    goto check;
again:
    ll_look<PITCH>(buf, w);
check:
    if (miss() & (++it < SPIN)) goto again;
    return (ll_val(w[0]) + ll_val(w[1])) + (ll_val(w[2]) + ll_val(w[3]));
}
__device__ __forceinline__ float sum8(uint32_t a, int pitch) {
    float s[8];
#pragma unroll
    for (int w = 0; w < 8; w++) s[w] = ldsf(a + w * pitch);
    return ((s[0] + s[1]) + (s[2] + s[3])) + ((s[4] + s[5]) + (s[6] + s[7]));
}
__device__ __forceinline__ float sum5(float a, float b, float c, float d, float e) { return ((a + b) + (c + d)) + e; }
__device__ __forceinline__ float ln_part(uint2 xp, int lane) {
    const float x0 = bf_lo(xp.x), x1 = bf_hi(xp.x), x2 = bf_lo(xp.y), x3 = bf_hi(xp.y);
    const float s1 = (x0 + x1) + (x2 + x3), s2 = (x0 * x0 + x1 * x1) + (x2 * x2 + x3 * x3);
    return ((lane & 16) ? s2 : s1) + shx((lane & 16) ? s1 : s2, 16);
}
__device__ __forceinline__ float ln_rstd(float mean, float msq) { return rsq(fmaxf(msq - mean * mean, 0.f) + 1e-5f); }
__device__ __forceinline__ float score(const uint4 (&v)[6], const uint4 (&qf)[3]) {
    float d[2][4];
#pragma unroll
    for (int j = 0; j < 2; j++) d[j][0] = d[j][1] = d[j][2] = d[j][3] = 0.f;
#pragma unroll
    for (int i = 0; i < 3; i++) { mma(d[0], v[2 * i], qf[i].x, qf[i].y); mma(d[1], v[2 * i + 1], qf[i].z, qf[i].w); }
    return (d[0][0] + d[0][3]) + (d[1][0] + d[1][3]);
}
__device__ __forceinline__ float k_side(uint32_t sb, uint2 x) {
    const uint32_t qq = lds32(sb + SM_VEC + (x.y & 0xffff));
    return (bf_lo(x.x) * bf_lo(qq) + bf_hi(x.x) * bf_hi(qq)) * 0x1p-64f;
}
__device__ __forceinline__ void k_fix(const __nv_bfloat16* k, uint32_t bad, int warp, int lane) {
    const uint32_t sb = smem_base(), g = lane >> 2, sa = sb + SM_PART + warp * 768 + 256;
    const uint2 x = lds64(sb + SM_EXC + warp * 128 + (lane & 15) * 8);
    if ((int)x.y >= 0x40000000 && lane < 16) asm volatile("red.shared.add.f32 [%0], %1;" :: "r"(sa + ((x.y >> 16) & 511)), "f"(k_side(sb, x)) : "memory");
    __syncwarp();
#pragma unroll 1
    for (bad &= 0xffff; bad; bad &= bad - 1) {
        const int e = __ffs(bad) - 1;
        const __nv_bfloat16* kp = k + (e * 256 + (g >> 1) + 4 * (g & 1)) * DH + (lane & 3) * 8;
        uint4 v[6], qf[3];
#pragma unroll
        for (int i = 0; i < 6; i++) v[i] = *reinterpret_cast<const uint4*>(kp + i * 32);
#pragma unroll
        for (int i = 0; i < 3; i++) qf[i] = lds128(sb + SM_VEC + (lane & 7) * 48 + i * 16);
        stsf(sa + e * 32 + g * 4, score(v, qf) * 0x1p-64f);
    }
    __syncwarp();
}
constexpr float CS = 0.07216878364870322f * 1.4426950408889634f;
__device__ __forceinline__ void head_weight(const u64* a, u64 pm, u64 pl, int layer, int lane) {
    const uint32_t sb = smem_base(), tag = lds32(sb + SM_EPOCH) * 4 + 2 + 2 * layer;
#pragma unroll 1
    for (int it = 0; it < SPIN; it++) {
        if (__all_sync(~0u, ll_tag(pm) == tag && ll_tag(pl) == tag)) break;
        ld_rlx2(a, pm, pl);
    }
    const float f = ex2((ll_val(pm) - warp_max(ll_val(pm))) * CS);
    const float w = f * rcp(warp_sum(f * ll_val(pl)));
    if (lane < 8) stsf(sb + SM_FAC + lane * 4, w);
}
constexpr uint32_t ONES = 0x3f803f80u;

__global__ void __launch_bounds__(NTHR, 1) fused_kernel(const __grid_constant__ Params P) {
    const uint32_t sb = smem_base();
    const int bx = blockIdx.x;
    if (__all_sync(~0u, threadIdx.x >= NTHR - 32) && elect()) {
        asm volatile("mbarrier.init.shared::cta.b64 [%0], 1;" :: "r"(sb + SM_CBAR + CB_WQ * 8));
        asm volatile("mbarrier.init.shared::cta.b64 [%0], 1;" :: "r"(sb + SM_CBAR + 80));
        asm volatile("fence.mbarrier_init.release.cluster;" ::: "memory");
        mbar_expect(sb + SM_CBAR + CB_WQ * 8, 5 * HALF);
        mbar_expect(sb + SM_CBAR + 80, HALF);
        tma3(sb, &P.tm[TM_KH], 0, (bx >> 2) * SK + (SK - WIN) + (bx & 3) * 64, sb + SM_CBAR + 80, POL_FIRST);
#pragma unroll 1
        for (int i = 0; i < 5; i++) tma3(sb + SM_WQR + (i == 4 ? 0 : i + 1) * HALF, &P.tm[TM_WQ], (bx >> 2) * 3, (bx & 3) * 160 + i * 32, sb + SM_CBAR + CB_WQ * 8, POL_FIRST);
    }
    __syncwarp();
    int id = bx * NTHR + threadIdx.x, tid, lane, g, t, key, warp, cta, mlp, rowc, roww, j40;
    uint32_t maskA, maskB, barw, subw, prow;
    auto fresh = [&]() {
        const int cw = __shfl_sync(~0u, id >> 5, 0);
        id = pin(id); tid = id & 255; lane = id & 31; g = lane >> 2; t = lane & 3; key = (g >> 1) + 4 * (g & 1);
        const uint32_t m = (g & 1) ? 0xffff0000u : 0x0000ffffu;
        maskA = (g & 2) ? 0u : m; maskB = (g & 2) ? m : 0u;
        warp = cw & 7; cta = cw >> 3;
        mlp = (cta & 3) == 3 ? 96 : (cta >> 2) * 3 + (cta & 3);
        rowc = (cta >> 2) * SK + (SK - WIN) + (cta & 3) * 64; roww = rowc + warp * 8;
        j40 = (cta & 3) * 40;
        barw = sb + SM_BAR + warp * 96; subw = sb + warp * SUB; prow = sb + SM_PART + warp * 768;
    };
    fresh();
    auto fresh_lane = [&]() { id = pin(id); tid = id & 255; lane = id & 31; g = lane >> 2; t = lane & 3; };
    auto pinf = [&](float v) { return __uint_as_float(pin(__float_as_uint(v) | (id >> 16))); };

    TSTAMP(0);
    if (tid == 64) { uint32_t now; asm volatile("mov.u32 %0, %globaltimer_lo;" : "=r"(now)); sts32(sb + SM_T0, now); }

    const CUtensorMap* tmk = reinterpret_cast<const CUtensorMap*>(__shfl_sync(~0u, (u64)&P.tm[0] + (lane >> 5), 0));
    auto c4 = [&]() { return 32 * min(warp, 4) + 16 * (t >> 1) + 2 * g + (t & 1); };
    auto xcol = [&](int i, int tt) { return (i < 2 ? 64 * i + 8 * warp : 128 + 8 * (warp >> 1)) + 2 * tt; };
    uint2 xp;
    uint32_t px[3], small;
    auto issue_first = [&](int j) {
        mbar_expect(sb + SM_CBAR + 80 + j * 8, HALF);
        tma3(sb + j * HALF, tmk + TM_KH, 0, rowc + (j >> 1) * 256 + (j & 1) * 32, sb + SM_CBAR + 80 + j * 8, POL_FIRST);
    };
    if (elect()) {
        if (warp != 2) asm volatile("mbarrier.init.shared::cta.b64 [%0], 1;" :: "r"(sb + SM_CBAR + 64 + warp * 8));
#pragma unroll
        for (int i = 0; i < 9; i++) asm volatile("mbarrier.init.shared::cta.b64 [%0], 1;" :: "r"(barw + i * 8));
        asm volatile("mbarrier.init.shared::cta.b64 [%0], 1;" :: "r"(sb + SM_CBAR + warp * 8));
        asm volatile("mbarrier.init.shared::cta.b64 [%0], 1;" :: "r"(sb + SM_CBAR + 128 + warp * 8));
        if (warp < 3) asm volatile("mbarrier.init.shared::cta.b64 [%0], %1;" :: "r"(sb + SM_CBAR + 192 + warp * 8), "r"(warp == 2 ? 8 : 1));
        sts64(barw + 80, 0, 0);
        asm volatile("fence.mbarrier_init.release.cluster;" ::: "memory");
        asm volatile("prefetch.tensormap [%0];" :: "l"(tmk + warp) : "memory");
    }
    __syncwarp();
    asm volatile("ld.global.nc.v2.u32 {%0,%1}, [%2];" : "=r"(xp.x), "=r"(xp.y) : "l"(P.x + 4 * c4()) : "memory");
#pragma unroll
    for (int i = 0; i < 3; i++) asm volatile("ld.global.nc.u32 %0, [%1];" : "=r"(px[i]) : "l"(P.x + 4 * j40 + xcol(i, t)) : "memory");
    asm volatile("ld.relaxed.gpu.global.u32 %0, [%1];" : "=r"(small) : "l"(lane < 16 ? (const void*)(P.b1 + min(mlp, 95) * 16 + (lane & 14)) : (const void*)&P.g->epoch) : "memory");
    if (tid < NCB + 8) sts64(sb + SM_CNT + tid * 8, 0, 0);
    unsigned char* accg = reinterpret_cast<unsigned char*>(__shfl_sync(~0u, (u64)P.g->acc + (lane >> 5), 0));
    auto release = [&](const uint4& tw) {
        uint32_t old;
        __syncwarp();
        asm volatile("atom.relaxed.cta.shared.add.u32 %0, [%1], 1;" : "=r"(old) : "r"(sb + SM_CNT + (tw.x & 0xf8)) : "memory");
        return old;
    };
    auto refill = [&](const uint4& tw, uint32_t old) {
        if (__any_sync(~0u, (old & 127) == 127 && (tw.y & 2))) {
            wait_until(lds32(sb + SM_T0) + tw.z);
            if (elect()) issue_half(tw.y, sb, rowc, cta, tmk);
            __syncwarp();
        }
    };
    __syncthreads();
    auto issue_paced = [&](int j0, int j1) {
        if (warp >= j0 && warp < j1) {
            wait_until(lds32(sb + SM_T0) + PACES + warp * PACE / 2);
            if (elect()) issue_first(warp);
            __syncwarp();
        }
    };

    uint32_t offV0, offV2;
    auto calc_offsets = [&]() {
        offV0 = subw + (6 * t) * 128 + ((g ^ ((6 * t) & 7)) << 4);
        offV2 = subw + (6 * t + 2) * 128 + ((g ^ ((6 * t + 2) & 7)) << 4);
    };
    calc_offsets();

    auto load_v = [&](uint4 (&v)[6], uint32_t so) {
        v[0] = lds128(offV0 + so); v[1] = lds128((offV0 ^ 16) + so + 128); v[2] = lds128(offV2 + so);
        v[3] = lds128((offV2 ^ 16) + so + 128); v[4] = lds128((offV0 ^ 64) + so + 512); v[5] = lds128((offV0 ^ 80) + so + 640);
    };
    auto issue_v = [&](auto I, int dw, uint32_t done = ~0u) {
        constexpr Step c = SCH.st[I.value];
        const uint32_t bar = barw + dw * 96 + c.slot * 8;
        mbar_expect(bar, done & SUB);
        tma_v(subw + dw * SUB + c.slot * TILE, tmk, roww * 3 + dw * 24 + c.unit * 768, bar);
    };
    auto reads_done = [&]() { __syncwarp(); return lds32(sb + SM_M1); };
    auto refill2 = [&](auto I, uint32_t done = ~0u) { __syncwarp(); if (elect()) issue_v(I, 0, done); };
    uint4 wq0[6], wqh[3], wq1[6];
    auto load_wq1 = [&](int i) { wq1[i] = lds128((i == 2 ? offV2 : i == 3 ? (offV2 ^ 16) + 128 : (offV0 ^ (i * 16)) + i * 128) + SM_WQ + TILE); };
    auto load_wq = [&]() {
        load_v(wq0, SM_WQ);
        const uint32_t so = SM_WQR - ((warp + 1) >> 1) * SUB;
        wqh[0] = lds128(((warp & 1) ? (offV2 ^ 16) + 128 : offV0) + so);
        wqh[1] = lds128(((warp & 1) ? (offV0 ^ 64) + 512 : (offV0 ^ 16) + 128) + so);
        wqh[2] = lds128(((warp & 1) ? (offV0 ^ 80) + 640 : offV2) + so);
    };
    uint4 kr[8][6];
    const unsigned char* rap;
    u64 rw[2];
    auto look_rw = [&]() { rw[0] = ld_rlx(rap); rw[1] = ld_rlx(rap + 40 * ACC_PITCH); };
    auto q_proj = [&](auto L, uint32_t (&p)[3], uint32_t pst) {
        if (L.value == 0 && g >= 4) p[0] = p[1] = p[2] = ONES;
        float a[3][4], b[3][4];
        const uint32_t dH = __byte_perm(p[2], 0, (warp & 1) ? 0x3232 : 0x1010);
        const uint32_t dA = __byte_perm(p[0], 0, 0x1010), dB = __byte_perm(p[0], 0, 0x3232), dC = __byte_perm(p[1], 0, 0x1010), dD = __byte_perm(p[1], 0, 0x3232);
#pragma unroll
        for (int i = 0; i < 3; i++) load_wq1(i);
#pragma unroll
        for (int j = 0; j < 3; j++) { a[j][0] = a[j][1] = a[j][2] = a[j][3] = 0.f; mma(a[j], wq0[j], dA & maskA, dA & maskB); }
#pragma unroll
        for (int j = 0; j < 3; j++) { b[j][0] = b[j][1] = b[j][2] = b[j][3] = 0.f; mma(b[j], wq0[j + 3], dB & maskA, dB & maskB); }
#pragma unroll
        for (int j = 0; j < 3; j++) mma(a[j], wqh[j], dH & maskA, dH & maskB);
#pragma unroll
        for (int i = 3; i < 6; i++) load_wq1(i);
#pragma unroll
        for (int j = 0; j < 3; j++) mma(b[j], wq1[j], dC & maskA, dC & maskB);
#pragma unroll
        for (int j = 0; j < 3; j++) mma(a[j], wq1[j + 3], dD & maskA, dD & maskB);
#pragma unroll
        for (int j = 0; j < 3; j++) {
            if (L.value) {
#pragma unroll
                for (int k = 0; k < 2; k++) { a[j][k] += b[j][k]; add_if(t & 2, a[j][k], a[j][k + 2], b[j][k + 2]); }
                sts64f(pst + j * 256, a[j][0], a[j][1]);
            } else sts128f(pst + j * 256, a[j][0] + b[j][0], a[j][1] + b[j][1], a[j][2] + b[j][2], a[j][3] + b[j][3]);
        }
        CSTAMP(23, __float_as_uint(a[2][1]));
        uint32_t tag;
        if (L.value) tag = lds32(sb + SM_EPOCH) * 4 + 3;
        u64* pub = L.value ? &P.g->ll[cta][tid] : &P.g->l0[cta][tid];
        if (L.value == 0) asm volatile("fence.proxy.async.shared::cta;" ::: "memory");
        TSTAMPL(21);
        __syncthreads();
        if (!L.value) tag = lds32(sb + SM_EPOCH) * 4 + 1;
#pragma unroll 1
        for (int k = 0; k < 2 - L.value; k++) st_rlx_if(tid < 192, pub + k * 192, ll_pack(sum8(sb + (k ? SM_CSP : SM_PART) + tid * 4, 768), tag));
        TSTAMPL(23);
            CSTAMP(24, tag);
    };
    auto ln_stats = [&]() {
        float ss = ln_part(xp, lane);
        ss += shx(ss, 8); ss += shx(ss, 4); ss += shx(ss, 2); ss += shx(ss, 1);
        stsf(sb + SM_STAT + min(warp, 5) * 8 + (lane >> 4) * 4, ss);
    };
    auto ln_final = [&](float& mean, float& rstd) {
        float2 v[5];
#pragma unroll
        for (int w = 0; w < 5; w++) v[w] = lds64f(sb + SM_STAT + w * 8);
        mean = sum5(v[0].x, v[1].x, v[2].x, v[3].x, v[4].x) * (1.f / D_MODEL);
        const float msq = sum5(v[0].y, v[1].y, v[2].y, v[3].y, v[4].y) * (1.f / D_MODEL);
        rstd = ln_rstd(mean, msq);
        stsf(sb + SM_FXS, msq);
    };
    auto q_addr = [&](int d) { return sb + SM_VEC + (((d >> 1) & 1) * 4 + ((d >> 3) & 3)) * 48 + (d >> 5) * 8 + ((d >> 2) & 1) * 4 + (d & 1) * 2; };
    {
#pragma unroll
        for (int u = 0; u < 8; u++)
#pragma unroll
            for (int i = 0; i < 6; i++) kr[u][i] = lds128(sb + SM_CS + (u * 6 + i) * 16);
        issue_paced(1, NIM);
        ln_stats();
        if (tid == 16) { sts32(sb + SM_EPOCH, small); sts32(sb + SM_M1, ~0u); }
        else if (tid < 16) sts32(sb + SM_B1 + tid * 4, (tid & 1) ? small & 0xffff0000u : small << 16);
        mbar_wait(sb + SM_CBAR + CB_WQ * 8, 0);
        load_wq();
        q_proj(IC<0>{}, px, sb + (t < 2 ? SM_PART : SM_CSP) + warp * 768 + (8 * g + 4 * (t & 1)) * 4);
    }
    {
        uint32_t offQ, offL;
        auto calc_ql = [&]() {
            offQ = pin(sb + SM_VEC + (lane & 7) * 48);
            offL = pin(subw + lane * 16);
        };

        auto issue_w = [&](auto L, int which) {
            const uint32_t bar = sb + SM_CBAR + (CB_W1 + which) * 8;
            if (mlp == 96) asm volatile("mbarrier.arrive.shared::cta.b64 _, [%0];" :: "r"(bar) : "memory");
            else {
                mbar_expect(bar, 20480);
                if (which) {
                    tma3(sb + (L.value ? 3 * TILE : SM_W2), tmk + TM_W2, 0, mlp * 16, bar, POL_FIRST);
                    if (!L.value) tma3_pf(tmk + TM_W2, 0, mlp * 16, POL_NORMAL);
                    if (!L.value) asm volatile("cp.async.bulk.prefetch.L2.global.L2::cache_hint [%0], 20480, %1;" :: "l"(P.w1 + mlp * 10240), "l"((u64)POL_NORMAL << 32) : "memory");
                }
                else asm volatile("cp.async.bulk.tensor.3d.shared::cluster.global.mbarrier::complete_tx::bytes.L2::cache_hint [%0], [%1, {%2, %3, %3}], [%4], %5;"
                                  :: "r"(sb + (L.value ? 2 * TILE : SM_W1)), "l"(tmk + TM_W1), "r"(mlp * 16), "r"(0), "r"(bar), "l"((u64)POL_FIRST << 32) : "memory");
            }
        };
        float acc[3][4];
        auto load_q = [&](uint4 (&qf)[3]) {
#pragma unroll
            for (int i = 0; i < 3; i++) qf[i] = lds128(offQ + i * 16);
        };
        auto softmax = [&](float S0, float S1, float S2, float S3) {
            int mi = __float_as_int(fmaxf(fmaxf(S0, S1), fmaxf(S2, S3)));
            mi = __reduce_max_sync(~0u, mi ^ ((mi >> 31) & 0x7fffffff));
            const float mrun = __int_as_float(mi ^ ((mi >> 31) & 0x7fffffff));
            const float p0 = ex2((S0 - mrun) * CS), p1 = ex2((S1 - mrun) * CS), p2 = ex2((S2 - mrun) * CS), p3 = ex2((S3 - mrun) * CS);
            const uint32_t pa = pack_bf(p0, p1), pb = pack_bf(p2, p3), pw = prow + 256 + (key >> 1) * 80 + t * 4 + (key & 1) * 2;
            sts16(pw, pa); sts16(pw + 16, pa >> 16); sts16(pw + 32, pb); sts16(pw + 48, pb >> 16);
            __syncwarp();
#pragma unroll
            for (int j = 0; j < 3; j++) acc[j][0] = acc[j][1] = acc[j][2] = acc[j][3] = 0.f;
            return make_float2(mrun, (p0 + p1) + (p2 + p3));
        };
        auto pv = [&](const uint4 (&v)[6], uint32_t pp) {
            const uint32_t dA = __byte_perm(pp, 0, 0x1010), dB = __byte_perm(pp, 0, 0x3232);
            mma(acc[0], v[0], dA & maskA, dA & maskB); mma(acc[1], v[1], dA & maskA, dA & maskB); mma(acc[2], v[2], dA & maskA, dA & maskB);
            mma(acc[0], v[3], dB & maskA, dB & maskB); mma(acc[1], v[4], dB & maskA, dB & maskB); mma(acc[2], v[5], dB & maskA, dB & maskB);
        };
        auto sa = [&]() { return prow + 256 + t * 32 + g * 4; };
        auto pass1 = [&]() {
            issue_paced(NIM, NI1);
            fresh();
            calc_ql();
            __syncthreads();
            sts64(prow + lane * 8, xp.x, xp.y);
            int e = 0;
            const uint4* tab = P.tile + (warp >> 2);
            uint4 tw = tab[0];
            uint32_t ka[3];
#pragma unroll
            for (int j = 0; j < 3; j++) ka[j] = pin(subw + key * 384 + j * 128 + ((t ^ ((3 * key + j) & 7)) << 4));
            auto load_k = [&](uint4 (&v)[6], uint32_t so) {
#pragma unroll
                for (int i = 0; i < 6; i++) v[i] = lds128(((i & 1) ? ka[i >> 1] ^ 64 : ka[i >> 1]) + so);
            };
            const uint32_t s0 = pin(prow + 256 + g * 4), sca = pin(sb + SM_SC + warp * 128 + g * 16);
#pragma unroll 1
            do {
                const uint4 tn = tab[2 * e + 2];
                uint4 v[6], qf[3];
                if (tw.x & (G_A | G_B | G_C)) {
                    if ((tw.x & G_A) && warp == 7 && elect()) {
                        mbar_expect(sb + SM_CBAR + CB_SNAP * 8, HALF);
                        asm volatile("cp.async.bulk.shared::cluster.global.mbarrier::complete_tx::bytes [%0], [%1], 12288, [%2];"
                                     :: "r"(sb + SM_SNAP), "l"(&P.g->l0[cta & ~3][0]), "r"(sb + SM_CBAR + CB_SNAP * 8) : "memory");
                    }
                    if (tw.x & G_B) {
                        if (warp < 6) {
                            mbar_wait(sb + SM_CBAR + CB_SNAP * 8, 0);
                            float qc[2] = {0.f, 0.f}, mean, rstd;
#pragma unroll 1
                            for (int k = 0; k < 2; k++) {
                                u64 qw[4];
#pragma unroll
                                for (int i = 0; i < 4; i++) { const uint2 x = lds64(sb + SM_SNAP + i * 3072 + k * 1536 + tid * 8); qw[i] = x.x | (u64)x.y << 32; }
                                qc[0] = qc[1];
                                qc[1] = ll_gather<384>(&P.g->l0[cta & ~3][k * 192 + tid], lds32(sb + SM_EPOCH) * 4 + 1, qw);
                            }
                            ln_final(mean, rstd);
                            stsf(sb + SM_CS + tid * 4, qc[1]);
                            const float q = (qc[0] - mean * qc[1]) * rstd;
                            sts16(q_addr(tid), pack_bf(q, q));
                        }
                        __syncthreads();
                        if (warp == 7 && elect()) issue_half(UC<load_word(12)>::value, sb, rowc, cta, tmk);
                        TSTAMP(2);
                    }
                    if (tw.x & G_C) {
                        load_k(v, (e - LATEAT) * TILE);
                        load_q(qf);
                        stsf(s0 + (e - LATEAT) * 32, score(v, qf));
                    }
                }
                load_q(qf);
                mbar_wait(sb + SM_CBAR + (tw.x & 0xf8), tw.x >> 31);
                TRACE(e);
                load_k(v, tw.x & 0x3f000);
                const uint32_t old = release(tw);
                const float s = score(v, qf);
                uint32_t m;
                {
                    uint32_t a[6];
#pragma unroll
                    for (int i = 0; i < 6; i++) a[i] = bf2_amax(bf2_amax(v[i].x, v[i].y), bf2_amax(v[i].z, v[i].w));
                    m = bf2_amax(bf2_amax(bf2_amax(a[0], a[1]), bf2_amax(a[2], a[3])), bf2_amax(a[4], a[5]));
                }
                m = bf2_amax(m, m >> 16) & 0x7f80;
                m = max(m, __shfl_xor_sync(~0u, m, 1));
                stsf(s0 + e * 32, s);
                m = max(m, __shfl_xor_sync(~0u, m, 2));
                refill(tw, old);
                const uint32_t b = min(max(m, 15u << 7) - (15u << 7), 126u << 7);
                const uint32_t dn = ((127u << 7) - b) * 0x10001u, up = ((127u << 7 | 0x8000u) + b) * 0x10001u;
                uint32_t c[18], any = m > (141u << 7);
#pragma unroll
                for (int i = 0; i < 6; i++) {
                    const uint32_t y0 = bf2_mul(v[i].x, dn), y1 = bf2_mul(v[i].y, dn), y2 = bf2_mul(v[i].z, dn), y3 = bf2_mul(v[i].w, dn);
                    v[i] = make_uint4(bf2_fma(y0, up, v[i].x), bf2_fma(y1, up, v[i].y), bf2_fma(y2, up, v[i].z), bf2_fma(y3, up, v[i].w));
                    any |= v[i].x | v[i].y;
                    any |= v[i].z | v[i].w;
                    const uint32_t hb = __byte_perm(y2, y3, 0x7531);
                    c[3 * i] = __byte_perm(y0, y1, 0x6420); c[3 * i + 1] = __byte_perm(y2, y3, 0x6420);
                    c[3 * i + 2] = __byte_perm(y0, y1, 0x7531) | __funnelshift_r(hb, hb, 4);
                }
                asm volatile("st.shared.u8 [%0], %1;" :: "r"(sca + (e & 3) * 4 + (e >> 2)), "r"((b >> 7) + 63) : "memory");
                const bool rare = __any_sync(~0u, any);
                k_keep(kr, c, e, offL);
                if (rare) k_rare(v[0], v[1], v[2], v[3], v[4], v[5], m > (141u << 7), e, warp, lane);
                tw = tn;
            } while (++e < 16);
            asm volatile("fence.proxy.async.shared::cta;" ::: "memory");
            __syncwarp();
            TSTAMP(10);
            fresh(); calc_offsets();
            offV0 = pin(offV0); offV2 = pin(offV2);
            {
                const uint2 st = lds64(barw + 80);
                const uint32_t xa = sb + SM_EXC + warp * 128 + (lane & 15) * 8 + 4;
                uint32_t pos = lds32(xa), lt;
                asm volatile("mov.u32 %0, %lanemask_lt;" : "=r"(lt));
                if (lane >= st.x) pos = 0x80000000u;
                const bool dup = (__match_any_sync(~0u, pos >> 16) & lt) && lane < st.x;
                if (lane < 16) sts32(xa, dup ? pos | 0x40000000u : pos);
                if (__any_sync(~0u, dup)) sts32(barw + 84, st.y | 0x10000u);
                const float2 ml = softmax(ldsf(sa()), ldsf(sa() + 128), ldsf(sa() + 256), ldsf(sa() + 384));
                sts64f(sb + SM_ML + warp * 8, ml.x, warp_sum(ml.y));
            }
            u64 pm = 0, pl = 0;
#pragma unroll 1
            do {
                const uint4 tn = tab[2 * e + 2];
                if (tw.x & (G_A | G_B | G_C)) {
                    if (tw.x & G_A) {
                        if (lane < 24) st_rlx(&P.g->ll[cta][warp * 24 + lane], 0ull);
                        else if (lane < 28) st_rlx(&P.g->ll[cta][168 + warp * 4 + lane], ll_pack(ldsf(sb + SM_ML + warp * 8 + (lane & 1) * 4), lds32(sb + SM_EPOCH) * 4 + 2));
                    }
                    if (warp == 0 && cta < 80 && elect()) {
                        if (tw.x & G_A) {
#pragma unroll 1
                            for (int k = 0; k < 12; k++) {
                                const int r = k < 4 ? k & 2 : (k >> 1 & 2) + 1;
                                asm volatile("cp.async.bulk.global.shared::cta.bulk_group [%0], [%1], 64;"
                                             :: "l"(P.g->acc + r * ACC_BYTES + (k < 4 ? cta * ACC1_PITCH + (k & 1) * 64 : (cta * ACC_PITCH & ~127) + (k & 3) * 64)), "r"(sb + SM_ZERO) : "memory");
                            }
                            asm volatile("cp.async.bulk.commit_group;" ::: "memory");
                        }
                        if (tw.x & G_B) asm volatile("cp.async.bulk.wait_group 0;\nred.relaxed.gpu.global.add.u32 [%0], 1;" :: "l"(&P.g->zeroed) : "memory");
                    }
                    if (warp == 2) {
                        if (tw.x & G_B) ld_rlx2(&P.g->ll[cta ^ (lane >> 3)][192 + (lane & 7) * 4], pm, pl);
                        if (tw.x & G_C) head_weight(&P.g->ll[cta ^ (lane >> 3)][192 + (lane & 7) * 4], pm, pl, 0, lane);
                    }
                    __syncwarp();
                }
                const uint32_t pp = lds32(prow + 256 + t * 80 + ((tw.x >> 20) & 255));
                mbar_wait(sb + SM_CBAR + (tw.x & 0xf8), tw.x >> 31);
                TRACE(e);
                uint4 v[6];
                load_v(v, tw.x & 0x3f000);
                refill(tw, release(tw));
                pv(v, pp);
                tw = tn;
            } while (++e < 32);
        };
        uint32_t osa, ora, owa, orow, otag;
        u64* olb;
        float xc;
        auto o_setup = [&](auto L) {
            fresh();
            const int lz = lane, d = warp * 24 + min(lz, 23);
            osa = pin(prow + ((lz >> 2) * 8 + (lz & 1) * 4 + (lz & 2)) * 4);
            ora = pin(sb + SM_PART + d * 4);
            olb = pin(&P.g->ll[cta & ~3][d]);
            orow = pin((lz & 1) + 2 * (lz & 2) + 2 * (lz >> 4));
            owa = pin(sb + SM_RING + warp * 1536 + orow * 64 + ((((lz >> 2) & 3) ^ (orow >> 1)) << 4));
            otag = lds32(sb + SM_EPOCH) * 4 + 2 + 2 * L.value;
            uint32_t x; asm volatile("ld.shared.u16 %0, [%1];" : "=r"(x) : "r"(prow + ((cta & 1) * 16 + (lz >> 3) * 4 + (cta & 2) + ((lz >> 2) & 1)) * 8 + (lz & 3) * 2) : "memory");
            xc = bf_lo(x) * (1.f / 32);
        };
        auto wo_at = [&](auto A) {
            constexpr uint32_t x = WOP ^ A.value * 0x11111;
            if constexpr (A.value > 0 && ((x - 0x11111) & ~x & 0x88888) != 0) {
                if ((WOP >> (4 * warp) & 15) == A.value) {
                    mbar_wait(sb + SM_CBAR + CB_REL * 8, 0);
                    if (elect()) {
                        const uint32_t bar = sb + SM_CBAR + (CB_WO + warp) * 8;
                        mbar_expect(bar, HALF);
                        tma3(sb + SM_RING + (warp + (warp < 2 ? 3 : -2)) * HALF, tmk + TM_WO, (cta & 3) + 4 * warp, (cta >> 2) * DH, bar, POL_FIRST);
                    }
                    __syncwarp();
                }
            }
        };
        static_assert(ring_hs(64) == 3, "wo");
        auto pass2 = [&]() {
            constexpr IC<1> L{};
            refill2(IC<4>{});
            uint4 tb[8][3];
            auto load_tb = [&](auto I) {
#pragma unroll
                for (int i = 0; i < 3; i++) tb[I.value][i] = lds128(offL + (I.value >> 1) * TILE + ((I.value & 1) * 3 + i) * 512);
            };
            uint32_t m1, m1n, done;
            const u64* qb = &P.g->ll[cta & ~3][min(tid, 191)];
            {
                uint32_t x[2];
                fx2_wait<2>([&](int i) { return rap + i * 40 * ACC_PITCH; }, look_rw, rw, sb + SM_MSQ, ldsf(sb + SM_MSQ + 4), x);
                xp = make_uint2(x[0], x[1]);
                CSTAMP(25, xp.y);
            }
            ln_stats();
            u64 qw[4];
            offL = subw + lane * 16;
            static_for<0, NPRE>(load_tb);
            m1n = m1 = reads_done();
            ll_look<256>(qb, qw);
            const float cs = ldsf(sb + SM_CS + min(tid, 191) * 4);
            const uint32_t qtag = lds32(sb + SM_EPOCH) * 4 + 3, qa = pin(q_addr(min(tid, 191)));
            fresh_lane();
            offQ = sb + SM_VEC + (lane & 7) * 48; offL = subw + lane * 16;
            __syncthreads();
            auto vwait = [&](auto I) { mbar_wait(barw + IC<SCH.st[I.value].slot>::value * 8, IC<SCH.st[I.value].par>::value); };
            bool ok;
            {
                float mean, rstd;
                ln_final(mean, rstd);
                const float sq = shx(rstd * 0x1p64f, 0), q0 = shx(-mean * cs * sq, 0);
                CSTAMP(26, __float_as_uint(q0));
                refill2(IC<5>{}, m1);
                sts64(prow + lane * 8, xp.x, xp.y);
                sts128f(prow + 256 + lane * 16, 0.f, 0.f, 0.f, 0.f);
                const float q = ll_gather<256>(qb, qtag, qw) * sq + q0;
                sts16(qa, pack_bf(q, q));
                TSTAMPL(24);
                CSTAMP(27, __float_as_uint(q));
            }
            __syncthreads();
            uint4 qf[3];
            load_q(qf);
            CSTAMP(28, qf[0].x);
            float S[4], d[2][4];
            auto vload = [&](auto I) {
                constexpr int p = I.value;
                constexpr Step c = SCH.st[p];
                load_v(kr[p & 7], c.slot * TILE);
                if constexpr (c.next >= 0 && p >= NPARK) {
                    static_assert(c.next - 9 < c.mma0, "the slot's last tile has been multiplied");
                    refill2(IC<c.next>{});
                }
                if constexpr (p == 11) { __syncwarp(); if (elect()) asm volatile("mbarrier.arrive.shared::cta.b64 _, [%0];" :: "r"(sb + SM_CBAR + CB_REL * 8) : "memory"); }
            };
            static_for<0, 96>([&](auto F) {
                constexpr int f = F.value, i = f % 6, u = kunit(f / 6), w = 3 * f % 12;
                uint4 (&src)[3] = *reinterpret_cast<uint4 (*)[3]>(f < 32 ? &tb[f / 4 & 7][0] : &kr[(f / 8 + 4) & 7][(f / 4 & 1) * 3]);
                const uint4 a = k_unpack(word<w % 4>(src[w / 4]), word<(w + 1) % 4>(src[(w + 1) / 4]), word<(w + 2) % 4>(src[(w + 2) / 4]), m1);
                if constexpr (f % 8 == (f < 32 ? RF0 : RF1) + M1D) m1 = m1n;
                if constexpr (f % 4 == 3 && f / 4 + NPRE < 8) {
                    load_tb(IC<f / 4 + NPRE>{});
                    if constexpr (f % 8 == 7) done = reads_done();
                }
                if constexpr (f >= 8 && f < 32 && f % 8 == RF0) { refill2(IC<5 + f / 8>{}, done); m1n = lds32(sb + SM_M1); }
                if constexpr (f >= 40 && f % 8 == RF1) {
                    if constexpr (PARKS >> (f / 8 - 5) & 1) { refill2(IC<SCH.st[popc(PARKS & ((1 << (f / 8 - 5)) - 1))].next>{}, done); m1n = lds32(sb + SM_M1); }
                }
                if constexpr (i < 2) d[i][0] = d[i][1] = d[i][2] = d[i][3] = 0.f;
                mma(d[i & 1], a, (i & 1) ? qf[i / 2].z : qf[i / 2].x, (i & 1) ? qf[i / 2].w : qf[i / 2].y);
                if constexpr (i == 5) {
                    if constexpr (u == 11 || ((u & 3) == 0 && u != 8)) S[u >> 2] = (d[0][0] + d[0][3]) + (d[1][0] + d[1][3]);
                    else add_if(t == (u & 3), S[u >> 2], d[0][0] + d[0][3], d[1][0] + d[1][3]);
                    if constexpr (f < 64) S[u >> 2] = shx(S[u >> 2], 0);
                }
                if constexpr (f == 31) { fresh(); calc_offsets(); ok = mbar_test(barw + IC<SCH.st[0].slot>::value * 8, 0); }
                if constexpr (f == 48) {
                    const uint2 x = lds64(sb + SM_EXC + warp * 128 + (lane & 15) * 8);
                    const float c = k_side(sb, x);
                    if (x.y < 0x40000000u) stsf(prow + 256 + (x.y >> 16), c);
                }
                if constexpr (f >= 32 && f % 8 == 7) {
                    if constexpr (PARKS >> (f / 8 - 4) & 1) {
                        constexpr int p = popc(PARKS & ((1 << (f / 8 - 4)) - 1));
                        if (!ok) vwait(IC<p>{});
                        vload(IC<p>{});
                        done = reads_done();
                        ok = mbar_test(barw + IC<SCH.st[p + 1].slot>::value * 8, IC<SCH.st[p + 1].par>::value);
                    }
                }
            });
            if constexpr (PARKS & 0x80) refill2(IC<SCH.st[NPARK - 1].next>{}, done);
            uint32_t bad = lds32(barw + 84);
            const uint32_t sc = lds32(sb + SM_SC + tid * 4);
            __syncwarp();
            if (bad) k_fix(P.k + (size_t)roww * DH, bad, warp, lane);
            TSTAMP(30);
            CSTAMP(29, __float_as_uint(S[2]));
            const float2 ml = softmax(S[0] * __uint_as_float((sc & 255) << 23) + ldsf(sa()), S[1] * __uint_as_float((sc & 0xff00) << 15) + ldsf(sa() + 128),
                                      S[2] * __uint_as_float((sc & 0xff0000) << 7) + ldsf(sa() + 256), S[3] * __uint_as_float((sc >> 24) << 23) + ldsf(sa() + 384));
            uint4 pq[4];
#pragma unroll
            for (int j = 0; j < 4; j++) pq[j] = lds128(prow + 256 + t * 80 + j * 16);
            TSTAMP(1);
            CSTAMP(30, pq[3].w);
            if (!ok) vwait(IC<NPARK>{});
            float ac2[3][4];
#pragma unroll
            for (int j = 0; j < 3; j++) ac2[j][0] = ac2[j][1] = ac2[j][2] = ac2[j][3] = 0.f;
            const uint32_t sl = (g & 1) ? 0x1044 : 0x4410, sh = (g & 1) ? 0x3244 : 0x4432;
            const uint32_t sA0 = (g & 2) ? 0x4444 : sl, sA1 = (g & 2) ? sl : 0x4444, sB0 = (g & 2) ? 0x4444 : sh, sB1 = (g & 2) ? sh : 0x4444;
            u64 pm = 0, pl = 0;
            static_for<NPARK, 16>([&](auto I) {
                constexpr int p = I.value;
                static_assert(p - SCH.st[p].mma0 < 8, "buffer in use");
                vload(I);
                if constexpr (p < 15) ok = mbar_test(barw + IC<SCH.st[p + 1].slot>::value * 8, IC<SCH.st[p + 1].par>::value);
                static_for<SCH.st[p].mma0, SCH.st[p].mma0 + SCH.st[p].nmma>([&](auto J) {
                    constexpr int u = SCH.st[J.value].unit;
                    const uint32_t pp = word<u & 3>(pq[u >> 2]), a0 = __byte_perm(pp, 0, sA0), a1 = __byte_perm(pp, 0, sA1), b0 = __byte_perm(pp, 0, sB0), b1 = __byte_perm(pp, 0, sB1);
#pragma unroll
                    for (int j = 0; j < 3; j++) mma(acc[j], kr[J.value & 7][j], a0, a1);
#pragma unroll
                    for (int j = 0; j < 3; j++) mma(ac2[j], kr[J.value & 7][j + 3], b0, b1);
                });
                if constexpr (p == NPARK) {
                    const float l = warp_sum(ml.y);
                    st_rlx_if(lane < 4, &P.g->ll[cta][192 + warp * 4 + lane], ll_pack((lane & 1) ? l : ml.x, lds32(sb + SM_EPOCH) * 4 + 4));
                }
                if constexpr (p == HWAT) { if (warp == 6) ld_rlx2(&P.g->ll[cta ^ (lane >> 3)][192 + (lane & 7) * 4], pm, pl); }
                if constexpr (p == 13) o_setup(L);
                if constexpr (p == HWAT + 2) { if (warp == 6) head_weight(&P.g->ll[cta ^ (lane >> 3)][192 + (lane & 7) * 4], pm, pl, 1, lane); }
                wo_at(IC<p - 10>{});
                if constexpr (p < 15) { if (!ok) mbar_wait(barw + IC<SCH.st[p + 1].slot>::value * 8, IC<SCH.st[p + 1].par>::value); TRACE(33 + p); }
            });
#pragma unroll
            for (int j = 0; j < 3; j++)
#pragma unroll
                for (int k = 0; k < 2; k++) { acc[j][k] += ac2[j][k]; add_if(t & 2, acc[j][k], acc[j][k + 2], ac2[j][k + 2]); }
        };

        const unsigned char* ap;
        uint32_t hpa, hsa, hst, w2a, la;
        uint2 b2v;
        float b1v, cs1;
        auto mlp_global = [&](auto L) {
            const int cz = c4();
            ap = accg + 2 * L.value * ACC_BYTES + (cz >> 1) * ACC1_PITCH + (cz & 1) * 16;
            if (L.value) ap = pin(ap);
            rap = pin(accg + (2 * L.value + 1) * ACC_BYTES + (cz >> 2) * ACC_PITCH + (cz & 3) * 8);
            asm volatile("ld.global.nc.v2.u32 {%0,%1}, [%2];" : "=r"(b2v.x), "=r"(b2v.y) : "l"(P.b2 + 4 * cz));
        };
        auto mlp_shared = [&](auto L) {
            const int lz = lane;
            hpa = pin(sb + SM_PART + warp * 256 + ((lz & 2) * 4 + (lz >> 2)) * 16 + (L.value ? 0 : (lz & 1) * 4));
            hsa = pin(sb + SM_PART + (lz & 15) * 16); hst = pin(sb + SM_PART + (lz & 15) * 16 + warp * 256 + 8 + (lz >> 4) * 4);
            w2a = pin(sb + (L.value ? 3 * TILE : SM_W2) + ((lz & 3) * 10 + 2 * warp) * 128 + (((lz >> 2) ^ ((2 * lz + 2 * warp) & 6)) << 4));
            la = sb + (L.value ? 2 * TILE : SM_W1) + warp * 4096 + (lz & 4) * 512 + (lz & 2) * 64 + (lz & 1) * 32 + (lz >> 4) * 64 + ((((lz >> 3) ^ (lz >> 1)) & 1) << 4);
            b1v = ldsf(sb + SM_B1 + (lz & 15) * 4);
            if (L.value) { la = pin(la); cs1 = ldsf(sb + SM_ML + (lz & 15) * 4); }
            else fresh();
        };
        uint32_t pa;
        unsigned char* rop;
        uint32_t wpa;
        float sc1;
        auto sum_setup = [&](auto L) {
            const int lz = lane, word = warp * 128 + (cta & 3) * 32 + lz;
            wpa = pin(sb + SM_RING + warp * 1536 + ((((lz >> 2) * 8 + (lz & 1) * 4) * 4) ^ ((((lz >> 1) ^ (lz >> 4)) & 1) ? 256 + 64 : 0)));
            sc1 = pinf(fx2_scale(ldsf(sb + SM_FXS)) * 0.25f);
            pa = pin(sb + SM_RING + warp * 256 + ((lz * 4) ^ ((warp & 1) * 64)));
            rop = pin(accg + 2 * L.value * ACC_BYTES + (word >> 3) * ACC1_PITCH + (word & 7) * 4);
        };
        auto out_proj = [&](auto L) {
            TSTAMP2(3);
            CSTAMP(0, __float_as_uint(acc[2][1]));
            __syncwarp();
#pragma unroll
            for (int j = 0; j < 3; j++) {
                if (L.value == 0 && (t & 2)) { acc[j][0] = acc[j][2]; acc[j][1] = acc[j][3]; }
                sts64f(osa + 256 * j, acc[j][0], acc[j][1]);
            }
            __syncthreads();
            {
                float s[8];
#pragma unroll
                for (int w = 0; w < 8; w++) s[w] = ldsf(ora + w * 768);
                const uint4 fa = lds128(sb + SM_FAC), fb = lds128(sb + SM_FAC + 16);
            CSTAMP(1, __float_as_uint(s[0]));
                const float own = ((s[0] * __uint_as_float(fa.x) + s[1] * __uint_as_float(fa.y)) + (s[2] * __uint_as_float(fa.z) + s[3] * __uint_as_float(fa.w))) +
                                  ((s[4] * __uint_as_float(fb.x) + s[5] * __uint_as_float(fb.y)) + (s[6] * __uint_as_float(fb.z) + s[7] * __uint_as_float(fb.w)));
                st_rlx_if(lane < 24, olb + (cta & 3) * 256, ll_pack(own, otag));
            CSTAMP(2, __float_as_uint(own));
            }
            TSTAMPL(29);
            if (L.value == 0) fresh();
            if (L.value) wo_at(IC<6>{});
            if (L.value == 0 && warp == 7) {
#pragma unroll 1
                for (int it = 0; it < SPIN; it++) {
                    uint32_t v; asm volatile("ld.acquire.gpu.global.u32 %0, [%1];" : "=r"(v) : "l"(&P.g->zeroed) : "memory");
                    if (__all_sync(~0u, v == (lds32(sb + SM_EPOCH) + 1) * 80)) break;
                }
            }
            constexpr int NW = L.value ? NWO1 : 3;
            uint4 v[5][3];
            u64 ow[4];
            auto read_wo = [&](auto J) {
#pragma unroll
                for (int p = 0; p < 3; p++) v[J.value][p] = lds128(((J.value & 1) ? owa ^ 144 : owa) + ring_hs(64 + J.value) * HALF + p * 512);
            };
            static_for<0, NW>([&](auto J) {
                if (L.value && J.value == 0) { sum_setup(L); maskA = pin(maskA); maskB = pin(maskB); }
                if (J.value == 2) { ll_look<256>(olb, ow); if (L.value) { mlp_shared(L); mlp_global(L); } }
                mbar_wait(sb + SM_CBAR + (CB_WO + J.value) * 8, L.value);
                read_wo(J);
                if (L.value == 0 && J.value == 2) {
                    __syncwarp();
                    if (elect() && cnt_inc(sb + SM_CNT + CB_W1 * 8, 7) == 7) issue_w(L, 0);
                    __syncwarp();
                }
                if (L.value == 1 && J.value == 2) {
                    if (warp == 7 && elect()) issue_w(L, 0);
                    __syncwarp();
                }
            });
            sched_fence();
            const float o = ll_gather<256>(olb, otag, ow);
            CSTAMP(3, __float_as_uint(o));
            TSTAMP2(4);
            bool ok = true;
            if constexpr (NW < 5) ok = mbar_test(sb + SM_CBAR + (CB_WO + 4) * 8, L.value);
            if constexpr (NW < 4) ok &= mbar_test(sb + SM_CBAR + (CB_WO + 3) * 8, L.value);
            const uint32_t od = pack_bf(o, o);
            uint32_t oa[3], ob[3];
#pragma unroll
            for (int p = 0; p < 3; p++) { const uint32_t op = __shfl_sync(~0u, od, 8 * p + orow); oa[p] = op & maskA; ob[p] = op & maskB; }
            CSTAMP(4, oa[2]);
            float y[5][4];
#pragma unroll
            for (int j = 0; j < 5; j++) y[j][0] = y[j][1] = y[j][2] = y[j][3] = 0.f;
            auto rest = [&]() {
                if (!ok) static_for<NW, 5>([&](auto J) { mbar_wait(sb + SM_CBAR + (CB_WO + J.value) * 8, L.value); });
                static_for<NW, 5>(read_wo);
                __syncwarp();
            };
            if (L.value) rest();
#pragma unroll
            for (int p = 0; p < 3; p++)
#pragma unroll
                for (int j = 0; j < NW; j++) mma(y[j], v[j][p], oa[p], ob[p]);
            if (!L.value) { rest(); sum_setup(L); }
#pragma unroll
            for (int p = 0; p < 3; p++)
#pragma unroll
                for (int j = NW; j < 5; j++) mma(y[j], v[j][p], oa[p], ob[p]);
            CSTAMP(5, __float_as_uint(y[4][3]));
#pragma unroll
            for (int j = 0; j < 5; j += 2) {
                if (j < 4 && (t >> 1) != (g >> 2)) { y[j][0] = y[j + 1][0]; y[j][1] = y[j + 1][1]; y[j][2] = y[j + 1][2]; y[j][3] = y[j + 1][3]; }
                sts128f(wpa + j * 256, y[j]);
            }
            TSTAMP2(5);
        };
        u64 yw[2];
        bool wide;
        float msq = 0.f, yf[4] = {};
        auto mlp_part = [&](auto L) {
            bar_sync(0, 256);
            CSTAMP(6, __float_as_uint(sc1));
            const float s = (sum8(pa, 1536) + xc) + sum8(pa + 128, 1536), sm = s * sc1 + FX2_ONE;
            CSTAMP(7, __float_as_uint(s));
            const bool wide1 = !(fabsf(sm - FX2_ONE) < FX1LIM);
            asm volatile("red.relaxed.gpu.global.add.u32 [%0], %1;" :: "l"(rop), "r"(wide1 ? 0u : __float_as_uint(sm) * 128u + (1u - 0x4b400000u * 128u)) : "memory");
            const uint32_t c0 = clk();
            TSTAMP2(6);
            if (L.value == 0) bar_arrive(2, 256);
            if (wide1) {
                fx_send(rop + 64 + (lane & 7) * 4, s, ldsf(sb + SM_FXS), rop, 64);
                asm volatile("red.relaxed.gpu.global.add.u32 [%0], 1;" :: "l"(rop) : "memory");
            }
            __syncwarp();
            if (L.value == 1 && mlp == 96) { TDUMP(); asm volatile("exit;"); }
            uint4 wf[8], w2r[8];
            uint4 w;
            auto look = [&]() { asm volatile("ld.relaxed.gpu.global.v4.u32 {%0,%1,%2,%3}, [%4];" : "=r"(w.x), "=r"(w.y), "=r"(w.z), "=r"(w.w) : "l"(ap) : "memory"); };
            auto read_w1 = [&]() {
#pragma unroll
                for (int j = 0; j < 8; j++) wf[j] = ldsm_t(la + j * 256);
            };
            auto read_w2 = [&]() {
#pragma unroll
                for (int i = 0; i < 8; i++) w2r[i] = lds128(((i & 1) ? (w2a ^ 16) + 128 : w2a) + (i >> 1) * 5120);
            };
            const float inv = pinf(fx_inv(sc1) * (1.f / 128)), off = L.value ? pinf(fx_inv(sc1) * -0.25f) : inv * -32.f;
            if (L.value == 0) { fresh(); mlp_global(L); }
            mbar_wait(sb + SM_CBAR + CB_W1 * 8, L.value);
            if (L.value == 1) read_w1();
            while (clk() - c0 < AR1D);
            look();
            if (L.value == 0) { mlp_shared(L); read_w1(); bar_arrive(3, 256); }
            else { mbar_wait(sb + SM_CBAR + CB_W2 * 8, 1); read_w2(); }
            TSTAMPL(28);
            {
                sched_fence();
                auto miss = [&]() {
                    xp = make_uint2(pack_bf((float)(int)w.x * inv + off, (float)(int)w.y * inv + off), pack_bf((float)(int)w.z * inv + off, (float)(int)w.w * inv + off));
                    uint32_t a, b;
                    asm("lop3.b32 %0, %1, %2, 32, 0x7e;" : "=r"(a) : "r"(w.x), "r"(w.y));
                    asm("lop3.b32 %0, %1, %2, 32, 0x7e;" : "=r"(b) : "r"(w.z), "r"(w.w));
                    return __any_sync(~0u, (a | b) & 96);
                };
                if (miss()) {
                    int it = 0;
#pragma unroll 1
                    do {
                        if (!__any_sync(~0u, ~(w.x & w.y & w.z & w.w) & 32)) { xp.x = fx1_wide(ap, ldsf(sb + SM_FXS)); xp.y = fx1_wide(ap + 8, ldsf(sb + SM_FXS)); break; }
                        look();
                    } while (miss() & (++it < SPIN));
                }
                CSTAMP(8, w.w);
            }
            TSTAMP2(7);
            CSTAMP(9, xp.y);
            {
                bool ok = true;
                if (L.value == 0) ok = mbar_test(sb + SM_CBAR + CB_W2 * 8, 0);
                const bool ev = L.value || !(g & 1), od = L.value || (g & 1);
                const uint32_t e0 = ev ? xp.x : ONES, e1 = ev ? xp.y : ONES, o0 = od ? xp.x : ONES, o1 = od ? xp.y : ONES;
                float d[8][4];
#pragma unroll
                for (int j = 0; j < 8; j++) { d[j][0] = d[j][1] = d[j][2] = d[j][3] = 0.f; mma(d[j], wf[j], (j & 1) ? o0 : e0, (j & 1) ? o1 : e1); }
                float ss = ln_part(xp, lane);
                ss += shx(ss, 8); ss += shx(ss, 4);
                float r[4], dd;
#pragma unroll
                for (int k = 0; k < 4; k += 1 + L.value) r[k] = d[0][k] + d[1][k ^ 1];
#pragma unroll
                for (int j = 1; j < 4; j++)
#pragma unroll
                    for (int k = 0; k < 4; k += 1 + L.value) add_if(t == j, r[k], d[2 * j][k], d[2 * j + 1][k ^ 1]);
                CSTAMP(10, __float_as_uint(r[2]));
                if (L.value) {
                    dd = ((t & 2) ? r[2] : r[0]) + shx((t & 2) ? r[0] : r[2], 2);
                    ss += shx(ss, 2);
                    dd += shx(dd, 1);
                } else {
                    const float a = ((t & 1) ? r[1] : r[0]) + shx((t & 1) ? r[0] : r[1], 1), b = ((t & 1) ? r[3] : r[2]) + shx((t & 1) ? r[2] : r[3], 1);
                    ss += shx(ss, 2);
                    dd = ((t & 2) ? b : a) + shx((t & 2) ? a : b, 2);
                }
                ss += shx(ss, 1);
                stsf(hpa, dd);
                stsf(hst, ss);
                CSTAMP(11, __float_as_uint(dd + ss));
                if (!ok) mbar_wait(sb + SM_CBAR + CB_W2 * 8, L.value);
            }
            TSTAMPL(25);
            bar_sync(1, 160);
            uint4 hp[5];
#pragma unroll
            for (int w = 0; w < 5; w++) hp[w] = lds128(hsa + w * 256);
            CSTAMP(12, hp[0].x);
            auto hs = [&](auto K) { return sum5(__uint_as_float(word<K.value>(hp[0])), __uint_as_float(word<K.value>(hp[1])), __uint_as_float(word<K.value>(hp[2])),
                                                __uint_as_float(word<K.value>(hp[3])), __uint_as_float(word<K.value>(hp[4]))); };
            const float mean = hs(IC<2>{}) * (1.f / D_MODEL);
            msq = hs(IC<3>{}) * (1.f / D_MODEL);
            if (L.value == 0) cs1 = hs(IC<1>{});
            float hv = hs(IC<0>{}) - mean * cs1;
            CSTAMP(13, __float_as_uint(hv));
            const float sc2 = fx2_scale(msq), lim = fx_inv(sc2) * FX2LIM;
            if (L.value == 0) {
                read_w2();
                bar_arrive(4, 256);
                wide = false;
                if (mlp == 96) return;
            }
            hv = hv * ln_rstd(mean, msq) + b1v;
            CSTAMP(14, __float_as_uint(hv));
            hv = hv * rcp(1.f + ex2(hv * (-2.302208198f - 0.1029432397f * hv * hv)));
            const uint32_t hd = pack_bf(hv, hv);
            CSTAMP(15, hd);
            TSTAMPL(27);
            float ym[4][4];
#pragma unroll
            for (int i = 0; i < 2; i++) {
                ym[i][0] = ym[i][1] = ym[i][2] = ym[i][3] = 0.f;
                const float f = mlp < 64 ? 1.f / 64 : 0.f;
                ym[i + 2][0] = (bf_lo(xp.x) + bf_lo(b2v.x)) * f; ym[i + 2][1] = (bf_hi(xp.x) + bf_hi(b2v.x)) * f;
                ym[i + 2][2] = (bf_lo(xp.y) + bf_lo(b2v.y)) * f; ym[i + 2][3] = (bf_hi(xp.y) + bf_hi(b2v.y)) * f;
            }
#pragma unroll
            for (int i = 0; i < 4; i++) {
                const uint32_t hh = __shfl_sync(~0u, hd, 4 * i + t);
                mma(ym[(i & 1) * 2], w2r[2 * i], hh & maskA, hh & maskB);
                mma(ym[(i & 1) * 2 + 1], w2r[2 * i + 1], hh & maskA, hh & maskB);
            }
#pragma unroll
            for (int k = 0; k < 4; k++) { yf[k] = ym[0][k] + ym[2][k]; add_if(t & 2, yf[k], ym[1][k], ym[3][k]); }
            CSTAMP(16, __float_as_uint(yf[3]));
            yw[0] = fx2_pack(yf[0] * sc2 + FX2_ONE, yf[1] * sc2 + FX2_ONE); yw[1] = fx2_pack(yf[2] * sc2 + FX2_ONE, yf[3] * sc2 + FX2_ONE);
            wide = !(fmaxf(fmaxf(fabsf(yf[0]), fabsf(yf[1])), fmaxf(fabsf(yf[2]), fabsf(yf[3]))) < lim);
            if (wide) yw[0] = yw[1] = 0;
            if (L.value == 0) {
#pragma unroll
                for (int k = 0; k < 2; k++) asm volatile("red.relaxed.gpu.global.add.u64 [%0], %1;" :: "l"(rap + k * 40 * ACC_PITCH), "l"(yw[k]) : "memory");
            }
        };
        auto send_wide = [&]() {
#pragma unroll 1
            for (int k = 0; k < 4; k++, yf[0] = yf[1], yf[1] = yf[2], yf[2] = yf[3]) {
                const unsigned char* a = rap + (k >> 1) * 40 * ACC_PITCH;
                fx_send(a + 64 + (k & 1) * 32, yf[0], msq, a, 256);
            }
            yw[0] = yw[1] = 1;
        };

        pass1();
        o_setup(IC<0>{});
        out_proj(IC<0>{});
        uint32_t c0;
        if (warp < 5) {
            mlp_part(IC<0>{});
            c0 = clk() + (mlp == 96 ? PCD : 0);
            stsf(sb + SM_ML + (lane & 15) * 4, cs1);
            TSTAMP(8);
            if (__any_sync(~0u, wide)) {
                if (wide) {
                    send_wide();
#pragma unroll
                    for (int k = 0; k < 2; k++) asm volatile("red.relaxed.gpu.global.add.u64 [%0], 1;" :: "l"(rap + k * 40 * ACC_PITCH) : "memory");
                }
                __syncwarp();
            }
            fresh(); calc_offsets();
            load_wq();
        } else {
            bar_sync(0, 256);
            if (warp == 5 && elect()) {
                asm volatile("fence.proxy.async.shared::cta;" ::: "memory");
                issue_w(IC<0>{}, 1);
            }
            __syncwarp();
            fresh(); calc_offsets();
            load_wq();
#pragma unroll 1
            for (int ph = 0; ph < 3; ph++) {
                bar_sync(ph + 2, 256);
                c0 = clk();
                if (ph == 2) {
                    msq = sum5(ldsf(sb + SM_PART + 12), ldsf(sb + SM_PART + 268), ldsf(sb + SM_PART + 524), ldsf(sb + SM_PART + 780), ldsf(sb + SM_PART + 1036)) * (1.f / D_MODEL);
                    bar_arrive(5, 256);
                }
                if (elect()) {
                    asm volatile("fence.proxy.async.shared::cta;" ::: "memory");
                    const uint32_t gap = ph == 0 ? WG1 : ph == 1 ? WG2 : WG3;
                    uint32_t c1 = c0 + (ph == 0 ? WD1 : 0) + (warp - 5) * gap;
#pragma unroll 1
                    for (int k = warp + (ph == 0 ? -5 : ph == 1 ? 9 : 1); k < (ph == 0 ? 9 : ph == 1 ? 20 : 14); k += 3, c1 += 3 * gap) {
                        const int i = ph == 0 && k >= 6 ? k + 23 : k;
                        const uint32_t bar = sb + SM_BAR + (i & 7) * 96 + 32 + (i & 24);
                        while ((int)(clk() - c1) < 0);
                        mbar_expect(bar, SUB);
                        tma_v(sb + SM_RING + i * SUB, tmk,
                              rowc * 3 + (i & 7) * 24 + ((UC<SCH.st[0].unit | SCH.st[1].unit << 8 | SCH.st[2].unit << 16 | SCH.st[3].unit << 24>::value >> (i & 24)) & 15) * 768, bar);
                    }
                }
                __syncwarp();
            }
            c0 += PCD;
        }
        {
            constexpr IC<1> L{};
            fresh();
            const int col = xcol(g & 3, t), cw = j40 + (col >> 2);
            const unsigned char* xa = pin(accg + ACC_BYTES + ((cw >> 2) + (col & 2) * 20) * ACC_PITCH + (cw & 3) * 8);
            const uint32_t pst = pin(prow + (g * 8 + (t & 1) * 4 + (t & 2)) * 4);
            const float inv = pinf(fx2_inv(msq));
            sts64f(sb + SM_MSQ, msq, inv);
            rap = pin(accg + ACC_BYTES + (c4() >> 2) * ACC_PITCH + (c4() & 3) * 8);
            fresh();
            maskA = pin(maskA); maskB = pin(maskB);
            u64 w[1];
            uint32_t x1[1], x2[3];
            auto look = [&]() { w[0] = ld_rlx(xa); };
            if (warp < 5) bar_sync(5, 256);
            while ((int)(clk() - c0) < ARDELAY);
            look();
            while ((int)(clk() - c0) < ARDELAY + DPOST);
            if (warp < 5 && elect()) {
                issue_v(IC<3>{}, 0);
                if (warp < 4) issue_v(IC<2>{}, 4);
            }
            __syncwarp();
            fx2_wait<1>([&](int) { return xa; }, look, w, sb + SM_MSQ, inv, x1);
            if (warp < 5) look_rw(); else rw[0] = rw[1] = 96;
#pragma unroll
            for (int i = 0; i < 3; i++) x2[i] = __shfl_sync(~0u, x1[0], 4 * i + t);
            TSTAMP(9);
            CSTAMP(22, x2[2]);
            q_proj(L, x2, pst);
            pass2();
            out_proj(L);
            if (warp >= 5) {
                bar_arrive(0, 256);
                if (warp == 5 && elect()) issue_w(L, 1);
                TDUMP();
                return;
            }
            mlp_part(L);
            u64 old[2];
            auto add = [&]() {
#pragma unroll
                for (int k = 0; k < 2; k++) asm volatile("atom.relaxed.gpu.global.add.u64 %0, [%1], %2;" : "=l"(old[k]) : "l"(rap + k * 40 * ACC_PITCH), "l"(yw[k]) : "memory");
            };
            add();
            uint32_t* op = pin(reinterpret_cast<uint32_t*>(P.out) + 2 * c4());
            const float inv2 = pinf(fx2_inv(msq));
            if (wide) { send_wide(); add(); }
            TSTAMP(18);
            CSTAMP(17, hi32(yw[1]));
            __syncwarp();
            CSTAMP(18, lo32(old[0]) ^ lo32(old[1]));
#pragma unroll
            for (int k = 0; k < 2; k++) {
                yw[k] += old[k];
                asm volatile("{\n.reg .pred p;\nsetp.eq.u32 p, %2, 96;\n@p st.global.u32 [%0], %1;\n}"
                             :: "l"(op + k), "r"(fx2_get(yw[k], inv2)), "r"(lo32(yw[k]) & 511) : "memory");
            }
            if ((lo32(yw[0]) & 255) == 96 && tid == 0) P.g->epoch = lds32(sb + SM_EPOCH) + 1;
#pragma unroll
            for (int k = 0; k < 2; k++) if ((lo32(yw[k]) & 511) == 256 + 96) op[k] = fx2_wide(rap + k * 40 * ACC_PITCH, msq);
            TSTAMP(19);
            CSTAMP(19, lo32(yw[1]));
            TDUMP();
        }
    }
}

typedef CUresult (*EncodeFn)(CUtensorMap*, CUtensorMapDataType, cuuint32_t, void*, const cuuint64_t*, const cuuint64_t*, const cuuint32_t*,
                             const cuuint32_t*, CUtensorMapInterleave, CUtensorMapSwizzle, CUtensorMapL2promotion, CUtensorMapFloatOOBfill);

}

extern "C" void kernel_launch(void* const* d_in, const int* in_sizes, int n_in, void* d_out, int out_size) {
    (void)in_sizes; (void)n_in; (void)out_size;
    static EncodeFn enc = nullptr;
    static void* scratch = nullptr;
    if (!enc) {
        void* fn = nullptr;
        cudaDriverEntryPointQueryResult qr;
        cudaGetDriverEntryPoint("cuTensorMapEncodeTiled", &fn, cudaEnableDefault, &qr);
        enc = (EncodeFn)fn;
        cudaGetSymbolAddress(&scratch, g_scratch);
        cudaFuncSetAttribute(fused_kernel, cudaFuncAttributeMaxDynamicSharedMemorySize, SM_TOTAL);
    }
    Params P = {};
    auto map3 = [&](int m, int in, cuuint64_t d0, cuuint64_t d1, cuuint64_t d2, cuuint64_t s1, cuuint64_t s2, cuuint32_t b0, cuuint32_t b1, cuuint32_t b2,
                    CUtensorMapSwizzle sw, int promo) {
        const cuuint64_t dim[3] = {d0, d1, d2}, str[2] = {s1, s2};
        const cuuint32_t box[3] = {b0, b1, b2}, ones[3] = {1, 1, 1};
        enc(&P.tm[m], CU_TENSOR_MAP_DATA_TYPE_BFLOAT16, d2 ? 3 : 2, d_in[in], dim, str, box, ones, CU_TENSOR_MAP_INTERLEAVE_NONE, sw, (CUtensorMapL2promotion)promo,
            CU_TENSOR_MAP_FLOAT_OOB_FILL_NONE);
    };
    map3(TM_KH, 1, 64, 3, NHEAD * SK, 128, DH * 2, 64, 3, 32, CU_TENSOR_MAP_SWIZZLE_128B, 0);
    map3(TM_VH, 2, 64, 3, NHEAD * SK, 128, DH * 2, 64, 3, 32, CU_TENSOR_MAP_SWIZZLE_128B, 0);
    map3(TM_VP, 2, 64, 3, NHEAD * SK, 128, DH * 2, 8, 3, 32, CU_TENSOR_MAP_SWIZZLE_NONE, 0);
    map3(TM_V, 2, 64, NHEAD * SK * 3, 0, 128, 0, 64, 24, 0, CU_TENSOR_MAP_SWIZZLE_128B, 0);
    map3(TM_WO, 4, 32, 20, NHEAD * DH, 64, D_MODEL * 2, 32, 1, DH, CU_TENSOR_MAP_SWIZZLE_64B, 2);
    map3(TM_WOP, 4, 32, 20, NHEAD * DH, 64, D_MODEL * 2, 8, 1, DH, CU_TENSOR_MAP_SWIZZLE_NONE, 0);
    map3(TM_WQ, 3, 64, NHEAD * 3, D_MODEL, 128, NHEAD * DH * 2, 64, 3, 32, CU_TENSOR_MAP_SWIZZLE_128B, 0);
    map3(TM_W1, 6, DFF, 128, 5, DFF * 2, DFF * 256, 16, 128, 5, CU_TENSOR_MAP_SWIZZLE_32B, 2);
    map3(TM_W2, 8, 64, 10, DFF, 128, D_MODEL * 2, 64, 10, 16, CU_TENSOR_MAP_SWIZZLE_128B, 0);
    P.x = (const __nv_bfloat16*)d_in[0];
    P.k = (const __nv_bfloat16*)d_in[1];
    P.b1 = (const __nv_bfloat16*)d_in[7];
    P.b2 = (const __nv_bfloat16*)d_in[9];
    P.w1 = (const __nv_bfloat16*)d_in[6];
    P.out = (__nv_bfloat16*)d_out;
    P.g = (Scratch*)(((uintptr_t)scratch + ACC_BYTES - 1) & ~(uintptr_t)(ACC_BYTES - 1));
    for (int i = 0; i < 64; i++) P.tile[i] = make_uint4(SCH.tile[i][0], SCH.tile[i][1], SCH.tile[i][2], 0);
    fused_kernel<<<NCTA, NTHR, SM_TOTAL, cudaStreamPerThread>>>(P);
}
```

```cpp
#include <cuda_runtime.h>
#include <cuda_bf16.h>
#include <cuda.h>
#include <stdint.h>

namespace {

constexpr int D_MODEL = 640, NHEAD = 32, SK = 32768, DH = 192, WIN = 4096, DFF = 1536;
constexpr int NCTA = 128, NTHR = 256;
constexpr int TILE = 64 * DH * 2;
constexpr int HALF = TILE / 2;
constexpr int SUB = 8 * DH * 2;
constexpr int SM_RING = 4 * TILE;
constexpr int SM_W2 = SM_RING + 20480, SM_W1 = SM_W2 + 20480;
constexpr int SM_WQR = 6 * TILE + HALF, SM_WQ = 7 * TILE;
constexpr int SM_PART = 9 * TILE;
constexpr int SM_EXC = SM_PART + 6144;
constexpr int SM_SC = SM_EXC + 1024;
constexpr int SM_BAR = SM_SC + 1024;
constexpr int SM_VEC = SM_BAR + 768;
constexpr int SM_CS = SM_VEC + 384;
constexpr int SM_FAC = SM_CS + 768;
constexpr int SM_ML = SM_FAC + 32;
constexpr int SM_B1 = SM_ML + 64;
constexpr int SM_STAT = SM_B1 + 64;
constexpr int NCB = 28;
constexpr int CB_WO = 18, CB_W1 = 23, CB_W2 = 24, CB_SNAP = 25, CB_REL = 26, CB_WQ = 27;
constexpr int SM_CBAR = SM_STAT + 48;
constexpr int SM_CNT = SM_CBAR + NCB * 8;
constexpr int SM_ZERO = SM_CNT + NCB * 8;
constexpr int SM_EPOCH = SM_ZERO + 64;
constexpr int SM_FXS = SM_EPOCH + 4;
constexpr int SM_T0 = SM_FXS + 4;
constexpr int SM_M1 = SM_T0 + 4;
constexpr int SM_MSQ = SM_M1 + 4;
constexpr int SM_TS = SM_MSQ + 8;
constexpr int SM_TOTAL = 232448;
static_assert(SM_TS + 320 <= SM_TOTAL && SM_ZERO % 16 == 0, "smem");
constexpr int NEXC = 16;

constexpr int SPIN = 1 << 20;
enum { TM_V = 0, TM_KH = 1, TM_VH = 2, TM_WO = 3, TM_VP = 4, TM_WOP = 5, TM_W1 = 6, TM_W2 = 7, TM_WQ = 8 };
constexpr uint32_t POL_NORMAL = 0x16F00000u, POL_FIRST = 0x12F00000u;

#define PACE 980
#define PACE0 1500
#define PACES 1300
#define NIM 4
#define NI1 6
#define ETRIG 0x54321000
#define PFREE 66
#define SNAPAT 1
#define LATEAT 5
#define PUBAT 28
#define HW0 30
#define HW1 31
#define AR1D 250
#define ARDELAY 720
#define DPOST 200
#define PCD 350
#define WD1 100
#define WG1 140
#define WG2 120
#define WG3 65
#define VORD2 0x7685943a2b1cd0efull
#define VSLOT 0x1087654321087654ull
#define VTRIG 0xba73210
#define PARKS 0xa5
#define RF0 1
#define RF1 2
#define M1D 1
#define LAG0 12
#define NMMA 2
#define HWAT 12
#define WOP 0x44433
#define NWO1 4
#define FX1LIM 524288.f
#define FX2LIM 524288.f

constexpr uint32_t G_A = 1u << 28, G_B = 1u << 29, G_C = 1u << 30;
__host__ __device__ constexpr int ring_hs(int j) { return (j + 4) % 5; }
__host__ __device__ constexpr uint32_t load_word(int j) {
    if (j >= 64) return (uint32_t)(j - 64) << 20 | (SM_RING + ring_hs(j) * HALF) | TM_WO << 8 | (CB_WO + j - 64) << 3 | 2;
    const int e = j >> 1, isv = e >= 16, unit = e & 15;
    return (uint32_t)(unit * 256 + (j & 1) * 32) << 20 | (j < 8 ? j * HALF : SM_RING + ring_hs(j) * HALF) | (TM_KH + isv) << 8 | (j < 8 ? 10 + j : (j - 8) % 10) << 3 | 2 | !isv;
}
__host__ __device__ constexpr int popc(int v) { return v ? (v & 1) + popc(v >> 1) : 0; }
constexpr int NPARK = popc(PARKS), NPRE = 2;
constexpr int SM_SNAP = SM_RING + ring_hs(12) * HALF, SM_CSP = SM_RING + ring_hs(11) * HALF;
struct Step { int unit, slot, par, next, mma0, nmma; };
struct Sched { uint32_t tile[64][3]; Step st[16]; };
constexpr Sched make_sched() {
    Sched s{};
    for (int j = 0; j < 64; j++) {
        const int e = j >> 1;
        const uint32_t d = load_word(j);
        uint32_t w = (uint32_t)(j < 8 ? 0 : (j - 8) / 10 & 1) << 31 | (e & 15) * 4 << 20 | ((d & 0x3f000) - (j & 1) * HALF) | (d & 0xf8);
        if (e == PUBAT || e == SNAPAT) w |= G_A;
        if (e == HW0 || e == 4) w |= G_B;
        if ((e >= LATEAT && e < LATEAT + 4) || e == HW1) w |= G_C;
        s.tile[j][0] = w;
    }
    for (int j = NI1; j < 69; j++) {
        if (j == 12) continue;
        const int at = j < 12 ? (ETRIG >> (4 * (j - 4)) & 15) : j - 5;
        s.tile[at][1] = load_word(j);
        s.tile[at][2] = j >= PFREE ? 0 : PACE0 + j * PACE / 2;
    }
    int done = 0;
    for (int p = 0; p < 16; p++) {
        Step& c = s.st[p];
        c.unit = (int)(VORD2 >> (4 * p) & 15); c.slot = (int)(VSLOT >> (4 * p) & 15); c.par = p >= 9; c.next = -1;
        c.mma0 = done;
        if (p >= NPARK) { const int avail = p - done + (p >= LAG0); c.nmma = p == 15 ? 16 - done : (avail < NMMA ? avail : NMMA); done += c.nmma; }
    }
    for (int p = 9; p < 16; p++) s.st[VTRIG >> (4 * (p - 9)) & 15].next = p;
    return s;
}
constexpr Sched SCH = make_sched();
__host__ __device__ constexpr int kunit(int o) { return o < 5 ? o + 11 : o == 5 ? 10 : o - 6; }

template <int I> struct IC { static constexpr int value = I; };
template <uint32_t I> struct UC { static constexpr uint32_t value = I; };
template <int A, int B, class F> __device__ __forceinline__ void static_for(F&& f) {
    if constexpr (A < B) { f(IC<A>{}); static_for<A + 1, B>(f); }
}

typedef unsigned long long u64;
constexpr int ACC_BYTES = 65536;
__host__ __device__ constexpr int acc_pitch(int r) { return (r & 1) ? 832 : 256; }
struct alignas(1024) Scratch {
    unsigned char acc[4 * ACC_BYTES];
    u64 l0[NCTA][384];
    u64 ll[NCTA][256];
    alignas(128) unsigned epoch;
    alignas(128) unsigned zeroed;
};
__device__ __align__(1024) unsigned char g_scratch[sizeof(Scratch) + ACC_BYTES];

struct Params {
    CUtensorMap tm[9];
    const __nv_bfloat16 *x, *k, *b1, *b2, *w1;
    __nv_bfloat16* out;
    Scratch* g;
    uint4 tile[66];
};

#define TSTAMP(i)
#define TSTAMP2(i)
#define TSTAMPL(i)
#define TDUMP()
#define CSTAMP(i, x)
#define TRACE(i)

__device__ __forceinline__ void mbar_wait(uint32_t bar, uint32_t parity) {
    asm volatile("{\n.reg .pred p;\nLOOP:\nmbarrier.try_wait.parity.shared::cta.b64 p, [%0], %1;\n@!p bra.uni LOOP;\n}" :: "r"(bar), "r"(parity) : "memory");
}
__device__ __forceinline__ bool mbar_test(uint32_t bar, uint32_t parity) {
    uint32_t r;
    asm volatile("{\n.reg .pred p;\nmbarrier.test_wait.parity.shared::cta.b64 p, [%1], %2;\nselp.u32 %0, 1, 0, p;\n}" : "=r"(r) : "r"(bar), "r"(parity) : "memory");
    return __all_sync(~0u, r);
}
__device__ __forceinline__ bool elect() {
    uint32_t r;
    asm volatile("{\n.reg .pred p;\nelect.sync _|p, 0xffffffff;\nselp.u32 %0, 1, 0, p;\n}" : "=r"(r));
    return r != 0;
}
__device__ __forceinline__ void mbar_expect(uint32_t bar, uint32_t bytes) {
    asm volatile("mbarrier.arrive.expect_tx.shared::cta.b64 _, [%0], %1;" :: "r"(bar), "r"(bytes) : "memory");
}
__device__ __forceinline__ uint4 lds128(uint32_t a) {
    uint4 v; asm volatile("ld.shared.v4.u32 {%0,%1,%2,%3}, [%4];" : "=r"(v.x), "=r"(v.y), "=r"(v.z), "=r"(v.w) : "r"(a) : "memory"); return v;
}
__device__ __forceinline__ uint4 ldsm_t(uint32_t a) {
    uint4 v; asm volatile("ldmatrix.sync.aligned.m8n8.x4.trans.shared.b16 {%0,%1,%2,%3}, [%4];" : "=r"(v.x), "=r"(v.y), "=r"(v.z), "=r"(v.w) : "r"(a) : "memory"); return v;
}
__device__ __forceinline__ uint2 lds64(uint32_t a) {
    uint2 v; asm volatile("ld.shared.v2.u32 {%0,%1}, [%2];" : "=r"(v.x), "=r"(v.y) : "r"(a) : "memory"); return v;
}
__device__ __forceinline__ float2 lds64f(uint32_t a) { const uint2 v = lds64(a); return make_float2(__uint_as_float(v.x), __uint_as_float(v.y)); }
__device__ __forceinline__ uint32_t lds32(uint32_t a) {
    uint32_t v; asm volatile("ld.shared.u32 %0, [%1];" : "=r"(v) : "r"(a) : "memory"); return v;
}
__device__ __forceinline__ float ldsf(uint32_t a) { return __uint_as_float(lds32(a)); }
__device__ __forceinline__ void sts32(uint32_t a, uint32_t v) { asm volatile("st.shared.u32 [%0], %1;" :: "r"(a), "r"(v) : "memory"); }
__device__ __forceinline__ void stsf(uint32_t a, float v) { sts32(a, __float_as_uint(v)); }
__device__ __forceinline__ void sts16(uint32_t a, uint32_t v) { asm volatile("st.shared.u16 [%0], %1;" :: "r"(a), "h"((uint16_t)v) : "memory"); }
__device__ __forceinline__ void sts64(uint32_t a, uint32_t x, uint32_t y) { asm volatile("st.shared.v2.u32 [%0], {%1,%2};" :: "r"(a), "r"(x), "r"(y) : "memory"); }
__device__ __forceinline__ void sts64f(uint32_t a, float x, float y) { sts64(a, __float_as_uint(x), __float_as_uint(y)); }
__device__ __forceinline__ void sts128f(uint32_t a, float x, float y, float z, float w) {
    asm volatile("st.shared.v4.f32 [%0], {%1,%2,%3,%4};" :: "r"(a), "f"(x), "f"(y), "f"(z), "f"(w) : "memory");
}
__device__ __forceinline__ void mma(float (&c)[4], const uint4& a, uint32_t b0, uint32_t b1) {
    asm volatile("mma.sync.aligned.m16n8k16.row.col.f32.bf16.bf16.f32 {%0,%1,%2,%3}, {%4,%5,%6,%7}, {%8,%9}, {%0,%1,%2,%3};"
                 : "+f"(c[0]), "+f"(c[1]), "+f"(c[2]), "+f"(c[3]) : "r"(a.x), "r"(a.y), "r"(a.z), "r"(a.w), "r"(b0), "r"(b1));
}
__device__ __forceinline__ u64 ld_rlx(const void* p) {
    u64 a; asm volatile("ld.relaxed.gpu.global.u64 %0, [%1];" : "=l"(a) : "l"(p) : "memory"); return a;
}
__device__ __forceinline__ void ld_rlx2(const void* p, u64& a, u64& b) {
    asm volatile("ld.relaxed.gpu.global.v2.u64 {%0,%1}, [%2];" : "=l"(a), "=l"(b) : "l"(p) : "memory");
}
__device__ __forceinline__ void st_rlx(void* p, u64 a) { asm volatile("st.relaxed.gpu.global.u64 [%0], %1;" :: "l"(p), "l"(a) : "memory"); }
__device__ __forceinline__ u64 ll_pack(float v, uint32_t tag) { return ((u64)tag << 32) | __float_as_uint(v); }
__device__ __forceinline__ float ll_val(u64 w) { return __uint_as_float((uint32_t)w); }
__device__ __forceinline__ uint32_t ll_tag(u64 w) { return (uint32_t)(w >> 32); }
__device__ __forceinline__ float bf_lo(uint32_t u) { return __uint_as_float(u << 16); }
__device__ __forceinline__ float bf_hi(uint32_t u) { return __uint_as_float(u & 0xffff0000u); }
__device__ __forceinline__ uint32_t pack_bf(float lo, float hi) {
    uint32_t r; asm("cvt.rn.bf16x2.f32 %0, %1, %2;" : "=r"(r) : "f"(hi), "f"(lo)); return r;
}
__device__ __forceinline__ float ex2(float v) { float r; asm("ex2.approx.ftz.f32 %0, %1;" : "=f"(r) : "f"(v)); return r; }
__device__ __forceinline__ float rcp(float v) { float r; asm("rcp.approx.ftz.f32 %0, %1;" : "=f"(r) : "f"(v)); return r; }
__device__ __forceinline__ float rsq(float v) { float r; asm("rsqrt.approx.ftz.f32 %0, %1;" : "=f"(r) : "f"(v)); return r; }
__device__ __forceinline__ void bar_sync(int id, int n) { asm volatile("bar.sync %0, %1;" :: "r"(id), "r"(n) : "memory"); }
__device__ __forceinline__ uint32_t clk() { uint32_t c; asm volatile("mov.u32 %0, %clock;" : "=r"(c)); return c; }
__device__ __forceinline__ void sched_fence() { __syncwarp(); while (clk() == 0x9e3779b9u); }
__device__ __forceinline__ uint32_t pin(uint32_t v) { return __shfl_xor_sync(~0u, v, 0); }
__device__ __forceinline__ float shx(float v, int o) { return __shfl_xor_sync(~0u, v, o); }

__device__ __forceinline__ u64 fx_pack(float v, float scale) { return ((u64)__float2ll_rn(v * scale) & ~255ull) | 1ull; }
__device__ __forceinline__ float fx_scale(float meansq) {
    const int e = max(((int)(__float_as_uint(meansq) >> 23) - 127) >> 1, -6);
    return __uint_as_float((uint32_t)(127 + 32 - e) << 23);
}
__device__ __forceinline__ float fx_inv(float scale) { return __uint_as_float((254u << 23) - __float_as_uint(scale)); }
__device__ __forceinline__ uint32_t lo32(u64 w) { uint32_t l; asm("mov.b64 {%0, _}, %1;" : "=r"(l) : "l"(w)); return l; }
__device__ __forceinline__ int hi32(u64 w) { int h; asm("mov.b64 {_, %0}, %1;" : "=r"(h) : "l"(w)); return h; }
__device__ __forceinline__ float fx_val(u64 w) { return (float)hi32(w) * 4294967296.f + (float)lo32(w); }
constexpr float FX2_ONE = 12582912.f;
__device__ __forceinline__ float fx2_scale(float meansq) { return __uint_as_float((uint32_t)(127 + 16 - max(((int)(__float_as_uint(meansq) >> 23) - 127) >> 1, -100)) << 23); }
__device__ __forceinline__ u64 fx2_pack(float a, float b) {
    const uint32_t lo = __float_as_uint(a) * 512u + (1u - 0x4b400000u * 512u);
    return lo | (u64)(__float_as_uint(b) * 16u - 0x4b400000u * 16u + (uint32_t)((int)lo >> 31)) << 32;
}
__device__ __forceinline__ float fx2_lo(u64 w, float inv) { return (float)(int)(__funnelshift_r(lo32(w), hi32(w), 4) & ~31u) * (inv * 0.5f); }
__device__ __forceinline__ float fx2_hi(u64 w, float inv) { return (float)((hi32(w) + 8) & ~15) * inv; }
__device__ __forceinline__ uint32_t fx2_get(u64 w, float inv) {
    return pack_bf((float)(int)__funnelshift_r(lo32(w), hi32(w), 4) * (inv * 0.5f) - inv * 3.f, (float)hi32(w) * inv);
}
__device__ __forceinline__ float fx2_inv(float meansq) { return fx_inv(fx2_scale(meansq)) * 0.0625f; }
__device__ __noinline__ uint32_t fx2_wide(const unsigned char* a, float meansq) {
    __threadfence();
    const u64 w = ld_rlx(a);
    const float inv = fx_inv(fx_scale(meansq));
    return pack_bf(fx2_lo(w, fx2_inv(meansq)) + fx_val(ld_rlx(a + 64)) * inv, fx2_hi(w, fx2_inv(meansq)) + fx_val(ld_rlx(a + 128)) * inv);
}
__device__ __noinline__ uint32_t fx1_wide(const unsigned char* a, float meansq) {
    __threadfence();
    const u64 w = ld_rlx(a);
    const unsigned char* b = a + 64 + (reinterpret_cast<u64>(a) & 63);
    const float inv = fx_inv(fx_scale(meansq)), inv1 = fx2_inv(meansq) * 0.5f;
    return pack_bf((float)(int)(lo32(w) & ~127u) * inv1 + fx_val(ld_rlx(b)) * inv, (float)(hi32(w) & ~127) * inv1 + fx_val(ld_rlx(b + 8)) * inv);
}
__device__ __noinline__ void fx_send(const unsigned char* wide, float v, float meansq, const unsigned char* a, uint32_t flag) {
    asm volatile("red.relaxed.gpu.global.add.u64 [%0], %1;" :: "l"(wide), "l"(fx_pack(v, fx_scale(meansq))) : "memory");
    __threadfence();
    asm volatile("red.relaxed.gpu.global.or.b32 [%0], %1;" :: "l"(a), "r"(flag) : "memory");
}
template <int N, class A, class F> __device__ __forceinline__ void fx2_wait(A a, F look, u64 (&w)[N], uint32_t msqa, float inv, uint32_t (&x)[N]) {
    auto miss = [&]() {
#pragma unroll
        for (int i = 0; i < N; i++) x[i] = fx2_get(w[i], inv);
        return __any_sync(~0u, ((lo32(w[0]) ^ 96) | (lo32(w[N - 1]) ^ 96)) & 0x160);
    };
    if (miss()) {
        int it = 0;
#pragma unroll 1
        do {
            if (__all_sync(~0u, (lo32(w[0]) & lo32(w[N - 1]) & 96) == 96)) {
#pragma unroll
                for (int i = 0; i < N; i++) x[i] = fx2_wide(a(i), ldsf(msqa));
                break;
            }
            look();
        } while (miss() & (++it < SPIN));
    }
}
__device__ __forceinline__ void st_rlx_if(bool p, void* a, u64 v) {
    asm volatile("{\n.reg .pred p;\nsetp.ne.u32 p, %2, 0;\n@p st.relaxed.gpu.global.u64 [%0], %1;\n}" :: "l"(a), "l"(v), "r"((uint32_t)p) : "memory");
}
__device__ __forceinline__ void sts128f(uint32_t a, const float (&v)[4]) { sts128f(a, v[0], v[1], v[2], v[3]); }
__device__ __forceinline__ void bar_arrive(int id, int n) { asm volatile("bar.arrive %0, %1;" :: "r"(id), "r"(n) : "memory"); }
template <class T> __device__ __forceinline__ T* pin(T* p) { return reinterpret_cast<T*>(__shfl_xor_sync(~0u, (u64)p, 0)); }

__device__ __forceinline__ void tma3(uint32_t dst, const CUtensorMap* tm, int c1, int c2, uint32_t bar, uint32_t pol) {
    asm volatile("cp.async.bulk.tensor.3d.shared::cluster.global.mbarrier::complete_tx::bytes.L2::cache_hint [%0], [%1, {%2, %3, %4}], [%5], %6;"
                 :: "r"(dst), "l"(tm), "r"(0), "r"(c1), "r"(c2), "r"(bar), "l"((u64)pol << 32) : "memory");
}
__device__ __forceinline__ void tma_v(uint32_t dst, const CUtensorMap* tm, int line, uint32_t bar) {
    asm volatile("cp.async.bulk.tensor.2d.shared::cluster.global.mbarrier::complete_tx::bytes.L2::cache_hint [%0], [%1, {%2, %3}], [%4], %5;"
                 :: "r"(dst), "l"(tm), "r"(0), "r"(line), "r"(bar), "l"((u64)POL_FIRST << 32) : "memory");
}
__device__ __forceinline__ void tma3_pf(const CUtensorMap* tm, int c1, int c2, uint32_t pol) {
    asm volatile("cp.async.bulk.prefetch.tensor.3d.L2.global.tile.L2::cache_hint [%0, {%1, %2, %3}], %4;"
                 :: "l"(tm), "r"(0), "r"(c1), "r"(c2), "l"((u64)pol << 32) : "memory");
}
__device__ __forceinline__ void issue_half(uint32_t d, uint32_t sb, int rowc, int cta, const CUtensorMap* tm0) {
    const uint32_t bar = sb + SM_CBAR + (d & 0xf8);
    const CUtensorMap* tm = tm0 + ((d >> 8) & 3);
    const bool wo = (d & 0x300) == TM_WO << 8;
    const int c1 = wo ? (cta & 3) + 4 * (d >> 20) : 0, c2 = wo ? (cta >> 2) * DH : rowc + (d >> 20);
    mbar_expect(bar, HALF);
    tma3(sb + (d & 0x3f000), tm, c1, c2, bar, POL_FIRST);
    if (!(d & 1)) tma3_pf(tm + 2, c1, c2, POL_NORMAL);
}
__device__ __forceinline__ uint32_t cnt_inc(uint32_t a, uint32_t last) {
    uint32_t old; asm volatile("atom.relaxed.cta.shared.inc.u32 %0, [%1], %2;" : "=r"(old) : "r"(a), "r"(last) : "memory"); return old;
}
__device__ __forceinline__ void wait_until(uint32_t due) {
#pragma unroll 1
    for (int it = 0; it < 4096; it++) { uint32_t now; asm volatile("mov.u32 %0, %globaltimer_lo;" : "=r"(now)); if ((int)(now - due) >= 0) break; }
}
__device__ __forceinline__ uint32_t bf2_mul(uint32_t a, uint32_t b) { uint32_t r; asm("mul.rn.bf16x2 %0, %1, %2;" : "=r"(r) : "r"(a), "r"(b)); return r; }
__device__ __forceinline__ uint32_t bf2_fma(uint32_t a, uint32_t b, uint32_t c) { uint32_t r; asm("fma.rn.bf16x2 %0, %1, %2, %3;" : "=r"(r) : "r"(a), "r"(b), "r"(c)); return r; }
__device__ __forceinline__ uint32_t bf2_amax(uint32_t a, uint32_t b) { uint32_t r; asm("max.NaN.xorsign.abs.bf16x2 %0, %1, %2;" : "=r"(r) : "r"(a), "r"(b)); return r; }
__device__ __forceinline__ uint4 k_unpack(uint32_t l0, uint32_t l1, uint32_t h, uint32_t m1) {
    const uint32_t ha = h & 0x87878787u, hc = ha * m1 + h, hb = __funnelshift_l(hc, hc, 4);
    return make_uint4(__byte_perm(l0, ha, 0x5140), __byte_perm(l0, ha, 0x7362), __byte_perm(l1, hb, 0x5140), __byte_perm(l1, hb, 0x7362));
}
#define KR4(u, i) "+r"(kr[u][i].x), "+r"(kr[u][i].y), "+r"(kr[u][i].z), "+r"(kr[u][i].w)
#define KR6(u) KR4(u, 0), KR4(u, 1), KR4(u, 2), KR4(u, 3), KR4(u, 4), KR4(u, 5)
__device__ __forceinline__ void k_keep(uint4 (&kr)[8][6], const uint32_t (&c)[18], int e, uint32_t a) {
    asm volatile("{\nKT: .branchtargets K0, K1, K2, K3, K4, K5, K6, K7, K8, K9, K10, K11, K12, K13, K14, K15;\nbrx.idx.uni %210, KT;\n"
                 "K0: mov.b32 %12, %192; mov.b32 %13, %193; mov.b32 %14, %194; mov.b32 %15, %195; mov.b32 %16, %196; mov.b32 %17, %197; mov.b32 %18, %198; mov.b32 %19, %199; mov.b32 %20, %200; mov.b32 %21, %201; mov.b32 %22, %202; mov.b32 %23, %203; mov.b32 %24, %204; mov.b32 %25, %205; mov.b32 %26, %206; mov.b32 %27, %207; mov.b32 %28, %208; mov.b32 %29, %209; bra.uni KE;\n"
                 "K1: mov.b32 %30, %192; mov.b32 %31, %193; mov.b32 %32, %194; mov.b32 %33, %195; mov.b32 %34, %196; mov.b32 %35, %197; mov.b32 %36, %198; mov.b32 %37, %199; mov.b32 %38, %200; mov.b32 %39, %201; mov.b32 %40, %202; mov.b32 %41, %203; mov.b32 %42, %204; mov.b32 %43, %205; mov.b32 %44, %206; mov.b32 %45, %207; mov.b32 %46, %208; mov.b32 %47, %209; bra.uni KE;\n"
                 "K2: mov.b32 %48, %192; mov.b32 %49, %193; mov.b32 %50, %194; mov.b32 %51, %195; mov.b32 %52, %196; mov.b32 %53, %197; mov.b32 %54, %198; mov.b32 %55, %199; mov.b32 %56, %200; mov.b32 %57, %201; mov.b32 %58, %202; mov.b32 %59, %203; mov.b32 %60, %204; mov.b32 %61, %205; mov.b32 %62, %206; mov.b32 %63, %207; mov.b32 %64, %208; mov.b32 %65, %209; bra.uni KE;\n"
                 "K3: mov.b32 %66, %192; mov.b32 %67, %193; mov.b32 %68, %194; mov.b32 %69, %195; mov.b32 %70, %196; mov.b32 %71, %197; mov.b32 %72, %198; mov.b32 %73, %199; mov.b32 %74, %200; mov.b32 %75, %201; mov.b32 %76, %202; mov.b32 %77, %203; mov.b32 %78, %204; mov.b32 %79, %205; mov.b32 %80, %206; mov.b32 %81, %207; mov.b32 %82, %208; mov.b32 %83, %209; bra.uni KE;\n"
                 "K4: mov.b32 %84, %192; mov.b32 %85, %193; mov.b32 %86, %194; mov.b32 %87, %195; mov.b32 %88, %196; mov.b32 %89, %197; mov.b32 %90, %198; mov.b32 %91, %199; mov.b32 %92, %200; mov.b32 %93, %201; mov.b32 %94, %202; mov.b32 %95, %203; mov.b32 %96, %204; mov.b32 %97, %205; mov.b32 %98, %206; mov.b32 %99, %207; mov.b32 %100, %208; mov.b32 %101, %209; bra.uni KE;\n"
                 "K5: mov.b32 %102, %192; mov.b32 %103, %193; mov.b32 %104, %194; mov.b32 %105, %195; mov.b32 %106, %196; mov.b32 %107, %197; mov.b32 %108, %198; mov.b32 %109, %199; mov.b32 %110, %200; mov.b32 %111, %201; mov.b32 %112, %202; mov.b32 %113, %203; mov.b32 %114, %204; mov.b32 %115, %205; mov.b32 %116, %206; mov.b32 %117, %207; mov.b32 %118, %208; mov.b32 %119, %209; bra.uni KE;\n"
                 "K6: mov.b32 %120, %192; mov.b32 %121, %193; mov.b32 %122, %194; mov.b32 %123, %195; mov.b32 %124, %196; mov.b32 %125, %197; mov.b32 %126, %198; mov.b32 %127, %199; mov.b32 %128, %200; mov.b32 %129, %201; mov.b32 %130, %202; mov.b32 %131, %203; mov.b32 %132, %204; mov.b32 %133, %205; mov.b32 %134, %206; mov.b32 %135, %207; mov.b32 %136, %208; mov.b32 %137, %209; bra.uni KE;\n"
                 "K7: mov.b32 %138, %192; mov.b32 %139, %193; mov.b32 %140, %194; mov.b32 %141, %195; mov.b32 %142, %196; mov.b32 %143, %197; mov.b32 %144, %198; mov.b32 %145, %199; mov.b32 %146, %200; mov.b32 %147, %201; mov.b32 %148, %202; mov.b32 %149, %203; mov.b32 %150, %204; mov.b32 %151, %205; mov.b32 %152, %206; mov.b32 %153, %207; mov.b32 %154, %208; mov.b32 %155, %209; bra.uni KE;\n"
                 "K8: mov.b32 %156, %192; mov.b32 %157, %193; mov.b32 %158, %194; mov.b32 %159, %195; mov.b32 %160, %196; mov.b32 %161, %197; mov.b32 %162, %198; mov.b32 %163, %199; mov.b32 %164, %200; mov.b32 %165, %201; mov.b32 %166, %202; mov.b32 %167, %203; mov.b32 %168, %204; mov.b32 %169, %205; mov.b32 %170, %206; mov.b32 %171, %207; mov.b32 %172, %208; mov.b32 %173, %209; bra.uni KE;\n"
                 "K9: mov.b32 %174, %192; mov.b32 %175, %193; mov.b32 %176, %194; mov.b32 %177, %195; mov.b32 %178, %196; mov.b32 %179, %197; mov.b32 %180, %198; mov.b32 %181, %199; mov.b32 %182, %200; mov.b32 %183, %201; mov.b32 %184, %202; mov.b32 %185, %203; mov.b32 %186, %204; mov.b32 %187, %205; mov.b32 %188, %206; mov.b32 %189, %207; mov.b32 %190, %208; mov.b32 %191, %209; bra.uni KE;\n"
                 "K10: st.shared.v2.b32 [%211+75784], {%192, %193}; st.shared.v2.b32 [%211+76288], {%194, %195}; st.shared.v2.b32 [%211+76296], {%196, %197}; mov.b32 %0, %198; mov.b32 %1, %199; mov.b32 %2, %200; mov.b32 %3, %201; mov.b32 %4, %202; mov.b32 %5, %203; mov.b32 %6, %204; mov.b32 %7, %205; mov.b32 %8, %206; mov.b32 %9, %207; mov.b32 %10, %208; mov.b32 %11, %209; bra.uni KE;\n"
                 "K11: st.shared.v2.b32 [%211+0], {%192, %193}; st.shared.v2.b32 [%211+8], {%194, %195}; st.shared.v2.b32 [%211+512], {%196, %197}; st.shared.v2.b32 [%211+520], {%198, %199}; st.shared.v2.b32 [%211+1024], {%200, %201}; st.shared.v2.b32 [%211+1032], {%202, %203}; st.shared.v2.b32 [%211+1536], {%204, %205}; st.shared.v2.b32 [%211+1544], {%206, %207}; st.shared.v2.b32 [%211+2048], {%208, %209}; bra.uni KE;\n"
                 "K12: st.shared.v2.b32 [%211+2056], {%192, %193}; st.shared.v2.b32 [%211+2560], {%194, %195}; st.shared.v2.b32 [%211+2568], {%196, %197}; st.shared.v2.b32 [%211+24576], {%198, %199}; st.shared.v2.b32 [%211+24584], {%200, %201}; st.shared.v2.b32 [%211+25088], {%202, %203}; st.shared.v2.b32 [%211+25096], {%204, %205}; st.shared.v2.b32 [%211+25600], {%206, %207}; st.shared.v2.b32 [%211+25608], {%208, %209}; bra.uni KE;\n"
                 "K13: st.shared.v2.b32 [%211+26112], {%192, %193}; st.shared.v2.b32 [%211+26120], {%194, %195}; st.shared.v2.b32 [%211+26624], {%196, %197}; st.shared.v2.b32 [%211+26632], {%198, %199}; st.shared.v2.b32 [%211+27136], {%200, %201}; st.shared.v2.b32 [%211+27144], {%202, %203}; st.shared.v2.b32 [%211+49152], {%204, %205}; st.shared.v2.b32 [%211+49160], {%206, %207}; st.shared.v2.b32 [%211+49664], {%208, %209}; bra.uni KE;\n"
                 "K14: st.shared.v2.b32 [%211+49672], {%192, %193}; st.shared.v2.b32 [%211+50176], {%194, %195}; st.shared.v2.b32 [%211+50184], {%196, %197}; st.shared.v2.b32 [%211+50688], {%198, %199}; st.shared.v2.b32 [%211+50696], {%200, %201}; st.shared.v2.b32 [%211+51200], {%202, %203}; st.shared.v2.b32 [%211+51208], {%204, %205}; st.shared.v2.b32 [%211+51712], {%206, %207}; st.shared.v2.b32 [%211+51720], {%208, %209}; bra.uni KE;\n"
                 "K15: st.shared.v2.b32 [%211+73728], {%192, %193}; st.shared.v2.b32 [%211+73736], {%194, %195}; st.shared.v2.b32 [%211+74240], {%196, %197}; st.shared.v2.b32 [%211+74248], {%198, %199}; st.shared.v2.b32 [%211+74752], {%200, %201}; st.shared.v2.b32 [%211+74760], {%202, %203}; st.shared.v2.b32 [%211+75264], {%204, %205}; st.shared.v2.b32 [%211+75272], {%206, %207}; st.shared.v2.b32 [%211+75776], {%208, %209}; \nKE:\n}"
                 : KR6(0), KR6(1), KR6(2), KR6(3), KR6(4), KR6(5), KR6(6), KR6(7)
                 : "r"(c[0]), "r"(c[1]), "r"(c[2]), "r"(c[3]), "r"(c[4]), "r"(c[5]), "r"(c[6]), "r"(c[7]), "r"(c[8]), "r"(c[9]), "r"(c[10]), "r"(c[11]), "r"(c[12]), "r"(c[13]), "r"(c[14]), "r"(c[15]), "r"(c[16]), "r"(c[17]), "r"(e), "r"(a) : "memory");
}
__device__ __forceinline__ uint32_t smem_base() { extern __shared__ __align__(1024) unsigned char smem[]; return (uint32_t)__cvta_generic_to_shared(smem); }
__device__ __forceinline__ void k_rare(uint4 v0, uint4 v1, uint4 v2, uint4 v3, uint4 v4, uint4 v5, uint32_t odd, int e, int warp, int lane) {
    const uint32_t sb = smem_base(), g = lane >> 2, t = lane & 3, st = sb + SM_BAR + warp * 96 + 80;
    uint32_t lt; asm volatile("mov.u32 %0, %lanemask_lt;" : "=r"(lt));
    const uint4 v[6] = {v0, v1, v2, v3, v4, v5};
    odd <<= 6;
#pragma unroll
    for (int i = 0; i < 6; i++) if (v[i].x | v[i].y | v[i].z | v[i].w) odd |= 1u << i;
    odd = __reduce_or_sync(~0u, odd);
    uint32_t n = odd >= 64 ? NEXC + 1 : __shfl_sync(~0u, lds32(st), 0);
#pragma unroll 1
    for (; odd && n <= NEXC; odd &= odd - 1) {
        const int i = __ffs(odd) - 1;
#pragma unroll
        for (int k = 1; k < 6; k++) if (i == k) v0 = v[k];
#pragma unroll 1
        for (int k = 0; k < 4; k++, v0.x = v0.y, v0.y = v0.z, v0.z = v0.w) {
            const uint32_t who = __ballot_sync(~0u, v0.x), at = n + __popc(who & lt);
            sts64(v0.x && at < NEXC ? sb + SM_EXC + warp * 128 + at * 8 : st + 8, v0.x, (e * 32 + g * 4) << 16 | (((k & 1) * 4 + t) * 48 + i * 8 + (k >> 1) * 4));
            n += __popc(who);
        }
    }
    const uint32_t bad = lds32(st + 4);
    __syncwarp();
    if (n <= NEXC) sts32(st, n);
    else {
        sts32(st + 4, bad | 1u << e);
        asm volatile("st.shared.u8 [%0], %1;" :: "r"(sb + SM_SC + warp * 128 + g * 16 + (e & 3) * 4 + (e >> 2)), "r"(0) : "memory");
    }
    __syncwarp();
}
template <int K> __device__ __forceinline__ uint32_t& word(uint4& v) { if constexpr (K == 0) return v.x; else if constexpr (K == 1) return v.y; else if constexpr (K == 2) return v.z; else return v.w; }
__device__ __forceinline__ void add_if(bool p, float& d, float a, float b) {
    asm volatile("{\n.reg .pred p;\nsetp.ne.u32 p, %3, 0;\n@p add.f32 %0, %1, %2;\n}" : "+f"(d) : "f"(a), "f"(b), "r"((uint32_t)p));
}
__device__ __forceinline__ float warp_max(float v) {
#pragma unroll
    for (int o = 16; o; o >>= 1) v = fmaxf(v, shx(v, o));
    return v;
}
__device__ __forceinline__ float warp_sum(float v) {
#pragma unroll
    for (int o = 16; o; o >>= 1) v += shx(v, o);
    return v;
}
template <int PITCH> __device__ __forceinline__ void ll_look(const u64* buf, u64 (&w)[4]) {
#pragma unroll
    for (int i = 0; i < 4; i++) w[i] = ld_rlx(buf + i * PITCH);
}
template <int PITCH> __device__ __forceinline__ float ll_gather(const u64* buf, uint32_t tag, u64 (&w)[4]) {
    auto miss = [&]() {
        uint32_t a, b;
        asm("lop3.b32 %0, %1, %2, %3, 0x7e;" : "=r"(a) : "r"(ll_tag(w[0])), "r"(ll_tag(w[1])), "r"(tag));
        asm("lop3.b32 %0, %1, %2, %3, 0x7e;" : "=r"(b) : "r"(ll_tag(w[2])), "r"(ll_tag(w[3])), "r"(tag));
        return __any_sync(~0u, a | b);
    };
    int it = 0;
    goto check;
again:
    ll_look<PITCH>(buf, w);
check:
    if (miss() & (++it < SPIN)) goto again;
    return (ll_val(w[0]) + ll_val(w[1])) + (ll_val(w[2]) + ll_val(w[3]));
}
__device__ __forceinline__ float sum8(uint32_t a, int pitch) {
    float s[8];
#pragma unroll
    for (int w = 0; w < 8; w++) s[w] = ldsf(a + w * pitch);
    return ((s[0] + s[1]) + (s[2] + s[3])) + ((s[4] + s[5]) + (s[6] + s[7]));
}
__device__ __forceinline__ float sum5(float a, float b, float c, float d, float e) { return ((a + b) + (c + d)) + e; }
__device__ __forceinline__ float ln_part(uint2 xp, int lane) {
    const float x0 = bf_lo(xp.x), x1 = bf_hi(xp.x), x2 = bf_lo(xp.y), x3 = bf_hi(xp.y);
    const float s1 = (x0 + x1) + (x2 + x3), s2 = (x0 * x0 + x1 * x1) + (x2 * x2 + x3 * x3);
    return ((lane & 16) ? s2 : s1) + shx((lane & 16) ? s1 : s2, 16);
}
__device__ __forceinline__ float ln_rstd(float mean, float msq) { return rsq(fmaxf(msq - mean * mean, 0.f) + 1e-5f); }
__device__ __forceinline__ float score(const uint4 (&v)[6], const uint4 (&qf)[3]) {
    float d[2][4];
#pragma unroll
    for (int j = 0; j < 2; j++) d[j][0] = d[j][1] = d[j][2] = d[j][3] = 0.f;
#pragma unroll
    for (int i = 0; i < 3; i++) { mma(d[0], v[2 * i], qf[i].x, qf[i].y); mma(d[1], v[2 * i + 1], qf[i].z, qf[i].w); }
    return (d[0][0] + d[0][3]) + (d[1][0] + d[1][3]);
}
__device__ __forceinline__ float k_side(uint32_t sb, uint2 x) {
    const uint32_t qq = lds32(sb + SM_VEC + (x.y & 0xffff));
    return (bf_lo(x.x) * bf_lo(qq) + bf_hi(x.x) * bf_hi(qq)) * 0x1p-64f;
}
__device__ __forceinline__ void k_fix(const __nv_bfloat16* k, uint32_t bad, int warp, int lane) {
    const uint32_t sb = smem_base(), g = lane >> 2, sa = sb + SM_PART + warp * 768 + 256;
    const uint2 x = lds64(sb + SM_EXC + warp * 128 + (lane & 15) * 8);
    if ((int)x.y >= 0x40000000 && lane < 16) asm volatile("red.shared.add.f32 [%0], %1;" :: "r"(sa + ((x.y >> 16) & 511)), "f"(k_side(sb, x)) : "memory");
    __syncwarp();
#pragma unroll 1
    for (bad &= 0xffff; bad; bad &= bad - 1) {
        const int e = __ffs(bad) - 1;
        const __nv_bfloat16* kp = k + (e * 256 + (g >> 1) + 4 * (g & 1)) * DH + (lane & 3) * 8;
        uint4 v[6], qf[3];
#pragma unroll
        for (int i = 0; i < 6; i++) v[i] = *reinterpret_cast<const uint4*>(kp + i * 32);
#pragma unroll
        for (int i = 0; i < 3; i++) qf[i] = lds128(sb + SM_VEC + (lane & 7) * 48 + i * 16);
        stsf(sa + e * 32 + g * 4, score(v, qf) * 0x1p-64f);
    }
    __syncwarp();
}
constexpr float CS = 0.07216878364870322f * 1.4426950408889634f;
__device__ __forceinline__ void head_weight(const u64* a, u64 pm, u64 pl, int layer, int lane) {
    const uint32_t sb = smem_base(), tag = lds32(sb + SM_EPOCH) * 4 + 2 + 2 * layer;
#pragma unroll 1
    for (int it = 0; it < SPIN; it++) {
        if (__all_sync(~0u, ll_tag(pm) == tag && ll_tag(pl) == tag)) break;
        ld_rlx2(a, pm, pl);
    }
    const float f = ex2((ll_val(pm) - warp_max(ll_val(pm))) * CS);
    const float w = f * rcp(warp_sum(f * ll_val(pl)));
    if (lane < 8) stsf(sb + SM_FAC + lane * 4, w);
}
constexpr uint32_t ONES = 0x3f803f80u;

__global__ void __launch_bounds__(NTHR, 1) fused_kernel(const __grid_constant__ Params P) {
    const uint32_t sb = smem_base();
    const int bx = blockIdx.x;
    if (__all_sync(~0u, threadIdx.x >= NTHR - 32) && elect()) {
        asm volatile("mbarrier.init.shared::cta.b64 [%0], 1;" :: "r"(sb + SM_CBAR + CB_WQ * 8));
        asm volatile("mbarrier.init.shared::cta.b64 [%0], 1;" :: "r"(sb + SM_CBAR + 80));
        asm volatile("fence.mbarrier_init.release.cluster;" ::: "memory");
        mbar_expect(sb + SM_CBAR + CB_WQ * 8, 5 * HALF);
        mbar_expect(sb + SM_CBAR + 80, HALF);
        tma3(sb, &P.tm[TM_KH], 0, (bx >> 2) * SK + (SK - WIN) + (bx & 3) * 64, sb + SM_CBAR + 80, POL_FIRST);
#pragma unroll 1
        for (int i = 0; i < 5; i++) tma3(sb + SM_WQR + (i == 4 ? 0 : i + 1) * HALF, &P.tm[TM_WQ], (bx >> 2) * 3, (bx & 3) * 160 + i * 32, sb + SM_CBAR + CB_WQ * 8, POL_FIRST);
    }
    __syncwarp();
    int id = bx * NTHR + threadIdx.x, tid, lane, g, t, key, warp, cta, mlp, rowc, roww, j40;
    uint32_t maskA, maskB, barw, subw, prow;
    auto fresh = [&]() {
        const int cw = __shfl_sync(~0u, id >> 5, 0);
        id = pin(id); tid = id & 255; lane = id & 31; g = lane >> 2; t = lane & 3; key = (g >> 1) + 4 * (g & 1);
        const uint32_t m = (g & 1) ? 0xffff0000u : 0x0000ffffu;
        maskA = (g & 2) ? 0u : m; maskB = (g & 2) ? m : 0u;
        warp = cw & 7; cta = cw >> 3;
        mlp = (cta & 3) == 3 ? 96 : (cta >> 2) * 3 + (cta & 3);
        rowc = (cta >> 2) * SK + (SK - WIN) + (cta & 3) * 64; roww = rowc + warp * 8;
        j40 = (cta & 3) * 40;
        barw = sb + SM_BAR + warp * 96; subw = sb + warp * SUB; prow = sb + SM_PART + warp * 768;
    };
    fresh();
    auto fresh_lane = [&]() { id = pin(id); tid = id & 255; lane = id & 31; g = lane >> 2; t = lane & 3; };
    auto pinf = [&](float v) { return __uint_as_float(pin(__float_as_uint(v) | (id >> 16))); };

    TSTAMP(0);
    if (tid == 64) { uint32_t now; asm volatile("mov.u32 %0, %globaltimer_lo;" : "=r"(now)); sts32(sb + SM_T0, now); }

    const CUtensorMap* tmk = reinterpret_cast<const CUtensorMap*>(__shfl_sync(~0u, (u64)&P.tm[0] + (lane >> 5), 0));
    auto c4 = [&]() { return 32 * min(warp, 4) + 16 * (t >> 1) + 2 * g + (t & 1); };
    auto xcol = [&](int i, int tt) { return (i < 2 ? 64 * i + 8 * warp : 128 + 8 * (warp >> 1)) + 2 * tt; };
    uint2 xp;
    uint32_t px[3], small;
    auto issue_first = [&](int j) {
        mbar_expect(sb + SM_CBAR + 80 + j * 8, HALF);
        tma3(sb + j * HALF, tmk + TM_KH, 0, rowc + (j >> 1) * 256 + (j & 1) * 32, sb + SM_CBAR + 80 + j * 8, POL_FIRST);
    };
    if (elect()) {
        if (warp != 2) asm volatile("mbarrier.init.shared::cta.b64 [%0], 1;" :: "r"(sb + SM_CBAR + 64 + warp * 8));
#pragma unroll
        for (int i = 0; i < 9; i++) asm volatile("mbarrier.init.shared::cta.b64 [%0], 1;" :: "r"(barw + i * 8));
        asm volatile("mbarrier.init.shared::cta.b64 [%0], 1;" :: "r"(sb + SM_CBAR + warp * 8));
        asm volatile("mbarrier.init.shared::cta.b64 [%0], 1;" :: "r"(sb + SM_CBAR + 128 + warp * 8));
        if (warp < 3) asm volatile("mbarrier.init.shared::cta.b64 [%0], %1;" :: "r"(sb + SM_CBAR + 192 + warp * 8), "r"(warp == 2 ? 8 : 1));
        sts64(barw + 80, 0, 0);
        asm volatile("fence.mbarrier_init.release.cluster;" ::: "memory");
        asm volatile("prefetch.tensormap [%0];" :: "l"(tmk + warp) : "memory");
    }
    __syncwarp();
    asm volatile("ld.global.nc.v2.u32 {%0,%1}, [%2];" : "=r"(xp.x), "=r"(xp.y) : "l"(P.x + 4 * c4()) : "memory");
#pragma unroll
    for (int i = 0; i < 3; i++) asm volatile("ld.global.nc.u32 %0, [%1];" : "=r"(px[i]) : "l"(P.x + 4 * j40 + xcol(i, t)) : "memory");
    asm volatile("ld.relaxed.gpu.global.u32 %0, [%1];" : "=r"(small) : "l"(lane < 16 ? (const void*)(P.b1 + min(mlp, 95) * 16 + (lane & 14)) : (const void*)&P.g->epoch) : "memory");
    if (tid < NCB + 8) sts64(sb + SM_CNT + tid * 8, 0, 0);
    unsigned char* accg = reinterpret_cast<unsigned char*>(__shfl_sync(~0u, (u64)P.g->acc + (lane >> 5), 0));
    auto release = [&](const uint4& tw) {
        uint32_t old;
        __syncwarp();
        asm volatile("atom.relaxed.cta.shared.add.u32 %0, [%1], 1;" : "=r"(old) : "r"(sb + SM_CNT + (tw.x & 0xf8)) : "memory");
        return old;
    };
    auto refill = [&](const uint4& tw, uint32_t old) {
        if (__any_sync(~0u, (old & 127) == 127 && (tw.y & 2))) {
            wait_until(lds32(sb + SM_T0) + tw.z);
            if (elect()) issue_half(tw.y, sb, rowc, cta, tmk);
            __syncwarp();
        }
    };
    __syncthreads();
    auto issue_paced = [&](int j0, int j1) {
        if (warp >= j0 && warp < j1) {
            wait_until(lds32(sb + SM_T0) + PACES + warp * PACE / 2);
            if (elect()) issue_first(warp);
            __syncwarp();
        }
    };

    uint32_t offV0, offV2;
    auto calc_offsets = [&]() {
        offV0 = subw + (6 * t) * 128 + ((g ^ ((6 * t) & 7)) << 4);
        offV2 = subw + (6 * t + 2) * 128 + ((g ^ ((6 * t + 2) & 7)) << 4);
    };
    calc_offsets();

    auto load_v = [&](uint4 (&v)[6], uint32_t so) {
        v[0] = lds128(offV0 + so); v[1] = lds128((offV0 ^ 16) + so + 128); v[2] = lds128(offV2 + so);
        v[3] = lds128((offV2 ^ 16) + so + 128); v[4] = lds128((offV0 ^ 64) + so + 512); v[5] = lds128((offV0 ^ 80) + so + 640);
    };
    auto issue_v = [&](auto I, int dw, uint32_t done = ~0u) {
        constexpr Step c = SCH.st[I.value];
        const uint32_t bar = barw + dw * 96 + c.slot * 8;
        mbar_expect(bar, done & SUB);
        tma_v(subw + dw * SUB + c.slot * TILE, tmk, roww * 3 + dw * 24 + c.unit * 768, bar);
    };
    auto reads_done = [&]() { __syncwarp(); return lds32(sb + SM_M1); };
    auto refill2 = [&](auto I, uint32_t done = ~0u) { __syncwarp(); if (elect()) issue_v(I, 0, done); };
    uint4 wq0[6], wqh[3], wq1[6];
    auto load_wq1 = [&](int i) { wq1[i] = lds128((i == 2 ? offV2 : i == 3 ? (offV2 ^ 16) + 128 : (offV0 ^ (i * 16)) + i * 128) + SM_WQ + TILE); };
    auto load_wq = [&]() {
        load_v(wq0, SM_WQ);
        const uint32_t so = SM_WQR - ((warp + 1) >> 1) * SUB;
        wqh[0] = lds128(((warp & 1) ? (offV2 ^ 16) + 128 : offV0) + so);
        wqh[1] = lds128(((warp & 1) ? (offV0 ^ 64) + 512 : (offV0 ^ 16) + 128) + so);
        wqh[2] = lds128(((warp & 1) ? (offV0 ^ 80) + 640 : offV2) + so);
    };
    uint4 kr[8][6];
    const unsigned char* rap;
    u64 rw[2];
    auto look_rw = [&]() { rw[0] = ld_rlx(rap); rw[1] = ld_rlx(rap + 20 * acc_pitch(1)); };
    auto q_proj = [&](auto L, uint32_t (&p)[3], uint32_t pst) {
        if (L.value == 0 && g >= 4) p[0] = p[1] = p[2] = ONES;
        float a[3][4], b[3][4];
        const uint32_t dH = __byte_perm(p[2], 0, (warp & 1) ? 0x3232 : 0x1010);
        const uint32_t dA = __byte_perm(p[0], 0, 0x1010), dB = __byte_perm(p[0], 0, 0x3232), dC = __byte_perm(p[1], 0, 0x1010), dD = __byte_perm(p[1], 0, 0x3232);
#pragma unroll
        for (int i = 0; i < 3; i++) load_wq1(i);
#pragma unroll
        for (int j = 0; j < 3; j++) { a[j][0] = a[j][1] = a[j][2] = a[j][3] = 0.f; mma(a[j], wq0[j], dA & maskA, dA & maskB); }
#pragma unroll
        for (int j = 0; j < 3; j++) { b[j][0] = b[j][1] = b[j][2] = b[j][3] = 0.f; mma(b[j], wq0[j + 3], dB & maskA, dB & maskB); }
#pragma unroll
        for (int j = 0; j < 3; j++) mma(a[j], wqh[j], dH & maskA, dH & maskB);
#pragma unroll
        for (int i = 3; i < 6; i++) load_wq1(i);
#pragma unroll
        for (int j = 0; j < 3; j++) mma(b[j], wq1[j], dC & maskA, dC & maskB);
#pragma unroll
        for (int j = 0; j < 3; j++) mma(a[j], wq1[j + 3], dD & maskA, dD & maskB);
#pragma unroll
        for (int j = 0; j < 3; j++) {
            if (L.value) {
#pragma unroll
                for (int k = 0; k < 2; k++) { a[j][k] += b[j][k]; add_if(t & 2, a[j][k], a[j][k + 2], b[j][k + 2]); }
                sts64f(pst + j * 256, a[j][0], a[j][1]);
            } else sts128f(pst + j * 256, a[j][0] + b[j][0], a[j][1] + b[j][1], a[j][2] + b[j][2], a[j][3] + b[j][3]);
        }
        CSTAMP(23, __float_as_uint(a[2][1]));
        uint32_t tag;
        if (L.value) tag = lds32(sb + SM_EPOCH) * 4 + 3;
        u64* pub = L.value ? &P.g->ll[cta][tid] : &P.g->l0[cta][tid];
        if (L.value == 0) asm volatile("fence.proxy.async.shared::cta;" ::: "memory");
        TSTAMPL(21);
        __syncthreads();
        if (!L.value) tag = lds32(sb + SM_EPOCH) * 4 + 1;
#pragma unroll 1
        for (int k = 0; k < 2 - L.value; k++) st_rlx_if(tid < 192, pub + k * 192, ll_pack(sum8(sb + (k ? SM_CSP : SM_PART) + tid * 4, 768), tag));
        TSTAMPL(23);
            CSTAMP(24, tag);
    };
    auto ln_stats = [&]() {
        float ss = ln_part(xp, lane);
        ss += shx(ss, 8); ss += shx(ss, 4); ss += shx(ss, 2); ss += shx(ss, 1);
        stsf(sb + SM_STAT + min(warp, 5) * 8 + (lane >> 4) * 4, ss);
    };
    auto ln_final = [&](float& mean, float& rstd) {
        float2 v[5];
#pragma unroll
        for (int w = 0; w < 5; w++) v[w] = lds64f(sb + SM_STAT + w * 8);
        mean = sum5(v[0].x, v[1].x, v[2].x, v[3].x, v[4].x) * (1.f / D_MODEL);
        const float msq = sum5(v[0].y, v[1].y, v[2].y, v[3].y, v[4].y) * (1.f / D_MODEL);
        rstd = ln_rstd(mean, msq);
        stsf(sb + SM_FXS, msq);
    };
    auto q_addr = [&](int d) { return sb + SM_VEC + (((d >> 1) & 1) * 4 + ((d >> 3) & 3)) * 48 + (d >> 5) * 8 + ((d >> 2) & 1) * 4 + (d & 1) * 2; };
    {
#pragma unroll
        for (int u = 0; u < 8; u++)
#pragma unroll
            for (int i = 0; i < 6; i++) kr[u][i] = lds128(sb + SM_CS + (u * 6 + i) * 16);
        issue_paced(1, NIM);
        ln_stats();
        if (tid == 16) { sts32(sb + SM_EPOCH, small); sts32(sb + SM_M1, ~0u); }
        else if (tid < 16) sts32(sb + SM_B1 + tid * 4, (tid & 1) ? small & 0xffff0000u : small << 16);
        mbar_wait(sb + SM_CBAR + CB_WQ * 8, 0);
        load_wq();
        q_proj(IC<0>{}, px, sb + (t < 2 ? SM_PART : SM_CSP) + warp * 768 + (8 * g + 4 * (t & 1)) * 4);
    }
    {
        uint32_t offQ, offL;
        auto calc_ql = [&]() {
            offQ = pin(sb + SM_VEC + (lane & 7) * 48);
            offL = pin(subw + lane * 16);
        };

        auto issue_w = [&](auto L, int which) {
            const uint32_t bar = sb + SM_CBAR + (CB_W1 + which) * 8;
            if (mlp == 96) asm volatile("mbarrier.arrive.shared::cta.b64 _, [%0];" :: "r"(bar) : "memory");
            else {
                mbar_expect(bar, 20480);
                if (which) {
                    tma3(sb + (L.value ? 3 * TILE : SM_W2), tmk + TM_W2, 0, mlp * 16, bar, POL_FIRST);
                    if (!L.value) tma3_pf(tmk + TM_W2, 0, mlp * 16, POL_NORMAL);
                    if (!L.value) asm volatile("cp.async.bulk.prefetch.L2.global.L2::cache_hint [%0], 20480, %1;" :: "l"(P.w1 + mlp * 10240), "l"((u64)POL_NORMAL << 32) : "memory");
                }
                else asm volatile("cp.async.bulk.tensor.3d.shared::cluster.global.mbarrier::complete_tx::bytes.L2::cache_hint [%0], [%1, {%2, %3, %3}], [%4], %5;"
                                  :: "r"(sb + (L.value ? 2 * TILE : SM_W1)), "l"(tmk + TM_W1), "r"(mlp * 16), "r"(0), "r"(bar), "l"((u64)POL_FIRST << 32) : "memory");
            }
        };
        float acc[3][4];
        auto load_q = [&](uint4 (&qf)[3]) {
#pragma unroll
            for (int i = 0; i < 3; i++) qf[i] = lds128(offQ + i * 16);
        };
        auto softmax = [&](float S0, float S1, float S2, float S3) {
            int mi = __float_as_int(fmaxf(fmaxf(S0, S1), fmaxf(S2, S3)));
            mi = __reduce_max_sync(~0u, mi ^ ((mi >> 31) & 0x7fffffff));
            const float mrun = __int_as_float(mi ^ ((mi >> 31) & 0x7fffffff));
            const float p0 = ex2((S0 - mrun) * CS), p1 = ex2((S1 - mrun) * CS), p2 = ex2((S2 - mrun) * CS), p3 = ex2((S3 - mrun) * CS);
            const uint32_t pa = pack_bf(p0, p1), pb = pack_bf(p2, p3), pw = prow + 256 + (key >> 1) * 80 + t * 4 + (key & 1) * 2;
            sts16(pw, pa); sts16(pw + 16, pa >> 16); sts16(pw + 32, pb); sts16(pw + 48, pb >> 16);
            __syncwarp();
#pragma unroll
            for (int j = 0; j < 3; j++) acc[j][0] = acc[j][1] = acc[j][2] = acc[j][3] = 0.f;
            return make_float2(mrun, (p0 + p1) + (p2 + p3));
        };
        auto pv = [&](const uint4 (&v)[6], uint32_t pp) {
            const uint32_t dA = __byte_perm(pp, 0, 0x1010), dB = __byte_perm(pp, 0, 0x3232);
            mma(acc[0], v[0], dA & maskA, dA & maskB); mma(acc[1], v[1], dA & maskA, dA & maskB); mma(acc[2], v[2], dA & maskA, dA & maskB);
            mma(acc[0], v[3], dB & maskA, dB & maskB); mma(acc[1], v[4], dB & maskA, dB & maskB); mma(acc[2], v[5], dB & maskA, dB & maskB);
        };
        auto sa = [&]() { return prow + 256 + t * 32 + g * 4; };
        auto pass1 = [&]() {
            issue_paced(NIM, NI1);
            fresh();
            calc_ql();
            __syncthreads();
            sts64(prow + lane * 8, xp.x, xp.y);
            int e = 0;
            const uint4* tab = P.tile + (warp >> 2);
            uint4 tw = tab[0];
            uint32_t ka[3];
#pragma unroll
            for (int j = 0; j < 3; j++) ka[j] = pin(subw + key * 384 + j * 128 + ((t ^ ((3 * key + j) & 7)) << 4));
            auto load_k = [&](uint4 (&v)[6], uint32_t so) {
#pragma unroll
                for (int i = 0; i < 6; i++) v[i] = lds128(((i & 1) ? ka[i >> 1] ^ 64 : ka[i >> 1]) + so);
            };
            const uint32_t s0 = pin(prow + 256 + g * 4), sca = pin(sb + SM_SC + warp * 128 + g * 16);
#pragma unroll 1
            do {
                const uint4 tn = tab[2 * e + 2];
                uint4 v[6], qf[3];
                if (tw.x & (G_A | G_B | G_C)) {
                    if ((tw.x & G_A) && warp == 7 && elect()) {
                        mbar_expect(sb + SM_CBAR + CB_SNAP * 8, HALF);
                        asm volatile("cp.async.bulk.shared::cluster.global.mbarrier::complete_tx::bytes [%0], [%1], 12288, [%2];"
                                     :: "r"(sb + SM_SNAP), "l"(&P.g->l0[cta & ~3][0]), "r"(sb + SM_CBAR + CB_SNAP * 8) : "memory");
                    }
                    if (tw.x & G_B) {
                        if (warp < 6) {
                            mbar_wait(sb + SM_CBAR + CB_SNAP * 8, 0);
                            float qc[2] = {0.f, 0.f}, mean, rstd;
#pragma unroll 1
                            for (int k = 0; k < 2; k++) {
                                u64 qw[4];
#pragma unroll
                                for (int i = 0; i < 4; i++) { const uint2 x = lds64(sb + SM_SNAP + i * 3072 + k * 1536 + tid * 8); qw[i] = x.x | (u64)x.y << 32; }
                                qc[0] = qc[1];
                                qc[1] = ll_gather<384>(&P.g->l0[cta & ~3][k * 192 + tid], lds32(sb + SM_EPOCH) * 4 + 1, qw);
                            }
                            ln_final(mean, rstd);
                            stsf(sb + SM_CS + tid * 4, qc[1]);
                            const float q = (qc[0] - mean * qc[1]) * rstd;
                            sts16(q_addr(tid), pack_bf(q, q));
                        }
                        __syncthreads();
                        if (warp == 7 && elect()) issue_half(UC<load_word(12)>::value, sb, rowc, cta, tmk);
                        TSTAMP(2);
                    }
                    if (tw.x & G_C) {
                        load_k(v, (e - LATEAT) * TILE);
                        load_q(qf);
                        stsf(s0 + (e - LATEAT) * 32, score(v, qf));
                    }
                }
                load_q(qf);
                mbar_wait(sb + SM_CBAR + (tw.x & 0xf8), tw.x >> 31);
                TRACE(e);
                load_k(v, tw.x & 0x3f000);
                const uint32_t old = release(tw);
                const float s = score(v, qf);
                uint32_t m;
                {
                    uint32_t a[6];
#pragma unroll
                    for (int i = 0; i < 6; i++) a[i] = bf2_amax(bf2_amax(v[i].x, v[i].y), bf2_amax(v[i].z, v[i].w));
                    m = bf2_amax(bf2_amax(bf2_amax(a[0], a[1]), bf2_amax(a[2], a[3])), bf2_amax(a[4], a[5]));
                }
                m = bf2_amax(m, m >> 16) & 0x7f80;
                m = max(m, __shfl_xor_sync(~0u, m, 1));
                stsf(s0 + e * 32, s);
                m = max(m, __shfl_xor_sync(~0u, m, 2));
                refill(tw, old);
                const uint32_t b = min(max(m, 15u << 7) - (15u << 7), 126u << 7);
                const uint32_t dn = ((127u << 7) - b) * 0x10001u, up = ((127u << 7 | 0x8000u) + b) * 0x10001u;
                uint32_t c[18], any = m > (141u << 7);
#pragma unroll
                for (int i = 0; i < 6; i++) {
                    const uint32_t y0 = bf2_mul(v[i].x, dn), y1 = bf2_mul(v[i].y, dn), y2 = bf2_mul(v[i].z, dn), y3 = bf2_mul(v[i].w, dn);
                    v[i] = make_uint4(bf2_fma(y0, up, v[i].x), bf2_fma(y1, up, v[i].y), bf2_fma(y2, up, v[i].z), bf2_fma(y3, up, v[i].w));
                    any |= v[i].x | v[i].y;
                    any |= v[i].z | v[i].w;
                    const uint32_t hb = __byte_perm(y2, y3, 0x7531);
                    c[3 * i] = __byte_perm(y0, y1, 0x6420); c[3 * i + 1] = __byte_perm(y2, y3, 0x6420);
                    c[3 * i + 2] = __byte_perm(y0, y1, 0x7531) | __funnelshift_r(hb, hb, 4);
                }
                asm volatile("st.shared.u8 [%0], %1;" :: "r"(sca + (e & 3) * 4 + (e >> 2)), "r"((b >> 7) + 63) : "memory");
                const bool rare = __any_sync(~0u, any);
                k_keep(kr, c, e, offL);
                if (rare) k_rare(v[0], v[1], v[2], v[3], v[4], v[5], m > (141u << 7), e, warp, lane);
                tw = tn;
            } while (++e < 16);
            asm volatile("fence.proxy.async.shared::cta;" ::: "memory");
            __syncwarp();
            TSTAMP(10);
            fresh(); calc_offsets();
            offV0 = pin(offV0); offV2 = pin(offV2);
            {
                const uint2 st = lds64(barw + 80);
                const uint32_t xa = sb + SM_EXC + warp * 128 + (lane & 15) * 8 + 4;
                uint32_t pos = lds32(xa), lt;
                asm volatile("mov.u32 %0, %lanemask_lt;" : "=r"(lt));
                if (lane >= st.x) pos = 0x80000000u;
                const bool dup = (__match_any_sync(~0u, pos >> 16) & lt) && lane < st.x;
                if (lane < 16) sts32(xa, dup ? pos | 0x40000000u : pos);
                if (__any_sync(~0u, dup)) sts32(barw + 84, st.y | 0x10000u);
                const float2 ml = softmax(ldsf(sa()), ldsf(sa() + 128), ldsf(sa() + 256), ldsf(sa() + 384));
                sts64f(sb + SM_ML + warp * 8, ml.x, warp_sum(ml.y));
            }
            u64 pm = 0, pl = 0;
#pragma unroll 1
            do {
                const uint4 tn = tab[2 * e + 2];
                if (tw.x & (G_A | G_B | G_C)) {
                    if (tw.x & G_A) {
                        if (lane < 24) st_rlx(&P.g->ll[cta][warp * 24 + lane], 0ull);
                        else if (lane < 28) st_rlx(&P.g->ll[cta][168 + warp * 4 + lane], ll_pack(ldsf(sb + SM_ML + warp * 8 + (lane & 1) * 4), lds32(sb + SM_EPOCH) * 4 + 2));
                    }
                    if (warp == 0 && cta < 80 && elect()) {
                        if (tw.x & G_A) {
#pragma unroll 1
                            for (int k = 0; k < 8; k++) {
                                const int r = (cta & 1) * 2 + (k >> 2);
                                asm volatile("cp.async.bulk.global.shared::cta.bulk_group [%0], [%1], 64;"
                                             :: "l"(P.g->acc + r * ACC_BYTES + ((cta >> 1) * acc_pitch(r) & ~127) + (k & 3) * 64), "r"(sb + SM_ZERO) : "memory");
                            }
                            asm volatile("cp.async.bulk.commit_group;" ::: "memory");
                        }
                        if (tw.x & G_B) asm volatile("cp.async.bulk.wait_group 0;\nred.relaxed.gpu.global.add.u32 [%0], 1;" :: "l"(&P.g->zeroed) : "memory");
                    }
                    if (warp == 2) {
                        if (tw.x & G_B) ld_rlx2(&P.g->ll[cta ^ (lane >> 3)][192 + (lane & 7) * 4], pm, pl);
                        if (tw.x & G_C) head_weight(&P.g->ll[cta ^ (lane >> 3)][192 + (lane & 7) * 4], pm, pl, 0, lane);
                    }
                    __syncwarp();
                }
                const uint32_t pp = lds32(prow + 256 + t * 80 + ((tw.x >> 20) & 255));
                mbar_wait(sb + SM_CBAR + (tw.x & 0xf8), tw.x >> 31);
                TRACE(e);
                uint4 v[6];
                load_v(v, tw.x & 0x3f000);
                refill(tw, release(tw));
                pv(v, pp);
                tw = tn;
            } while (++e < 32);
        };
        uint32_t osa, ora, owa, orow, otag;
        u64* olb;
        float xc;
        auto o_setup = [&](auto L) {
            fresh();
            const int lz = lane, d = warp * 24 + min(lz, 23);
            osa = pin(prow + ((lz >> 2) * 8 + (lz & 1) * 4 + (lz & 2)) * 4);
            ora = pin(sb + SM_PART + d * 4);
            olb = pin(&P.g->ll[cta & ~3][d]);
            orow = pin((lz & 1) + 2 * (lz & 2) + 2 * (lz >> 4));
            owa = pin(sb + SM_RING + warp * 1536 + orow * 64 + ((((lz >> 2) & 3) ^ (orow >> 1)) << 4));
            otag = lds32(sb + SM_EPOCH) * 4 + 2 + 2 * L.value;
            uint32_t x; asm volatile("ld.shared.u16 %0, [%1];" : "=r"(x) : "r"(prow + ((cta & 1) * 16 + (lz >> 3) * 4 + (cta & 2) + ((lz >> 2) & 1)) * 8 + (lz & 3) * 2) : "memory");
            xc = bf_lo(x) * (1.f / 32);
        };
        auto wo_at = [&](auto A) {
            constexpr uint32_t x = WOP ^ A.value * 0x11111;
            if constexpr (A.value > 0 && ((x - 0x11111) & ~x & 0x88888) != 0) {
                if ((WOP >> (4 * warp) & 15) == A.value) {
                    mbar_wait(sb + SM_CBAR + CB_REL * 8, 0);
                    if (elect()) {
                        const uint32_t bar = sb + SM_CBAR + (CB_WO + warp) * 8;
                        mbar_expect(bar, HALF);
                        tma3(sb + SM_RING + (warp + (warp < 2 ? 3 : -2)) * HALF, tmk + TM_WO, (cta & 3) + 4 * warp, (cta >> 2) * DH, bar, POL_FIRST);
                    }
                    __syncwarp();
                }
            }
        };
        static_assert(ring_hs(64) == 3, "wo");
        auto pass2 = [&]() {
            constexpr IC<1> L{};
            refill2(IC<4>{});
            uint4 tb[8][3];
            auto load_tb = [&](auto I) {
#pragma unroll
                for (int i = 0; i < 3; i++) tb[I.value][i] = lds128(offL + (I.value >> 1) * TILE + ((I.value & 1) * 3 + i) * 512);
            };
            uint32_t m1, m1n, done;
            const u64* qb = &P.g->ll[cta & ~3][min(tid, 191)];
            {
                uint32_t x[2];
                fx2_wait<2>([&](int i) { return rap + i * 20 * acc_pitch(1); }, look_rw, rw, sb + SM_MSQ, ldsf(sb + SM_MSQ + 4), x);
                xp = make_uint2(x[0], x[1]);
                CSTAMP(25, xp.y);
            }
            ln_stats();
            u64 qw[4];
            offL = subw + lane * 16;
            static_for<0, NPRE>(load_tb);
            m1n = m1 = reads_done();
            ll_look<256>(qb, qw);
            const float cs = ldsf(sb + SM_CS + min(tid, 191) * 4);
            const uint32_t qtag = lds32(sb + SM_EPOCH) * 4 + 3, qa = pin(q_addr(min(tid, 191)));
            fresh_lane();
            offQ = sb + SM_VEC + (lane & 7) * 48; offL = subw + lane * 16;
            __syncthreads();
            auto vwait = [&](auto I) { mbar_wait(barw + IC<SCH.st[I.value].slot>::value * 8, IC<SCH.st[I.value].par>::value); };
            bool ok;
            {
                float mean, rstd;
                ln_final(mean, rstd);
                const float sq = shx(rstd * 0x1p64f, 0), q0 = shx(-mean * cs * sq, 0);
                CSTAMP(26, __float_as_uint(q0));
                refill2(IC<5>{}, m1);
                sts64(prow + lane * 8, xp.x, xp.y);
                sts128f(prow + 256 + lane * 16, 0.f, 0.f, 0.f, 0.f);
                const float q = ll_gather<256>(qb, qtag, qw) * sq + q0;
                sts16(qa, pack_bf(q, q));
                TSTAMPL(24);
                CSTAMP(27, __float_as_uint(q));
            }
            __syncthreads();
            uint4 qf[3];
            load_q(qf);
            CSTAMP(28, qf[0].x);
            float S[4], d[2][4];
            auto vload = [&](auto I) {
                constexpr int p = I.value;
                constexpr Step c = SCH.st[p];
                load_v(kr[p & 7], c.slot * TILE);
                if constexpr (c.next >= 0 && p >= NPARK) {
                    static_assert(c.next - 9 < c.mma0, "the slot's last tile has been multiplied");
                    refill2(IC<c.next>{});
                }
                if constexpr (p == 11) { __syncwarp(); if (elect()) asm volatile("mbarrier.arrive.shared::cta.b64 _, [%0];" :: "r"(sb + SM_CBAR + CB_REL * 8) : "memory"); }
            };
            static_for<0, 96>([&](auto F) {
                constexpr int f = F.value, i = f % 6, u = kunit(f / 6), w = 3 * f % 12;
                uint4 (&src)[3] = *reinterpret_cast<uint4 (*)[3]>(f < 32 ? &tb[f / 4 & 7][0] : &kr[(f / 8 + 4) & 7][(f / 4 & 1) * 3]);
                const uint4 a = k_unpack(word<w % 4>(src[w / 4]), word<(w + 1) % 4>(src[(w + 1) / 4]), word<(w + 2) % 4>(src[(w + 2) / 4]), m1);
                if constexpr (f % 8 == (f < 32 ? RF0 : RF1) + M1D) m1 = m1n;
                if constexpr (f % 4 == 3 && f / 4 + NPRE < 8) {
                    load_tb(IC<f / 4 + NPRE>{});
                    if constexpr (f % 8 == 7) done = reads_done();
                }
                if constexpr (f >= 8 && f < 32 && f % 8 == RF0) { refill2(IC<5 + f / 8>{}, done); m1n = lds32(sb + SM_M1); }
                if constexpr (f >= 40 && f % 8 == RF1) {
                    if constexpr (PARKS >> (f / 8 - 5) & 1) { refill2(IC<SCH.st[popc(PARKS & ((1 << (f / 8 - 5)) - 1))].next>{}, done); m1n = lds32(sb + SM_M1); }
                }
                if constexpr (i < 2) d[i][0] = d[i][1] = d[i][2] = d[i][3] = 0.f;
                mma(d[i & 1], a, (i & 1) ? qf[i / 2].z : qf[i / 2].x, (i & 1) ? qf[i / 2].w : qf[i / 2].y);
                if constexpr (i == 5) {
                    if constexpr (u == 11 || ((u & 3) == 0 && u != 8)) S[u >> 2] = (d[0][0] + d[0][3]) + (d[1][0] + d[1][3]);
                    else add_if(t == (u & 3), S[u >> 2], d[0][0] + d[0][3], d[1][0] + d[1][3]);
                    if constexpr (f < 64) S[u >> 2] = shx(S[u >> 2], 0);
                }
                if constexpr (f == 31) { fresh(); calc_offsets(); ok = mbar_test(barw + IC<SCH.st[0].slot>::value * 8, 0); }
                if constexpr (f == 48) {
                    const uint2 x = lds64(sb + SM_EXC + warp * 128 + (lane & 15) * 8);
                    const float c = k_side(sb, x);
                    if (x.y < 0x40000000u) stsf(prow + 256 + (x.y >> 16), c);
                }
                if constexpr (f >= 32 && f % 8 == 7) {
                    if constexpr (PARKS >> (f / 8 - 4) & 1) {
                        constexpr int p = popc(PARKS & ((1 << (f / 8 - 4)) - 1));
                        if (!ok) vwait(IC<p>{});
                        vload(IC<p>{});
                        done = reads_done();
                        ok = mbar_test(barw + IC<SCH.st[p + 1].slot>::value * 8, IC<SCH.st[p + 1].par>::value);
                    }
                }
            });
            if constexpr (PARKS & 0x80) refill2(IC<SCH.st[NPARK - 1].next>{}, done);
            uint32_t bad = lds32(barw + 84);
            const uint32_t sc = lds32(sb + SM_SC + tid * 4);
            __syncwarp();
            if (bad) k_fix(P.k + (size_t)roww * DH, bad, warp, lane);
            TSTAMP(30);
            CSTAMP(29, __float_as_uint(S[2]));
            const float2 ml = softmax(S[0] * __uint_as_float((sc & 255) << 23) + ldsf(sa()), S[1] * __uint_as_float((sc & 0xff00) << 15) + ldsf(sa() + 128),
                                      S[2] * __uint_as_float((sc & 0xff0000) << 7) + ldsf(sa() + 256), S[3] * __uint_as_float((sc >> 24) << 23) + ldsf(sa() + 384));
            uint4 pq[4];
#pragma unroll
            for (int j = 0; j < 4; j++) pq[j] = lds128(prow + 256 + t * 80 + j * 16);
            TSTAMP(1);
            CSTAMP(30, pq[3].w);
            if (!ok) vwait(IC<NPARK>{});
            float ac2[3][4];
#pragma unroll
            for (int j = 0; j < 3; j++) ac2[j][0] = ac2[j][1] = ac2[j][2] = ac2[j][3] = 0.f;
            const uint32_t sl = (g & 1) ? 0x1044 : 0x4410, sh = (g & 1) ? 0x3244 : 0x4432;
            const uint32_t sA0 = (g & 2) ? 0x4444 : sl, sA1 = (g & 2) ? sl : 0x4444, sB0 = (g & 2) ? 0x4444 : sh, sB1 = (g & 2) ? sh : 0x4444;
            u64 pm = 0, pl = 0;
            static_for<NPARK, 16>([&](auto I) {
                constexpr int p = I.value;
                static_assert(p - SCH.st[p].mma0 < 8, "buffer in use");
                vload(I);
                if constexpr (p < 15) ok = mbar_test(barw + IC<SCH.st[p + 1].slot>::value * 8, IC<SCH.st[p + 1].par>::value);
                static_for<SCH.st[p].mma0, SCH.st[p].mma0 + SCH.st[p].nmma>([&](auto J) {
                    constexpr int u = SCH.st[J.value].unit;
                    const uint32_t pp = word<u & 3>(pq[u >> 2]), a0 = __byte_perm(pp, 0, sA0), a1 = __byte_perm(pp, 0, sA1), b0 = __byte_perm(pp, 0, sB0), b1 = __byte_perm(pp, 0, sB1);
#pragma unroll
                    for (int j = 0; j < 3; j++) mma(acc[j], kr[J.value & 7][j], a0, a1);
#pragma unroll
                    for (int j = 0; j < 3; j++) mma(ac2[j], kr[J.value & 7][j + 3], b0, b1);
                });
                if constexpr (p == NPARK) {
                    const float l = warp_sum(ml.y);
                    st_rlx_if(lane < 4, &P.g->ll[cta][192 + warp * 4 + lane], ll_pack((lane & 1) ? l : ml.x, lds32(sb + SM_EPOCH) * 4 + 4));
                }
                if constexpr (p == HWAT) { if (warp == 6) ld_rlx2(&P.g->ll[cta ^ (lane >> 3)][192 + (lane & 7) * 4], pm, pl); }
                if constexpr (p == 13) o_setup(L);
                if constexpr (p == HWAT + 2) { if (warp == 6) head_weight(&P.g->ll[cta ^ (lane >> 3)][192 + (lane & 7) * 4], pm, pl, 1, lane); }
                wo_at(IC<p - 10>{});
                if constexpr (p < 15) { if (!ok) mbar_wait(barw + IC<SCH.st[p + 1].slot>::value * 8, IC<SCH.st[p + 1].par>::value); TRACE(33 + p); }
            });
#pragma unroll
            for (int j = 0; j < 3; j++)
#pragma unroll
                for (int k = 0; k < 2; k++) { acc[j][k] += ac2[j][k]; add_if(t & 2, acc[j][k], acc[j][k + 2], ac2[j][k + 2]); }
        };

        const unsigned char* ap;
        uint32_t hpa, hsa, hst, w2a, la;
        uint2 b2v;
        float b1v, cs1;
        auto mlp_global = [&](auto L) {
            const int cz = c4();
            ap = accg + 2 * L.value * ACC_BYTES + (cz >> 2) * acc_pitch(0) + (cz & 3) * 16;
            if (L.value) ap = pin(ap);
            rap = pin(accg + (2 * L.value + 1) * ACC_BYTES + (cz >> 3) * acc_pitch(2 * L.value + 1) + (cz & 7) * 8);
            asm volatile("ld.global.nc.v2.u32 {%0,%1}, [%2];" : "=r"(b2v.x), "=r"(b2v.y) : "l"(P.b2 + 4 * cz));
        };
        auto mlp_shared = [&](auto L) {
            const int lz = lane;
            hpa = pin(sb + SM_PART + warp * 256 + ((lz & 2) * 4 + (lz >> 2)) * 16 + (L.value ? 0 : (lz & 1) * 4));
            hsa = pin(sb + SM_PART + (lz & 15) * 16); hst = pin(sb + SM_PART + (lz & 15) * 16 + warp * 256 + 8 + (lz >> 4) * 4);
            w2a = pin(sb + (L.value ? 3 * TILE : SM_W2) + ((lz & 3) * 10 + 2 * warp) * 128 + (((lz >> 2) ^ ((2 * lz + 2 * warp) & 6)) << 4));
            la = sb + (L.value ? 2 * TILE : SM_W1) + warp * 4096 + (lz & 4) * 512 + (lz & 2) * 64 + (lz & 1) * 32 + (lz >> 4) * 64 + ((((lz >> 3) ^ (lz >> 1)) & 1) << 4);
            b1v = ldsf(sb + SM_B1 + (lz & 15) * 4);
            if (L.value) { la = pin(la); cs1 = ldsf(sb + SM_ML + (lz & 15) * 4); }
            else fresh();
        };
        uint32_t pa;
        unsigned char* rop;
        uint32_t wpa;
        float sc1;
        auto sum_setup = [&](auto L) {
            const int lz = lane, word = warp * 128 + (cta & 3) * 32 + lz;
            wpa = pin(sb + SM_RING + warp * 1536 + ((((lz >> 2) * 8 + (lz & 1) * 4) * 4) ^ ((((lz >> 1) ^ (lz >> 4)) & 1) ? 256 + 64 : 0)));
            sc1 = pinf(fx2_scale(ldsf(sb + SM_FXS)) * 0.25f);
            pa = pin(sb + SM_RING + warp * 256 + ((lz * 4) ^ ((warp & 1) * 64)));
            rop = pin(accg + 2 * L.value * ACC_BYTES + (word >> 4) * acc_pitch(0) + (word & 15) * 4);
        };
        auto out_proj = [&](auto L) {
            TSTAMP2(3);
            CSTAMP(0, __float_as_uint(acc[2][1]));
            __syncwarp();
#pragma unroll
            for (int j = 0; j < 3; j++) {
                if (L.value == 0 && (t & 2)) { acc[j][0] = acc[j][2]; acc[j][1] = acc[j][3]; }
                sts64f(osa + 256 * j, acc[j][0], acc[j][1]);
            }
            __syncthreads();
            {
                float s[8];
#pragma unroll
                for (int w = 0; w < 8; w++) s[w] = ldsf(ora + w * 768);
                const uint4 fa = lds128(sb + SM_FAC), fb = lds128(sb + SM_FAC + 16);
            CSTAMP(1, __float_as_uint(s[0]));
                const float own = ((s[0] * __uint_as_float(fa.x) + s[1] * __uint_as_float(fa.y)) + (s[2] * __uint_as_float(fa.z) + s[3] * __uint_as_float(fa.w))) +
                                  ((s[4] * __uint_as_float(fb.x) + s[5] * __uint_as_float(fb.y)) + (s[6] * __uint_as_float(fb.z) + s[7] * __uint_as_float(fb.w)));
                st_rlx_if(lane < 24, olb + (cta & 3) * 256, ll_pack(own, otag));
            CSTAMP(2, __float_as_uint(own));
            }
            TSTAMPL(29);
            if (L.value == 0) fresh();
            if (L.value) wo_at(IC<6>{});
            if (L.value == 0 && warp == 7) {
#pragma unroll 1
                for (int it = 0; it < SPIN; it++) {
                    uint32_t v; asm volatile("ld.acquire.gpu.global.u32 %0, [%1];" : "=r"(v) : "l"(&P.g->zeroed) : "memory");
                    if (__all_sync(~0u, v == (lds32(sb + SM_EPOCH) + 1) * 80)) break;
                }
            }
            constexpr int NW = L.value ? NWO1 : 3;
            uint4 v[5][3];
            u64 ow[4];
            auto read_wo = [&](auto J) {
#pragma unroll
                for (int p = 0; p < 3; p++) v[J.value][p] = lds128(((J.value & 1) ? owa ^ 144 : owa) + ring_hs(64 + J.value) * HALF + p * 512);
            };
            static_for<0, NW>([&](auto J) {
                if (L.value && J.value == 0) { sum_setup(L); maskA = pin(maskA); maskB = pin(maskB); }
                if (J.value == 2) { ll_look<256>(olb, ow); if (L.value) { mlp_shared(L); mlp_global(L); } }
                mbar_wait(sb + SM_CBAR + (CB_WO + J.value) * 8, L.value);
                read_wo(J);
                if (L.value == 0 && J.value == 2) {
                    __syncwarp();
                    if (elect() && cnt_inc(sb + SM_CNT + CB_W1 * 8, 7) == 7) issue_w(L, 0);
                    __syncwarp();
                }
                if (L.value == 1 && J.value == 2) {
                    if (warp == 7 && elect()) issue_w(L, 0);
                    __syncwarp();
                }
            });
            sched_fence();
            const float o = ll_gather<256>(olb, otag, ow);
            CSTAMP(3, __float_as_uint(o));
            TSTAMP2(4);
            bool ok = true;
            if constexpr (NW < 5) ok = mbar_test(sb + SM_CBAR + (CB_WO + 4) * 8, L.value);
            if constexpr (NW < 4) ok &= mbar_test(sb + SM_CBAR + (CB_WO + 3) * 8, L.value);
            const uint32_t od = pack_bf(o, o);
            uint32_t oa[3], ob[3];
#pragma unroll
            for (int p = 0; p < 3; p++) { const uint32_t op = __shfl_sync(~0u, od, 8 * p + orow); oa[p] = op & maskA; ob[p] = op & maskB; }
            CSTAMP(4, oa[2]);
            float y[5][4];
#pragma unroll
            for (int j = 0; j < 5; j++) y[j][0] = y[j][1] = y[j][2] = y[j][3] = 0.f;
            auto rest = [&]() {
                if (!ok) static_for<NW, 5>([&](auto J) { mbar_wait(sb + SM_CBAR + (CB_WO + J.value) * 8, L.value); });
                static_for<NW, 5>(read_wo);
                __syncwarp();
            };
            if (L.value) rest();
#pragma unroll
            for (int p = 0; p < 3; p++)
#pragma unroll
                for (int j = 0; j < NW; j++) mma(y[j], v[j][p], oa[p], ob[p]);
            if (!L.value) { rest(); sum_setup(L); }
#pragma unroll
            for (int p = 0; p < 3; p++)
#pragma unroll
                for (int j = NW; j < 5; j++) mma(y[j], v[j][p], oa[p], ob[p]);
            CSTAMP(5, __float_as_uint(y[4][3]));
#pragma unroll
            for (int j = 0; j < 5; j += 2) {
                if (j < 4 && (t >> 1) != (g >> 2)) { y[j][0] = y[j + 1][0]; y[j][1] = y[j + 1][1]; y[j][2] = y[j + 1][2]; y[j][3] = y[j + 1][3]; }
                sts128f(wpa + j * 256, y[j]);
            }
            TSTAMP2(5);
        };
        u64 yw[2];
        bool wide;
        float msq = 0.f, yf[4] = {};
        auto mlp_part = [&](auto L) {
            bar_sync(0, 256);
            CSTAMP(6, __float_as_uint(sc1));
            const float s = (sum8(pa, 1536) + xc) + sum8(pa + 128, 1536), sm = s * sc1 + FX2_ONE;
            CSTAMP(7, __float_as_uint(s));
            const bool wide1 = !(fabsf(sm - FX2_ONE) < FX1LIM);
            asm volatile("red.relaxed.gpu.global.add.u32 [%0], %1;" :: "l"(rop), "r"(wide1 ? 0u : __float_as_uint(sm) * 128u + (1u - 0x4b400000u * 128u)) : "memory");
            const uint32_t c0 = clk();
            TSTAMP2(6);
            if (L.value == 0) bar_arrive(2, 256);
            if (wide1) {
                fx_send(rop + 64 + (lane & 15) * 4, s, ldsf(sb + SM_FXS), rop, 64);
                asm volatile("red.relaxed.gpu.global.add.u32 [%0], 1;" :: "l"(rop) : "memory");
            }
            __syncwarp();
            if (L.value == 1 && mlp == 96) { TDUMP(); asm volatile("exit;"); }
            uint4 wf[8], w2r[8];
            uint4 w;
            auto look = [&]() { asm volatile("ld.relaxed.gpu.global.v4.u32 {%0,%1,%2,%3}, [%4];" : "=r"(w.x), "=r"(w.y), "=r"(w.z), "=r"(w.w) : "l"(ap) : "memory"); };
            auto read_w1 = [&]() {
#pragma unroll
                for (int j = 0; j < 8; j++) wf[j] = ldsm_t(la + j * 256);
            };
            auto read_w2 = [&]() {
#pragma unroll
                for (int i = 0; i < 8; i++) w2r[i] = lds128(((i & 1) ? (w2a ^ 16) + 128 : w2a) + (i >> 1) * 5120);
            };
            const float inv = pinf(fx_inv(sc1) * (1.f / 128)), off = L.value ? pinf(fx_inv(sc1) * -0.25f) : inv * -32.f;
            if (L.value == 0) { fresh(); mlp_global(L); }
            mbar_wait(sb + SM_CBAR + CB_W1 * 8, L.value);
            if (L.value == 1) read_w1();
            while (clk() - c0 < AR1D);
            look();
            if (L.value == 0) { mlp_shared(L); read_w1(); bar_arrive(3, 256); }
            else { mbar_wait(sb + SM_CBAR + CB_W2 * 8, 1); read_w2(); }
            TSTAMPL(28);
            {
                sched_fence();
                auto miss = [&]() {
                    xp = make_uint2(pack_bf((float)(int)w.x * inv + off, (float)(int)w.y * inv + off), pack_bf((float)(int)w.z * inv + off, (float)(int)w.w * inv + off));
                    uint32_t a, b;
                    asm("lop3.b32 %0, %1, %2, 32, 0x7e;" : "=r"(a) : "r"(w.x), "r"(w.y));
                    asm("lop3.b32 %0, %1, %2, 32, 0x7e;" : "=r"(b) : "r"(w.z), "r"(w.w));
                    return __any_sync(~0u, (a | b) & 96);
                };
                if (miss()) {
                    int it = 0;
#pragma unroll 1
                    do {
                        if (!__any_sync(~0u, ~(w.x & w.y & w.z & w.w) & 32)) { xp.x = fx1_wide(ap, ldsf(sb + SM_FXS)); xp.y = fx1_wide(ap + 8, ldsf(sb + SM_FXS)); break; }
                        look();
                    } while (miss() & (++it < SPIN));
                }
                CSTAMP(8, w.w);
            }
            TSTAMP2(7);
            CSTAMP(9, xp.y);
            {
                bool ok = true;
                if (L.value == 0) ok = mbar_test(sb + SM_CBAR + CB_W2 * 8, 0);
                const bool ev = L.value || !(g & 1), od = L.value || (g & 1);
                const uint32_t e0 = ev ? xp.x : ONES, e1 = ev ? xp.y : ONES, o0 = od ? xp.x : ONES, o1 = od ? xp.y : ONES;
                float d[8][4];
#pragma unroll
                for (int j = 0; j < 8; j++) { d[j][0] = d[j][1] = d[j][2] = d[j][3] = 0.f; mma(d[j], wf[j], (j & 1) ? o0 : e0, (j & 1) ? o1 : e1); }
                float ss = ln_part(xp, lane);
                ss += shx(ss, 8); ss += shx(ss, 4);
                float r[4], dd;
#pragma unroll
                for (int k = 0; k < 4; k += 1 + L.value) r[k] = d[0][k] + d[1][k ^ 1];
#pragma unroll
                for (int j = 1; j < 4; j++)
#pragma unroll
                    for (int k = 0; k < 4; k += 1 + L.value) add_if(t == j, r[k], d[2 * j][k], d[2 * j + 1][k ^ 1]);
                CSTAMP(10, __float_as_uint(r[2]));
                if (L.value) {
                    dd = ((t & 2) ? r[2] : r[0]) + shx((t & 2) ? r[0] : r[2], 2);
                    ss += shx(ss, 2);
                    dd += shx(dd, 1);
                } else {
                    const float a = ((t & 1) ? r[1] : r[0]) + shx((t & 1) ? r[0] : r[1], 1), b = ((t & 1) ? r[3] : r[2]) + shx((t & 1) ? r[2] : r[3], 1);
                    ss += shx(ss, 2);
                    dd = ((t & 2) ? b : a) + shx((t & 2) ? a : b, 2);
                }
                ss += shx(ss, 1);
                stsf(hpa, dd);
                stsf(hst, ss);
                CSTAMP(11, __float_as_uint(dd + ss));
                if (!ok) mbar_wait(sb + SM_CBAR + CB_W2 * 8, L.value);
            }
            TSTAMPL(25);
            bar_sync(1, 160);
            uint4 hp[5];
#pragma unroll
            for (int w = 0; w < 5; w++) hp[w] = lds128(hsa + w * 256);
            CSTAMP(12, hp[0].x);
            auto hs = [&](auto K) { return sum5(__uint_as_float(word<K.value>(hp[0])), __uint_as_float(word<K.value>(hp[1])), __uint_as_float(word<K.value>(hp[2])),
                                                __uint_as_float(word<K.value>(hp[3])), __uint_as_float(word<K.value>(hp[4]))); };
            const float mean = hs(IC<2>{}) * (1.f / D_MODEL);
            msq = hs(IC<3>{}) * (1.f / D_MODEL);
            if (L.value == 0) cs1 = hs(IC<1>{});
            float hv = hs(IC<0>{}) - mean * cs1;
            CSTAMP(13, __float_as_uint(hv));
            const float sc2 = fx2_scale(msq), lim = fx_inv(sc2) * FX2LIM;
            if (L.value == 0) {
                read_w2();
                bar_arrive(4, 256);
                wide = false;
                if (mlp == 96) return;
            }
            hv = hv * ln_rstd(mean, msq) + b1v;
            CSTAMP(14, __float_as_uint(hv));
            hv = hv * rcp(1.f + ex2(hv * (-2.302208198f - 0.1029432397f * hv * hv)));
            const uint32_t hd = pack_bf(hv, hv);
            CSTAMP(15, hd);
            TSTAMPL(27);
            float ym[4][4];
#pragma unroll
            for (int i = 0; i < 2; i++) {
                ym[i][0] = ym[i][1] = ym[i][2] = ym[i][3] = 0.f;
                const float f = mlp < 64 ? 1.f / 64 : 0.f;
                ym[i + 2][0] = (bf_lo(xp.x) + bf_lo(b2v.x)) * f; ym[i + 2][1] = (bf_hi(xp.x) + bf_hi(b2v.x)) * f;
                ym[i + 2][2] = (bf_lo(xp.y) + bf_lo(b2v.y)) * f; ym[i + 2][3] = (bf_hi(xp.y) + bf_hi(b2v.y)) * f;
            }
#pragma unroll
            for (int i = 0; i < 4; i++) {
                const uint32_t hh = __shfl_sync(~0u, hd, 4 * i + t);
                mma(ym[(i & 1) * 2], w2r[2 * i], hh & maskA, hh & maskB);
                mma(ym[(i & 1) * 2 + 1], w2r[2 * i + 1], hh & maskA, hh & maskB);
            }
#pragma unroll
            for (int k = 0; k < 4; k++) { yf[k] = ym[0][k] + ym[2][k]; add_if(t & 2, yf[k], ym[1][k], ym[3][k]); }
            CSTAMP(16, __float_as_uint(yf[3]));
            yw[0] = fx2_pack(yf[0] * sc2 + FX2_ONE, yf[1] * sc2 + FX2_ONE); yw[1] = fx2_pack(yf[2] * sc2 + FX2_ONE, yf[3] * sc2 + FX2_ONE);
            wide = !(fmaxf(fmaxf(fabsf(yf[0]), fabsf(yf[1])), fmaxf(fabsf(yf[2]), fabsf(yf[3]))) < lim);
            if (wide) yw[0] = yw[1] = 0;
            if (L.value == 0) {
#pragma unroll
                for (int k = 0; k < 2; k++) asm volatile("red.relaxed.gpu.global.add.u64 [%0], %1;" :: "l"(rap + k * 20 * acc_pitch(1)), "l"(yw[k]) : "memory");
            }
        };
        auto send_wide = [&](int pitch) {
#pragma unroll 1
            for (int k = 0; k < 4; k++, yf[0] = yf[1], yf[1] = yf[2], yf[2] = yf[3]) {
                const unsigned char* a = rap + (k >> 1) * 20 * pitch;
                fx_send(a + 64 + (k & 1) * 64, yf[0], msq, a, 256);
            }
            yw[0] = yw[1] = 1;
        };

        pass1();
        o_setup(IC<0>{});
        out_proj(IC<0>{});
        uint32_t c0;
        if (warp < 5) {
            mlp_part(IC<0>{});
            c0 = clk() + (mlp == 96 ? PCD : 0);
            stsf(sb + SM_ML + (lane & 15) * 4, cs1);
            TSTAMP(8);
            if (__any_sync(~0u, wide)) {
                if (wide) {
                    send_wide(acc_pitch(1));
#pragma unroll
                    for (int k = 0; k < 2; k++) asm volatile("red.relaxed.gpu.global.add.u64 [%0], 1;" :: "l"(rap + k * 20 * acc_pitch(1)) : "memory");
                }
                __syncwarp();
            }
            fresh(); calc_offsets();
            load_wq();
        } else {
            bar_sync(0, 256);
            if (warp == 5 && elect()) {
                asm volatile("fence.proxy.async.shared::cta;" ::: "memory");
                issue_w(IC<0>{}, 1);
            }
            __syncwarp();
            fresh(); calc_offsets();
            load_wq();
#pragma unroll 1
            for (int ph = 0; ph < 3; ph++) {
                bar_sync(ph + 2, 256);
                c0 = clk();
                if (ph == 2) {
                    msq = sum5(ldsf(sb + SM_PART + 12), ldsf(sb + SM_PART + 268), ldsf(sb + SM_PART + 524), ldsf(sb + SM_PART + 780), ldsf(sb + SM_PART + 1036)) * (1.f / D_MODEL);
                    bar_arrive(5, 256);
                }
                if (elect()) {
                    asm volatile("fence.proxy.async.shared::cta;" ::: "memory");
                    const uint32_t gap = ph == 0 ? WG1 : ph == 1 ? WG2 : WG3;
                    uint32_t c1 = c0 + (ph == 0 ? WD1 : 0) + (warp - 5) * gap;
#pragma unroll 1
                    for (int k = warp + (ph == 0 ? -5 : ph == 1 ? 9 : 1); k < (ph == 0 ? 9 : ph == 1 ? 20 : 14); k += 3, c1 += 3 * gap) {
                        const int i = ph == 0 && k >= 6 ? k + 23 : k;
                        const uint32_t bar = sb + SM_BAR + (i & 7) * 96 + 32 + (i & 24);
                        while ((int)(clk() - c1) < 0);
                        mbar_expect(bar, SUB);
                        tma_v(sb + SM_RING + i * SUB, tmk,
                              rowc * 3 + (i & 7) * 24 + ((UC<SCH.st[0].unit | SCH.st[1].unit << 8 | SCH.st[2].unit << 16 | SCH.st[3].unit << 24>::value >> (i & 24)) & 15) * 768, bar);
                    }
                }
                __syncwarp();
            }
            c0 += PCD;
        }
        {
            constexpr IC<1> L{};
            fresh();
            const int col = xcol(g & 3, t), cw = j40 + (col >> 2);
            const unsigned char* xa = pin(accg + ACC_BYTES + ((cw >> 3) + (col & 2) * 10) * acc_pitch(1) + (cw & 7) * 8);
            const uint32_t pst = pin(prow + (g * 8 + (t & 1) * 4 + (t & 2)) * 4);
            const float inv = pinf(fx2_inv(msq));
            sts64f(sb + SM_MSQ, msq, inv);
            rap = pin(accg + ACC_BYTES + (c4() >> 3) * acc_pitch(1) + (c4() & 7) * 8);
            fresh();
            maskA = pin(maskA); maskB = pin(maskB);
            u64 w[1];
            uint32_t x1[1], x2[3];
            auto look = [&]() { w[0] = ld_rlx(xa); };
            if (warp < 5) bar_sync(5, 256);
            while ((int)(clk() - c0) < ARDELAY);
            look();
            while ((int)(clk() - c0) < ARDELAY + DPOST);
            if (warp < 5 && elect()) {
                issue_v(IC<3>{}, 0);
                if (warp < 4) issue_v(IC<2>{}, 4);
            }
            __syncwarp();
            fx2_wait<1>([&](int) { return xa; }, look, w, sb + SM_MSQ, inv, x1);
            if (warp < 5) look_rw(); else rw[0] = rw[1] = 96;
#pragma unroll
            for (int i = 0; i < 3; i++) x2[i] = __shfl_sync(~0u, x1[0], 4 * i + t);
            TSTAMP(9);
            CSTAMP(22, x2[2]);
            q_proj(L, x2, pst);
            pass2();
            out_proj(L);
            if (warp >= 5) {
                bar_arrive(0, 256);
                if (warp == 5 && elect()) issue_w(L, 1);
                TDUMP();
                return;
            }
            mlp_part(L);
            u64 old[2];
            auto add = [&]() {
#pragma unroll
                for (int k = 0; k < 2; k++) asm volatile("atom.relaxed.gpu.global.add.u64 %0, [%1], %2;" : "=l"(old[k]) : "l"(rap + k * 20 * acc_pitch(3)), "l"(yw[k]) : "memory");
            };
            add();
            uint32_t* op = pin(reinterpret_cast<uint32_t*>(P.out) + 2 * c4());
            const float inv2 = pinf(fx2_inv(msq));
            if (wide) { send_wide(acc_pitch(3)); add(); }
            TSTAMP(18);
            CSTAMP(17, hi32(yw[1]));
            __syncwarp();
            CSTAMP(18, lo32(old[0]) ^ lo32(old[1]));
#pragma unroll
            for (int k = 0; k < 2; k++) {
                yw[k] += old[k];
                asm volatile("{\n.reg .pred p;\nsetp.eq.u32 p, %2, 96;\n@p st.global.u32 [%0], %1;\n}"
                             :: "l"(op + k), "r"(fx2_get(yw[k], inv2)), "r"(lo32(yw[k]) & 511) : "memory");
            }
            if ((lo32(yw[0]) & 255) == 96 && tid == 0) P.g->epoch = lds32(sb + SM_EPOCH) + 1;
#pragma unroll
            for (int k = 0; k < 2; k++) if ((lo32(yw[k]) & 511) == 256 + 96) op[k] = fx2_wide(rap + k * 20 * acc_pitch(3), msq);
            TSTAMP(19);
            CSTAMP(19, lo32(yw[1]));
            TDUMP();
        }
    }
}

typedef CUresult (*EncodeFn)(CUtensorMap*, CUtensorMapDataType, cuuint32_t, void*, const cuuint64_t*, const cuuint64_t*, const cuuint32_t*,
                             const cuuint32_t*, CUtensorMapInterleave, CUtensorMapSwizzle, CUtensorMapL2promotion, CUtensorMapFloatOOBfill);

}

extern "C" void kernel_launch(void* const* d_in, const int* in_sizes, int n_in, void* d_out, int out_size) {
    (void)in_sizes; (void)n_in; (void)out_size;
    static EncodeFn enc = nullptr;
    static void* scratch = nullptr;
    if (!enc) {
        void* fn = nullptr;
        cudaDriverEntryPointQueryResult qr;
        cudaGetDriverEntryPoint("cuTensorMapEncodeTiled", &fn, cudaEnableDefault, &qr);
        enc = (EncodeFn)fn;
        cudaGetSymbolAddress(&scratch, g_scratch);
        cudaFuncSetAttribute(fused_kernel, cudaFuncAttributeMaxDynamicSharedMemorySize, SM_TOTAL);
    }
    Params P = {};
    auto map3 = [&](int m, int in, cuuint64_t d0, cuuint64_t d1, cuuint64_t d2, cuuint64_t s1, cuuint64_t s2, cuuint32_t b0, cuuint32_t b1, cuuint32_t b2,
                    CUtensorMapSwizzle sw, int promo) {
        const cuuint64_t dim[3] = {d0, d1, d2}, str[2] = {s1, s2};
        const cuuint32_t box[3] = {b0, b1, b2}, ones[3] = {1, 1, 1};
        enc(&P.tm[m], CU_TENSOR_MAP_DATA_TYPE_BFLOAT16, d2 ? 3 : 2, d_in[in], dim, str, box, ones, CU_TENSOR_MAP_INTERLEAVE_NONE, sw, (CUtensorMapL2promotion)promo,
            CU_TENSOR_MAP_FLOAT_OOB_FILL_NONE);
    };
    map3(TM_KH, 1, 64, 3, NHEAD * SK, 128, DH * 2, 64, 3, 32, CU_TENSOR_MAP_SWIZZLE_128B, 0);
    map3(TM_VH, 2, 64, 3, NHEAD * SK, 128, DH * 2, 64, 3, 32, CU_TENSOR_MAP_SWIZZLE_128B, 0);
    map3(TM_VP, 2, 64, 3, NHEAD * SK, 128, DH * 2, 8, 3, 32, CU_TENSOR_MAP_SWIZZLE_NONE, 0);
    map3(TM_V, 2, 64, NHEAD * SK * 3, 0, 128, 0, 64, 24, 0, CU_TENSOR_MAP_SWIZZLE_128B, 0);
    map3(TM_WO, 4, 32, 20, NHEAD * DH, 64, D_MODEL * 2, 32, 1, DH, CU_TENSOR_MAP_SWIZZLE_64B, 2);
    map3(TM_WOP, 4, 32, 20, NHEAD * DH, 64, D_MODEL * 2, 8, 1, DH, CU_TENSOR_MAP_SWIZZLE_NONE, 0);
    map3(TM_WQ, 3, 64, NHEAD * 3, D_MODEL, 128, NHEAD * DH * 2, 64, 3, 32, CU_TENSOR_MAP_SWIZZLE_128B, 0);
    map3(TM_W1, 6, DFF, 128, 5, DFF * 2, DFF * 256, 16, 128, 5, CU_TENSOR_MAP_SWIZZLE_32B, 2);
    map3(TM_W2, 8, 64, 10, DFF, 128, D_MODEL * 2, 64, 10, 16, CU_TENSOR_MAP_SWIZZLE_128B, 0);
    P.x = (const __nv_bfloat16*)d_in[0];
    P.k = (const __nv_bfloat16*)d_in[1];
    P.b1 = (const __nv_bfloat16*)d_in[7];
    P.b2 = (const __nv_bfloat16*)d_in[9];
    P.w1 = (const __nv_bfloat16*)d_in[6];
    P.out = (__nv_bfloat16*)d_out;
    P.g = (Scratch*)(((uintptr_t)scratch + ACC_BYTES - 1) & ~(uintptr_t)(ACC_BYTES - 1));
    for (int i = 0; i < 64; i++) P.tile[i] = make_uint4(SCH.tile[i][0], SCH.tile[i][1], SCH.tile[i][2], 0);
    fused_kernel<<<NCTA, NTHR, SM_TOTAL, cudaStreamPerThread>>>(P);
}
```

```cpp
#include <cuda_runtime.h>
#include <cuda_bf16.h>
#include <cuda.h>
#include <stdint.h>

namespace {

constexpr int D_MODEL = 640, NHEAD = 32, SK = 32768, DH = 192, WIN = 4096, DFF = 1536;
constexpr int NCTA = 128, NTHR = 256;
constexpr int TILE = 64 * DH * 2;
constexpr int HALF = TILE / 2;
constexpr int SUB = 8 * DH * 2;
constexpr int SM_RING = 4 * TILE;
constexpr int SM_W2 = SM_RING + 20480, SM_W1 = SM_W2 + 20480;
constexpr int SM_WQR = 6 * TILE + HALF, SM_WQ = 7 * TILE;
constexpr int SM_PART = 9 * TILE;
constexpr int SM_EXC = SM_PART + 6144;
constexpr int SM_SC = SM_EXC + 1024;
constexpr int SM_BAR = SM_SC + 1024;
constexpr int SM_VEC = SM_BAR + 768;
constexpr int SM_CS = SM_VEC + 384;
constexpr int SM_FAC = SM_CS + 768;
constexpr int SM_ML = SM_FAC + 32;
constexpr int SM_B1 = SM_ML + 64;
constexpr int SM_STAT = SM_B1 + 64;
constexpr int NCB = 28;
constexpr int CB_WO = 18, CB_W1 = 23, CB_W2 = 24, CB_SNAP = 25, CB_REL = 26, CB_WQ = 27;
constexpr int SM_CBAR = SM_STAT + 48;
constexpr int SM_CNT = SM_CBAR + NCB * 8;
constexpr int SM_ZERO = SM_CNT + NCB * 8;
constexpr int SM_EPOCH = SM_ZERO + 64;
constexpr int SM_FXS = SM_EPOCH + 4;
constexpr int SM_T0 = SM_FXS + 4;
constexpr int SM_M1 = SM_T0 + 4;
constexpr int SM_MSQ = SM_M1 + 4;
constexpr int SM_TS = SM_MSQ + 8;
constexpr int SM_TOTAL = 232448;
static_assert(SM_TS + 320 <= SM_TOTAL && SM_ZERO % 16 == 0, "smem");
constexpr int NEXC = 16;

constexpr int SPIN = 1 << 20;
enum { TM_V = 0, TM_KH = 1, TM_VH = 2, TM_WO = 3, TM_VP = 4, TM_WOP = 5, TM_W1 = 6, TM_W2 = 7, TM_WQ = 8 };
constexpr uint32_t POL_NORMAL = 0x16F00000u, POL_FIRST = 0x12F00000u;

#define PACE 980
#define PACE0 1500
#define PACES 1300
#define NI1 6
#define ETRIG 0x54321000
#define PFREE 66
#define SNAPAT 2
#define LATEAT 5
#define PUBAT 28
#define HW0 30
#define HW1 31
#define AR1D 250
#define ARDELAY 720
#define DPOST 200
#define PCD 350
#define WD1 100
#define WG1 140
#define WG2 120
#define WG3 65
#define VORD2 0x7685943a2b1cd0efull
#define VSLOT 0x1087654321087654ull
#define VTRIG 0xba73210
#define PARKS 0xa5
#define RF0 1
#define RF1 2
#define M1D 1
#define LAG0 12
#define NMMA 2
#define HWAT 12
#define WOP 0x44433
#define NWO1 4
#define FX1LIM 524288.f
#define FX2LIM 524288.f

constexpr uint32_t G_A = 1u << 28, G_B = 1u << 29, G_C = 1u << 30;
__host__ __device__ constexpr int ring_hs(int j) { return (j + 4) % 5; }
__host__ __device__ constexpr uint32_t load_word(int j) {
    if (j >= 64) return (uint32_t)(j - 64) << 20 | (SM_RING + ring_hs(j) * HALF) | TM_WO << 8 | (CB_WO + j - 64) << 3 | 2;
    const int e = j >> 1, isv = e >= 16, unit = e & 15;
    return (uint32_t)(unit * 256 + (j & 1) * 32) << 20 | (j < 8 ? j * HALF : SM_RING + ring_hs(j) * HALF) | (TM_KH + isv) << 8 | (j < 8 ? 10 + j : (j - 8) % 10) << 3 | 2 | !isv;
}
__host__ __device__ constexpr int popc(int v) { return v ? (v & 1) + popc(v >> 1) : 0; }
constexpr int NPARK = popc(PARKS), NPRE = 2;
constexpr int SM_SNAP = SM_RING + ring_hs(12) * HALF, SM_CSP = SM_RING + ring_hs(11) * HALF;
struct Step { int unit, slot, par, next, mma0, nmma; };
struct Sched { uint32_t tile[64][3]; Step st[16]; };
constexpr Sched make_sched() {
    Sched s{};
    for (int j = 0; j < 64; j++) {
        const int e = j >> 1;
        const uint32_t d = load_word(j);
        uint32_t w = (uint32_t)(j < 8 ? 0 : (j - 8) / 10 & 1) << 31 | (e & 15) * 4 << 20 | ((d & 0x3f000) - (j & 1) * HALF) | (d & 0xf8);
        if (e == PUBAT || e == SNAPAT) w |= G_A;
        if (e == HW0 || e == 4) w |= G_B;
        if ((e >= LATEAT && e < LATEAT + 4) || e == HW1) w |= G_C;
        s.tile[j][0] = w;
    }
    for (int j = NI1; j < 69; j++) {
        if (j == 12) continue;
        const int at = j < 12 ? (ETRIG >> (4 * (j - 4)) & 15) : j - 5;
        s.tile[at][1] = load_word(j);
        s.tile[at][2] = j >= PFREE ? 0 : PACE0 + j * PACE / 2;
    }
    int done = 0;
    for (int p = 0; p < 16; p++) {
        Step& c = s.st[p];
        c.unit = (int)(VORD2 >> (4 * p) & 15); c.slot = (int)(VSLOT >> (4 * p) & 15); c.par = p >= 9; c.next = -1;
        c.mma0 = done;
        if (p >= NPARK) { const int avail = p - done + (p >= LAG0); c.nmma = p == 15 ? 16 - done : (avail < NMMA ? avail : NMMA); done += c.nmma; }
    }
    for (int p = 9; p < 16; p++) s.st[VTRIG >> (4 * (p - 9)) & 15].next = p;
    return s;
}
constexpr Sched SCH = make_sched();
__host__ __device__ constexpr int kunit(int o) { return o < 5 ? o + 11 : o == 5 ? 10 : o - 6; }

template <int I> struct IC { static constexpr int value = I; };
template <uint32_t I> struct UC { static constexpr uint32_t value = I; };
template <int A, int B, class F> __device__ __forceinline__ void static_for(F&& f) {
    if constexpr (A < B) { f(IC<A>{}); static_for<A + 1, B>(f); }
}

typedef unsigned long long u64;
constexpr int ACC_BYTES = 65536;
__host__ __device__ constexpr int acc_pitch(int r) { return (r & 1) ? 832 : 256; }
struct alignas(1024) Scratch {
    unsigned char acc[4 * ACC_BYTES];
    u64 l0[NCTA][384];
    u64 ll[NCTA][256];
    alignas(128) unsigned epoch;
    alignas(128) unsigned zeroed;
};
__device__ __align__(1024) unsigned char g_scratch[sizeof(Scratch) + ACC_BYTES];

struct Params {
    CUtensorMap tm[9];
    const __nv_bfloat16 *x, *k, *b1, *b2, *w1;
    __nv_bfloat16* out;
    Scratch* g;
    uint4 tile[66];
};

#define TSTAMP(i)
#define TSTAMP2(i)
#define TSTAMPL(i)
#define TDUMP()
#define CSTAMP(i, x)
#define TRACE(i)

__device__ __forceinline__ void mbar_wait(uint32_t bar, uint32_t parity) {
    asm volatile("{\n.reg .pred p;\nLOOP:\nmbarrier.try_wait.parity.shared::cta.b64 p, [%0], %1;\n@!p bra.uni LOOP;\n}" :: "r"(bar), "r"(parity) : "memory");
}
__device__ __forceinline__ bool mbar_test(uint32_t bar, uint32_t parity) {
    uint32_t r;
    asm volatile("{\n.reg .pred p;\nmbarrier.test_wait.parity.shared::cta.b64 p, [%1], %2;\nselp.u32 %0, 1, 0, p;\n}" : "=r"(r) : "r"(bar), "r"(parity) : "memory");
    return __all_sync(~0u, r);
}
__device__ __forceinline__ bool elect() {
    uint32_t r;
    asm volatile("{\n.reg .pred p;\nelect.sync _|p, 0xffffffff;\nselp.u32 %0, 1, 0, p;\n}" : "=r"(r));
    return r != 0;
}
__device__ __forceinline__ void mbar_expect(uint32_t bar, uint32_t bytes) {
    asm volatile("mbarrier.arrive.expect_tx.shared::cta.b64 _, [%0], %1;" :: "r"(bar), "r"(bytes) : "memory");
}
__device__ __forceinline__ uint4 lds128(uint32_t a) {
    uint4 v; asm volatile("ld.shared.v4.u32 {%0,%1,%2,%3}, [%4];" : "=r"(v.x), "=r"(v.y), "=r"(v.z), "=r"(v.w) : "r"(a) : "memory"); return v;
}
__device__ __forceinline__ uint4 ldsm_t(uint32_t a) {
    uint4 v; asm volatile("ldmatrix.sync.aligned.m8n8.x4.trans.shared.b16 {%0,%1,%2,%3}, [%4];" : "=r"(v.x), "=r"(v.y), "=r"(v.z), "=r"(v.w) : "r"(a) : "memory"); return v;
}
__device__ __forceinline__ uint2 lds64(uint32_t a) {
    uint2 v; asm volatile("ld.shared.v2.u32 {%0,%1}, [%2];" : "=r"(v.x), "=r"(v.y) : "r"(a) : "memory"); return v;
}
__device__ __forceinline__ float2 lds64f(uint32_t a) { const uint2 v = lds64(a); return make_float2(__uint_as_float(v.x), __uint_as_float(v.y)); }
__device__ __forceinline__ uint32_t lds32(uint32_t a) {
    uint32_t v; asm volatile("ld.shared.u32 %0, [%1];" : "=r"(v) : "r"(a) : "memory"); return v;
}
__device__ __forceinline__ float ldsf(uint32_t a) { return __uint_as_float(lds32(a)); }
__device__ __forceinline__ void sts32(uint32_t a, uint32_t v) { asm volatile("st.shared.u32 [%0], %1;" :: "r"(a), "r"(v) : "memory"); }
__device__ __forceinline__ void stsf(uint32_t a, float v) { sts32(a, __float_as_uint(v)); }
__device__ __forceinline__ void sts16(uint32_t a, uint32_t v) { asm volatile("st.shared.u16 [%0], %1;" :: "r"(a), "h"((uint16_t)v) : "memory"); }
__device__ __forceinline__ void sts64(uint32_t a, uint32_t x, uint32_t y) { asm volatile("st.shared.v2.u32 [%0], {%1,%2};" :: "r"(a), "r"(x), "r"(y) : "memory"); }
__device__ __forceinline__ void sts64f(uint32_t a, float x, float y) { sts64(a, __float_as_uint(x), __float_as_uint(y)); }
__device__ __forceinline__ void sts128f(uint32_t a, float x, float y, float z, float w) {
    asm volatile("st.shared.v4.f32 [%0], {%1,%2,%3,%4};" :: "r"(a), "f"(x), "f"(y), "f"(z), "f"(w) : "memory");
}
__device__ __forceinline__ void mma(float (&c)[4], const uint4& a, uint32_t b0, uint32_t b1) {
    asm volatile("mma.sync.aligned.m16n8k16.row.col.f32.bf16.bf16.f32 {%0,%1,%2,%3}, {%4,%5,%6,%7}, {%8,%9}, {%0,%1,%2,%3};"
                 : "+f"(c[0]), "+f"(c[1]), "+f"(c[2]), "+f"(c[3]) : "r"(a.x), "r"(a.y), "r"(a.z), "r"(a.w), "r"(b0), "r"(b1));
}
__device__ __forceinline__ u64 ld_rlx(const void* p) {
    u64 a; asm volatile("ld.relaxed.gpu.global.u64 %0, [%1];" : "=l"(a) : "l"(p) : "memory"); return a;
}
__device__ __forceinline__ void ld_rlx2(const void* p, u64& a, u64& b) {
    asm volatile("ld.relaxed.gpu.global.v2.u64 {%0,%1}, [%2];" : "=l"(a), "=l"(b) : "l"(p) : "memory");
}
__device__ __forceinline__ void st_rlx(void* p, u64 a) { asm volatile("st.relaxed.gpu.global.u64 [%0], %1;" :: "l"(p), "l"(a) : "memory"); }
__device__ __forceinline__ u64 ll_pack(float v, uint32_t tag) { return ((u64)tag << 32) | __float_as_uint(v); }
__device__ __forceinline__ float ll_val(u64 w) { return __uint_as_float((uint32_t)w); }
__device__ __forceinline__ uint32_t ll_tag(u64 w) { return (uint32_t)(w >> 32); }
__device__ __forceinline__ float bf_lo(uint32_t u) { return __uint_as_float(u << 16); }
__device__ __forceinline__ float bf_hi(uint32_t u) { return __uint_as_float(u & 0xffff0000u); }
__device__ __forceinline__ uint32_t pack_bf(float lo, float hi) {
    uint32_t r; asm("cvt.rn.bf16x2.f32 %0, %1, %2;" : "=r"(r) : "f"(hi), "f"(lo)); return r;
}
__device__ __forceinline__ float ex2(float v) { float r; asm("ex2.approx.ftz.f32 %0, %1;" : "=f"(r) : "f"(v)); return r; }
__device__ __forceinline__ float rcp(float v) { float r; asm("rcp.approx.ftz.f32 %0, %1;" : "=f"(r) : "f"(v)); return r; }
__device__ __forceinline__ float rsq(float v) { float r; asm("rsqrt.approx.ftz.f32 %0, %1;" : "=f"(r) : "f"(v)); return r; }
__device__ __forceinline__ void bar_sync(int id, int n) { asm volatile("bar.sync %0, %1;" :: "r"(id), "r"(n) : "memory"); }
__device__ __forceinline__ uint32_t clk() { uint32_t c; asm volatile("mov.u32 %0, %clock;" : "=r"(c)); return c; }
__device__ __forceinline__ void sched_fence() { __syncwarp(); while (clk() == 0x9e3779b9u); }
__device__ __forceinline__ uint32_t pin(uint32_t v) { return __shfl_xor_sync(~0u, v, 0); }
__device__ __forceinline__ float shx(float v, int o) { return __shfl_xor_sync(~0u, v, o); }

__device__ __forceinline__ u64 fx_pack(float v, float scale) { return ((u64)__float2ll_rn(v * scale) & ~255ull) | 1ull; }
__device__ __forceinline__ float fx_scale(float meansq) {
    const int e = max(((int)(__float_as_uint(meansq) >> 23) - 127) >> 1, -6);
    return __uint_as_float((uint32_t)(127 + 32 - e) << 23);
}
__device__ __forceinline__ float fx_inv(float scale) { return __uint_as_float((254u << 23) - __float_as_uint(scale)); }
__device__ __forceinline__ uint32_t lo32(u64 w) { uint32_t l; asm("mov.b64 {%0, _}, %1;" : "=r"(l) : "l"(w)); return l; }
__device__ __forceinline__ int hi32(u64 w) { int h; asm("mov.b64 {_, %0}, %1;" : "=r"(h) : "l"(w)); return h; }
__device__ __forceinline__ float fx_val(u64 w) { return (float)hi32(w) * 4294967296.f + (float)lo32(w); }
constexpr float FX2_ONE = 12582912.f;
__device__ __forceinline__ float fx2_scale(float meansq) { return __uint_as_float((uint32_t)(127 + 16 - max(((int)(__float_as_uint(meansq) >> 23) - 127) >> 1, -100)) << 23); }
__device__ __forceinline__ u64 fx2_pack(float a, float b) {
    const uint32_t lo = __float_as_uint(a) * 512u + (1u - 0x4b400000u * 512u);
    return lo | (u64)(__float_as_uint(b) * 16u - 0x4b400000u * 16u + (uint32_t)((int)lo >> 31)) << 32;
}
__device__ __forceinline__ float fx2_lo(u64 w, float inv) { return (float)(int)(__funnelshift_r(lo32(w), hi32(w), 4) & ~31u) * (inv * 0.5f); }
__device__ __forceinline__ float fx2_hi(u64 w, float inv) { return (float)((hi32(w) + 8) & ~15) * inv; }
__device__ __forceinline__ uint32_t fx2_get(u64 w, float inv) {
    return pack_bf((float)(int)__funnelshift_r(lo32(w), hi32(w), 4) * (inv * 0.5f) - inv * 3.f, (float)hi32(w) * inv);
}
__device__ __forceinline__ float fx2_inv(float meansq) { return fx_inv(fx2_scale(meansq)) * 0.0625f; }
__device__ __noinline__ uint32_t fx2_wide(const unsigned char* a, float meansq) {
    __threadfence();
    const u64 w = ld_rlx(a);
    const float inv = fx_inv(fx_scale(meansq));
    return pack_bf(fx2_lo(w, fx2_inv(meansq)) + fx_val(ld_rlx(a + 64)) * inv, fx2_hi(w, fx2_inv(meansq)) + fx_val(ld_rlx(a + 128)) * inv);
}
__device__ __noinline__ uint32_t fx1_wide(const unsigned char* a, float meansq) {
    __threadfence();
    const u64 w = ld_rlx(a);
    const unsigned char* b = a + 64 + (reinterpret_cast<u64>(a) & 63);
    const float inv = fx_inv(fx_scale(meansq)), inv1 = fx2_inv(meansq) * 0.5f;
    return pack_bf((float)(int)(lo32(w) & ~127u) * inv1 + fx_val(ld_rlx(b)) * inv, (float)(hi32(w) & ~127) * inv1 + fx_val(ld_rlx(b + 8)) * inv);
}
__device__ __noinline__ void fx_send(const unsigned char* wide, float v, float meansq, const unsigned char* a, uint32_t flag) {
    asm volatile("red.relaxed.gpu.global.add.u64 [%0], %1;" :: "l"(wide), "l"(fx_pack(v, fx_scale(meansq))) : "memory");
    __threadfence();
    asm volatile("red.relaxed.gpu.global.or.b32 [%0], %1;" :: "l"(a), "r"(flag) : "memory");
}
template <int N, class A, class F> __device__ __forceinline__ void fx2_wait(A a, F look, u64 (&w)[N], uint32_t msqa, float inv, uint32_t (&x)[N]) {
    auto miss = [&]() {
#pragma unroll
        for (int i = 0; i < N; i++) x[i] = fx2_get(w[i], inv);
        return __any_sync(~0u, ((lo32(w[0]) ^ 96) | (lo32(w[N - 1]) ^ 96)) & 0x160);
    };
    if (miss()) {
        int it = 0;
#pragma unroll 1
        do {
            if (__all_sync(~0u, (lo32(w[0]) & lo32(w[N - 1]) & 96) == 96)) {
#pragma unroll
                for (int i = 0; i < N; i++) x[i] = fx2_wide(a(i), ldsf(msqa));
                break;
            }
            look();
        } while (miss() & (++it < SPIN));
    }
}
__device__ __forceinline__ void st_rlx_if(bool p, void* a, u64 v) {
    asm volatile("{\n.reg .pred p;\nsetp.ne.u32 p, %2, 0;\n@p st.relaxed.gpu.global.u64 [%0], %1;\n}" :: "l"(a), "l"(v), "r"((uint32_t)p) : "memory");
}
__device__ __forceinline__ void sts128f(uint32_t a, const float (&v)[4]) { sts128f(a, v[0], v[1], v[2], v[3]); }
__device__ __forceinline__ void bar_arrive(int id, int n) { asm volatile("bar.arrive %0, %1;" :: "r"(id), "r"(n) : "memory"); }
template <class T> __device__ __forceinline__ T* pin(T* p) { return reinterpret_cast<T*>(__shfl_xor_sync(~0u, (u64)p, 0)); }

__device__ __forceinline__ void tma3(uint32_t dst, const CUtensorMap* tm, int c1, int c2, uint32_t bar, uint32_t pol) {
    asm volatile("cp.async.bulk.tensor.3d.shared::cluster.global.mbarrier::complete_tx::bytes.L2::cache_hint [%0], [%1, {%2, %3, %4}], [%5], %6;"
                 :: "r"(dst), "l"(tm), "r"(0), "r"(c1), "r"(c2), "r"(bar), "l"((u64)pol << 32) : "memory");
}
__device__ __forceinline__ void tma_v(uint32_t dst, const CUtensorMap* tm, int line, uint32_t bar) {
    asm volatile("cp.async.bulk.tensor.2d.shared::cluster.global.mbarrier::complete_tx::bytes.L2::cache_hint [%0], [%1, {%2, %3}], [%4], %5;"
                 :: "r"(dst), "l"(tm), "r"(0), "r"(line), "r"(bar), "l"((u64)POL_FIRST << 32) : "memory");
}
__device__ __forceinline__ void tma3_pf(const CUtensorMap* tm, int c1, int c2, uint32_t pol) {
    asm volatile("cp.async.bulk.prefetch.tensor.3d.L2.global.tile.L2::cache_hint [%0, {%1, %2, %3}], %4;"
                 :: "l"(tm), "r"(0), "r"(c1), "r"(c2), "l"((u64)pol << 32) : "memory");
}
__device__ __forceinline__ void issue_half(uint32_t d, uint32_t sb, int rowc, int cta, const CUtensorMap* tm0) {
    const uint32_t bar = sb + SM_CBAR + (d & 0xf8);
    const CUtensorMap* tm = tm0 + ((d >> 8) & 3);
    const bool wo = (d & 0x300) == TM_WO << 8;
    const int c1 = wo ? (cta & 3) + 4 * (d >> 20) : 0, c2 = wo ? (cta >> 2) * DH : rowc + (d >> 20);
    mbar_expect(bar, HALF);
    tma3(sb + (d & 0x3f000), tm, c1, c2, bar, POL_FIRST);
    if (!(d & 1)) tma3_pf(tm + 2, c1, c2, POL_NORMAL);
}
__device__ __forceinline__ uint32_t cnt_inc(uint32_t a, uint32_t last) {
    uint32_t old; asm volatile("atom.relaxed.cta.shared.inc.u32 %0, [%1], %2;" : "=r"(old) : "r"(a), "r"(last) : "memory"); return old;
}
__device__ __forceinline__ void wait_until(uint32_t due) {
#pragma unroll 1
    for (int it = 0; it < 4096; it++) { uint32_t now; asm volatile("mov.u32 %0, %globaltimer_lo;" : "=r"(now)); if ((int)(now - due) >= 0) break; }
}
__device__ __forceinline__ uint32_t bf2_mul(uint32_t a, uint32_t b) { uint32_t r; asm("mul.rn.bf16x2 %0, %1, %2;" : "=r"(r) : "r"(a), "r"(b)); return r; }
__device__ __forceinline__ uint32_t bf2_fma(uint32_t a, uint32_t b, uint32_t c) { uint32_t r; asm("fma.rn.bf16x2 %0, %1, %2, %3;" : "=r"(r) : "r"(a), "r"(b), "r"(c)); return r; }
__device__ __forceinline__ uint32_t bf2_amax(uint32_t a, uint32_t b) { uint32_t r; asm("max.NaN.xorsign.abs.bf16x2 %0, %1, %2;" : "=r"(r) : "r"(a), "r"(b)); return r; }
__device__ __forceinline__ uint4 k_unpack(uint32_t l0, uint32_t l1, uint32_t h, uint32_t m1) {
    const uint32_t ha = h & 0x87878787u, hc = ha * m1 + h, hb = __funnelshift_l(hc, hc, 4);
    return make_uint4(__byte_perm(l0, ha, 0x5140), __byte_perm(l0, ha, 0x7362), __byte_perm(l1, hb, 0x5140), __byte_perm(l1, hb, 0x7362));
}
#define KR4(u, i) "+r"(kr[u][i].x), "+r"(kr[u][i].y), "+r"(kr[u][i].z), "+r"(kr[u][i].w)
#define KR6(u) KR4(u, 0), KR4(u, 1), KR4(u, 2), KR4(u, 3), KR4(u, 4), KR4(u, 5)
__device__ __forceinline__ void k_keep(uint4 (&kr)[8][6], const uint32_t (&c)[18], int e, uint32_t a) {
    asm volatile("{\nKT: .branchtargets K0, K1, K2, K3, K4, K5, K6, K7, K8, K9, K10, K11, K12, K13, K14, K15;\nbrx.idx.uni %210, KT;\n"
                 "K0: mov.b32 %12, %192; mov.b32 %13, %193; mov.b32 %14, %194; mov.b32 %15, %195; mov.b32 %16, %196; mov.b32 %17, %197; mov.b32 %18, %198; mov.b32 %19, %199; mov.b32 %20, %200; mov.b32 %21, %201; mov.b32 %22, %202; mov.b32 %23, %203; mov.b32 %24, %204; mov.b32 %25, %205; mov.b32 %26, %206; mov.b32 %27, %207; mov.b32 %28, %208; mov.b32 %29, %209; bra.uni KE;\n"
                 "K1: mov.b32 %30, %192; mov.b32 %31, %193; mov.b32 %32, %194; mov.b32 %33, %195; mov.b32 %34, %196; mov.b32 %35, %197; mov.b32 %36, %198; mov.b32 %37, %199; mov.b32 %38, %200; mov.b32 %39, %201; mov.b32 %40, %202; mov.b32 %41, %203; mov.b32 %42, %204; mov.b32 %43, %205; mov.b32 %44, %206; mov.b32 %45, %207; mov.b32 %46, %208; mov.b32 %47, %209; bra.uni KE;\n"
                 "K2: mov.b32 %48, %192; mov.b32 %49, %193; mov.b32 %50, %194; mov.b32 %51, %195; mov.b32 %52, %196; mov.b32 %53, %197; mov.b32 %54, %198; mov.b32 %55, %199; mov.b32 %56, %200; mov.b32 %57, %201; mov.b32 %58, %202; mov.b32 %59, %203; mov.b32 %60, %204; mov.b32 %61, %205; mov.b32 %62, %206; mov.b32 %63, %207; mov.b32 %64, %208; mov.b32 %65, %209; bra.uni KE;\n"
                 "K3: mov.b32 %66, %192; mov.b32 %67, %193; mov.b32 %68, %194; mov.b32 %69, %195; mov.b32 %70, %196; mov.b32 %71, %197; mov.b32 %72, %198; mov.b32 %73, %199; mov.b32 %74, %200; mov.b32 %75, %201; mov.b32 %76, %202; mov.b32 %77, %203; mov.b32 %78, %204; mov.b32 %79, %205; mov.b32 %80, %206; mov.b32 %81, %207; mov.b32 %82, %208; mov.b32 %83, %209; bra.uni KE;\n"
                 "K4: mov.b32 %84, %192; mov.b32 %85, %193; mov.b32 %86, %194; mov.b32 %87, %195; mov.b32 %88, %196; mov.b32 %89, %197; mov.b32 %90, %198; mov.b32 %91, %199; mov.b32 %92, %200; mov.b32 %93, %201; mov.b32 %94, %202; mov.b32 %95, %203; mov.b32 %96, %204; mov.b32 %97, %205; mov.b32 %98, %206; mov.b32 %99, %207; mov.b32 %100, %208; mov.b32 %101, %209; bra.uni KE;\n"
                 "K5: mov.b32 %102, %192; mov.b32 %103, %193; mov.b32 %104, %194; mov.b32 %105, %195; mov.b32 %106, %196; mov.b32 %107, %197; mov.b32 %108, %198; mov.b32 %109, %199; mov.b32 %110, %200; mov.b32 %111, %201; mov.b32 %112, %202; mov.b32 %113, %203; mov.b32 %114, %204; mov.b32 %115, %205; mov.b32 %116, %206; mov.b32 %117, %207; mov.b32 %118, %208; mov.b32 %119, %209; bra.uni KE;\n"
                 "K6: mov.b32 %120, %192; mov.b32 %121, %193; mov.b32 %122, %194; mov.b32 %123, %195; mov.b32 %124, %196; mov.b32 %125, %197; mov.b32 %126, %198; mov.b32 %127, %199; mov.b32 %128, %200; mov.b32 %129, %201; mov.b32 %130, %202; mov.b32 %131, %203; mov.b32 %132, %204; mov.b32 %133, %205; mov.b32 %134, %206; mov.b32 %135, %207; mov.b32 %136, %208; mov.b32 %137, %209; bra.uni KE;\n"
                 "K7: mov.b32 %138, %192; mov.b32 %139, %193; mov.b32 %140, %194; mov.b32 %141, %195; mov.b32 %142, %196; mov.b32 %143, %197; mov.b32 %144, %198; mov.b32 %145, %199; mov.b32 %146, %200; mov.b32 %147, %201; mov.b32 %148, %202; mov.b32 %149, %203; mov.b32 %150, %204; mov.b32 %151, %205; mov.b32 %152, %206; mov.b32 %153, %207; mov.b32 %154, %208; mov.b32 %155, %209; bra.uni KE;\n"
                 "K8: mov.b32 %156, %192; mov.b32 %157, %193; mov.b32 %158, %194; mov.b32 %159, %195; mov.b32 %160, %196; mov.b32 %161, %197; mov.b32 %162, %198; mov.b32 %163, %199; mov.b32 %164, %200; mov.b32 %165, %201; mov.b32 %166, %202; mov.b32 %167, %203; mov.b32 %168, %204; mov.b32 %169, %205; mov.b32 %170, %206; mov.b32 %171, %207; mov.b32 %172, %208; mov.b32 %173, %209; bra.uni KE;\n"
                 "K9: mov.b32 %174, %192; mov.b32 %175, %193; mov.b32 %176, %194; mov.b32 %177, %195; mov.b32 %178, %196; mov.b32 %179, %197; mov.b32 %180, %198; mov.b32 %181, %199; mov.b32 %182, %200; mov.b32 %183, %201; mov.b32 %184, %202; mov.b32 %185, %203; mov.b32 %186, %204; mov.b32 %187, %205; mov.b32 %188, %206; mov.b32 %189, %207; mov.b32 %190, %208; mov.b32 %191, %209; bra.uni KE;\n"
                 "K10: st.shared.v2.b32 [%211+75784], {%192, %193}; st.shared.v2.b32 [%211+76288], {%194, %195}; st.shared.v2.b32 [%211+76296], {%196, %197}; mov.b32 %0, %198; mov.b32 %1, %199; mov.b32 %2, %200; mov.b32 %3, %201; mov.b32 %4, %202; mov.b32 %5, %203; mov.b32 %6, %204; mov.b32 %7, %205; mov.b32 %8, %206; mov.b32 %9, %207; mov.b32 %10, %208; mov.b32 %11, %209; bra.uni KE;\n"
                 "K11: st.shared.v2.b32 [%211+0], {%192, %193}; st.shared.v2.b32 [%211+8], {%194, %195}; st.shared.v2.b32 [%211+512], {%196, %197}; st.shared.v2.b32 [%211+520], {%198, %199}; st.shared.v2.b32 [%211+1024], {%200, %201}; st.shared.v2.b32 [%211+1032], {%202, %203}; st.shared.v2.b32 [%211+1536], {%204, %205}; st.shared.v2.b32 [%211+1544], {%206, %207}; st.shared.v2.b32 [%211+2048], {%208, %209}; bra.uni KE;\n"
                 "K12: st.shared.v2.b32 [%211+2056], {%192, %193}; st.shared.v2.b32 [%211+2560], {%194, %195}; st.shared.v2.b32 [%211+2568], {%196, %197}; st.shared.v2.b32 [%211+24576], {%198, %199}; st.shared.v2.b32 [%211+24584], {%200, %201}; st.shared.v2.b32 [%211+25088], {%202, %203}; st.shared.v2.b32 [%211+25096], {%204, %205}; st.shared.v2.b32 [%211+25600], {%206, %207}; st.shared.v2.b32 [%211+25608], {%208, %209}; bra.uni KE;\n"
                 "K13: st.shared.v2.b32 [%211+26112], {%192, %193}; st.shared.v2.b32 [%211+26120], {%194, %195}; st.shared.v2.b32 [%211+26624], {%196, %197}; st.shared.v2.b32 [%211+26632], {%198, %199}; st.shared.v2.b32 [%211+27136], {%200, %201}; st.shared.v2.b32 [%211+27144], {%202, %203}; st.shared.v2.b32 [%211+49152], {%204, %205}; st.shared.v2.b32 [%211+49160], {%206, %207}; st.shared.v2.b32 [%211+49664], {%208, %209}; bra.uni KE;\n"
                 "K14: st.shared.v2.b32 [%211+49672], {%192, %193}; st.shared.v2.b32 [%211+50176], {%194, %195}; st.shared.v2.b32 [%211+50184], {%196, %197}; st.shared.v2.b32 [%211+50688], {%198, %199}; st.shared.v2.b32 [%211+50696], {%200, %201}; st.shared.v2.b32 [%211+51200], {%202, %203}; st.shared.v2.b32 [%211+51208], {%204, %205}; st.shared.v2.b32 [%211+51712], {%206, %207}; st.shared.v2.b32 [%211+51720], {%208, %209}; bra.uni KE;\n"
                 "K15: st.shared.v2.b32 [%211+73728], {%192, %193}; st.shared.v2.b32 [%211+73736], {%194, %195}; st.shared.v2.b32 [%211+74240], {%196, %197}; st.shared.v2.b32 [%211+74248], {%198, %199}; st.shared.v2.b32 [%211+74752], {%200, %201}; st.shared.v2.b32 [%211+74760], {%202, %203}; st.shared.v2.b32 [%211+75264], {%204, %205}; st.shared.v2.b32 [%211+75272], {%206, %207}; st.shared.v2.b32 [%211+75776], {%208, %209}; \nKE:\n}"
                 : KR6(0), KR6(1), KR6(2), KR6(3), KR6(4), KR6(5), KR6(6), KR6(7)
                 : "r"(c[0]), "r"(c[1]), "r"(c[2]), "r"(c[3]), "r"(c[4]), "r"(c[5]), "r"(c[6]), "r"(c[7]), "r"(c[8]), "r"(c[9]), "r"(c[10]), "r"(c[11]), "r"(c[12]), "r"(c[13]), "r"(c[14]), "r"(c[15]), "r"(c[16]), "r"(c[17]), "r"(e), "r"(a) : "memory");
}
__device__ __forceinline__ uint32_t smem_base() { extern __shared__ __align__(1024) unsigned char smem[]; return (uint32_t)__cvta_generic_to_shared(smem); }
__device__ __forceinline__ void k_rare(uint4 v0, uint4 v1, uint4 v2, uint4 v3, uint4 v4, uint4 v5, uint32_t odd, int e, int warp, int lane) {
    const uint32_t sb = smem_base(), g = lane >> 2, t = lane & 3, st = sb + SM_BAR + warp * 96 + 80;
    uint32_t lt; asm volatile("mov.u32 %0, %lanemask_lt;" : "=r"(lt));
    const uint4 v[6] = {v0, v1, v2, v3, v4, v5};
    odd <<= 6;
#pragma unroll
    for (int i = 0; i < 6; i++) if (v[i].x | v[i].y | v[i].z | v[i].w) odd |= 1u << i;
    odd = __reduce_or_sync(~0u, odd);
    uint32_t n = odd >= 64 ? NEXC + 1 : __shfl_sync(~0u, lds32(st), 0);
#pragma unroll 1
    for (; odd && n <= NEXC; odd &= odd - 1) {
        const int i = __ffs(odd) - 1;
#pragma unroll
        for (int k = 1; k < 6; k++) if (i == k) v0 = v[k];
#pragma unroll 1
        for (int k = 0; k < 4; k++, v0.x = v0.y, v0.y = v0.z, v0.z = v0.w) {
            const uint32_t who = __ballot_sync(~0u, v0.x), at = n + __popc(who & lt);
            sts64(v0.x && at < NEXC ? sb + SM_EXC + warp * 128 + at * 8 : st + 8, v0.x, (e * 32 + g * 4) << 16 | (((k & 1) * 4 + t) * 48 + i * 8 + (k >> 1) * 4));
            n += __popc(who);
        }
    }
    const uint32_t bad = lds32(st + 4);
    __syncwarp();
    if (n <= NEXC) sts32(st, n);
    else {
        sts32(st + 4, bad | 1u << e);
        asm volatile("st.shared.u8 [%0], %1;" :: "r"(sb + SM_SC + warp * 128 + g * 16 + (e & 3) * 4 + (e >> 2)), "r"(0) : "memory");
    }
    __syncwarp();
}
template <int K> __device__ __forceinline__ uint32_t& word(uint4& v) { if constexpr (K == 0) return v.x; else if constexpr (K == 1) return v.y; else if constexpr (K == 2) return v.z; else return v.w; }
__device__ __forceinline__ void add_if(bool p, float& d, float a, float b) {
    asm volatile("{\n.reg .pred p;\nsetp.ne.u32 p, %3, 0;\n@p add.f32 %0, %1, %2;\n}" : "+f"(d) : "f"(a), "f"(b), "r"((uint32_t)p));
}
__device__ __forceinline__ float warp_max(float v) {
#pragma unroll
    for (int o = 16; o; o >>= 1) v = fmaxf(v, shx(v, o));
    return v;
}
__device__ __forceinline__ float warp_sum(float v) {
#pragma unroll
    for (int o = 16; o; o >>= 1) v += shx(v, o);
    return v;
}
template <int PITCH> __device__ __forceinline__ void ll_look(const u64* buf, u64 (&w)[4]) {
#pragma unroll
    for (int i = 0; i < 4; i++) w[i] = ld_rlx(buf + i * PITCH);
}
template <int PITCH> __device__ __forceinline__ float ll_gather(const u64* buf, uint32_t tag, u64 (&w)[4]) {
    auto miss = [&]() {
        uint32_t a, b;
        asm("lop3.b32 %0, %1, %2, %3, 0x7e;" : "=r"(a) : "r"(ll_tag(w[0])), "r"(ll_tag(w[1])), "r"(tag));
        asm("lop3.b32 %0, %1, %2, %3, 0x7e;" : "=r"(b) : "r"(ll_tag(w[2])), "r"(ll_tag(w[3])), "r"(tag));
        return __any_sync(~0u, a | b);
    };
    int it = 0;
    goto check;
again:
    ll_look<PITCH>(buf, w);
check:
    if (miss() & (++it < SPIN)) goto again;
    return (ll_val(w[0]) + ll_val(w[1])) + (ll_val(w[2]) + ll_val(w[3]));
}
__device__ __forceinline__ float sum8(uint32_t a, int pitch) {
    float s[8];
#pragma unroll
    for (int w = 0; w < 8; w++) s[w] = ldsf(a + w * pitch);
    return ((s[0] + s[1]) + (s[2] + s[3])) + ((s[4] + s[5]) + (s[6] + s[7]));
}
__device__ __forceinline__ float sum5(float a, float b, float c, float d, float e) { return ((a + b) + (c + d)) + e; }
__device__ __forceinline__ float ln_part(uint2 xp, int lane) {
    const float x0 = bf_lo(xp.x), x1 = bf_hi(xp.x), x2 = bf_lo(xp.y), x3 = bf_hi(xp.y);
    const float s1 = (x0 + x1) + (x2 + x3), s2 = (x0 * x0 + x1 * x1) + (x2 * x2 + x3 * x3);
    return ((lane & 16) ? s2 : s1) + shx((lane & 16) ? s1 : s2, 16);
}
__device__ __forceinline__ float ln_rstd(float mean, float msq) { return rsq(fmaxf(msq - mean * mean, 0.f) + 1e-5f); }
__device__ __forceinline__ float score(const uint4 (&v)[6], const uint4 (&qf)[3]) {
    float d[2][4];
#pragma unroll
    for (int j = 0; j < 2; j++) d[j][0] = d[j][1] = d[j][2] = d[j][3] = 0.f;
#pragma unroll
    for (int i = 0; i < 3; i++) { mma(d[0], v[2 * i], qf[i].x, qf[i].y); mma(d[1], v[2 * i + 1], qf[i].z, qf[i].w); }
    return (d[0][0] + d[0][3]) + (d[1][0] + d[1][3]);
}
__device__ __forceinline__ float k_side(uint32_t sb, uint2 x) {
    const uint32_t qq = lds32(sb + SM_VEC + (x.y & 0xffff));
    return (bf_lo(x.x) * bf_lo(qq) + bf_hi(x.x) * bf_hi(qq)) * 0x1p-64f;
}
__device__ __forceinline__ void k_fix(const __nv_bfloat16* k, uint32_t bad, int warp, int lane) {
    const uint32_t sb = smem_base(), g = lane >> 2, sa = sb + SM_PART + warp * 768 + 256;
    const uint2 x = lds64(sb + SM_EXC + warp * 128 + (lane & 15) * 8);
    if ((int)x.y >= 0x40000000 && lane < 16) asm volatile("red.shared.add.f32 [%0], %1;" :: "r"(sa + ((x.y >> 16) & 511)), "f"(k_side(sb, x)) : "memory");
    __syncwarp();
#pragma unroll 1
    for (bad &= 0xffff; bad; bad &= bad - 1) {
        const int e = __ffs(bad) - 1;
        const __nv_bfloat16* kp = k + (e * 256 + (g >> 1) + 4 * (g & 1)) * DH + (lane & 3) * 8;
        uint4 v[6], qf[3];
#pragma unroll
        for (int i = 0; i < 6; i++) v[i] = *reinterpret_cast<const uint4*>(kp + i * 32);
#pragma unroll
        for (int i = 0; i < 3; i++) qf[i] = lds128(sb + SM_VEC + (lane & 7) * 48 + i * 16);
        stsf(sa + e * 32 + g * 4, score(v, qf) * 0x1p-64f);
    }
    __syncwarp();
}
constexpr float CS = 0.07216878364870322f * 1.4426950408889634f;
__device__ __forceinline__ void head_weight(const u64* a, u64 pm, u64 pl, int layer, int lane) {
    const uint32_t sb = smem_base(), tag = lds32(sb + SM_EPOCH) * 4 + 2 + 2 * layer;
#pragma unroll 1
    for (int it = 0; it < SPIN; it++) {
        if (__all_sync(~0u, ll_tag(pm) == tag && ll_tag(pl) == tag)) break;
        ld_rlx2(a, pm, pl);
    }
    const float f = ex2((ll_val(pm) - warp_max(ll_val(pm))) * CS);
    const float w = f * rcp(warp_sum(f * ll_val(pl)));
    if (lane < 8) stsf(sb + SM_FAC + lane * 4, w);
}
constexpr uint32_t ONES = 0x3f803f80u;

__global__ void __launch_bounds__(NTHR, 1) fused_kernel(const __grid_constant__ Params P) {
    const uint32_t sb = smem_base();
    const int bx = blockIdx.x;
    if (__all_sync(~0u, threadIdx.x >= NTHR - 32) && elect()) {
        asm volatile("mbarrier.init.shared::cta.b64 [%0], 1;" :: "r"(sb + SM_CBAR + CB_WQ * 8));
        asm volatile("mbarrier.init.shared::cta.b64 [%0], 1;" :: "r"(sb + SM_CBAR + 80));
        asm volatile("fence.mbarrier_init.release.cluster;" ::: "memory");
        mbar_expect(sb + SM_CBAR + CB_WQ * 8, 5 * HALF);
        mbar_expect(sb + SM_CBAR + 80, HALF);
        tma3(sb, &P.tm[TM_KH], 0, (bx >> 2) * SK + (SK - WIN) + (bx & 3) * 64, sb + SM_CBAR + 80, POL_FIRST);
#pragma unroll 1
        for (int i = 0; i < 5; i++) tma3(sb + SM_WQR + (i == 4 ? 0 : i + 1) * HALF, &P.tm[TM_WQ], (bx >> 2) * 3, (bx & 3) * 160 + i * 32, sb + SM_CBAR + CB_WQ * 8, POL_FIRST);
    }
    __syncwarp();
    int id = bx * NTHR + threadIdx.x, tid, lane, g, t, key, warp, cta, mlp, rowc, roww, j40;
    uint32_t maskA, maskB, barw, subw, prow;
    auto fresh = [&]() {
        const int cw = __shfl_sync(~0u, id >> 5, 0);
        id = pin(id); tid = id & 255; lane = id & 31; g = lane >> 2; t = lane & 3; key = (g >> 1) + 4 * (g & 1);
        const uint32_t m = (g & 1) ? 0xffff0000u : 0x0000ffffu;
        maskA = (g & 2) ? 0u : m; maskB = (g & 2) ? m : 0u;
        warp = cw & 7; cta = cw >> 3;
        mlp = (cta & 3) == 3 ? 96 : (cta >> 2) * 3 + (cta & 3);
        rowc = (cta >> 2) * SK + (SK - WIN) + (cta & 3) * 64; roww = rowc + warp * 8;
        j40 = (cta & 3) * 40;
        barw = sb + SM_BAR + warp * 96; subw = sb + warp * SUB; prow = sb + SM_PART + warp * 768;
    };
    fresh();
    auto fresh_lane = [&]() { id = pin(id); tid = id & 255; lane = id & 31; g = lane >> 2; t = lane & 3; };
    auto pinf = [&](float v) { return __uint_as_float(pin(__float_as_uint(v) | (id >> 16))); };

    TSTAMP(0);
    if (tid == 64) { uint32_t now; asm volatile("mov.u32 %0, %globaltimer_lo;" : "=r"(now)); sts32(sb + SM_T0, now); }

    const CUtensorMap* tmk = reinterpret_cast<const CUtensorMap*>(__shfl_sync(~0u, (u64)&P.tm[0] + (lane >> 5), 0));
    auto c4 = [&]() { return 32 * min(warp, 4) + 16 * (t >> 1) + 2 * g + (t & 1); };
    auto xcol = [&](int i, int tt) { return (i < 2 ? 64 * i + 8 * warp : 128 + 8 * (warp >> 1)) + 2 * tt; };
    uint2 xp;
    uint32_t px[3], small;
    if (elect()) {
        if (warp != 2) asm volatile("mbarrier.init.shared::cta.b64 [%0], 1;" :: "r"(sb + SM_CBAR + 64 + warp * 8));
#pragma unroll
        for (int i = 0; i < 9; i++) asm volatile("mbarrier.init.shared::cta.b64 [%0], 1;" :: "r"(barw + i * 8));
        asm volatile("mbarrier.init.shared::cta.b64 [%0], 1;" :: "r"(sb + SM_CBAR + warp * 8));
        asm volatile("mbarrier.init.shared::cta.b64 [%0], 1;" :: "r"(sb + SM_CBAR + 128 + warp * 8));
        if (warp < 3) asm volatile("mbarrier.init.shared::cta.b64 [%0], %1;" :: "r"(sb + SM_CBAR + 192 + warp * 8), "r"(warp == 2 ? 8 : 1));
        sts64(barw + 80, 0, 0);
        asm volatile("fence.mbarrier_init.release.cluster;" ::: "memory");
        asm volatile("prefetch.tensormap [%0];" :: "l"(tmk + warp) : "memory");
    }
    __syncwarp();
    asm volatile("ld.global.nc.v2.u32 {%0,%1}, [%2];" : "=r"(xp.x), "=r"(xp.y) : "l"(P.x + 4 * c4()) : "memory");
#pragma unroll
    for (int i = 0; i < 3; i++) asm volatile("ld.global.nc.u32 %0, [%1];" : "=r"(px[i]) : "l"(P.x + 4 * j40 + xcol(i, t)) : "memory");
    asm volatile("ld.relaxed.gpu.global.u32 %0, [%1];" : "=r"(small) : "l"(lane < 16 ? (const void*)(P.b1 + min(mlp, 95) * 16 + (lane & 14)) : (const void*)&P.g->epoch) : "memory");
    if (tid < NCB + 8) sts64(sb + SM_CNT + tid * 8, 0, 0);
    unsigned char* accg = reinterpret_cast<unsigned char*>(__shfl_sync(~0u, (u64)P.g->acc + (lane >> 5), 0));
    auto release = [&](const uint4& tw) {
        uint32_t old;
        __syncwarp();
        asm volatile("atom.relaxed.cta.shared.add.u32 %0, [%1], 1;" : "=r"(old) : "r"(sb + SM_CNT + (tw.x & 0xf8)) : "memory");
        return old;
    };
    auto refill = [&](const uint4& tw, uint32_t old) {
        if (__any_sync(~0u, (old & 127) == 127 && (tw.y & 2))) {
            wait_until(lds32(sb + SM_T0) + tw.z);
            if (elect()) issue_half(tw.y, sb, rowc, cta, tmk);
            __syncwarp();
        }
    };
    __syncthreads();

    uint32_t offV0, offV2;
    auto calc_offsets = [&]() {
        offV0 = subw + (6 * t) * 128 + ((g ^ ((6 * t) & 7)) << 4);
        offV2 = subw + (6 * t + 2) * 128 + ((g ^ ((6 * t + 2) & 7)) << 4);
    };
    calc_offsets();

    auto load_v = [&](uint4 (&v)[6], uint32_t so) {
        v[0] = lds128(offV0 + so); v[1] = lds128((offV0 ^ 16) + so + 128); v[2] = lds128(offV2 + so);
        v[3] = lds128((offV2 ^ 16) + so + 128); v[4] = lds128((offV0 ^ 64) + so + 512); v[5] = lds128((offV0 ^ 80) + so + 640);
    };
    auto issue_v = [&](auto I, int dw, uint32_t done = ~0u) {
        constexpr Step c = SCH.st[I.value];
        const uint32_t bar = barw + dw * 96 + c.slot * 8;
        mbar_expect(bar, done & SUB);
        tma_v(subw + dw * SUB + c.slot * TILE, tmk, roww * 3 + dw * 24 + c.unit * 768, bar);
    };
    auto reads_done = [&]() { __syncwarp(); return lds32(sb + SM_M1); };
    auto refill2 = [&](auto I, uint32_t done = ~0u) { __syncwarp(); if (elect()) issue_v(I, 0, done); };
    uint4 wq0[6], wqh[3], wq1[6];
    auto load_wq1 = [&](int i) { wq1[i] = lds128((i == 2 ? offV2 : i == 3 ? (offV2 ^ 16) + 128 : (offV0 ^ (i * 16)) + i * 128) + SM_WQ + TILE); };
    auto load_wq = [&]() {
        load_v(wq0, SM_WQ);
        const uint32_t so = SM_WQR - ((warp + 1) >> 1) * SUB;
        wqh[0] = lds128(((warp & 1) ? (offV2 ^ 16) + 128 : offV0) + so);
        wqh[1] = lds128(((warp & 1) ? (offV0 ^ 64) + 512 : (offV0 ^ 16) + 128) + so);
        wqh[2] = lds128(((warp & 1) ? (offV0 ^ 80) + 640 : offV2) + so);
    };
    uint4 kr[8][6];
    const unsigned char* rap;
    u64 rw[2];
    auto look_rw = [&]() { rw[0] = ld_rlx(rap); rw[1] = ld_rlx(rap + 20 * acc_pitch(1)); };
    auto q_proj = [&](auto L, uint32_t (&p)[3], uint32_t pst) {
        if (L.value == 0 && g >= 4) p[0] = p[1] = p[2] = ONES;
        float a[3][4], b[3][4];
        const uint32_t dH = __byte_perm(p[2], 0, (warp & 1) ? 0x3232 : 0x1010);
        const uint32_t dA = __byte_perm(p[0], 0, 0x1010), dB = __byte_perm(p[0], 0, 0x3232), dC = __byte_perm(p[1], 0, 0x1010), dD = __byte_perm(p[1], 0, 0x3232);
#pragma unroll
        for (int i = 0; i < 3; i++) load_wq1(i);
#pragma unroll
        for (int j = 0; j < 3; j++) { a[j][0] = a[j][1] = a[j][2] = a[j][3] = 0.f; mma(a[j], wq0[j], dA & maskA, dA & maskB); }
#pragma unroll
        for (int j = 0; j < 3; j++) { b[j][0] = b[j][1] = b[j][2] = b[j][3] = 0.f; mma(b[j], wq0[j + 3], dB & maskA, dB & maskB); }
#pragma unroll
        for (int j = 0; j < 3; j++) mma(a[j], wqh[j], dH & maskA, dH & maskB);
#pragma unroll
        for (int i = 3; i < 6; i++) load_wq1(i);
#pragma unroll
        for (int j = 0; j < 3; j++) mma(b[j], wq1[j], dC & maskA, dC & maskB);
#pragma unroll
        for (int j = 0; j < 3; j++) mma(a[j], wq1[j + 3], dD & maskA, dD & maskB);
#pragma unroll
        for (int j = 0; j < 3; j++) {
            if (L.value) {
#pragma unroll
                for (int k = 0; k < 2; k++) { a[j][k] += b[j][k]; add_if(t & 2, a[j][k], a[j][k + 2], b[j][k + 2]); }
                sts64f(pst + j * 256, a[j][0], a[j][1]);
            } else sts128f(pst + j * 256, a[j][0] + b[j][0], a[j][1] + b[j][1], a[j][2] + b[j][2], a[j][3] + b[j][3]);
        }
        CSTAMP(23, __float_as_uint(a[2][1]));
        uint32_t tag;
        if (L.value) tag = lds32(sb + SM_EPOCH) * 4 + 3;
        u64* pub = L.value ? &P.g->ll[cta][tid] : &P.g->l0[cta][tid];
        if (L.value == 0) asm volatile("fence.proxy.async.shared::cta;" ::: "memory");
        TSTAMPL(21);
        __syncthreads();
        if (!L.value) tag = lds32(sb + SM_EPOCH) * 4 + 1;
#pragma unroll 1
        for (int k = 0; k < 2 - L.value; k++) st_rlx_if(tid < 192, pub + k * 192, ll_pack(sum8(sb + (k ? SM_CSP : SM_PART) + tid * 4, 768), tag));
        TSTAMPL(23);
            CSTAMP(24, tag);
    };
    auto ln_stats = [&]() {
        float ss = ln_part(xp, lane);
        ss += shx(ss, 8); ss += shx(ss, 4); ss += shx(ss, 2); ss += shx(ss, 1);
        stsf(sb + SM_STAT + min(warp, 5) * 8 + (lane >> 4) * 4, ss);
    };
    auto ln_final = [&](float& mean, float& rstd) {
        float2 v[5];
#pragma unroll
        for (int w = 0; w < 5; w++) v[w] = lds64f(sb + SM_STAT + w * 8);
        mean = sum5(v[0].x, v[1].x, v[2].x, v[3].x, v[4].x) * (1.f / D_MODEL);
        const float msq = sum5(v[0].y, v[1].y, v[2].y, v[3].y, v[4].y) * (1.f / D_MODEL);
        rstd = ln_rstd(mean, msq);
        stsf(sb + SM_FXS, msq);
    };
    auto q_addr = [&](int d) { return sb + SM_VEC + (((d >> 1) & 1) * 4 + ((d >> 3) & 3)) * 48 + (d >> 5) * 8 + ((d >> 2) & 1) * 4 + (d & 1) * 2; };
    {
#pragma unroll
        for (int u = 0; u < 8; u++)
#pragma unroll
            for (int i = 0; i < 6; i++) kr[u][i] = lds128(sb + SM_CS + (u * 6 + i) * 16);
        if (warp >= 1 && warp < NI1) {
            wait_until(lds32(sb + SM_T0) + PACES + warp * PACE / 2);
            if (elect()) {
                mbar_expect(sb + SM_CBAR + 80 + warp * 8, HALF);
                tma3(sb + warp * HALF, tmk + TM_KH, 0, rowc + (warp >> 1) * 256 + (warp & 1) * 32, sb + SM_CBAR + 80 + warp * 8, POL_FIRST);
            }
            __syncwarp();
        }
        ln_stats();
        if (tid == 16) { sts32(sb + SM_EPOCH, small); sts32(sb + SM_M1, ~0u); }
        else if (tid < 16) sts32(sb + SM_B1 + tid * 4, (tid & 1) ? small & 0xffff0000u : small << 16);
        mbar_wait(sb + SM_CBAR + CB_WQ * 8, 0);
        load_wq();
        q_proj(IC<0>{}, px, sb + (t < 2 ? SM_PART : SM_CSP) + warp * 768 + (8 * g + 4 * (t & 1)) * 4);
    }
    {
        uint32_t offQ, offL;
        auto calc_ql = [&]() {
            offQ = pin(sb + SM_VEC + (lane & 7) * 48);
            offL = pin(subw + lane * 16);
        };

        auto issue_w = [&](auto L, int which) {
            const uint32_t bar = sb + SM_CBAR + (CB_W1 + which) * 8;
            if (mlp == 96) asm volatile("mbarrier.arrive.shared::cta.b64 _, [%0];" :: "r"(bar) : "memory");
            else {
                mbar_expect(bar, 20480);
                if (which) {
                    tma3(sb + (L.value ? 3 * TILE : SM_W2), tmk + TM_W2, 0, mlp * 16, bar, POL_FIRST);
                    if (!L.value) tma3_pf(tmk + TM_W2, 0, mlp * 16, POL_NORMAL);
                    if (!L.value) asm volatile("cp.async.bulk.prefetch.L2.global.L2::cache_hint [%0], 20480, %1;" :: "l"(P.w1 + mlp * 10240), "l"((u64)POL_NORMAL << 32) : "memory");
                }
                else asm volatile("cp.async.bulk.tensor.3d.shared::cluster.global.mbarrier::complete_tx::bytes.L2::cache_hint [%0], [%1, {%2, %3, %3}], [%4], %5;"
                                  :: "r"(sb + (L.value ? 2 * TILE : SM_W1)), "l"(tmk + TM_W1), "r"(mlp * 16), "r"(0), "r"(bar), "l"((u64)POL_FIRST << 32) : "memory");
            }
        };
        float acc[3][4];
        auto load_q = [&](uint4 (&qf)[3]) {
#pragma unroll
            for (int i = 0; i < 3; i++) qf[i] = lds128(offQ + i * 16);
        };
        auto softmax = [&](float S0, float S1, float S2, float S3) {
            int mi = __float_as_int(fmaxf(fmaxf(S0, S1), fmaxf(S2, S3)));
            mi = __reduce_max_sync(~0u, mi ^ ((mi >> 31) & 0x7fffffff));
            const float mrun = __int_as_float(mi ^ ((mi >> 31) & 0x7fffffff));
            const float p0 = ex2((S0 - mrun) * CS), p1 = ex2((S1 - mrun) * CS), p2 = ex2((S2 - mrun) * CS), p3 = ex2((S3 - mrun) * CS);
            const uint32_t pa = pack_bf(p0, p1), pb = pack_bf(p2, p3), pw = prow + 256 + (key >> 1) * 80 + t * 4 + (key & 1) * 2;
            sts16(pw, pa); sts16(pw + 16, pa >> 16); sts16(pw + 32, pb); sts16(pw + 48, pb >> 16);
            __syncwarp();
#pragma unroll
            for (int j = 0; j < 3; j++) acc[j][0] = acc[j][1] = acc[j][2] = acc[j][3] = 0.f;
            return make_float2(mrun, (p0 + p1) + (p2 + p3));
        };
        auto pv = [&](const uint4 (&v)[6], uint32_t pp) {
            const uint32_t dA = __byte_perm(pp, 0, 0x1010), dB = __byte_perm(pp, 0, 0x3232);
            mma(acc[0], v[0], dA & maskA, dA & maskB); mma(acc[1], v[1], dA & maskA, dA & maskB); mma(acc[2], v[2], dA & maskA, dA & maskB);
            mma(acc[0], v[3], dB & maskA, dB & maskB); mma(acc[1], v[4], dB & maskA, dB & maskB); mma(acc[2], v[5], dB & maskA, dB & maskB);
        };
        auto sa = [&]() { return prow + 256 + t * 32 + g * 4; };
        auto pass1 = [&]() {
            fresh();
            calc_ql();
            __syncthreads();
            sts64(prow + lane * 8, xp.x, xp.y);
            int e = 0;
            const uint4* tab = P.tile + (warp >> 2);
            uint4 tw = tab[0];
            uint32_t ka[3];
#pragma unroll
            for (int j = 0; j < 3; j++) ka[j] = pin(subw + key * 384 + j * 128 + ((t ^ ((3 * key + j) & 7)) << 4));
            auto load_k = [&](uint4 (&v)[6], uint32_t so) {
#pragma unroll
                for (int i = 0; i < 6; i++) v[i] = lds128(((i & 1) ? ka[i >> 1] ^ 64 : ka[i >> 1]) + so);
            };
            const uint32_t s0 = pin(prow + 256 + g * 4), sca = pin(sb + SM_SC + warp * 128 + g * 16);
#pragma unroll 1
            do {
                const uint4 tn = tab[2 * e + 2];
                uint4 v[6], qf[3];
                if (tw.x & (G_A | G_B | G_C)) {
                    if ((tw.x & G_A) && warp == 7 && elect()) {
                        mbar_expect(sb + SM_CBAR + CB_SNAP * 8, HALF);
                        asm volatile("cp.async.bulk.shared::cluster.global.mbarrier::complete_tx::bytes [%0], [%1], 12288, [%2];"
                                     :: "r"(sb + SM_SNAP), "l"(&P.g->l0[cta & ~3][0]), "r"(sb + SM_CBAR + CB_SNAP * 8) : "memory");
                    }
                    if (tw.x & G_B) {
                        if (warp < 6) {
                            mbar_wait(sb + SM_CBAR + CB_SNAP * 8, 0);
                            float qc[2] = {0.f, 0.f}, mean, rstd;
#pragma unroll 1
                            for (int k = 0; k < 2; k++) {
                                u64 qw[4];
#pragma unroll
                                for (int i = 0; i < 4; i++) { const uint2 x = lds64(sb + SM_SNAP + i * 3072 + k * 1536 + tid * 8); qw[i] = x.x | (u64)x.y << 32; }
                                qc[0] = qc[1];
                                qc[1] = ll_gather<384>(&P.g->l0[cta & ~3][k * 192 + tid], lds32(sb + SM_EPOCH) * 4 + 1, qw);
                            }
                            ln_final(mean, rstd);
                            stsf(sb + SM_CS + tid * 4, qc[1]);
                            const float q = (qc[0] - mean * qc[1]) * rstd;
                            sts16(q_addr(tid), pack_bf(q, q));
                        }
                        __syncthreads();
                        if (warp == 7 && elect()) issue_half(UC<load_word(12)>::value, sb, rowc, cta, tmk);
                        TSTAMP(2);
                    }
                    if (tw.x & G_C) {
                        load_k(v, (e - LATEAT) * TILE);
                        load_q(qf);
                        stsf(s0 + (e - LATEAT) * 32, score(v, qf));
                    }
                }
                load_q(qf);
                mbar_wait(sb + SM_CBAR + (tw.x & 0xf8), tw.x >> 31);
                TRACE(e);
                load_k(v, tw.x & 0x3f000);
                const uint32_t old = release(tw);
                const float s = score(v, qf);
                uint32_t m;
                {
                    uint32_t a[6];
#pragma unroll
                    for (int i = 0; i < 6; i++) a[i] = bf2_amax(bf2_amax(v[i].x, v[i].y), bf2_amax(v[i].z, v[i].w));
                    m = bf2_amax(bf2_amax(bf2_amax(a[0], a[1]), bf2_amax(a[2], a[3])), bf2_amax(a[4], a[5]));
                }
                m = bf2_amax(m, m >> 16) & 0x7f80;
                m = max(m, __shfl_xor_sync(~0u, m, 1));
                stsf(s0 + e * 32, s);
                m = max(m, __shfl_xor_sync(~0u, m, 2));
                refill(tw, old);
                const uint32_t b = min(max(m, 15u << 7) - (15u << 7), 126u << 7);
                const uint32_t dn = ((127u << 7) - b) * 0x10001u, up = ((127u << 7 | 0x8000u) + b) * 0x10001u;
                uint32_t c[18], any = m > (141u << 7);
#pragma unroll
                for (int i = 0; i < 6; i++) {
                    const uint32_t y0 = bf2_mul(v[i].x, dn), y1 = bf2_mul(v[i].y, dn), y2 = bf2_mul(v[i].z, dn), y3 = bf2_mul(v[i].w, dn);
                    v[i] = make_uint4(bf2_fma(y0, up, v[i].x), bf2_fma(y1, up, v[i].y), bf2_fma(y2, up, v[i].z), bf2_fma(y3, up, v[i].w));
                    any |= v[i].x | v[i].y;
                    any |= v[i].z | v[i].w;
                    const uint32_t hb = __byte_perm(y2, y3, 0x7531);
                    c[3 * i] = __byte_perm(y0, y1, 0x6420); c[3 * i + 1] = __byte_perm(y2, y3, 0x6420);
                    c[3 * i + 2] = __byte_perm(y0, y1, 0x7531) | __funnelshift_r(hb, hb, 4);
                }
                asm volatile("st.shared.u8 [%0], %1;" :: "r"(sca + (e & 3) * 4 + (e >> 2)), "r"((b >> 7) + 63) : "memory");
                const bool rare = __any_sync(~0u, any);
                k_keep(kr, c, e, offL);
                if (rare) k_rare(v[0], v[1], v[2], v[3], v[4], v[5], m > (141u << 7), e, warp, lane);
                tw = tn;
            } while (++e < 16);
            asm volatile("fence.proxy.async.shared::cta;" ::: "memory");
            __syncwarp();
            TSTAMP(10);
            fresh(); calc_offsets();
            offV0 = pin(offV0); offV2 = pin(offV2);
            {
                const uint2 st = lds64(barw + 80);
                const uint32_t xa = sb + SM_EXC + warp * 128 + (lane & 15) * 8 + 4;
                uint32_t pos = lds32(xa), lt;
                asm volatile("mov.u32 %0, %lanemask_lt;" : "=r"(lt));
                if (lane >= st.x) pos = 0x80000000u;
                const bool dup = (__match_any_sync(~0u, pos >> 16) & lt) && lane < st.x;
                if (lane < 16) sts32(xa, dup ? pos | 0x40000000u : pos);
                if (__any_sync(~0u, dup)) sts32(barw + 84, st.y | 0x10000u);
                const float2 ml = softmax(ldsf(sa()), ldsf(sa() + 128), ldsf(sa() + 256), ldsf(sa() + 384));
                sts64f(sb + SM_ML + warp * 8, ml.x, warp_sum(ml.y));
            }
            u64 pm = 0, pl = 0;
#pragma unroll 1
            do {
                const uint4 tn = tab[2 * e + 2];
                if (tw.x & (G_A | G_B | G_C)) {
                    if (tw.x & G_A) {
                        if (lane < 24) st_rlx(&P.g->ll[cta][warp * 24 + lane], 0ull);
                        else if (lane < 28) st_rlx(&P.g->ll[cta][168 + warp * 4 + lane], ll_pack(ldsf(sb + SM_ML + warp * 8 + (lane & 1) * 4), lds32(sb + SM_EPOCH) * 4 + 2));
                    }
                    if (warp == 0 && cta < 80 && elect()) {
                        if (tw.x & G_A) {
#pragma unroll 1
                            for (int k = 0; k < 8; k++) {
                                const int r = (cta & 1) * 2 + (k >> 2);
                                asm volatile("cp.async.bulk.global.shared::cta.bulk_group [%0], [%1], 64;"
                                             :: "l"(P.g->acc + r * ACC_BYTES + ((cta >> 1) * acc_pitch(r) & ~127) + (k & 3) * 64), "r"(sb + SM_ZERO) : "memory");
                            }
                            asm volatile("cp.async.bulk.commit_group;" ::: "memory");
                        }
                        if (tw.x & G_B) asm volatile("cp.async.bulk.wait_group 0;\nred.relaxed.gpu.global.add.u32 [%0], 1;" :: "l"(&P.g->zeroed) : "memory");
                    }
                    if (warp == 2) {
                        if (tw.x & G_B) ld_rlx2(&P.g->ll[cta ^ (lane >> 3)][192 + (lane & 7) * 4], pm, pl);
                        if (tw.x & G_C) head_weight(&P.g->ll[cta ^ (lane >> 3)][192 + (lane & 7) * 4], pm, pl, 0, lane);
                    }
                    __syncwarp();
                }
                const uint32_t pp = lds32(prow + 256 + t * 80 + ((tw.x >> 20) & 255));
                mbar_wait(sb + SM_CBAR + (tw.x & 0xf8), tw.x >> 31);
                TRACE(e);
                uint4 v[6];
                load_v(v, tw.x & 0x3f000);
                refill(tw, release(tw));
                pv(v, pp);
                tw = tn;
            } while (++e < 32);
        };
        uint32_t osa, ora, owa, orow, otag;
        u64* olb;
        float xc;
        auto o_setup = [&](auto L) {
            fresh();
            const int lz = lane, d = warp * 24 + min(lz, 23);
            osa = pin(prow + ((lz >> 2) * 8 + (lz & 1) * 4 + (lz & 2)) * 4);
            ora = pin(sb + SM_PART + d * 4);
            olb = pin(&P.g->ll[cta & ~3][d]);
            orow = pin((lz & 1) + 2 * (lz & 2) + 2 * (lz >> 4));
            owa = pin(sb + SM_RING + warp * 1536 + orow * 64 + ((((lz >> 2) & 3) ^ (orow >> 1)) << 4));
            otag = lds32(sb + SM_EPOCH) * 4 + 2 + 2 * L.value;
            uint32_t x; asm volatile("ld.shared.u16 %0, [%1];" : "=r"(x) : "r"(prow + ((cta & 1) * 16 + (lz >> 3) * 4 + (cta & 2) + ((lz >> 2) & 1)) * 8 + (lz & 3) * 2) : "memory");
            xc = bf_lo(x) * (1.f / 32);
        };
        auto wo_at = [&](auto A) {
            constexpr uint32_t x = WOP ^ A.value * 0x11111;
            if constexpr (A.value > 0 && ((x - 0x11111) & ~x & 0x88888) != 0) {
                if ((WOP >> (4 * warp) & 15) == A.value) {
                    mbar_wait(sb + SM_CBAR + CB_REL * 8, 0);
                    if (elect()) {
                        const uint32_t bar = sb + SM_CBAR + (CB_WO + warp) * 8;
                        mbar_expect(bar, HALF);
                        tma3(sb + SM_RING + (warp + (warp < 2 ? 3 : -2)) * HALF, tmk + TM_WO, (cta & 3) + 4 * warp, (cta >> 2) * DH, bar, POL_FIRST);
                    }
                    __syncwarp();
                }
            }
        };
        static_assert(ring_hs(64) == 3, "wo");
        auto pass2 = [&]() {
            constexpr IC<1> L{};
            refill2(IC<4>{});
            uint4 tb[8][3];
            auto load_tb = [&](auto I) {
#pragma unroll
                for (int i = 0; i < 3; i++) tb[I.value][i] = lds128(offL + (I.value >> 1) * TILE + ((I.value & 1) * 3 + i) * 512);
            };
            uint32_t m1, m1n, done;
            const u64* qb = &P.g->ll[cta & ~3][min(tid, 191)];
            {
                uint32_t x[2];
                fx2_wait<2>([&](int i) { return rap + i * 20 * acc_pitch(1); }, look_rw, rw, sb + SM_MSQ, ldsf(sb + SM_MSQ + 4), x);
                xp = make_uint2(x[0], x[1]);
                CSTAMP(25, xp.y);
            }
            ln_stats();
            u64 qw[4];
            offL = subw + lane * 16;
            static_for<0, NPRE>(load_tb);
            m1n = m1 = reads_done();
            ll_look<256>(qb, qw);
            const float cs = ldsf(sb + SM_CS + min(tid, 191) * 4);
            const uint32_t qtag = lds32(sb + SM_EPOCH) * 4 + 3, qa = pin(q_addr(min(tid, 191)));
            fresh_lane();
            offQ = sb + SM_VEC + (lane & 7) * 48; offL = subw + lane * 16;
            __syncthreads();
            auto vwait = [&](auto I) { mbar_wait(barw + IC<SCH.st[I.value].slot>::value * 8, IC<SCH.st[I.value].par>::value); };
            bool ok;
            {
                float mean, rstd;
                ln_final(mean, rstd);
                const float sq = shx(rstd * 0x1p64f, 0), q0 = shx(-mean * cs * sq, 0);
                CSTAMP(26, __float_as_uint(q0));
                refill2(IC<5>{}, m1);
                sts64(prow + lane * 8, xp.x, xp.y);
                sts128f(prow + 256 + lane * 16, 0.f, 0.f, 0.f, 0.f);
                const float q = ll_gather<256>(qb, qtag, qw) * sq + q0;
                sts16(qa, pack_bf(q, q));
                TSTAMPL(24);
                CSTAMP(27, __float_as_uint(q));
            }
            __syncthreads();
            uint4 qf[3];
            load_q(qf);
            CSTAMP(28, qf[0].x);
            float S[4], d[2][4];
            auto vload = [&](auto I) {
                constexpr int p = I.value;
                constexpr Step c = SCH.st[p];
                load_v(kr[p & 7], c.slot * TILE);
                if constexpr (c.next >= 0 && p >= NPARK) {
                    static_assert(c.next - 9 < c.mma0, "the slot's last tile has been multiplied");
                    refill2(IC<c.next>{});
                }
                if constexpr (p == 11) { __syncwarp(); if (elect()) asm volatile("mbarrier.arrive.shared::cta.b64 _, [%0];" :: "r"(sb + SM_CBAR + CB_REL * 8) : "memory"); }
            };
            static_for<0, 96>([&](auto F) {
                constexpr int f = F.value, i = f % 6, u = kunit(f / 6), w = 3 * f % 12;
                uint4 (&src)[3] = *reinterpret_cast<uint4 (*)[3]>(f < 32 ? &tb[f / 4 & 7][0] : &kr[(f / 8 + 4) & 7][(f / 4 & 1) * 3]);
                const uint4 a = k_unpack(word<w % 4>(src[w / 4]), word<(w + 1) % 4>(src[(w + 1) / 4]), word<(w + 2) % 4>(src[(w + 2) / 4]), m1);
                if constexpr (f % 8 == (f < 32 ? RF0 : RF1) + M1D) m1 = m1n;
                if constexpr (f % 4 == 3 && f / 4 + NPRE < 8) {
                    load_tb(IC<f / 4 + NPRE>{});
                    if constexpr (f % 8 == 7) done = reads_done();
                }
                if constexpr (f >= 8 && f < 32 && f % 8 == RF0) { refill2(IC<5 + f / 8>{}, done); m1n = lds32(sb + SM_M1); }
                if constexpr (f >= 40 && f % 8 == RF1) {
                    if constexpr (PARKS >> (f / 8 - 5) & 1) { refill2(IC<SCH.st[popc(PARKS & ((1 << (f / 8 - 5)) - 1))].next>{}, done); m1n = lds32(sb + SM_M1); }
                }
                if constexpr (i < 2) d[i][0] = d[i][1] = d[i][2] = d[i][3] = 0.f;
                mma(d[i & 1], a, (i & 1) ? qf[i / 2].z : qf[i / 2].x, (i & 1) ? qf[i / 2].w : qf[i / 2].y);
                if constexpr (i == 5) {
                    if constexpr (u == 11 || ((u & 3) == 0 && u != 8)) S[u >> 2] = (d[0][0] + d[0][3]) + (d[1][0] + d[1][3]);
                    else add_if(t == (u & 3), S[u >> 2], d[0][0] + d[0][3], d[1][0] + d[1][3]);
                    if constexpr (f < 64) S[u >> 2] = shx(S[u >> 2], 0);
                }
                if constexpr (f == 31) { fresh(); calc_offsets(); ok = mbar_test(barw + IC<SCH.st[0].slot>::value * 8, 0); }
                if constexpr (f == 48) {
                    const uint2 x = lds64(sb + SM_EXC + warp * 128 + (lane & 15) * 8);
                    const float c = k_side(sb, x);
                    if (x.y < 0x40000000u) stsf(prow + 256 + (x.y >> 16), c);
                }
                if constexpr (f >= 32 && f % 8 == 7) {
                    if constexpr (PARKS >> (f / 8 - 4) & 1) {
                        constexpr int p = popc(PARKS & ((1 << (f / 8 - 4)) - 1));
                        if (!ok) vwait(IC<p>{});
                        vload(IC<p>{});
                        done = reads_done();
                        ok = mbar_test(barw + IC<SCH.st[p + 1].slot>::value * 8, IC<SCH.st[p + 1].par>::value);
                    }
                }
            });
            if constexpr (PARKS & 0x80) refill2(IC<SCH.st[NPARK - 1].next>{}, done);
            uint32_t bad = lds32(barw + 84);
            const uint32_t sc = lds32(sb + SM_SC + tid * 4);
            __syncwarp();
            if (bad) k_fix(P.k + (size_t)roww * DH, bad, warp, lane);
            TSTAMP(30);
            CSTAMP(29, __float_as_uint(S[2]));
            const float2 ml = softmax(S[0] * __uint_as_float((sc & 255) << 23) + ldsf(sa()), S[1] * __uint_as_float((sc & 0xff00) << 15) + ldsf(sa() + 128),
                                      S[2] * __uint_as_float((sc & 0xff0000) << 7) + ldsf(sa() + 256), S[3] * __uint_as_float((sc >> 24) << 23) + ldsf(sa() + 384));
            uint4 pq[4];
#pragma unroll
            for (int j = 0; j < 4; j++) pq[j] = lds128(prow + 256 + t * 80 + j * 16);
            TSTAMP(1);
            CSTAMP(30, pq[3].w);
            if (!ok) vwait(IC<NPARK>{});
            float ac2[3][4];
#pragma unroll
            for (int j = 0; j < 3; j++) ac2[j][0] = ac2[j][1] = ac2[j][2] = ac2[j][3] = 0.f;
            const uint32_t sl = (g & 1) ? 0x1044 : 0x4410, sh = (g & 1) ? 0x3244 : 0x4432;
            const uint32_t sA0 = (g & 2) ? 0x4444 : sl, sA1 = (g & 2) ? sl : 0x4444, sB0 = (g & 2) ? 0x4444 : sh, sB1 = (g & 2) ? sh : 0x4444;
            u64 pm = 0, pl = 0;
            static_for<NPARK, 16>([&](auto I) {
                constexpr int p = I.value;
                static_assert(p - SCH.st[p].mma0 < 8, "buffer in use");
                vload(I);
                if constexpr (p < 15) ok = mbar_test(barw + IC<SCH.st[p + 1].slot>::value * 8, IC<SCH.st[p + 1].par>::value);
                static_for<SCH.st[p].mma0, SCH.st[p].mma0 + SCH.st[p].nmma>([&](auto J) {
                    constexpr int u = SCH.st[J.value].unit;
                    const uint32_t pp = word<u & 3>(pq[u >> 2]), a0 = __byte_perm(pp, 0, sA0), a1 = __byte_perm(pp, 0, sA1), b0 = __byte_perm(pp, 0, sB0), b1 = __byte_perm(pp, 0, sB1);
#pragma unroll
                    for (int j = 0; j < 3; j++) mma(acc[j], kr[J.value & 7][j], a0, a1);
#pragma unroll
                    for (int j = 0; j < 3; j++) mma(ac2[j], kr[J.value & 7][j + 3], b0, b1);
                });
                if constexpr (p == NPARK) {
                    const float l = warp_sum(ml.y);
                    st_rlx_if(lane < 4, &P.g->ll[cta][192 + warp * 4 + lane], ll_pack((lane & 1) ? l : ml.x, lds32(sb + SM_EPOCH) * 4 + 4));
                }
                if constexpr (p == HWAT) { if (warp == 6) ld_rlx2(&P.g->ll[cta ^ (lane >> 3)][192 + (lane & 7) * 4], pm, pl); }
                if constexpr (p == 13) o_setup(L);
                if constexpr (p == HWAT + 2) { if (warp == 6) head_weight(&P.g->ll[cta ^ (lane >> 3)][192 + (lane & 7) * 4], pm, pl, 1, lane); }
                wo_at(IC<p - 10>{});
                if constexpr (p < 15) { if (!ok) mbar_wait(barw + IC<SCH.st[p + 1].slot>::value * 8, IC<SCH.st[p + 1].par>::value); TRACE(33 + p); }
            });
#pragma unroll
            for (int j = 0; j < 3; j++)
#pragma unroll
                for (int k = 0; k < 2; k++) { acc[j][k] += ac2[j][k]; add_if(t & 2, acc[j][k], acc[j][k + 2], ac2[j][k + 2]); }
        };

        const unsigned char* ap;
        uint32_t hpa, hsa, hst, w2a, la;
        uint2 b2v;
        float b1v, cs1;
        auto mlp_global = [&](auto L) {
            const int cz = c4();
            ap = accg + 2 * L.value * ACC_BYTES + (cz >> 2) * acc_pitch(0) + (cz & 3) * 16;
            if (L.value) ap = pin(ap);
            rap = pin(accg + (2 * L.value + 1) * ACC_BYTES + (cz >> 3) * acc_pitch(2 * L.value + 1) + (cz & 7) * 8);
            asm volatile("ld.global.nc.v2.u32 {%0,%1}, [%2];" : "=r"(b2v.x), "=r"(b2v.y) : "l"(P.b2 + 4 * cz));
        };
        auto mlp_shared = [&](auto L) {
            const int lz = lane;
            hpa = pin(sb + SM_PART + warp * 256 + ((lz & 2) * 4 + (lz >> 2)) * 16 + (L.value ? 0 : (lz & 1) * 4));
            hsa = pin(sb + SM_PART + (lz & 15) * 16); hst = pin(sb + SM_PART + (lz & 15) * 16 + warp * 256 + 8 + (lz >> 4) * 4);
            w2a = pin(sb + (L.value ? 3 * TILE : SM_W2) + ((lz & 3) * 10 + 2 * warp) * 128 + (((lz >> 2) ^ ((2 * lz + 2 * warp) & 6)) << 4));
            la = sb + (L.value ? 2 * TILE : SM_W1) + warp * 4096 + (lz & 4) * 512 + (lz & 2) * 64 + (lz & 1) * 32 + (lz >> 4) * 64 + ((((lz >> 3) ^ (lz >> 1)) & 1) << 4);
            b1v = ldsf(sb + SM_B1 + (lz & 15) * 4);
            if (L.value) { la = pin(la); cs1 = ldsf(sb + SM_ML + (lz & 15) * 4); }
            else fresh();
        };
        uint32_t pa;
        unsigned char* rop;
        uint32_t wpa;
        float sc1;
        auto sum_setup = [&](auto L) {
            const int lz = lane, word = warp * 128 + (cta & 3) * 32 + lz;
            wpa = pin(sb + SM_RING + warp * 1536 + ((((lz >> 2) * 8 + (lz & 1) * 4) * 4) ^ ((((lz >> 1) ^ (lz >> 4)) & 1) ? 256 + 64 : 0)));
            sc1 = pinf(fx2_scale(ldsf(sb + SM_FXS)) * 0.25f);
            pa = pin(sb + SM_RING + warp * 256 + ((lz * 4) ^ ((warp & 1) * 64)));
            rop = pin(accg + 2 * L.value * ACC_BYTES + (word >> 4) * acc_pitch(0) + (word & 15) * 4);
        };
        auto out_proj = [&](auto L) {
            TSTAMP2(3);
            CSTAMP(0, __float_as_uint(acc[2][1]));
            __syncwarp();
#pragma unroll
            for (int j = 0; j < 3; j++) {
                if (L.value == 0 && (t & 2)) { acc[j][0] = acc[j][2]; acc[j][1] = acc[j][3]; }
                sts64f(osa + 256 * j, acc[j][0], acc[j][1]);
            }
            __syncthreads();
            {
                float s[8];
#pragma unroll
                for (int w = 0; w < 8; w++) s[w] = ldsf(ora + w * 768);
                const uint4 fa = lds128(sb + SM_FAC), fb = lds128(sb + SM_FAC + 16);
            CSTAMP(1, __float_as_uint(s[0]));
                const float own = ((s[0] * __uint_as_float(fa.x) + s[1] * __uint_as_float(fa.y)) + (s[2] * __uint_as_float(fa.z) + s[3] * __uint_as_float(fa.w))) +
                                  ((s[4] * __uint_as_float(fb.x) + s[5] * __uint_as_float(fb.y)) + (s[6] * __uint_as_float(fb.z) + s[7] * __uint_as_float(fb.w)));
                st_rlx_if(lane < 24, olb + (cta & 3) * 256, ll_pack(own, otag));
            CSTAMP(2, __float_as_uint(own));
            }
            TSTAMPL(29);
            if (L.value == 0) fresh();
            if (L.value) wo_at(IC<6>{});
            if (L.value == 0 && warp == 7) {
#pragma unroll 1
                for (int it = 0; it < SPIN; it++) {
                    uint32_t v; asm volatile("ld.acquire.gpu.global.u32 %0, [%1];" : "=r"(v) : "l"(&P.g->zeroed) : "memory");
                    if (__all_sync(~0u, v == (lds32(sb + SM_EPOCH) + 1) * 80)) break;
                }
            }
            constexpr int NW = L.value ? NWO1 : 3;
            uint4 v[5][3];
            u64 ow[4];
            auto read_wo = [&](auto J) {
#pragma unroll
                for (int p = 0; p < 3; p++) v[J.value][p] = lds128(((J.value & 1) ? owa ^ 144 : owa) + ring_hs(64 + J.value) * HALF + p * 512);
            };
            static_for<0, NW>([&](auto J) {
                if (L.value && J.value == 0) { sum_setup(L); maskA = pin(maskA); maskB = pin(maskB); }
                if (J.value == 2) { ll_look<256>(olb, ow); if (L.value) { mlp_shared(L); mlp_global(L); } }
                mbar_wait(sb + SM_CBAR + (CB_WO + J.value) * 8, L.value);
                read_wo(J);
                if (L.value == 0 && J.value == 2) {
                    __syncwarp();
                    if (elect() && cnt_inc(sb + SM_CNT + CB_W1 * 8, 7) == 7) issue_w(L, 0);
                    __syncwarp();
                }
                if (L.value == 1 && J.value == 2) {
                    if (warp == 7 && elect()) issue_w(L, 0);
                    __syncwarp();
                }
            });
            sched_fence();
            const float o = ll_gather<256>(olb, otag, ow);
            CSTAMP(3, __float_as_uint(o));
            TSTAMP2(4);
            bool ok = true;
            if constexpr (NW < 5) ok = mbar_test(sb + SM_CBAR + (CB_WO + 4) * 8, L.value);
            if constexpr (NW < 4) ok &= mbar_test(sb + SM_CBAR + (CB_WO + 3) * 8, L.value);
            const uint32_t od = pack_bf(o, o);
            uint32_t oa[3], ob[3];
#pragma unroll
            for (int p = 0; p < 3; p++) { const uint32_t op = __shfl_sync(~0u, od, 8 * p + orow); oa[p] = op & maskA; ob[p] = op & maskB; }
            CSTAMP(4, oa[2]);
            float y[5][4];
#pragma unroll
            for (int j = 0; j < 5; j++) y[j][0] = y[j][1] = y[j][2] = y[j][3] = 0.f;
            auto rest = [&]() {
                if (!ok) static_for<NW, 5>([&](auto J) { mbar_wait(sb + SM_CBAR + (CB_WO + J.value) * 8, L.value); });
                static_for<NW, 5>(read_wo);
                __syncwarp();
            };
            if (L.value) rest();
#pragma unroll
            for (int p = 0; p < 3; p++)
#pragma unroll
                for (int j = 0; j < NW; j++) mma(y[j], v[j][p], oa[p], ob[p]);
            if (!L.value) { rest(); sum_setup(L); }
#pragma unroll
            for (int p = 0; p < 3; p++)
#pragma unroll
                for (int j = NW; j < 5; j++) mma(y[j], v[j][p], oa[p], ob[p]);
            CSTAMP(5, __float_as_uint(y[4][3]));
#pragma unroll
            for (int j = 0; j < 5; j += 2) {
                if (j < 4 && (t >> 1) != (g >> 2)) { y[j][0] = y[j + 1][0]; y[j][1] = y[j + 1][1]; y[j][2] = y[j + 1][2]; y[j][3] = y[j + 1][3]; }
                sts128f(wpa + j * 256, y[j]);
            }
            TSTAMP2(5);
        };
        u64 yw[2];
        bool wide;
        float msq = 0.f, yf[4] = {};
        auto mlp_part = [&](auto L) {
            bar_sync(0, 256);
            CSTAMP(6, __float_as_uint(sc1));
            const float s = (sum8(pa, 1536) + xc) + sum8(pa + 128, 1536), sm = s * sc1 + FX2_ONE;
            CSTAMP(7, __float_as_uint(s));
            const bool wide1 = !(fabsf(sm - FX2_ONE) < FX1LIM);
            asm volatile("red.relaxed.gpu.global.add.u32 [%0], %1;" :: "l"(rop), "r"(wide1 ? 0u : __float_as_uint(sm) * 128u + (1u - 0x4b400000u * 128u)) : "memory");
            const uint32_t c0 = clk();
            TSTAMP2(6);
            if (L.value == 0) bar_arrive(2, 256);
            if (wide1) {
                fx_send(rop + 64 + (lane & 15) * 4, s, ldsf(sb + SM_FXS), rop, 64);
                asm volatile("red.relaxed.gpu.global.add.u32 [%0], 1;" :: "l"(rop) : "memory");
            }
            __syncwarp();
            if (L.value == 1 && mlp == 96) { TDUMP(); asm volatile("exit;"); }
            uint4 wf[8], w2r[8];
            uint4 w;
            auto look = [&]() { asm volatile("ld.relaxed.gpu.global.v4.u32 {%0,%1,%2,%3}, [%4];" : "=r"(w.x), "=r"(w.y), "=r"(w.z), "=r"(w.w) : "l"(ap) : "memory"); };
            auto read_w1 = [&]() {
#pragma unroll
                for (int j = 0; j < 8; j++) wf[j] = ldsm_t(la + j * 256);
            };
            auto read_w2 = [&]() {
#pragma unroll
                for (int i = 0; i < 8; i++) w2r[i] = lds128(((i & 1) ? (w2a ^ 16) + 128 : w2a) + (i >> 1) * 5120);
            };
            const float inv = pinf(fx_inv(sc1) * (1.f / 128)), off = L.value ? pinf(fx_inv(sc1) * -0.25f) : inv * -32.f;
            if (L.value == 0) { fresh(); mlp_global(L); }
            mbar_wait(sb + SM_CBAR + CB_W1 * 8, L.value);
            if (L.value == 1) read_w1();
            while (clk() - c0 < AR1D);
            look();
            if (L.value == 0) { mlp_shared(L); read_w1(); bar_arrive(3, 256); }
            else { mbar_wait(sb + SM_CBAR + CB_W2 * 8, 1); read_w2(); }
            TSTAMPL(28);
            {
                sched_fence();
                auto miss = [&]() {
                    xp = make_uint2(pack_bf((float)(int)w.x * inv + off, (float)(int)w.y * inv + off), pack_bf((float)(int)w.z * inv + off, (float)(int)w.w * inv + off));
                    uint32_t a, b;
                    asm("lop3.b32 %0, %1, %2, 32, 0x7e;" : "=r"(a) : "r"(w.x), "r"(w.y));
                    asm("lop3.b32 %0, %1, %2, 32, 0x7e;" : "=r"(b) : "r"(w.z), "r"(w.w));
                    return __any_sync(~0u, (a | b) & 96);
                };
                if (miss()) {
                    int it = 0;
#pragma unroll 1
                    do {
                        if (!__any_sync(~0u, ~(w.x & w.y & w.z & w.w) & 32)) { xp.x = fx1_wide(ap, ldsf(sb + SM_FXS)); xp.y = fx1_wide(ap + 8, ldsf(sb + SM_FXS)); break; }
                        look();
                    } while (miss() & (++it < SPIN));
                }
                CSTAMP(8, w.w);
            }
            TSTAMP2(7);
            CSTAMP(9, xp.y);
            {
                bool ok = true;
                if (L.value == 0) ok = mbar_test(sb + SM_CBAR + CB_W2 * 8, 0);
                const bool ev = L.value || !(g & 1), od = L.value || (g & 1);
                const uint32_t e0 = ev ? xp.x : ONES, e1 = ev ? xp.y : ONES, o0 = od ? xp.x : ONES, o1 = od ? xp.y : ONES;
                float d[8][4];
#pragma unroll
                for (int j = 0; j < 8; j++) { d[j][0] = d[j][1] = d[j][2] = d[j][3] = 0.f; mma(d[j], wf[j], (j & 1) ? o0 : e0, (j & 1) ? o1 : e1); }
                float ss = ln_part(xp, lane);
                ss += shx(ss, 8); ss += shx(ss, 4);
                float r[4], dd;
#pragma unroll
                for (int k = 0; k < 4; k += 1 + L.value) r[k] = d[0][k] + d[1][k ^ 1];
#pragma unroll
                for (int j = 1; j < 4; j++)
#pragma unroll
                    for (int k = 0; k < 4; k += 1 + L.value) add_if(t == j, r[k], d[2 * j][k], d[2 * j + 1][k ^ 1]);
                CSTAMP(10, __float_as_uint(r[2]));
                if (L.value) {
                    dd = ((t & 2) ? r[2] : r[0]) + shx((t & 2) ? r[0] : r[2], 2);
                    ss += shx(ss, 2);
                    dd += shx(dd, 1);
                } else {
                    const float a = ((t & 1) ? r[1] : r[0]) + shx((t & 1) ? r[0] : r[1], 1), b = ((t & 1) ? r[3] : r[2]) + shx((t & 1) ? r[2] : r[3], 1);
                    ss += shx(ss, 2);
                    dd = ((t & 2) ? b : a) + shx((t & 2) ? a : b, 2);
                }
                ss += shx(ss, 1);
                stsf(hpa, dd);
                stsf(hst, ss);
                CSTAMP(11, __float_as_uint(dd + ss));
                if (!ok) mbar_wait(sb + SM_CBAR + CB_W2 * 8, L.value);
            }
            TSTAMPL(25);
            bar_sync(1, 160);
            uint4 hp[5];
#pragma unroll
            for (int w = 0; w < 5; w++) hp[w] = lds128(hsa + w * 256);
            CSTAMP(12, hp[0].x);
            auto hs = [&](auto K) { return sum5(__uint_as_float(word<K.value>(hp[0])), __uint_as_float(word<K.value>(hp[1])), __uint_as_float(word<K.value>(hp[2])),
                                                __uint_as_float(word<K.value>(hp[3])), __uint_as_float(word<K.value>(hp[4]))); };
            const float mean = hs(IC<2>{}) * (1.f / D_MODEL);
            msq = hs(IC<3>{}) * (1.f / D_MODEL);
            if (L.value == 0) cs1 = hs(IC<1>{});
            float hv = hs(IC<0>{}) - mean * cs1;
            CSTAMP(13, __float_as_uint(hv));
            const float sc2 = fx2_scale(msq), lim = fx_inv(sc2) * FX2LIM;
            if (L.value == 0) {
                read_w2();
                bar_arrive(4, 256);
                wide = false;
                if (mlp == 96) return;
            }
            hv = hv * ln_rstd(mean, msq) + b1v;
            CSTAMP(14, __float_as_uint(hv));
            hv = hv * rcp(1.f + ex2(hv * (-2.302208198f - 0.1029432397f * hv * hv)));
            const uint32_t hd = pack_bf(hv, hv);
            CSTAMP(15, hd);
            TSTAMPL(27);
            float ym[4][4];
#pragma unroll
            for (int i = 0; i < 2; i++) {
                ym[i][0] = ym[i][1] = ym[i][2] = ym[i][3] = 0.f;
                const float f = mlp < 64 ? 1.f / 64 : 0.f;
                ym[i + 2][0] = (bf_lo(xp.x) + bf_lo(b2v.x)) * f; ym[i + 2][1] = (bf_hi(xp.x) + bf_hi(b2v.x)) * f;
                ym[i + 2][2] = (bf_lo(xp.y) + bf_lo(b2v.y)) * f; ym[i + 2][3] = (bf_hi(xp.y) + bf_hi(b2v.y)) * f;
            }
#pragma unroll
            for (int i = 0; i < 4; i++) {
                const uint32_t hh = __shfl_sync(~0u, hd, 4 * i + t);
                mma(ym[(i & 1) * 2], w2r[2 * i], hh & maskA, hh & maskB);
                mma(ym[(i & 1) * 2 + 1], w2r[2 * i + 1], hh & maskA, hh & maskB);
            }
#pragma unroll
            for (int k = 0; k < 4; k++) { yf[k] = ym[0][k] + ym[2][k]; add_if(t & 2, yf[k], ym[1][k], ym[3][k]); }
            CSTAMP(16, __float_as_uint(yf[3]));
            yw[0] = fx2_pack(yf[0] * sc2 + FX2_ONE, yf[1] * sc2 + FX2_ONE); yw[1] = fx2_pack(yf[2] * sc2 + FX2_ONE, yf[3] * sc2 + FX2_ONE);
            wide = !(fmaxf(fmaxf(fabsf(yf[0]), fabsf(yf[1])), fmaxf(fabsf(yf[2]), fabsf(yf[3]))) < lim);
            if (wide) yw[0] = yw[1] = 0;
            if (L.value == 0) {
#pragma unroll
                for (int k = 0; k < 2; k++) asm volatile("red.relaxed.gpu.global.add.u64 [%0], %1;" :: "l"(rap + k * 20 * acc_pitch(1)), "l"(yw[k]) : "memory");
            }
        };
        auto send_wide = [&](int pitch) {
#pragma unroll 1
            for (int k = 0; k < 4; k++, yf[0] = yf[1], yf[1] = yf[2], yf[2] = yf[3]) {
                const unsigned char* a = rap + (k >> 1) * 20 * pitch;
                fx_send(a + 64 + (k & 1) * 64, yf[0], msq, a, 256);
            }
            yw[0] = yw[1] = 1;
        };

        pass1();
        o_setup(IC<0>{});
        out_proj(IC<0>{});
        uint32_t c0;
        if (warp < 5) {
            mlp_part(IC<0>{});
            c0 = clk() + (mlp == 96 ? PCD : 0);
            stsf(sb + SM_ML + (lane & 15) * 4, cs1);
            TSTAMP(8);
            if (__any_sync(~0u, wide)) {
                if (wide) {
                    send_wide(acc_pitch(1));
#pragma unroll
                    for (int k = 0; k < 2; k++) asm volatile("red.relaxed.gpu.global.add.u64 [%0], 1;" :: "l"(rap + k * 20 * acc_pitch(1)) : "memory");
                }
                __syncwarp();
            }
            fresh(); calc_offsets();
            load_wq();
        } else {
            bar_sync(0, 256);
            if (warp == 5 && elect()) {
                asm volatile("fence.proxy.async.shared::cta;" ::: "memory");
                issue_w(IC<0>{}, 1);
            }
            __syncwarp();
            fresh(); calc_offsets();
            load_wq();
#pragma unroll 1
            for (int ph = 0; ph < 3; ph++) {
                bar_sync(ph + 2, 256);
                c0 = clk();
                if (ph == 2) {
                    msq = sum5(ldsf(sb + SM_PART + 12), ldsf(sb + SM_PART + 268), ldsf(sb + SM_PART + 524), ldsf(sb + SM_PART + 780), ldsf(sb + SM_PART + 1036)) * (1.f / D_MODEL);
                    bar_arrive(5, 256);
                }
                if (elect()) {
                    asm volatile("fence.proxy.async.shared::cta;" ::: "memory");
                    const uint32_t gap = ph == 0 ? WG1 : ph == 1 ? WG2 : WG3;
                    uint32_t c1 = c0 + (ph == 0 ? WD1 : 0) + (warp - 5) * gap;
#pragma unroll 1
                    for (int k = warp + (ph == 0 ? -5 : ph == 1 ? 9 : 1); k < (ph == 0 ? 9 : ph == 1 ? 20 : 14); k += 3, c1 += 3 * gap) {
                        const int i = ph == 0 && k >= 6 ? k + 23 : k;
                        const uint32_t bar = sb + SM_BAR + (i & 7) * 96 + 32 + (i & 24);
                        while ((int)(clk() - c1) < 0);
                        mbar_expect(bar, SUB);
                        tma_v(sb + SM_RING + i * SUB, tmk,
                              rowc * 3 + (i & 7) * 24 + ((UC<SCH.st[0].unit | SCH.st[1].unit << 8 | SCH.st[2].unit << 16 | SCH.st[3].unit << 24>::value >> (i & 24)) & 15) * 768, bar);
                    }
                }
                __syncwarp();
            }
            c0 += PCD;
        }
        {
            constexpr IC<1> L{};
            fresh();
            const int col = xcol(g & 3, t), cw = j40 + (col >> 2);
            const unsigned char* xa = pin(accg + ACC_BYTES + ((cw >> 3) + (col & 2) * 10) * acc_pitch(1) + (cw & 7) * 8);
            const uint32_t pst = pin(prow + (g * 8 + (t & 1) * 4 + (t & 2)) * 4);
            const float inv = pinf(fx2_inv(msq));
            sts64f(sb + SM_MSQ, msq, inv);
            rap = pin(accg + ACC_BYTES + (c4() >> 3) * acc_pitch(1) + (c4() & 7) * 8);
            fresh();
            maskA = pin(maskA); maskB = pin(maskB);
            u64 w[1];
            uint32_t x1[1], x2[3];
            auto look = [&]() { w[0] = ld_rlx(xa); };
            if (warp < 5) bar_sync(5, 256);
            while ((int)(clk() - c0) < ARDELAY);
            look();
            while ((int)(clk() - c0) < ARDELAY + DPOST);
            if (warp < 5 && elect()) {
                issue_v(IC<3>{}, 0);
                if (warp < 4) issue_v(IC<2>{}, 4);
            }
            __syncwarp();
            fx2_wait<1>([&](int) { return xa; }, look, w, sb + SM_MSQ, inv, x1);
            if (warp < 5) look_rw(); else rw[0] = rw[1] = 96;
#pragma unroll
            for (int i = 0; i < 3; i++) x2[i] = __shfl_sync(~0u, x1[0], 4 * i + t);
            TSTAMP(9);
            CSTAMP(22, x2[2]);
            q_proj(L, x2, pst);
            pass2();
            out_proj(L);
            if (warp >= 5) {
                bar_arrive(0, 256);
                if (warp == 5 && elect()) issue_w(L, 1);
                TDUMP();
                return;
            }
            mlp_part(L);
            u64 old[2];
            auto add = [&]() {
#pragma unroll
                for (int k = 0; k < 2; k++) asm volatile("atom.relaxed.gpu.global.add.u64 %0, [%1], %2;" : "=l"(old[k]) : "l"(rap + k * 20 * acc_pitch(3)), "l"(yw[k]) : "memory");
            };
            add();
            uint32_t* op = pin(reinterpret_cast<uint32_t*>(P.out) + 2 * c4());
            const float inv2 = pinf(fx2_inv(msq));
            if (wide) { send_wide(acc_pitch(3)); add(); }
            TSTAMP(18);
            CSTAMP(17, hi32(yw[1]));
            __syncwarp();
            CSTAMP(18, lo32(old[0]) ^ lo32(old[1]));
#pragma unroll
            for (int k = 0; k < 2; k++) {
                yw[k] += old[k];
                asm volatile("{\n.reg .pred p;\nsetp.eq.u32 p, %2, 96;\n@p st.global.u32 [%0], %1;\n}"
                             :: "l"(op + k), "r"(fx2_get(yw[k], inv2)), "r"(lo32(yw[k]) & 511) : "memory");
            }
            if ((lo32(yw[0]) & 255) == 96 && tid == 0) P.g->epoch = lds32(sb + SM_EPOCH) + 1;
#pragma unroll
            for (int k = 0; k < 2; k++) if ((lo32(yw[k]) & 511) == 256 + 96) op[k] = fx2_wide(rap + k * 20 * acc_pitch(3), msq);
            TSTAMP(19);
            CSTAMP(19, lo32(yw[1]));
            TDUMP();
        }
    }
}

typedef CUresult (*EncodeFn)(CUtensorMap*, CUtensorMapDataType, cuuint32_t, void*, const cuuint64_t*, const cuuint64_t*, const cuuint32_t*,
                             const cuuint32_t*, CUtensorMapInterleave, CUtensorMapSwizzle, CUtensorMapL2promotion, CUtensorMapFloatOOBfill);

}

extern "C" void kernel_launch(void* const* d_in, const int* in_sizes, int n_in, void* d_out, int out_size) {
    (void)in_sizes; (void)n_in; (void)out_size;
    static EncodeFn enc = nullptr;
    static void* scratch = nullptr;
    if (!enc) {
        void* fn = nullptr;
        cudaDriverEntryPointQueryResult qr;
        cudaGetDriverEntryPoint("cuTensorMapEncodeTiled", &fn, cudaEnableDefault, &qr);
        enc = (EncodeFn)fn;
        cudaGetSymbolAddress(&scratch, g_scratch);
        cudaFuncSetAttribute(fused_kernel, cudaFuncAttributeMaxDynamicSharedMemorySize, SM_TOTAL);
    }
    Params P = {};
    auto map3 = [&](int m, int in, cuuint64_t d0, cuuint64_t d1, cuuint64_t d2, cuuint64_t s1, cuuint64_t s2, cuuint32_t b0, cuuint32_t b1, cuuint32_t b2,
                    CUtensorMapSwizzle sw, int promo) {
        const cuuint64_t dim[3] = {d0, d1, d2}, str[2] = {s1, s2};
        const cuuint32_t box[3] = {b0, b1, b2}, ones[3] = {1, 1, 1};
        enc(&P.tm[m], CU_TENSOR_MAP_DATA_TYPE_BFLOAT16, d2 ? 3 : 2, d_in[in], dim, str, box, ones, CU_TENSOR_MAP_INTERLEAVE_NONE, sw, (CUtensorMapL2promotion)promo,
            CU_TENSOR_MAP_FLOAT_OOB_FILL_NONE);
    };
    map3(TM_KH, 1, 64, 3, NHEAD * SK, 128, DH * 2, 64, 3, 32, CU_TENSOR_MAP_SWIZZLE_128B, 0);
    map3(TM_VH, 2, 64, 3, NHEAD * SK, 128, DH * 2, 64, 3, 32, CU_TENSOR_MAP_SWIZZLE_128B, 0);
    map3(TM_VP, 2, 64, 3, NHEAD * SK, 128, DH * 2, 8, 3, 32, CU_TENSOR_MAP_SWIZZLE_NONE, 0);
    map3(TM_V, 2, 64, NHEAD * SK * 3, 0, 128, 0, 64, 24, 0, CU_TENSOR_MAP_SWIZZLE_128B, 0);
    map3(TM_WO, 4, 32, 20, NHEAD * DH, 64, D_MODEL * 2, 32, 1, DH, CU_TENSOR_MAP_SWIZZLE_64B, 2);
    map3(TM_WOP, 4, 32, 20, NHEAD * DH, 64, D_MODEL * 2, 8, 1, DH, CU_TENSOR_MAP_SWIZZLE_NONE, 0);
    map3(TM_WQ, 3, 64, NHEAD * 3, D_MODEL, 128, NHEAD * DH * 2, 64, 3, 32, CU_TENSOR_MAP_SWIZZLE_128B, 0);
    map3(TM_W1, 6, DFF, 128, 5, DFF * 2, DFF * 256, 16, 128, 5, CU_TENSOR_MAP_SWIZZLE_32B, 2);
    map3(TM_W2, 8, 64, 10, DFF, 128, D_MODEL * 2, 64, 10, 16, CU_TENSOR_MAP_SWIZZLE_128B, 0);
    P.x = (const __nv_bfloat16*)d_in[0];
    P.k = (const __nv_bfloat16*)d_in[1];
    P.b1 = (const __nv_bfloat16*)d_in[7];
    P.b2 = (const __nv_bfloat16*)d_in[9];
    P.w1 = (const __nv_bfloat16*)d_in[6];
    P.out = (__nv_bfloat16*)d_out;
    P.g = (Scratch*)(((uintptr_t)scratch + ACC_BYTES - 1) & ~(uintptr_t)(ACC_BYTES - 1));
    for (int i = 0; i < 64; i++) P.tile[i] = make_uint4(SCH.tile[i][0], SCH.tile[i][1], SCH.tile[i][2], 0);
    fused_kernel<<<NCTA, NTHR, SM_TOTAL, cudaStreamPerThread>>>(P);
}
```

```cpp
#include <cuda_runtime.h>
#include <cuda_bf16.h>
#include <cuda.h>
#include <stdint.h>

namespace {

constexpr int D_MODEL = 640, NHEAD = 32, SK = 32768, DH = 192, WIN = 4096, DFF = 1536;
constexpr int NCTA = 128, NTHR = 256;
constexpr int TILE = 64 * DH * 2;
constexpr int HALF = TILE / 2;
constexpr int SUB = 8 * DH * 2;
constexpr int SM_RING = 4 * TILE;
constexpr int SM_W2 = SM_RING + 20480, SM_W1 = SM_W2 + 20480;
constexpr int SM_WQR = 6 * TILE + HALF, SM_WQ = 7 * TILE;
constexpr int SM_PART = 9 * TILE;
constexpr int SM_EXC = SM_PART + 6144;
constexpr int SM_SC = SM_EXC + 1024;
constexpr int SM_BAR = SM_SC + 1024;
constexpr int SM_VEC = SM_BAR + 768;
constexpr int SM_CS = SM_VEC + 384;
constexpr int SM_FAC = SM_CS + 768;
constexpr int SM_ML = SM_FAC + 32;
constexpr int SM_B1 = SM_ML + 64;
constexpr int SM_STAT = SM_B1 + 64;
constexpr int NCB = 28;
constexpr int CB_WO = 18, CB_W1 = 23, CB_W2 = 24, CB_SNAP = 25, CB_REL = 26, CB_WQ = 27;
constexpr int SM_CBAR = SM_STAT + 48;
constexpr int SM_CNT = SM_CBAR + NCB * 8;
constexpr int SM_ZERO = SM_CNT + NCB * 8;
constexpr int SM_EPOCH = SM_ZERO + 64;
constexpr int SM_FXS = SM_EPOCH + 4;
constexpr int SM_T0 = SM_FXS + 4;
constexpr int SM_M1 = SM_T0 + 4;
constexpr int SM_MSQ = SM_M1 + 4;
constexpr int SM_TS = SM_MSQ + 8;
constexpr int SM_TOTAL = 232448;
static_assert(SM_TS + 320 <= SM_TOTAL && SM_ZERO % 16 == 0, "smem");
constexpr int NEXC = 16;

constexpr int SPIN = 1 << 20;
enum { TM_V = 0, TM_KH = 1, TM_VH = 2, TM_WO = 3, TM_VP = 4, TM_WOP = 5, TM_W1 = 6, TM_W2 = 7, TM_WQ = 8 };
constexpr uint32_t POL_NORMAL = 0x16F00000u, POL_FIRST = 0x12F00000u;

#define PACE 980
#define PACE0 1500
#define PACES 1300
#define NI1 6
#define ETRIG 0x54321000
#define PFREE 66
#define SNAPAT 2
#define LATEAT 5
#define PUBAT 28
#define HW0 30
#define HW1 31
#define AR1D 250
#define ARDELAY 720
#define DPOST 200
#define PCD 350
#define WD1 100
#define WG1 140
#define WG2 120
#define WG3 65
#define VORD2 0x7685943a2b1cd0efull
#define VSLOT 0x1087654321087654ull
#define VTRIG 0xba73210
#define PARKS 0xa5
#define RF0 1
#define RF1 2
#define M1D 1
#define LAG0 12
#define NMMA 2
#define HWAT 12
#define WOP 0x44433
#define NWO1 4
#define FX1LIM 524288.f
#define FX2LIM 524288.f

constexpr uint32_t G_A = 1u << 28, G_B = 1u << 29, G_C = 1u << 30;
__host__ __device__ constexpr int ring_hs(int j) { return (j + 4) % 5; }
__host__ __device__ constexpr uint32_t load_word(int j) {
    if (j >= 64) return (uint32_t)(j - 64) << 20 | (SM_RING + ring_hs(j) * HALF) | TM_WO << 8 | (CB_WO + j - 64) << 3 | 2;
    const int e = j >> 1, isv = e >= 16, unit = e & 15;
    return (uint32_t)(unit * 256 + (j & 1) * 32) << 20 | (j < 8 ? j * HALF : SM_RING + ring_hs(j) * HALF) | (TM_KH + isv) << 8 | (j < 8 ? 10 + j : (j - 8) % 10) << 3 | 2 | !isv;
}
__host__ __device__ constexpr int popc(int v) { return v ? (v & 1) + popc(v >> 1) : 0; }
constexpr int NPARK = popc(PARKS), NPRE = 2;
constexpr int SM_SNAP = SM_RING + ring_hs(12) * HALF, SM_CSP = SM_RING + ring_hs(11) * HALF;
struct Step { int unit, slot, par, next, mma0, nmma; };
struct Sched { uint32_t tile[64][3]; Step st[16]; };
constexpr Sched make_sched() {
    Sched s{};
    for (int j = 0; j < 64; j++) {
        const int e = j >> 1;
        const uint32_t d = load_word(j);
        uint32_t w = (uint32_t)(j < 8 ? 0 : (j - 8) / 10 & 1) << 31 | (e & 15) * 4 << 20 | ((d & 0x3f000) - (j & 1) * HALF) | (d & 0xf8);
        if (e == PUBAT || e == SNAPAT) w |= G_A;
        if (e == HW0 || e == 4) w |= G_B;
        if ((e >= LATEAT && e < LATEAT + 4) || e == HW1) w |= G_C;
        s.tile[j][0] = w;
    }
    for (int j = NI1; j < 69; j++) {
        if (j == 12) continue;
        const int at = j < 12 ? (ETRIG >> (4 * (j - 4)) & 15) : j - 5;
        s.tile[at][1] = load_word(j);
        s.tile[at][2] = j >= PFREE ? 0 : PACE0 + j * PACE / 2;
    }
    int done = 0;
    for (int p = 0; p < 16; p++) {
        Step& c = s.st[p];
        c.unit = (int)(VORD2 >> (4 * p) & 15); c.slot = (int)(VSLOT >> (4 * p) & 15); c.par = p >= 9; c.next = -1;
        c.mma0 = done;
        if (p >= NPARK) { const int avail = p - done + (p >= LAG0); c.nmma = p == 15 ? 16 - done : (avail < NMMA ? avail : NMMA); done += c.nmma; }
    }
    for (int p = 9; p < 16; p++) s.st[VTRIG >> (4 * (p - 9)) & 15].next = p;
    return s;
}
constexpr Sched SCH = make_sched();
__host__ __device__ constexpr int kunit(int o) { return o < 5 ? o + 11 : o == 5 ? 10 : o - 6; }

template <int I> struct IC { static constexpr int value = I; };
template <uint32_t I> struct UC { static constexpr uint32_t value = I; };
template <int A, int B, class F> __device__ __forceinline__ void static_for(F&& f) {
    if constexpr (A < B) { f(IC<A>{}); static_for<A + 1, B>(f); }
}

typedef unsigned long long u64;
constexpr int ACC_BYTES = 65536;
__host__ __device__ constexpr int acc_pitch(int r) { return (r & 1) ? 832 : 256; }
struct alignas(1024) Scratch {
    unsigned char acc[4 * ACC_BYTES];
    u64 l0[NCTA][384];
    u64 ll[NCTA][256];
    alignas(128) unsigned epoch;
    alignas(128) unsigned zeroed;
};
__device__ __align__(1024) unsigned char g_scratch[sizeof(Scratch) + ACC_BYTES];

struct Params {
    CUtensorMap tm[9];
    const __nv_bfloat16 *x, *k, *b1, *b2, *w1;
    __nv_bfloat16* out;
    Scratch* g;
    uint4 tile[66];
};

#define TSTAMP(i)
#define TSTAMP2(i)
#define TSTAMPL(i)
#define TDUMP()
#define CSTAMP(i, x)
#define TRACE(i)

__device__ __forceinline__ void mbar_wait(uint32_t bar, uint32_t parity) {
    asm volatile("{\n.reg .pred p;\nLOOP:\nmbarrier.try_wait.parity.shared::cta.b64 p, [%0], %1;\n@!p bra.uni LOOP;\n}" :: "r"(bar), "r"(parity) : "memory");
}
__device__ __forceinline__ bool mbar_test(uint32_t bar, uint32_t parity) {
    uint32_t r;
    asm volatile("{\n.reg .pred p;\nmbarrier.test_wait.parity.shared::cta.b64 p, [%1], %2;\nselp.u32 %0, 1, 0, p;\n}" : "=r"(r) : "r"(bar), "r"(parity) : "memory");
    return __all_sync(~0u, r);
}
__device__ __forceinline__ bool elect() {
    uint32_t r;
    asm volatile("{\n.reg .pred p;\nelect.sync _|p, 0xffffffff;\nselp.u32 %0, 1, 0, p;\n}" : "=r"(r));
    return r != 0;
}
__device__ __forceinline__ void mbar_expect(uint32_t bar, uint32_t bytes) {
    asm volatile("mbarrier.arrive.expect_tx.shared::cta.b64 _, [%0], %1;" :: "r"(bar), "r"(bytes) : "memory");
}
__device__ __forceinline__ uint4 lds128(uint32_t a) {
    uint4 v; asm volatile("ld.shared.v4.u32 {%0,%1,%2,%3}, [%4];" : "=r"(v.x), "=r"(v.y), "=r"(v.z), "=r"(v.w) : "r"(a) : "memory"); return v;
}
__device__ __forceinline__ uint4 ldsm_t(uint32_t a) {
    uint4 v; asm volatile("ldmatrix.sync.aligned.m8n8.x4.trans.shared.b16 {%0,%1,%2,%3}, [%4];" : "=r"(v.x), "=r"(v.y), "=r"(v.z), "=r"(v.w) : "r"(a) : "memory"); return v;
}
__device__ __forceinline__ uint2 lds64(uint32_t a) {
    uint2 v; asm volatile("ld.shared.v2.u32 {%0,%1}, [%2];" : "=r"(v.x), "=r"(v.y) : "r"(a) : "memory"); return v;
}
__device__ __forceinline__ float2 lds64f(uint32_t a) { const uint2 v = lds64(a); return make_float2(__uint_as_float(v.x), __uint_as_float(v.y)); }
__device__ __forceinline__ uint32_t lds32(uint32_t a) {
    uint32_t v; asm volatile("ld.shared.u32 %0, [%1];" : "=r"(v) : "r"(a) : "memory"); return v;
}
__device__ __forceinline__ float ldsf(uint32_t a) { return __uint_as_float(lds32(a)); }
__device__ __forceinline__ void sts32(uint32_t a, uint32_t v) { asm volatile("st.shared.u32 [%0], %1;" :: "r"(a), "r"(v) : "memory"); }
__device__ __forceinline__ void stsf(uint32_t a, float v) { sts32(a, __float_as_uint(v)); }
__device__ __forceinline__ void sts16(uint32_t a, uint32_t v) { asm volatile("st.shared.u16 [%0], %1;" :: "r"(a), "h"((uint16_t)v) : "memory"); }
__device__ __forceinline__ void sts64(uint32_t a, uint32_t x, uint32_t y) { asm volatile("st.shared.v2.u32 [%0], {%1,%2};" :: "r"(a), "r"(x), "r"(y) : "memory"); }
__device__ __forceinline__ void sts64f(uint32_t a, float x, float y) { sts64(a, __float_as_uint(x), __float_as_uint(y)); }
__device__ __forceinline__ void sts128f(uint32_t a, float x, float y, float z, float w) {
    asm volatile("st.shared.v4.f32 [%0], {%1,%2,%3,%4};" :: "r"(a), "f"(x), "f"(y), "f"(z), "f"(w) : "memory");
}
__device__ __forceinline__ void mma(float (&c)[4], const uint4& a, uint32_t b0, uint32_t b1) {
    asm volatile("mma.sync.aligned.m16n8k16.row.col.f32.bf16.bf16.f32 {%0,%1,%2,%3}, {%4,%5,%6,%7}, {%8,%9}, {%0,%1,%2,%3};"
                 : "+f"(c[0]), "+f"(c[1]), "+f"(c[2]), "+f"(c[3]) : "r"(a.x), "r"(a.y), "r"(a.z), "r"(a.w), "r"(b0), "r"(b1));
}
__device__ __forceinline__ u64 ld_rlx(const void* p) {
    u64 a; asm volatile("ld.relaxed.gpu.global.u64 %0, [%1];" : "=l"(a) : "l"(p) : "memory"); return a;
}
__device__ __forceinline__ void ld_rlx2(const void* p, u64& a, u64& b) {
    asm volatile("ld.relaxed.gpu.global.v2.u64 {%0,%1}, [%2];" : "=l"(a), "=l"(b) : "l"(p) : "memory");
}
__device__ __forceinline__ void st_rlx(void* p, u64 a) { asm volatile("st.relaxed.gpu.global.u64 [%0], %1;" :: "l"(p), "l"(a) : "memory"); }
__device__ __forceinline__ u64 ll_pack(float v, uint32_t tag) { return ((u64)tag << 32) | __float_as_uint(v); }
__device__ __forceinline__ float ll_val(u64 w) { return __uint_as_float((uint32_t)w); }
__device__ __forceinline__ uint32_t ll_tag(u64 w) { return (uint32_t)(w >> 32); }
__device__ __forceinline__ float bf_lo(uint32_t u) { return __uint_as_float(u << 16); }
__device__ __forceinline__ float bf_hi(uint32_t u) { return __uint_as_float(u & 0xffff0000u); }
__device__ __forceinline__ uint32_t pack_bf(float lo, float hi) {
    uint32_t r; asm("cvt.rn.bf16x2.f32 %0, %1, %2;" : "=r"(r) : "f"(hi), "f"(lo)); return r;
}
__device__ __forceinline__ float ex2(float v) { float r; asm("ex2.approx.ftz.f32 %0, %1;" : "=f"(r) : "f"(v)); return r; }
__device__ __forceinline__ float rcp(float v) { float r; asm("rcp.approx.ftz.f32 %0, %1;" : "=f"(r) : "f"(v)); return r; }
__device__ __forceinline__ float rsq(float v) { float r; asm("rsqrt.approx.ftz.f32 %0, %1;" : "=f"(r) : "f"(v)); return r; }
__device__ __forceinline__ void bar_sync(int id, int n) { asm volatile("bar.sync %0, %1;" :: "r"(id), "r"(n) : "memory"); }
__device__ __forceinline__ uint32_t clk() { uint32_t c; asm volatile("mov.u32 %0, %clock;" : "=r"(c)); return c; }
__device__ __forceinline__ void sched_fence() { __syncwarp(); while (clk() == 0x9e3779b9u); }
__device__ __forceinline__ uint32_t pin(uint32_t v) { return __shfl_xor_sync(~0u, v, 0); }
__device__ __forceinline__ float shx(float v, int o) { return __shfl_xor_sync(~0u, v, o); }

__device__ __forceinline__ u64 fx_pack(float v, float scale) { return ((u64)__float2ll_rn(v * scale) & ~255ull) | 1ull; }
__device__ __forceinline__ float fx_scale(float meansq) {
    const int e = max(((int)(__float_as_uint(meansq) >> 23) - 127) >> 1, -6);
    return __uint_as_float((uint32_t)(127 + 32 - e) << 23);
}
__device__ __forceinline__ float fx_inv(float scale) { return __uint_as_float((254u << 23) - __float_as_uint(scale)); }
__device__ __forceinline__ uint32_t lo32(u64 w) { uint32_t l; asm("mov.b64 {%0, _}, %1;" : "=r"(l) : "l"(w)); return l; }
__device__ __forceinline__ int hi32(u64 w) { int h; asm("mov.b64 {_, %0}, %1;" : "=r"(h) : "l"(w)); return h; }
__device__ __forceinline__ float fx_val(u64 w) { return (float)hi32(w) * 4294967296.f + (float)lo32(w); }
constexpr float FX2_ONE = 12582912.f;
__device__ __forceinline__ float fx2_scale(float meansq) { return __uint_as_float((uint32_t)(127 + 16 - max(((int)(__float_as_uint(meansq) >> 23) - 127) >> 1, -100)) << 23); }
__device__ __forceinline__ u64 fx2_pack(float a, float b) {
    const uint32_t lo = __float_as_uint(a) * 512u + (1u - 0x4b400000u * 512u);
    return lo | (u64)(__float_as_uint(b) * 16u - 0x4b400000u * 16u + (uint32_t)((int)lo >> 31)) << 32;
}
__device__ __forceinline__ float fx2_lo(u64 w, float inv) { return (float)(int)(__funnelshift_r(lo32(w), hi32(w), 4) & ~31u) * (inv * 0.5f); }
__device__ __forceinline__ float fx2_hi(u64 w, float inv) { return (float)((hi32(w) + 8) & ~15) * inv; }
__device__ __forceinline__ uint32_t fx2_get(u64 w, float inv) {
    return pack_bf((float)(int)__funnelshift_r(lo32(w), hi32(w), 4) * (inv * 0.5f) - inv * 3.f, (float)hi32(w) * inv);
}
__device__ __forceinline__ float fx2_inv(float meansq) { return fx_inv(fx2_scale(meansq)) * 0.0625f; }
__device__ __noinline__ uint32_t fx2_wide(const unsigned char* a, float meansq) {
    __threadfence();
    const u64 w = ld_rlx(a);
    const float inv = fx_inv(fx_scale(meansq));
    return pack_bf(fx2_lo(w, fx2_inv(meansq)) + fx_val(ld_rlx(a + 64)) * inv, fx2_hi(w, fx2_inv(meansq)) + fx_val(ld_rlx(a + 128)) * inv);
}
__device__ __noinline__ uint32_t fx1_wide(const unsigned char* a, float meansq) {
    __threadfence();
    const u64 w = ld_rlx(a);
    const unsigned char* b = a + 64 + (reinterpret_cast<u64>(a) & 63);
    const float inv = fx_inv(fx_scale(meansq)), inv1 = fx2_inv(meansq) * 0.5f;
    return pack_bf((float)(int)(lo32(w) & ~127u) * inv1 + fx_val(ld_rlx(b)) * inv, (float)(hi32(w) & ~127) * inv1 + fx_val(ld_rlx(b + 8)) * inv);
}
__device__ __noinline__ void fx_send(const unsigned char* wide, float v, float meansq, const unsigned char* a, uint32_t flag) {
    asm volatile("red.relaxed.gpu.global.add.u64 [%0], %1;" :: "l"(wide), "l"(fx_pack(v, fx_scale(meansq))) : "memory");
    __threadfence();
    asm volatile("red.relaxed.gpu.global.or.b32 [%0], %1;" :: "l"(a), "r"(flag) : "memory");
}
template <int N, class A, class F> __device__ __forceinline__ void fx2_wait(A a, F look, u64 (&w)[N], uint32_t msqa, float inv, uint32_t (&x)[N]) {
    auto miss = [&]() {
#pragma unroll
        for (int i = 0; i < N; i++) x[i] = fx2_get(w[i], inv);
        return __any_sync(~0u, ((lo32(w[0]) ^ 96) | (lo32(w[N - 1]) ^ 96)) & 0x160);
    };
    if (miss()) {
        int it = 0;
#pragma unroll 1
        do {
            if (__all_sync(~0u, (lo32(w[0]) & lo32(w[N - 1]) & 96) == 96)) {
#pragma unroll
                for (int i = 0; i < N; i++) x[i] = fx2_wide(a(i), ldsf(msqa));
                break;
            }
            look();
        } while (miss() & (++it < SPIN));
    }
}
__device__ __forceinline__ void st_rlx_if(bool p, void* a, u64 v) {
    asm volatile("{\n.reg .pred p;\nsetp.ne.u32 p, %2, 0;\n@p st.relaxed.gpu.global.u64 [%0], %1;\n}" :: "l"(a), "l"(v), "r"((uint32_t)p) : "memory");
}
__device__ __forceinline__ void sts128f(uint32_t a, const float (&v)[4]) { sts128f(a, v[0], v[1], v[2], v[3]); }
__device__ __forceinline__ void bar_arrive(int id, int n) { asm volatile("bar.arrive %0, %1;" :: "r"(id), "r"(n) : "memory"); }
template <class T> __device__ __forceinline__ T* pin(T* p) { return reinterpret_cast<T*>(__shfl_xor_sync(~0u, (u64)p, 0)); }

__device__ __forceinline__ void tma3(uint32_t dst, const CUtensorMap* tm, int c1, int c2, uint32_t bar, uint32_t pol) {
    asm volatile("cp.async.bulk.tensor.3d.shared::cluster.global.mbarrier::complete_tx::bytes.L2::cache_hint [%0], [%1, {%2, %3, %4}], [%5], %6;"
                 :: "r"(dst), "l"(tm), "r"(0), "r"(c1), "r"(c2), "r"(bar), "l"((u64)pol << 32) : "memory");
}
__device__ __forceinline__ void tma_v(uint32_t dst, const CUtensorMap* tm, int line, uint32_t bar) {
    asm volatile("cp.async.bulk.tensor.2d.shared::cluster.global.mbarrier::complete_tx::bytes.L2::cache_hint [%0], [%1, {%2, %3}], [%4], %5;"
                 :: "r"(dst), "l"(tm), "r"(0), "r"(line), "r"(bar), "l"((u64)POL_FIRST << 32) : "memory");
}
__device__ __forceinline__ void tma3_pf(const CUtensorMap* tm, int c1, int c2, uint32_t pol) {
    asm volatile("cp.async.bulk.prefetch.tensor.3d.L2.global.tile.L2::cache_hint [%0, {%1, %2, %3}], %4;"
                 :: "l"(tm), "r"(0), "r"(c1), "r"(c2), "l"((u64)pol << 32) : "memory");
}
__device__ __forceinline__ void issue_half(uint32_t d, uint32_t sb, int rowc, int cta, const CUtensorMap* tm0) {
    const uint32_t bar = sb + SM_CBAR + (d & 0xf8);
    const CUtensorMap* tm = tm0 + ((d >> 8) & 3);
    const bool wo = (d & 0x300) == TM_WO << 8;
    const int c1 = wo ? (cta & 3) + 4 * (d >> 20) : 0, c2 = wo ? (cta >> 2) * DH : rowc + (d >> 20);
    mbar_expect(bar, HALF);
    tma3(sb + (d & 0x3f000), tm, c1, c2, bar, POL_FIRST);
    if (!(d & 1)) tma3_pf(tm + 2, c1, c2, POL_NORMAL);
}
__device__ __forceinline__ uint32_t cnt_inc(uint32_t a, uint32_t last) {
    uint32_t old; asm volatile("atom.relaxed.cta.shared.inc.u32 %0, [%1], %2;" : "=r"(old) : "r"(a), "r"(last) : "memory"); return old;
}
__device__ __forceinline__ void wait_until(uint32_t due) {
#pragma unroll 1
    for (int it = 0; it < 4096; it++) { uint32_t now; asm volatile("mov.u32 %0, %globaltimer_lo;" : "=r"(now)); if ((int)(now - due) >= 0) break; }
}
__device__ __forceinline__ uint32_t bf2_mul(uint32_t a, uint32_t b) { uint32_t r; asm("mul.rn.bf16x2 %0, %1, %2;" : "=r"(r) : "r"(a), "r"(b)); return r; }
__device__ __forceinline__ uint32_t bf2_fma(uint32_t a, uint32_t b, uint32_t c) { uint32_t r; asm("fma.rn.bf16x2 %0, %1, %2, %3;" : "=r"(r) : "r"(a), "r"(b), "r"(c)); return r; }
__device__ __forceinline__ uint32_t bf2_amax(uint32_t a, uint32_t b) { uint32_t r; asm("max.NaN.xorsign.abs.bf16x2 %0, %1, %2;" : "=r"(r) : "r"(a), "r"(b)); return r; }
__device__ __forceinline__ uint4 k_unpack(uint32_t l0, uint32_t l1, uint32_t h, uint32_t m1) {
    const uint32_t ha = h & 0x87878787u, hc = ha * m1 + h, hb = __funnelshift_l(hc, hc, 4);
    return make_uint4(__byte_perm(l0, ha, 0x5140), __byte_perm(l0, ha, 0x7362), __byte_perm(l1, hb, 0x5140), __byte_perm(l1, hb, 0x7362));
}
#define KR4(u, i) "+r"(kr[u][i].x), "+r"(kr[u][i].y), "+r"(kr[u][i].z), "+r"(kr[u][i].w)
#define KR6(u) KR4(u, 0), KR4(u, 1), KR4(u, 2), KR4(u, 3), KR4(u, 4), KR4(u, 5)
__device__ __forceinline__ void k_keep(uint4 (&kr)[8][6], const uint32_t (&c)[18], int e, uint32_t a) {
    asm volatile("{\nKT: .branchtargets K0, K1, K2, K3, K4, K5, K6, K7, K8, K9, K10, K11, K12, K13, K14, K15;\nbrx.idx.uni %210, KT;\n"
                 "K0: mov.b32 %12, %192; mov.b32 %13, %193; mov.b32 %14, %194; mov.b32 %15, %195; mov.b32 %16, %196; mov.b32 %17, %197; mov.b32 %18, %198; mov.b32 %19, %199; mov.b32 %20, %200; mov.b32 %21, %201; mov.b32 %22, %202; mov.b32 %23, %203; mov.b32 %24, %204; mov.b32 %25, %205; mov.b32 %26, %206; mov.b32 %27, %207; mov.b32 %28, %208; mov.b32 %29, %209; bra.uni KE;\n"
                 "K1: mov.b32 %30, %192; mov.b32 %31, %193; mov.b32 %32, %194; mov.b32 %33, %195; mov.b32 %34, %196; mov.b32 %35, %197; mov.b32 %36, %198; mov.b32 %37, %199; mov.b32 %38, %200; mov.b32 %39, %201; mov.b32 %40, %202; mov.b32 %41, %203; mov.b32 %42, %204; mov.b32 %43, %205; mov.b32 %44, %206; mov.b32 %45, %207; mov.b32 %46, %208; mov.b32 %47, %209; bra.uni KE;\n"
                 "K2: mov.b32 %48, %192; mov.b32 %49, %193; mov.b32 %50, %194; mov.b32 %51, %195; mov.b32 %52, %196; mov.b32 %53, %197; mov.b32 %54, %198; mov.b32 %55, %199; mov.b32 %56, %200; mov.b32 %57, %201; mov.b32 %58, %202; mov.b32 %59, %203; mov.b32 %60, %204; mov.b32 %61, %205; mov.b32 %62, %206; mov.b32 %63, %207; mov.b32 %64, %208; mov.b32 %65, %209; bra.uni KE;\n"
                 "K3: mov.b32 %66, %192; mov.b32 %67, %193; mov.b32 %68, %194; mov.b32 %69, %195; mov.b32 %70, %196; mov.b32 %71, %197; mov.b32 %72, %198; mov.b32 %73, %199; mov.b32 %74, %200; mov.b32 %75, %201; mov.b32 %76, %202; mov.b32 %77, %203; mov.b32 %78, %204; mov.b32 %79, %205; mov.b32 %80, %206; mov.b32 %81, %207; mov.b32 %82, %208; mov.b32 %83, %209; bra.uni KE;\n"
                 "K4: mov.b32 %84, %192; mov.b32 %85, %193; mov.b32 %86, %194; mov.b32 %87, %195; mov.b32 %88, %196; mov.b32 %89, %197; mov.b32 %90, %198; mov.b32 %91, %199; mov.b32 %92, %200; mov.b32 %93, %201; mov.b32 %94, %202; mov.b32 %95, %203; mov.b32 %96, %204; mov.b32 %97, %205; mov.b32 %98, %206; mov.b32 %99, %207; mov.b32 %100, %208; mov.b32 %101, %209; bra.uni KE;\n"
                 "K5: mov.b32 %102, %192; mov.b32 %103, %193; mov.b32 %104, %194; mov.b32 %105, %195; mov.b32 %106, %196; mov.b32 %107, %197; mov.b32 %108, %198; mov.b32 %109, %199; mov.b32 %110, %200; mov.b32 %111, %201; mov.b32 %112, %202; mov.b32 %113, %203; mov.b32 %114, %204; mov.b32 %115, %205; mov.b32 %116, %206; mov.b32 %117, %207; mov.b32 %118, %208; mov.b32 %119, %209; bra.uni KE;\n"
                 "K6: mov.b32 %120, %192; mov.b32 %121, %193; mov.b32 %122, %194; mov.b32 %123, %195; mov.b32 %124, %196; mov.b32 %125, %197; mov.b32 %126, %198; mov.b32 %127, %199; mov.b32 %128, %200; mov.b32 %129, %201; mov.b32 %130, %202; mov.b32 %131, %203; mov.b32 %132, %204; mov.b32 %133, %205; mov.b32 %134, %206; mov.b32 %135, %207; mov.b32 %136, %208; mov.b32 %137, %209; bra.uni KE;\n"
                 "K7: mov.b32 %138, %192; mov.b32 %139, %193; mov.b32 %140, %194; mov.b32 %141, %195; mov.b32 %142, %196; mov.b32 %143, %197; mov.b32 %144, %198; mov.b32 %145, %199; mov.b32 %146, %200; mov.b32 %147, %201; mov.b32 %148, %202; mov.b32 %149, %203; mov.b32 %150, %204; mov.b32 %151, %205; mov.b32 %152, %206; mov.b32 %153, %207; mov.b32 %154, %208; mov.b32 %155, %209; bra.uni KE;\n"
                 "K8: mov.b32 %156, %192; mov.b32 %157, %193; mov.b32 %158, %194; mov.b32 %159, %195; mov.b32 %160, %196; mov.b32 %161, %197; mov.b32 %162, %198; mov.b32 %163, %199; mov.b32 %164, %200; mov.b32 %165, %201; mov.b32 %166, %202; mov.b32 %167, %203; mov.b32 %168, %204; mov.b32 %169, %205; mov.b32 %170, %206; mov.b32 %171, %207; mov.b32 %172, %208; mov.b32 %173, %209; bra.uni KE;\n"
                 "K9: mov.b32 %174, %192; mov.b32 %175, %193; mov.b32 %176, %194; mov.b32 %177, %195; mov.b32 %178, %196; mov.b32 %179, %197; mov.b32 %180, %198; mov.b32 %181, %199; mov.b32 %182, %200; mov.b32 %183, %201; mov.b32 %184, %202; mov.b32 %185, %203; mov.b32 %186, %204; mov.b32 %187, %205; mov.b32 %188, %206; mov.b32 %189, %207; mov.b32 %190, %208; mov.b32 %191, %209; bra.uni KE;\n"
                 "K10: st.shared.v2.b32 [%211+75784], {%192, %193}; st.shared.v2.b32 [%211+76288], {%194, %195}; st.shared.v2.b32 [%211+76296], {%196, %197}; mov.b32 %0, %198; mov.b32 %1, %199; mov.b32 %2, %200; mov.b32 %3, %201; mov.b32 %4, %202; mov.b32 %5, %203; mov.b32 %6, %204; mov.b32 %7, %205; mov.b32 %8, %206; mov.b32 %9, %207; mov.b32 %10, %208; mov.b32 %11, %209; bra.uni KE;\n"
                 "K11: st.shared.v2.b32 [%211+0], {%192, %193}; st.shared.v2.b32 [%211+8], {%194, %195}; st.shared.v2.b32 [%211+512], {%196, %197}; st.shared.v2.b32 [%211+520], {%198, %199}; st.shared.v2.b32 [%211+1024], {%200, %201}; st.shared.v2.b32 [%211+1032], {%202, %203}; st.shared.v2.b32 [%211+1536], {%204, %205}; st.shared.v2.b32 [%211+1544], {%206, %207}; st.shared.v2.b32 [%211+2048], {%208, %209}; bra.uni KE;\n"
                 "K12: st.shared.v2.b32 [%211+2056], {%192, %193}; st.shared.v2.b32 [%211+2560], {%194, %195}; st.shared.v2.b32 [%211+2568], {%196, %197}; st.shared.v2.b32 [%211+24576], {%198, %199}; st.shared.v2.b32 [%211+24584], {%200, %201}; st.shared.v2.b32 [%211+25088], {%202, %203}; st.shared.v2.b32 [%211+25096], {%204, %205}; st.shared.v2.b32 [%211+25600], {%206, %207}; st.shared.v2.b32 [%211+25608], {%208, %209}; bra.uni KE;\n"
                 "K13: st.shared.v2.b32 [%211+26112], {%192, %193}; st.shared.v2.b32 [%211+26120], {%194, %195}; st.shared.v2.b32 [%211+26624], {%196, %197}; st.shared.v2.b32 [%211+26632], {%198, %199}; st.shared.v2.b32 [%211+27136], {%200, %201}; st.shared.v2.b32 [%211+27144], {%202, %203}; st.shared.v2.b32 [%211+49152], {%204, %205}; st.shared.v2.b32 [%211+49160], {%206, %207}; st.shared.v2.b32 [%211+49664], {%208, %209}; bra.uni KE;\n"
                 "K14: st.shared.v2.b32 [%211+49672], {%192, %193}; st.shared.v2.b32 [%211+50176], {%194, %195}; st.shared.v2.b32 [%211+50184], {%196, %197}; st.shared.v2.b32 [%211+50688], {%198, %199}; st.shared.v2.b32 [%211+50696], {%200, %201}; st.shared.v2.b32 [%211+51200], {%202, %203}; st.shared.v2.b32 [%211+51208], {%204, %205}; st.shared.v2.b32 [%211+51712], {%206, %207}; st.shared.v2.b32 [%211+51720], {%208, %209}; bra.uni KE;\n"
                 "K15: st.shared.v2.b32 [%211+73728], {%192, %193}; st.shared.v2.b32 [%211+73736], {%194, %195}; st.shared.v2.b32 [%211+74240], {%196, %197}; st.shared.v2.b32 [%211+74248], {%198, %199}; st.shared.v2.b32 [%211+74752], {%200, %201}; st.shared.v2.b32 [%211+74760], {%202, %203}; st.shared.v2.b32 [%211+75264], {%204, %205}; st.shared.v2.b32 [%211+75272], {%206, %207}; st.shared.v2.b32 [%211+75776], {%208, %209}; \nKE:\n}"
                 : KR6(0), KR6(1), KR6(2), KR6(3), KR6(4), KR6(5), KR6(6), KR6(7)
                 : "r"(c[0]), "r"(c[1]), "r"(c[2]), "r"(c[3]), "r"(c[4]), "r"(c[5]), "r"(c[6]), "r"(c[7]), "r"(c[8]), "r"(c[9]), "r"(c[10]), "r"(c[11]), "r"(c[12]), "r"(c[13]), "r"(c[14]), "r"(c[15]), "r"(c[16]), "r"(c[17]), "r"(e), "r"(a) : "memory");
}
__device__ __forceinline__ uint32_t smem_base() { extern __shared__ __align__(1024) unsigned char smem[]; return (uint32_t)__cvta_generic_to_shared(smem); }
__device__ __forceinline__ void k_rare(uint4 v0, uint4 v1, uint4 v2, uint4 v3, uint4 v4, uint4 v5, uint32_t odd, int e, int warp, int lane) {
    const uint32_t sb = smem_base(), g = lane >> 2, t = lane & 3, st = sb + SM_BAR + warp * 96 + 80;
    uint32_t lt; asm volatile("mov.u32 %0, %lanemask_lt;" : "=r"(lt));
    const uint4 v[6] = {v0, v1, v2, v3, v4, v5};
    odd <<= 6;
#pragma unroll
    for (int i = 0; i < 6; i++) if (v[i].x | v[i].y | v[i].z | v[i].w) odd |= 1u << i;
    odd = __reduce_or_sync(~0u, odd);
    uint32_t n = odd >= 64 ? NEXC + 1 : __shfl_sync(~0u, lds32(st), 0);
#pragma unroll 1
    for (; odd && n <= NEXC; odd &= odd - 1) {
        const int i = __ffs(odd) - 1;
#pragma unroll
        for (int k = 1; k < 6; k++) if (i == k) v0 = v[k];
#pragma unroll 1
        for (int k = 0; k < 4; k++, v0.x = v0.y, v0.y = v0.z, v0.z = v0.w) {
            const uint32_t who = __ballot_sync(~0u, v0.x), at = n + __popc(who & lt);
            sts64(v0.x && at < NEXC ? sb + SM_EXC + warp * 128 + at * 8 : st + 8, v0.x, (e * 32 + g * 4) << 16 | (((k & 1) * 4 + t) * 48 + i * 8 + (k >> 1) * 4));
            n += __popc(who);
        }
    }
    const uint32_t bad = lds32(st + 4);
    __syncwarp();
    if (n <= NEXC) sts32(st, n);
    else {
        sts32(st + 4, bad | 1u << e);
        asm volatile("st.shared.u8 [%0], %1;" :: "r"(sb + SM_SC + warp * 128 + g * 16 + (e & 3) * 4 + (e >> 2)), "r"(0) : "memory");
    }
    __syncwarp();
}
template <int K> __device__ __forceinline__ uint32_t& word(uint4& v) { if constexpr (K == 0) return v.x; else if constexpr (K == 1) return v.y; else if constexpr (K == 2) return v.z; else return v.w; }
__device__ __forceinline__ void add_if(bool p, float& d, float a, float b) {
    asm volatile("{\n.reg .pred p;\nsetp.ne.u32 p, %3, 0;\n@p add.f32 %0, %1, %2;\n}" : "+f"(d) : "f"(a), "f"(b), "r"((uint32_t)p));
}
__device__ __forceinline__ float warp_max(float v) {
#pragma unroll
    for (int o = 16; o; o >>= 1) v = fmaxf(v, shx(v, o));
    return v;
}
__device__ __forceinline__ float warp_sum(float v) {
#pragma unroll
    for (int o = 16; o; o >>= 1) v += shx(v, o);
    return v;
}
template <int PITCH> __device__ __forceinline__ void ll_look(const u64* buf, u64 (&w)[4]) {
#pragma unroll
    for (int i = 0; i < 4; i++) w[i] = ld_rlx(buf + i * PITCH);
}
template <int PITCH> __device__ __forceinline__ float ll_gather(const u64* buf, uint32_t tag, u64 (&w)[4]) {
    auto miss = [&]() {
        uint32_t a, b;
        asm("lop3.b32 %0, %1, %2, %3, 0x7e;" : "=r"(a) : "r"(ll_tag(w[0])), "r"(ll_tag(w[1])), "r"(tag));
        asm("lop3.b32 %0, %1, %2, %3, 0x7e;" : "=r"(b) : "r"(ll_tag(w[2])), "r"(ll_tag(w[3])), "r"(tag));
        return __any_sync(~0u, a | b);
    };
    int it = 0;
    goto check;
again:
    ll_look<PITCH>(buf, w);
check:
    if (miss() & (++it < SPIN)) goto again;
    return (ll_val(w[0]) + ll_val(w[1])) + (ll_val(w[2]) + ll_val(w[3]));
}
__device__ __forceinline__ float sum8(uint32_t a, int pitch) {
    float s[8];
#pragma unroll
    for (int w = 0; w < 8; w++) s[w] = ldsf(a + w * pitch);
    return ((s[0] + s[1]) + (s[2] + s[3])) + ((s[4] + s[5]) + (s[6] + s[7]));
}
__device__ __forceinline__ float sum5(float a, float b, float c, float d, float e) { return ((a + b) + (c + d)) + e; }
__device__ __forceinline__ float ln_part(uint2 xp, int lane) {
    const float x0 = bf_lo(xp.x), x1 = bf_hi(xp.x), x2 = bf_lo(xp.y), x3 = bf_hi(xp.y);
    const float s1 = (x0 + x1) + (x2 + x3), s2 = (x0 * x0 + x1 * x1) + (x2 * x2 + x3 * x3);
    return ((lane & 16) ? s2 : s1) + shx((lane & 16) ? s1 : s2, 16);
}
__device__ __forceinline__ float ln_rstd(float mean, float msq) { return rsq(fmaxf(msq - mean * mean, 0.f) + 1e-5f); }
__device__ __forceinline__ float score(const uint4 (&v)[6], const uint4 (&qf)[3]) {
    float d[2][4];
#pragma unroll
    for (int j = 0; j < 2; j++) d[j][0] = d[j][1] = d[j][2] = d[j][3] = 0.f;
#pragma unroll
    for (int i = 0; i < 3; i++) { mma(d[0], v[2 * i], qf[i].x, qf[i].y); mma(d[1], v[2 * i + 1], qf[i].z, qf[i].w); }
    return (d[0][0] + d[0][3]) + (d[1][0] + d[1][3]);
}
__device__ __forceinline__ float k_side(uint32_t sb, uint2 x) {
    const uint32_t qq = lds32(sb + SM_VEC + (x.y & 0xffff));
    return (bf_lo(x.x) * bf_lo(qq) + bf_hi(x.x) * bf_hi(qq)) * 0x1p-64f;
}
__device__ __forceinline__ void k_fix(const __nv_bfloat16* k, uint32_t bad, int warp, int lane) {
    const uint32_t sb = smem_base(), g = lane >> 2, sa = sb + SM_PART + warp * 768 + 256;
    const uint2 x = lds64(sb + SM_EXC + warp * 128 + (lane & 15) * 8);
    if ((int)x.y >= 0x40000000 && lane < 16) asm volatile("red.shared.add.f32 [%0], %1;" :: "r"(sa + ((x.y >> 16) & 511)), "f"(k_side(sb, x)) : "memory");
    __syncwarp();
#pragma unroll 1
    for (bad &= 0xffff; bad; bad &= bad - 1) {
        const int e = __ffs(bad) - 1;
        const __nv_bfloat16* kp = k + (e * 256 + (g >> 1) + 4 * (g & 1)) * DH + (lane & 3) * 8;
        uint4 v[6], qf[3];
#pragma unroll
        for (int i = 0; i < 6; i++) v[i] = *reinterpret_cast<const uint4*>(kp + i * 32);
#pragma unroll
        for (int i = 0; i < 3; i++) qf[i] = lds128(sb + SM_VEC + (lane & 7) * 48 + i * 16);
        stsf(sa + e * 32 + g * 4, score(v, qf) * 0x1p-64f);
    }
    __syncwarp();
}
constexpr float CS = 0.07216878364870322f * 1.4426950408889634f;
__device__ __forceinline__ void head_weight(const u64* a, u64 pm, u64 pl, int layer, int lane) {
    const uint32_t sb = smem_base(), tag = lds32(sb + SM_EPOCH) * 4 + 2 + 2 * layer;
#pragma unroll 1
    for (int it = 0; it < SPIN; it++) {
        if (__all_sync(~0u, ll_tag(pm) == tag && ll_tag(pl) == tag)) break;
        ld_rlx2(a, pm, pl);
    }
    const float f = ex2((ll_val(pm) - warp_max(ll_val(pm))) * CS);
    const float w = f * rcp(warp_sum(f * ll_val(pl)));
    if (lane < 8) stsf(sb + SM_FAC + lane * 4, w);
}
constexpr uint32_t ONES = 0x3f803f80u;

__global__ void __launch_bounds__(NTHR, 1) fused_kernel(const __grid_constant__ Params P) {
    const uint32_t sb = smem_base();
    const int bx = blockIdx.x;
    if (__all_sync(~0u, threadIdx.x >= NTHR - 32) && elect()) {
        asm volatile("mbarrier.init.shared::cta.b64 [%0], 1;" :: "r"(sb + SM_CBAR + CB_WQ * 8));
        asm volatile("mbarrier.init.shared::cta.b64 [%0], 1;" :: "r"(sb + SM_CBAR + 80));
        asm volatile("fence.mbarrier_init.release.cluster;" ::: "memory");
        mbar_expect(sb + SM_CBAR + CB_WQ * 8, 5 * HALF);
        mbar_expect(sb + SM_CBAR + 80, HALF);
        tma3(sb, &P.tm[TM_KH], 0, (bx >> 2) * SK + (SK - WIN) + (bx & 3) * 64, sb + SM_CBAR + 80, POL_FIRST);
#pragma unroll 1
        for (int i = 0; i < 5; i++) tma3(sb + SM_WQR + (i == 4 ? 0 : i + 1) * HALF, &P.tm[TM_WQ], (bx >> 2) * 3, (bx & 3) * 160 + i * 32, sb + SM_CBAR + CB_WQ * 8, POL_FIRST);
    }
    __syncwarp();
    int id = bx * NTHR + threadIdx.x, tid, lane, g, t, key, warp, cta, mlp, rowc, roww, j40;
    uint32_t maskA, maskB, barw, subw, prow;
    auto fresh = [&]() {
        const int cw = __shfl_sync(~0u, id >> 5, 0);
        id = pin(id); tid = id & 255; lane = id & 31; g = lane >> 2; t = lane & 3; key = (g >> 1) + 4 * (g & 1);
        const uint32_t m = (g & 1) ? 0xffff0000u : 0x0000ffffu;
        maskA = (g & 2) ? 0u : m; maskB = (g & 2) ? m : 0u;
        warp = cw & 7; cta = cw >> 3;
        mlp = (cta & 3) == 3 ? 96 : (cta >> 2) * 3 + (cta & 3);
        rowc = (cta >> 2) * SK + (SK - WIN) + (cta & 3) * 64; roww = rowc + warp * 8;
        j40 = (cta & 3) * 40;
        barw = sb + SM_BAR + warp * 96; subw = sb + warp * SUB; prow = sb + SM_PART + warp * 768;
    };
    fresh();
    auto fresh_lane = [&]() { id = pin(id); tid = id & 255; lane = id & 31; g = lane >> 2; t = lane & 3; };
    auto pinf = [&](float v) { return __uint_as_float(pin(__float_as_uint(v) | (id >> 16))); };

    TSTAMP(0);
    if (tid == 64) { uint32_t now; asm volatile("mov.u32 %0, %globaltimer_lo;" : "=r"(now)); sts32(sb + SM_T0, now); }

    const CUtensorMap* tmk = reinterpret_cast<const CUtensorMap*>(__shfl_sync(~0u, (u64)&P.tm[0] + (lane >> 5), 0));
    auto c4 = [&]() { return 32 * min(warp, 4) + 16 * (t >> 1) + 2 * g + (t & 1); };
    auto xcol = [&](int i, int tt) { return (i < 2 ? 64 * i + 8 * warp : 128 + 8 * (warp >> 1)) + 2 * tt; };
    uint2 xp;
    uint32_t px[3], small;
    if (elect()) {
        if (warp != 2) asm volatile("mbarrier.init.shared::cta.b64 [%0], 1;" :: "r"(sb + SM_CBAR + 64 + warp * 8));
#pragma unroll
        for (int i = 0; i < 9; i++) asm volatile("mbarrier.init.shared::cta.b64 [%0], 1;" :: "r"(barw + i * 8));
        asm volatile("mbarrier.init.shared::cta.b64 [%0], 1;" :: "r"(sb + SM_CBAR + warp * 8));
        asm volatile("mbarrier.init.shared::cta.b64 [%0], 1;" :: "r"(sb + SM_CBAR + 128 + warp * 8));
        if (warp < 3) asm volatile("mbarrier.init.shared::cta.b64 [%0], %1;" :: "r"(sb + SM_CBAR + 192 + warp * 8), "r"(warp == 2 ? 8 : 1));
        sts64(barw + 80, 0, 0);
        asm volatile("fence.mbarrier_init.release.cluster;" ::: "memory");
        asm volatile("prefetch.tensormap [%0];" :: "l"(tmk + warp) : "memory");
    }
    __syncwarp();
    asm volatile("ld.global.nc.v2.u32 {%0,%1}, [%2];" : "=r"(xp.x), "=r"(xp.y) : "l"(P.x + 4 * c4()) : "memory");
#pragma unroll
    for (int i = 0; i < 3; i++) asm volatile("ld.global.nc.u32 %0, [%1];" : "=r"(px[i]) : "l"(P.x + 4 * j40 + xcol(i, t)) : "memory");
    asm volatile("ld.relaxed.gpu.global.u32 %0, [%1];" : "=r"(small) : "l"(lane < 16 ? (const void*)(P.b1 + min(mlp, 95) * 16 + (lane & 14)) : (const void*)&P.g->epoch) : "memory");
    if (tid < NCB + 8) sts64(sb + SM_CNT + tid * 8, 0, 0);
    unsigned char* accg = reinterpret_cast<unsigned char*>(__shfl_sync(~0u, (u64)P.g->acc + (lane >> 5), 0));
    auto release = [&](const uint4& tw) {
        uint32_t old;
        __syncwarp();
        asm volatile("atom.relaxed.cta.shared.add.u32 %0, [%1], 1;" : "=r"(old) : "r"(sb + SM_CNT + (tw.x & 0xf8)) : "memory");
        return old;
    };
    auto refill = [&](const uint4& tw, uint32_t old) {
        if (__any_sync(~0u, (old & 127) == 127 && (tw.y & 2))) {
            wait_until(lds32(sb + SM_T0) + tw.z);
            if (elect()) issue_half(tw.y, sb, rowc, cta, tmk);
            __syncwarp();
        }
    };
    __syncthreads();

    uint32_t offV0, offV2;
    auto calc_offsets = [&]() {
        offV0 = subw + (6 * t) * 128 + ((g ^ ((6 * t) & 7)) << 4);
        offV2 = subw + (6 * t + 2) * 128 + ((g ^ ((6 * t + 2) & 7)) << 4);
    };
    calc_offsets();

    auto load_v = [&](uint4 (&v)[6], uint32_t so) {
        v[0] = lds128(offV0 + so); v[1] = lds128((offV0 ^ 16) + so + 128); v[2] = lds128(offV2 + so);
        v[3] = lds128((offV2 ^ 16) + so + 128); v[4] = lds128((offV0 ^ 64) + so + 512); v[5] = lds128((offV0 ^ 80) + so + 640);
    };
    auto issue_v = [&](auto I, int dw, uint32_t done = ~0u) {
        constexpr Step c = SCH.st[I.value];
        const uint32_t bar = barw + dw * 96 + c.slot * 8;
        mbar_expect(bar, done & SUB);
        tma_v(subw + dw * SUB + c.slot * TILE, tmk, roww * 3 + dw * 24 + c.unit * 768, bar);
    };
    auto reads_done = [&]() { __syncwarp(); return lds32(sb + SM_M1); };
    auto refill2 = [&](auto I, uint32_t done = ~0u) { __syncwarp(); if (elect()) issue_v(I, 0, done); };
    uint4 wq0[6], wqh[3], wq1[6];
    auto load_wq1 = [&](int i) { wq1[i] = lds128((i == 2 ? offV2 : i == 3 ? (offV2 ^ 16) + 128 : (offV0 ^ (i * 16)) + i * 128) + SM_WQ + TILE); };
    auto load_wq = [&]() {
        load_v(wq0, SM_WQ);
        const uint32_t so = SM_WQR - ((warp + 1) >> 1) * SUB;
        wqh[0] = lds128(((warp & 1) ? (offV2 ^ 16) + 128 : offV0) + so);
        wqh[1] = lds128(((warp & 1) ? (offV0 ^ 64) + 512 : (offV0 ^ 16) + 128) + so);
        wqh[2] = lds128(((warp & 1) ? (offV0 ^ 80) + 640 : offV2) + so);
    };
    uint4 kr[8][6];
    const unsigned char* rap;
    u64 rw[2];
    auto look_rw = [&]() { rw[0] = ld_rlx(rap); rw[1] = ld_rlx(rap + 20 * acc_pitch(1)); };
    auto q_proj = [&](auto L, uint32_t (&p)[3], uint32_t pst) {
        if (L.value == 0 && g >= 4) p[0] = p[1] = p[2] = ONES;
        float a[3][4], b[3][4];
        const uint32_t dH = __byte_perm(p[2], 0, (warp & 1) ? 0x3232 : 0x1010);
        const uint32_t dA = __byte_perm(p[0], 0, 0x1010), dB = __byte_perm(p[0], 0, 0x3232), dC = __byte_perm(p[1], 0, 0x1010), dD = __byte_perm(p[1], 0, 0x3232);
#pragma unroll
        for (int i = 0; i < 3; i++) load_wq1(i);
#pragma unroll
        for (int j = 0; j < 3; j++) { a[j][0] = a[j][1] = a[j][2] = a[j][3] = 0.f; mma(a[j], wq0[j], dA & maskA, dA & maskB); }
#pragma unroll
        for (int j = 0; j < 3; j++) { b[j][0] = b[j][1] = b[j][2] = b[j][3] = 0.f; mma(b[j], wq0[j + 3], dB & maskA, dB & maskB); }
#pragma unroll
        for (int j = 0; j < 3; j++) mma(a[j], wqh[j], dH & maskA, dH & maskB);
#pragma unroll
        for (int i = 3; i < 6; i++) load_wq1(i);
#pragma unroll
        for (int j = 0; j < 3; j++) mma(b[j], wq1[j], dC & maskA, dC & maskB);
#pragma unroll
        for (int j = 0; j < 3; j++) mma(a[j], wq1[j + 3], dD & maskA, dD & maskB);
#pragma unroll
        for (int j = 0; j < 3; j++) {
            if (L.value) {
#pragma unroll
                for (int k = 0; k < 2; k++) { a[j][k] += b[j][k]; add_if(t & 2, a[j][k], a[j][k + 2], b[j][k + 2]); }
                sts64f(pst + j * 256, a[j][0], a[j][1]);
            } else sts128f(pst + j * 256, a[j][0] + b[j][0], a[j][1] + b[j][1], a[j][2] + b[j][2], a[j][3] + b[j][3]);
        }
        CSTAMP(23, __float_as_uint(a[2][1]));
        uint32_t tag;
        if (L.value) tag = lds32(sb + SM_EPOCH) * 4 + 3;
        u64* pub = L.value ? &P.g->ll[cta][tid] : &P.g->l0[cta][tid];
        if (L.value == 0) asm volatile("fence.proxy.async.shared::cta;" ::: "memory");
        TSTAMPL(21);
        __syncthreads();
        if (!L.value) tag = lds32(sb + SM_EPOCH) * 4 + 1;
#pragma unroll 1
        for (int k = 0; k < 2 - L.value; k++) st_rlx_if(tid < 192, pub + k * 192, ll_pack(sum8(sb + (k ? SM_CSP : SM_PART) + tid * 4, 768), tag));
        TSTAMPL(23);
            CSTAMP(24, tag);
    };
    auto ln_stats = [&]() {
        float ss = ln_part(xp, lane);
        ss += shx(ss, 8); ss += shx(ss, 4); ss += shx(ss, 2); ss += shx(ss, 1);
        stsf(sb + SM_STAT + min(warp, 5) * 8 + (lane >> 4) * 4, ss);
    };
    auto ln_final = [&](float& mean, float& rstd) {
        float2 v[5];
#pragma unroll
        for (int w = 0; w < 5; w++) v[w] = lds64f(sb + SM_STAT + w * 8);
        mean = sum5(v[0].x, v[1].x, v[2].x, v[3].x, v[4].x) * (1.f / D_MODEL);
        const float msq = sum5(v[0].y, v[1].y, v[2].y, v[3].y, v[4].y) * (1.f / D_MODEL);
        rstd = ln_rstd(mean, msq);
        stsf(sb + SM_FXS, msq);
    };
    auto q_addr = [&](int d) { return sb + SM_VEC + (((d >> 1) & 1) * 4 + ((d >> 3) & 3)) * 48 + (d >> 5) * 8 + ((d >> 2) & 1) * 4 + (d & 1) * 2; };
    {
#pragma unroll
        for (int u = 0; u < 8; u++)
#pragma unroll
            for (int i = 0; i < 6; i++) kr[u][i] = lds128(sb + SM_CS + (u * 6 + i) * 16);
        if (warp >= 1 && warp < NI1) {
            wait_until(lds32(sb + SM_T0) + PACES + warp * PACE / 2);
            if (elect()) {
                mbar_expect(sb + SM_CBAR + 80 + warp * 8, HALF);
                tma3(sb + warp * HALF, tmk + TM_KH, 0, rowc + (warp >> 1) * 256 + (warp & 1) * 32, sb + SM_CBAR + 80 + warp * 8, POL_FIRST);
            }
            __syncwarp();
        }
        ln_stats();
        if (tid == 16) { sts32(sb + SM_EPOCH, small); sts32(sb + SM_M1, ~0u); }
        else if (tid < 16) sts32(sb + SM_B1 + tid * 4, (tid & 1) ? small & 0xffff0000u : small << 16);
        mbar_wait(sb + SM_CBAR + CB_WQ * 8, 0);
        load_wq();
        q_proj(IC<0>{}, px, sb + (t < 2 ? SM_PART : SM_CSP) + warp * 768 + (8 * g + 4 * (t & 1)) * 4);
    }
    {
        uint32_t offQ, offL;
        auto calc_ql = [&]() {
            offQ = pin(sb + SM_VEC + (lane & 7) * 48);
            offL = pin(subw + lane * 16);
        };

        auto issue_w = [&](auto L, int which) {
            const uint32_t bar = sb + SM_CBAR + (CB_W1 + which) * 8;
            if (mlp == 96) asm volatile("mbarrier.arrive.shared::cta.b64 _, [%0];" :: "r"(bar) : "memory");
            else {
                mbar_expect(bar, 20480);
                if (which) {
                    tma3(sb + (L.value ? 3 * TILE : SM_W2), tmk + TM_W2, 0, mlp * 16, bar, POL_FIRST);
                    if (!L.value) tma3_pf(tmk + TM_W2, 0, mlp * 16, POL_NORMAL);
                    if (!L.value) asm volatile("cp.async.bulk.prefetch.L2.global.L2::cache_hint [%0], 20480, %1;" :: "l"(P.w1 + mlp * 10240), "l"((u64)POL_NORMAL << 32) : "memory");
                }
                else asm volatile("cp.async.bulk.tensor.3d.shared::cluster.global.mbarrier::complete_tx::bytes.L2::cache_hint [%0], [%1, {%2, %3, %3}], [%4], %5;"
                                  :: "r"(sb + (L.value ? 2 * TILE : SM_W1)), "l"(tmk + TM_W1), "r"(mlp * 16), "r"(0), "r"(bar), "l"((u64)POL_FIRST << 32) : "memory");
            }
        };
        float acc[3][4];
        auto load_q = [&](uint4 (&qf)[3]) {
#pragma unroll
            for (int i = 0; i < 3; i++) qf[i] = lds128(offQ + i * 16);
        };
        auto softmax = [&](float S0, float S1, float S2, float S3) {
            int mi = __float_as_int(fmaxf(fmaxf(S0, S1), fmaxf(S2, S3)));
            mi = __reduce_max_sync(~0u, mi ^ ((mi >> 31) & 0x7fffffff));
            const float mrun = __int_as_float(mi ^ ((mi >> 31) & 0x7fffffff));
            const float p0 = ex2((S0 - mrun) * CS), p1 = ex2((S1 - mrun) * CS), p2 = ex2((S2 - mrun) * CS), p3 = ex2((S3 - mrun) * CS);
            const uint32_t pa = pack_bf(p0, p1), pb = pack_bf(p2, p3), pw = prow + 256 + (key >> 1) * 80 + t * 4 + (key & 1) * 2;
            sts16(pw, pa); sts16(pw + 16, pa >> 16); sts16(pw + 32, pb); sts16(pw + 48, pb >> 16);
            __syncwarp();
#pragma unroll
            for (int j = 0; j < 3; j++) acc[j][0] = acc[j][1] = acc[j][2] = acc[j][3] = 0.f;
            return make_float2(mrun, (p0 + p1) + (p2 + p3));
        };
        auto pv = [&](const uint4 (&v)[6], uint32_t pp) {
            const uint32_t dA = __byte_perm(pp, 0, 0x1010), dB = __byte_perm(pp, 0, 0x3232);
            mma(acc[0], v[0], dA & maskA, dA & maskB); mma(acc[1], v[1], dA & maskA, dA & maskB); mma(acc[2], v[2], dA & maskA, dA & maskB);
            mma(acc[0], v[3], dB & maskA, dB & maskB); mma(acc[1], v[4], dB & maskA, dB & maskB); mma(acc[2], v[5], dB & maskA, dB & maskB);
        };
        auto sa = [&]() { return prow + 256 + t * 32 + g * 4; };
        auto pass1 = [&]() {
            fresh();
            calc_ql();
            __syncthreads();
            sts64(prow + lane * 8, xp.x, xp.y);
            int e = 0;
            const uint4* tab = P.tile + (warp >> 2);
            uint4 tw = tab[0];
            uint32_t ka[3];
#pragma unroll
            for (int j = 0; j < 3; j++) ka[j] = pin(subw + key * 384 + j * 128 + ((t ^ ((3 * key + j) & 7)) << 4));
            auto load_k = [&](uint4 (&v)[6], uint32_t so) {
#pragma unroll
                for (int i = 0; i < 6; i++) v[i] = lds128(((i & 1) ? ka[i >> 1] ^ 64 : ka[i >> 1]) + so);
            };
            const uint32_t s0 = pin(prow + 256 + g * 4), sca = pin(sb + SM_SC + warp * 128 + g * 16);
#pragma unroll 1
            do {
                const uint4 tn = tab[2 * e + 2];
                uint4 v[6], qf[3];
                if (tw.x & (G_A | G_B | G_C)) {
                    if ((tw.x & G_A) && warp == 7 && elect()) {
                        mbar_expect(sb + SM_CBAR + CB_SNAP * 8, HALF);
                        asm volatile("cp.async.bulk.shared::cluster.global.mbarrier::complete_tx::bytes [%0], [%1], 12288, [%2];"
                                     :: "r"(sb + SM_SNAP), "l"(&P.g->l0[cta & ~3][0]), "r"(sb + SM_CBAR + CB_SNAP * 8) : "memory");
                    }
                    if (tw.x & G_B) {
                        if (warp < 6) {
                            mbar_wait(sb + SM_CBAR + CB_SNAP * 8, 0);
                            float qc[2] = {0.f, 0.f}, mean, rstd;
#pragma unroll 1
                            for (int k = 0; k < 2; k++) {
                                u64 qw[4];
#pragma unroll
                                for (int i = 0; i < 4; i++) { const uint2 x = lds64(sb + SM_SNAP + i * 3072 + k * 1536 + tid * 8); qw[i] = x.x | (u64)x.y << 32; }
                                qc[0] = qc[1];
                                qc[1] = ll_gather<384>(&P.g->l0[cta & ~3][k * 192 + tid], lds32(sb + SM_EPOCH) * 4 + 1, qw);
                            }
                            ln_final(mean, rstd);
                            stsf(sb + SM_CS + tid * 4, qc[1]);
                            const float q = (qc[0] - mean * qc[1]) * rstd;
                            sts16(q_addr(tid), pack_bf(q, q));
                        }
                        __syncthreads();
                        if (warp == 7 && elect()) issue_half(UC<load_word(12)>::value, sb, rowc, cta, tmk);
                        TSTAMP(2);
                    }
                    if (tw.x & G_C) {
                        load_k(v, (e - LATEAT) * TILE);
                        load_q(qf);
                        stsf(s0 + (e - LATEAT) * 32, score(v, qf));
                    }
                }
                load_q(qf);
                mbar_wait(sb + SM_CBAR + (tw.x & 0xf8), tw.x >> 31);
                TRACE(e);
                load_k(v, tw.x & 0x3f000);
                const uint32_t old = release(tw);
                const float s = score(v, qf);
                uint32_t m;
                {
                    uint32_t a[6];
#pragma unroll
                    for (int i = 0; i < 6; i++) a[i] = bf2_amax(bf2_amax(v[i].x, v[i].y), bf2_amax(v[i].z, v[i].w));
                    m = bf2_amax(bf2_amax(bf2_amax(a[0], a[1]), bf2_amax(a[2], a[3])), bf2_amax(a[4], a[5]));
                }
                m = bf2_amax(m, m >> 16) & 0x7f80;
                m = max(m, __shfl_xor_sync(~0u, m, 1));
                stsf(s0 + e * 32, s);
                m = max(m, __shfl_xor_sync(~0u, m, 2));
                refill(tw, old);
                const uint32_t b = min(max(m, 15u << 7) - (15u << 7), 126u << 7);
                const uint32_t dn = ((127u << 7) - b) * 0x10001u, up = ((127u << 7 | 0x8000u) + b) * 0x10001u;
                uint32_t c[18], any = m > (141u << 7);
#pragma unroll
                for (int i = 0; i < 6; i++) {
                    const uint32_t y0 = bf2_mul(v[i].x, dn), y1 = bf2_mul(v[i].y, dn), y2 = bf2_mul(v[i].z, dn), y3 = bf2_mul(v[i].w, dn);
                    v[i] = make_uint4(bf2_fma(y0, up, v[i].x), bf2_fma(y1, up, v[i].y), bf2_fma(y2, up, v[i].z), bf2_fma(y3, up, v[i].w));
                    any |= v[i].x | v[i].y;
                    any |= v[i].z | v[i].w;
                    const uint32_t hb = __byte_perm(y2, y3, 0x7531);
                    c[3 * i] = __byte_perm(y0, y1, 0x6420); c[3 * i + 1] = __byte_perm(y2, y3, 0x6420);
                    c[3 * i + 2] = __byte_perm(y0, y1, 0x7531) | __funnelshift_r(hb, hb, 4);
                }
                asm volatile("st.shared.u8 [%0], %1;" :: "r"(sca + (e & 3) * 4 + (e >> 2)), "r"((b >> 7) + 63) : "memory");
                const bool rare = __any_sync(~0u, any);
                k_keep(kr, c, e, offL);
                if (rare) k_rare(v[0], v[1], v[2], v[3], v[4], v[5], m > (141u << 7), e, warp, lane);
                tw = tn;
            } while (++e < 16);
            asm volatile("fence.proxy.async.shared::cta;" ::: "memory");
            __syncwarp();
            TSTAMP(10);
            fresh(); calc_offsets();
            offV0 = pin(offV0); offV2 = pin(offV2);
            {
                const uint2 st = lds64(barw + 80);
                const uint32_t xa = sb + SM_EXC + warp * 128 + (lane & 15) * 8 + 4;
                uint32_t pos = lds32(xa), lt;
                asm volatile("mov.u32 %0, %lanemask_lt;" : "=r"(lt));
                if (lane >= st.x) pos = 0x80000000u;
                const bool dup = (__match_any_sync(~0u, pos >> 16) & lt) && lane < st.x;
                if (lane < 16) sts32(xa, dup ? pos | 0x40000000u : pos);
                if (__any_sync(~0u, dup)) sts32(barw + 84, st.y | 0x10000u);
                const float2 ml = softmax(ldsf(sa()), ldsf(sa() + 128), ldsf(sa() + 256), ldsf(sa() + 384));
                sts64f(sb + SM_ML + warp * 8, ml.x, warp_sum(ml.y));
            }
            u64 pm = 0, pl = 0;
#pragma unroll 1
            do {
                const uint4 tn = tab[2 * e + 2];
                if (tw.x & (G_A | G_B | G_C)) {
                    if (tw.x & G_A) {
                        if (lane < 24) st_rlx(&P.g->ll[cta][warp * 24 + lane], 0ull);
                        else if (lane < 28) st_rlx(&P.g->ll[cta][168 + warp * 4 + lane], ll_pack(ldsf(sb + SM_ML + warp * 8 + (lane & 1) * 4), lds32(sb + SM_EPOCH) * 4 + 2));
                    }
                    if (warp == 0 && cta < 80 && elect()) {
                        if (tw.x & G_A) {
#pragma unroll 1
                            for (int k = 0; k < 8; k++) {
                                const int r = (cta & 1) * 2 + (k >> 2);
                                asm volatile("cp.async.bulk.global.shared::cta.bulk_group [%0], [%1], 64;"
                                             :: "l"(P.g->acc + r * ACC_BYTES + ((cta >> 1) * acc_pitch(r) & ~127) + (k & 3) * 64), "r"(sb + SM_ZERO) : "memory");
                            }
                            asm volatile("cp.async.bulk.commit_group;" ::: "memory");
                        }
                        if (tw.x & G_B) asm volatile("cp.async.bulk.wait_group 0;\nred.relaxed.gpu.global.add.u32 [%0], 1;" :: "l"(&P.g->zeroed) : "memory");
                    }
                    if (warp == 2) {
                        if (tw.x & G_B) ld_rlx2(&P.g->ll[cta ^ (lane >> 3)][192 + (lane & 7) * 4], pm, pl);
                        if (tw.x & G_C) head_weight(&P.g->ll[cta ^ (lane >> 3)][192 + (lane & 7) * 4], pm, pl, 0, lane);
                    }
                    __syncwarp();
                }
                const uint32_t pp = lds32(prow + 256 + t * 80 + ((tw.x >> 20) & 255));
                mbar_wait(sb + SM_CBAR + (tw.x & 0xf8), tw.x >> 31);
                TRACE(e);
                uint4 v[6];
                load_v(v, tw.x & 0x3f000);
                refill(tw, release(tw));
                pv(v, pp);
                tw = tn;
            } while (++e < 32);
        };
        uint32_t osa, ora, owa, orow, otag;
        u64* olb;
        float xc;
        auto o_setup = [&](auto L) {
            fresh();
            const int lz = lane, d = warp * 24 + min(lz, 23);
            osa = pin(prow + ((lz >> 2) * 8 + (lz & 1) * 4 + (lz & 2)) * 4);
            ora = pin(sb + SM_PART + d * 4);
            olb = pin(&P.g->ll[cta & ~3][d]);
            orow = pin((lz & 1) + 2 * (lz & 2) + 2 * (lz >> 4));
            owa = pin(sb + SM_RING + warp * 1536 + orow * 64 + ((((lz >> 2) & 3) ^ (orow >> 1)) << 4));
            otag = lds32(sb + SM_EPOCH) * 4 + 2 + 2 * L.value;
            uint32_t x; asm volatile("ld.shared.u16 %0, [%1];" : "=r"(x) : "r"(prow + ((cta & 1) * 16 + (lz >> 3) * 4 + (cta & 2) + ((lz >> 2) & 1)) * 8 + (lz & 3) * 2) : "memory");
            xc = bf_lo(x) * (1.f / 32);
        };
        auto wo_at = [&](auto A) {
            constexpr uint32_t x = WOP ^ A.value * 0x11111;
            if constexpr (A.value > 0 && ((x - 0x11111) & ~x & 0x88888) != 0) {
                if ((WOP >> (4 * warp) & 15) == A.value) {
                    mbar_wait(sb + SM_CBAR + CB_REL * 8, 0);
                    if (elect()) {
                        const uint32_t bar = sb + SM_CBAR + (CB_WO + warp) * 8;
                        mbar_expect(bar, HALF);
                        tma3(sb + SM_RING + (warp + (warp < 2 ? 3 : -2)) * HALF, tmk + TM_WO, (cta & 3) + 4 * warp, (cta >> 2) * DH, bar, POL_FIRST);
                    }
                    __syncwarp();
                }
            }
        };
        static_assert(ring_hs(64) == 3, "wo");
        auto pass2 = [&]() {
            constexpr IC<1> L{};
            refill2(IC<4>{});
            uint4 tb[8][3];
            auto load_tb = [&](auto I) {
#pragma unroll
                for (int i = 0; i < 3; i++) tb[I.value][i] = lds128(offL + (I.value >> 1) * TILE + ((I.value & 1) * 3 + i) * 512);
            };
            uint32_t m1, m1n, done;
            const u64* qb = &P.g->ll[cta & ~3][min(tid, 191)];
            {
                uint32_t x[2];
                fx2_wait<2>([&](int i) { return rap + i * 20 * acc_pitch(1); }, look_rw, rw, sb + SM_MSQ, ldsf(sb + SM_MSQ + 4), x);
                xp = make_uint2(x[0], x[1]);
                CSTAMP(25, xp.y);
            }
            ln_stats();
            u64 qw[4];
            offL = subw + lane * 16;
            static_for<0, NPRE>(load_tb);
            m1n = m1 = reads_done();
            ll_look<256>(qb, qw);
            const float cs = ldsf(sb + SM_CS + min(tid, 191) * 4);
            const uint32_t qtag = lds32(sb + SM_EPOCH) * 4 + 3, qa = pin(q_addr(min(tid, 191)));
            fresh_lane();
            offQ = sb + SM_VEC + (lane & 7) * 48; offL = subw + lane * 16;
            __syncthreads();
            auto vwait = [&](auto I) { mbar_wait(barw + IC<SCH.st[I.value].slot>::value * 8, IC<SCH.st[I.value].par>::value); };
            bool ok;
            {
                float mean, rstd;
                ln_final(mean, rstd);
                const float sq = shx(rstd * 0x1p64f, 0), q0 = shx(-mean * cs * sq, 0);
                CSTAMP(26, __float_as_uint(q0));
                refill2(IC<5>{}, m1);
                sts64(prow + lane * 8, xp.x, xp.y);
                sts128f(prow + 256 + lane * 16, 0.f, 0.f, 0.f, 0.f);
                const float q = ll_gather<256>(qb, qtag, qw) * sq + q0;
                sts16(qa, pack_bf(q, q));
                TSTAMPL(24);
                CSTAMP(27, __float_as_uint(q));
            }
            __syncthreads();
            uint4 qf[3];
            load_q(qf);
            CSTAMP(28, qf[0].x);
            float S[4], d[2][4];
            auto vload = [&](auto I) {
                constexpr int p = I.value;
                constexpr Step c = SCH.st[p];
                load_v(kr[p & 7], c.slot * TILE);
                if constexpr (c.next >= 0 && p >= NPARK) {
                    static_assert(c.next - 9 < c.mma0, "the slot's last tile has been multiplied");
                    refill2(IC<c.next>{});
                }
                if constexpr (p == 11) { __syncwarp(); if (elect()) asm volatile("mbarrier.arrive.shared::cta.b64 _, [%0];" :: "r"(sb + SM_CBAR + CB_REL * 8) : "memory"); }
            };
            static_for<0, 96>([&](auto F) {
                constexpr int f = F.value, i = f % 6, u = kunit(f / 6), w = 3 * f % 12;
                uint4 (&src)[3] = *reinterpret_cast<uint4 (*)[3]>(f < 32 ? &tb[f / 4 & 7][0] : &kr[(f / 8 + 4) & 7][(f / 4 & 1) * 3]);
                const uint4 a = k_unpack(word<w % 4>(src[w / 4]), word<(w + 1) % 4>(src[(w + 1) / 4]), word<(w + 2) % 4>(src[(w + 2) / 4]), m1);
                if constexpr (f % 8 == (f < 32 ? RF0 : RF1) + M1D) m1 = m1n;
                if constexpr (f % 4 == 3 && f / 4 + NPRE < 8) {
                    load_tb(IC<f / 4 + NPRE>{});
                    if constexpr (f % 8 == 7) done = reads_done();
                }
                if constexpr (f >= 8 && f < 32 && f % 8 == RF0) { refill2(IC<5 + f / 8>{}, done); m1n = lds32(sb + SM_M1); }
                if constexpr (f >= 40 && f % 8 == RF1) {
                    if constexpr (PARKS >> (f / 8 - 5) & 1) { refill2(IC<SCH.st[popc(PARKS & ((1 << (f / 8 - 5)) - 1))].next>{}, done); m1n = lds32(sb + SM_M1); }
                }
                if constexpr (i < 2) d[i][0] = d[i][1] = d[i][2] = d[i][3] = 0.f;
                mma(d[i & 1], a, (i & 1) ? qf[i / 2].z : qf[i / 2].x, (i & 1) ? qf[i / 2].w : qf[i / 2].y);
                if constexpr (i == 5) {
                    if constexpr (u == 11 || ((u & 3) == 0 && u != 8)) S[u >> 2] = (d[0][0] + d[0][3]) + (d[1][0] + d[1][3]);
                    else add_if(t == (u & 3), S[u >> 2], d[0][0] + d[0][3], d[1][0] + d[1][3]);
                    if constexpr (f < 64) S[u >> 2] = shx(S[u >> 2], 0);
                }
                if constexpr (f == 31) { fresh(); calc_offsets(); ok = mbar_test(barw + IC<SCH.st[0].slot>::value * 8, 0); }
                if constexpr (f == 48) {
                    const uint2 x = lds64(sb + SM_EXC + warp * 128 + (lane & 15) * 8);
                    const float c = k_side(sb, x);
                    if (x.y < 0x40000000u) stsf(prow + 256 + (x.y >> 16), c);
                }
                if constexpr (f >= 32 && f % 8 == 7) {
                    if constexpr (PARKS >> (f / 8 - 4) & 1) {
                        constexpr int p = popc(PARKS & ((1 << (f / 8 - 4)) - 1));
                        if (!ok) vwait(IC<p>{});
                        vload(IC<p>{});
                        done = reads_done();
                        ok = mbar_test(barw + IC<SCH.st[p + 1].slot>::value * 8, IC<SCH.st[p + 1].par>::value);
                    }
                }
            });
            if constexpr (PARKS & 0x80) refill2(IC<SCH.st[NPARK - 1].next>{}, done);
            uint32_t bad = lds32(barw + 84);
            const uint32_t sc = lds32(sb + SM_SC + tid * 4);
            __syncwarp();
            if (bad) k_fix(P.k + (size_t)roww * DH, bad, warp, lane);
            TSTAMP(30);
            CSTAMP(29, __float_as_uint(S[2]));
            const float2 ml = softmax(S[0] * __uint_as_float((sc & 255) << 23) + ldsf(sa()), S[1] * __uint_as_float((sc & 0xff00) << 15) + ldsf(sa() + 128),
                                      S[2] * __uint_as_float((sc & 0xff0000) << 7) + ldsf(sa() + 256), S[3] * __uint_as_float((sc >> 24) << 23) + ldsf(sa() + 384));
            uint4 pq[4];
#pragma unroll
            for (int j = 0; j < 4; j++) pq[j] = lds128(prow + 256 + t * 80 + j * 16);
            TSTAMP(1);
            CSTAMP(30, pq[3].w);
            if (!ok) vwait(IC<NPARK>{});
            float ac2[3][4];
#pragma unroll
            for (int j = 0; j < 3; j++) ac2[j][0] = ac2[j][1] = ac2[j][2] = ac2[j][3] = 0.f;
            const uint32_t sl = (g & 1) ? 0x1044 : 0x4410, sh = (g & 1) ? 0x3244 : 0x4432;
            const uint32_t sA0 = (g & 2) ? 0x4444 : sl, sA1 = (g & 2) ? sl : 0x4444, sB0 = (g & 2) ? 0x4444 : sh, sB1 = (g & 2) ? sh : 0x4444;
            u64 pm = 0, pl = 0;
            static_for<NPARK, 16>([&](auto I) {
                constexpr int p = I.value;
                static_assert(p - SCH.st[p].mma0 < 8, "buffer in use");
                vload(I);
                if constexpr (p < 15) ok = mbar_test(barw + IC<SCH.st[p + 1].slot>::value * 8, IC<SCH.st[p + 1].par>::value);
                static_for<SCH.st[p].mma0, SCH.st[p].mma0 + SCH.st[p].nmma>([&](auto J) {
                    constexpr int u = SCH.st[J.value].unit;
                    const uint32_t pp = word<u & 3>(pq[u >> 2]), a0 = __byte_perm(pp, 0, sA0), a1 = __byte_perm(pp, 0, sA1), b0 = __byte_perm(pp, 0, sB0), b1 = __byte_perm(pp, 0, sB1);
#pragma unroll
                    for (int j = 0; j < 3; j++) mma(acc[j], kr[J.value & 7][j], a0, a1);
#pragma unroll
                    for (int j = 0; j < 3; j++) mma(ac2[j], kr[J.value & 7][j + 3], b0, b1);
                });
                if constexpr (p == NPARK) {
                    const float l = warp_sum(ml.y);
                    st_rlx_if(lane < 4, &P.g->ll[cta][192 + warp * 4 + lane], ll_pack((lane & 1) ? l : ml.x, lds32(sb + SM_EPOCH) * 4 + 4));
                }
                if constexpr (p == HWAT) { if (warp == 6) ld_rlx2(&P.g->ll[cta ^ (lane >> 3)][192 + (lane & 7) * 4], pm, pl); }
                if constexpr (p == 13) o_setup(L);
                if constexpr (p == HWAT + 2) { if (warp == 6) head_weight(&P.g->ll[cta ^ (lane >> 3)][192 + (lane & 7) * 4], pm, pl, 1, lane); }
                wo_at(IC<p - 10>{});
                if constexpr (p < 15) { if (!ok) mbar_wait(barw + IC<SCH.st[p + 1].slot>::value * 8, IC<SCH.st[p + 1].par>::value); TRACE(33 + p); }
            });
#pragma unroll
            for (int j = 0; j < 3; j++)
#pragma unroll
                for (int k = 0; k < 2; k++) { acc[j][k] += ac2[j][k]; add_if(t & 2, acc[j][k], acc[j][k + 2], ac2[j][k + 2]); }
        };

        const unsigned char* ap;
        uint32_t hpa, hsa, hst, w2a, la;
        uint2 b2v;
        float b1v, cs1;
        auto mlp_global = [&](auto L) {
            const int cz = c4();
            ap = accg + 2 * L.value * ACC_BYTES + (cz >> 2) * acc_pitch(0) + (cz & 3) * 16;
            if (L.value) ap = pin(ap);
            rap = pin(accg + (2 * L.value + 1) * ACC_BYTES + (cz >> 3) * acc_pitch(2 * L.value + 1) + (cz & 7) * 8);
            asm volatile("ld.global.nc.v2.u32 {%0,%1}, [%2];" : "=r"(b2v.x), "=r"(b2v.y) : "l"(P.b2 + 4 * cz));
        };
        auto mlp_shared = [&](auto L) {
            const int lz = lane;
            hpa = pin(sb + SM_PART + warp * 256 + ((lz & 2) * 4 + (lz >> 2)) * 16 + (L.value ? 0 : (lz & 1) * 4));
            hsa = pin(sb + SM_PART + (lz & 15) * 16); hst = pin(sb + SM_PART + (lz & 15) * 16 + warp * 256 + 8 + (lz >> 4) * 4);
            w2a = pin(sb + (L.value ? 3 * TILE : SM_W2) + ((lz & 3) * 10 + 2 * warp) * 128 + (((lz >> 2) ^ ((2 * lz + 2 * warp) & 6)) << 4));
            la = sb + (L.value ? 2 * TILE : SM_W1) + warp * 4096 + (lz & 4) * 512 + (lz & 2) * 64 + (lz & 1) * 32 + (lz >> 4) * 64 + ((((lz >> 3) ^ (lz >> 1)) & 1) << 4);
            b1v = ldsf(sb + SM_B1 + (lz & 15) * 4);
            if (L.value) { la = pin(la); cs1 = ldsf(sb + SM_ML + (lz & 15) * 4); }
            else fresh();
        };
        uint32_t pa;
        unsigned char* rop;
        uint32_t wpa;
        float sc1;
        auto sum_setup = [&](auto L) {
            const int lz = lane, word = warp * 128 + (cta & 3) * 32 + lz;
            wpa = pin(sb + SM_RING + warp * 1536 + ((((lz >> 2) * 8 + (lz & 1) * 4) * 4) ^ ((((lz >> 1) ^ (lz >> 4)) & 1) ? 256 + 64 : 0)));
            sc1 = pinf(fx2_scale(ldsf(sb + SM_FXS)) * 0.25f);
            pa = pin(sb + SM_RING + warp * 256 + ((lz * 4) ^ ((warp & 1) * 64)));
            rop = pin(accg + 2 * L.value * ACC_BYTES + (word >> 4) * acc_pitch(0) + (word & 15) * 4);
        };
        auto out_proj = [&](auto L) {
            TSTAMP2(3);
            CSTAMP(0, __float_as_uint(acc[2][1]));
            __syncwarp();
#pragma unroll
            for (int j = 0; j < 3; j++) {
                if (L.value == 0 && (t & 2)) { acc[j][0] = acc[j][2]; acc[j][1] = acc[j][3]; }
                sts64f(osa + 256 * j, acc[j][0], acc[j][1]);
            }
            __syncthreads();
            {
                float s[8];
#pragma unroll
                for (int w = 0; w < 8; w++) s[w] = ldsf(ora + w * 768);
                const uint4 fa = lds128(sb + SM_FAC), fb = lds128(sb + SM_FAC + 16);
            CSTAMP(1, __float_as_uint(s[0]));
                const float own = ((s[0] * __uint_as_float(fa.x) + s[1] * __uint_as_float(fa.y)) + (s[2] * __uint_as_float(fa.z) + s[3] * __uint_as_float(fa.w))) +
                                  ((s[4] * __uint_as_float(fb.x) + s[5] * __uint_as_float(fb.y)) + (s[6] * __uint_as_float(fb.z) + s[7] * __uint_as_float(fb.w)));
                st_rlx_if(lane < 24, olb + (cta & 3) * 256, ll_pack(own, otag));
            CSTAMP(2, __float_as_uint(own));
            }
            TSTAMPL(29);
            if (L.value == 0) fresh();
            if (L.value) wo_at(IC<6>{});
            if (L.value == 0 && warp == 7) {
#pragma unroll 1
                for (int it = 0; it < SPIN; it++) {
                    uint32_t v; asm volatile("ld.acquire.gpu.global.u32 %0, [%1];" : "=r"(v) : "l"(&P.g->zeroed) : "memory");
                    if (__all_sync(~0u, v == (lds32(sb + SM_EPOCH) + 1) * 80)) break;
                }
            }
            constexpr int NW = L.value ? NWO1 : 3;
            uint4 v[5][3];
            u64 ow[4];
            auto read_wo = [&](auto J) {
#pragma unroll
                for (int p = 0; p < 3; p++) v[J.value][p] = lds128(((J.value & 1) ? owa ^ 144 : owa) + ring_hs(64 + J.value) * HALF + p * 512);
            };
            static_for<0, NW>([&](auto J) {
                if (L.value && J.value == 0) { sum_setup(L); maskA = pin(maskA); maskB = pin(maskB); }
                if (J.value == 2) { ll_look<256>(olb, ow); if (L.value) { mlp_shared(L); mlp_global(L); } }
                mbar_wait(sb + SM_CBAR + (CB_WO + J.value) * 8, L.value);
                read_wo(J);
                if (L.value == 0 && J.value == 2) {
                    __syncwarp();
                    if (elect() && cnt_inc(sb + SM_CNT + CB_W1 * 8, 7) == 7) issue_w(L, 0);
                    __syncwarp();
                }
                if (L.value == 1 && J.value == 2) {
                    if (warp == 7 && elect()) issue_w(L, 0);
                    __syncwarp();
                }
            });
            sched_fence();
            const float o = ll_gather<256>(olb, otag, ow);
            CSTAMP(3, __float_as_uint(o));
            TSTAMP2(4);
            bool ok = true;
            if constexpr (NW < 5) ok = mbar_test(sb + SM_CBAR + (CB_WO + 4) * 8, L.value);
            if constexpr (NW < 4) ok &= mbar_test(sb + SM_CBAR + (CB_WO + 3) * 8, L.value);
            const uint32_t od = pack_bf(o, o);
            uint32_t oa[3], ob[3];
#pragma unroll
            for (int p = 0; p < 3; p++) { const uint32_t op = __shfl_sync(~0u, od, 8 * p + orow); oa[p] = op & maskA; ob[p] = op & maskB; }
            CSTAMP(4, oa[2]);
            float y[5][4];
#pragma unroll
            for (int j = 0; j < 5; j++) y[j][0] = y[j][1] = y[j][2] = y[j][3] = 0.f;
            auto rest = [&]() {
                if (!ok) static_for<NW, 5>([&](auto J) { mbar_wait(sb + SM_CBAR + (CB_WO + J.value) * 8, L.value); });
                static_for<NW, 5>(read_wo);
                __syncwarp();
            };
            if (L.value) rest();
#pragma unroll
            for (int p = 0; p < 3; p++)
#pragma unroll
                for (int j = 0; j < NW; j++) mma(y[j], v[j][p], oa[p], ob[p]);
            if (!L.value) { rest(); sum_setup(L); }
#pragma unroll
            for (int p = 0; p < 3; p++)
#pragma unroll
                for (int j = NW; j < 5; j++) mma(y[j], v[j][p], oa[p], ob[p]);
            CSTAMP(5, __float_as_uint(y[4][3]));
#pragma unroll
            for (int j = 0; j < 5; j += 2) {
                if (j < 4 && (t >> 1) != (g >> 2)) { y[j][0] = y[j + 1][0]; y[j][1] = y[j + 1][1]; y[j][2] = y[j + 1][2]; y[j][3] = y[j + 1][3]; }
                sts128f(wpa + j * 256, y[j]);
            }
            TSTAMP2(5);
        };
        u64 yw[2];
        bool wide;
        float msq = 0.f, yf[4] = {};
        auto mlp_part = [&](auto L) {
            bar_sync(0, 256);
            CSTAMP(6, __float_as_uint(sc1));
            const float s = (sum8(pa, 1536) + xc) + sum8(pa + 128, 1536), sm = s * sc1 + FX2_ONE;
            CSTAMP(7, __float_as_uint(s));
            const bool wide1 = !(fabsf(sm - FX2_ONE) < FX1LIM);
            asm volatile("red.relaxed.gpu.global.add.u32 [%0], %1;" :: "l"(rop), "r"(wide1 ? 0u : __float_as_uint(sm) * 128u + (1u - 0x4b400000u * 128u)) : "memory");
            const uint32_t c0 = clk();
            TSTAMP2(6);
            if (L.value == 0) bar_arrive(2, 256);
            if (wide1) {
                fx_send(rop + 64 + (lane & 15) * 4, s, ldsf(sb + SM_FXS), rop, 64);
                asm volatile("red.relaxed.gpu.global.add.u32 [%0], 1;" :: "l"(rop) : "memory");
            }
            __syncwarp();
            if (L.value == 1 && mlp == 96) { TDUMP(); asm volatile("exit;"); }
            uint4 wf[8], w2r[8];
            uint4 w;
            auto look = [&]() { asm volatile("ld.relaxed.gpu.global.v4.u32 {%0,%1,%2,%3}, [%4];" : "=r"(w.x), "=r"(w.y), "=r"(w.z), "=r"(w.w) : "l"(ap) : "memory"); };
            auto read_w1 = [&]() {
#pragma unroll
                for (int j = 0; j < 8; j++) wf[j] = ldsm_t(la + j * 256);
            };
            auto read_w2 = [&]() {
#pragma unroll
                for (int i = 0; i < 8; i++) w2r[i] = lds128(((i & 1) ? (w2a ^ 16) + 128 : w2a) + (i >> 1) * 5120);
            };
            const float inv = pinf(fx_inv(sc1) * (1.f / 128)), off = L.value ? pinf(fx_inv(sc1) * -0.25f) : inv * -32.f;
            if (L.value == 0) { fresh(); mlp_global(L); }
            mbar_wait(sb + SM_CBAR + CB_W1 * 8, L.value);
            if (L.value == 1) read_w1();
            while (clk() - c0 < AR1D);
            look();
            if (L.value == 0) { mlp_shared(L); read_w1(); bar_arrive(3, 256); }
            else { mbar_wait(sb + SM_CBAR + CB_W2 * 8, 1); read_w2(); }
            TSTAMPL(28);
            {
                sched_fence();
                auto miss = [&]() {
                    xp = make_uint2(pack_bf((float)(int)w.x * inv + off, (float)(int)w.y * inv + off), pack_bf((float)(int)w.z * inv + off, (float)(int)w.w * inv + off));
                    uint32_t a, b;
                    asm("lop3.b32 %0, %1, %2, 32, 0x7e;" : "=r"(a) : "r"(w.x), "r"(w.y));
                    asm("lop3.b32 %0, %1, %2, 32, 0x7e;" : "=r"(b) : "r"(w.z), "r"(w.w));
                    return __any_sync(~0u, (a | b) & 96);
                };
                if (miss()) {
                    int it = 0;
#pragma unroll 1
                    do {
                        if (!__any_sync(~0u, ~(w.x & w.y & w.z & w.w) & 32)) { xp.x = fx1_wide(ap, ldsf(sb + SM_FXS)); xp.y = fx1_wide(ap + 8, ldsf(sb + SM_FXS)); break; }
                        look();
                    } while (miss() & (++it < SPIN));
                }
                CSTAMP(8, w.w);
            }
            TSTAMP2(7);
            CSTAMP(9, xp.y);
            {
                bool ok = true;
                if (L.value == 0) ok = mbar_test(sb + SM_CBAR + CB_W2 * 8, 0);
                const bool ev = L.value || !(g & 1), od = L.value || (g & 1);
                const uint32_t e0 = ev ? xp.x : ONES, e1 = ev ? xp.y : ONES, o0 = od ? xp.x : ONES, o1 = od ? xp.y : ONES;
                float d[8][4];
#pragma unroll
                for (int j = 0; j < 8; j++) { d[j][0] = d[j][1] = d[j][2] = d[j][3] = 0.f; mma(d[j], wf[j], (j & 1) ? o0 : e0, (j & 1) ? o1 : e1); }
                float ss = ln_part(xp, lane);
                ss += shx(ss, 8); ss += shx(ss, 4);
                float r[4], dd;
#pragma unroll
                for (int k = 0; k < 4; k += 1 + L.value) r[k] = d[0][k] + d[1][k ^ 1];
#pragma unroll
                for (int j = 1; j < 4; j++)
#pragma unroll
                    for (int k = 0; k < 4; k += 1 + L.value) add_if(t == j, r[k], d[2 * j][k], d[2 * j + 1][k ^ 1]);
                CSTAMP(10, __float_as_uint(r[2]));
                if (L.value) {
                    dd = ((t & 2) ? r[2] : r[0]) + shx((t & 2) ? r[0] : r[2], 2);
                    ss += shx(ss, 2);
                    dd += shx(dd, 1);
                } else {
                    const float a = ((t & 1) ? r[1] : r[0]) + shx((t & 1) ? r[0] : r[1], 1), b = ((t & 1) ? r[3] : r[2]) + shx((t & 1) ? r[2] : r[3], 1);
                    ss += shx(ss, 2);
                    dd = ((t & 2) ? b : a) + shx((t & 2) ? a : b, 2);
                }
                ss += shx(ss, 1);
                stsf(hpa, dd);
                stsf(hst, ss);
                CSTAMP(11, __float_as_uint(dd + ss));
                if (!ok) mbar_wait(sb + SM_CBAR + CB_W2 * 8, L.value);
            }
            TSTAMPL(25);
            bar_sync(1, 160);
            uint4 hp[5];
#pragma unroll
            for (int w = 0; w < 5; w++) hp[w] = lds128(hsa + w * 256);
            CSTAMP(12, hp[0].x);
            auto hs = [&](auto K) { return sum5(__uint_as_float(word<K.value>(hp[0])), __uint_as_float(word<K.value>(hp[1])), __uint_as_float(word<K.value>(hp[2])),
                                                __uint_as_float(word<K.value>(hp[3])), __uint_as_float(word<K.value>(hp[4]))); };
            const float mean = hs(IC<2>{}) * (1.f / D_MODEL);
            msq = hs(IC<3>{}) * (1.f / D_MODEL);
            if (L.value == 0) cs1 = hs(IC<1>{});
            float hv = hs(IC<0>{}) - mean * cs1;
            CSTAMP(13, __float_as_uint(hv));
            const float sc2 = fx2_scale(msq), lim = fx_inv(sc2) * FX2LIM;
            if (L.value == 0) {
                read_w2();
                bar_arrive(4, 256);
                wide = false;
                if (mlp == 96) return;
            }
            hv = hv * ln_rstd(mean, msq) + b1v;
            CSTAMP(14, __float_as_uint(hv));
            hv = hv * rcp(1.f + ex2(hv * (-2.302208198f - 0.1029432397f * hv * hv)));
            const uint32_t hd = pack_bf(hv, hv);
            CSTAMP(15, hd);
            TSTAMPL(27);
            float ym[4][4];
#pragma unroll
            for (int i = 0; i < 2; i++) {
                ym[i][0] = ym[i][1] = ym[i][2] = ym[i][3] = 0.f;
                const float f = mlp < 64 ? 1.f / 64 : 0.f;
                ym[i + 2][0] = (bf_lo(xp.x) + bf_lo(b2v.x)) * f; ym[i + 2][1] = (bf_hi(xp.x) + bf_hi(b2v.x)) * f;
                ym[i + 2][2] = (bf_lo(xp.y) + bf_lo(b2v.y)) * f; ym[i + 2][3] = (bf_hi(xp.y) + bf_hi(b2v.y)) * f;
            }
#pragma unroll
            for (int i = 0; i < 4; i++) {
                const uint32_t hh = __shfl_sync(~0u, hd, 4 * i + t);
                mma(ym[(i & 1) * 2], w2r[2 * i], hh & maskA, hh & maskB);
                mma(ym[(i & 1) * 2 + 1], w2r[2 * i + 1], hh & maskA, hh & maskB);
            }
#pragma unroll
            for (int k = 0; k < 4; k++) { yf[k] = ym[0][k] + ym[2][k]; add_if(t & 2, yf[k], ym[1][k], ym[3][k]); }
            CSTAMP(16, __float_as_uint(yf[3]));
            yw[0] = fx2_pack(yf[0] * sc2 + FX2_ONE, yf[1] * sc2 + FX2_ONE); yw[1] = fx2_pack(yf[2] * sc2 + FX2_ONE, yf[3] * sc2 + FX2_ONE);
            wide = !(fmaxf(fmaxf(fabsf(yf[0]), fabsf(yf[1])), fmaxf(fabsf(yf[2]), fabsf(yf[3]))) < lim);
            if (wide) yw[0] = yw[1] = 0;
            if (L.value == 0) {
#pragma unroll
                for (int k = 0; k < 2; k++) asm volatile("red.relaxed.gpu.global.add.u64 [%0], %1;" :: "l"(rap + k * 20 * acc_pitch(1)), "l"(yw[k]) : "memory");
            }
        };
        auto send_wide = [&](int pitch) {
#pragma unroll 1
            for (int k = 0; k < 4; k++, yf[0] = yf[1], yf[1] = yf[2], yf[2] = yf[3]) {
                const unsigned char* a = rap + (k >> 1) * 20 * pitch;
                fx_send(a + 64 + (k & 1) * 64, yf[0], msq, a, 256);
            }
            yw[0] = yw[1] = 1;
        };

        pass1();
        o_setup(IC<0>{});
        out_proj(IC<0>{});
        uint32_t c0;
        if (warp < 5) {
            mlp_part(IC<0>{});
            c0 = clk() + (mlp == 96 ? PCD : 0);
            stsf(sb + SM_ML + (lane & 15) * 4, cs1);
            TSTAMP(8);
            if (__any_sync(~0u, wide)) {
                if (wide) {
                    send_wide(acc_pitch(1));
#pragma unroll
                    for (int k = 0; k < 2; k++) asm volatile("red.relaxed.gpu.global.add.u64 [%0], 1;" :: "l"(rap + k * 20 * acc_pitch(1)) : "memory");
                }
                __syncwarp();
            }
            fresh(); calc_offsets();
            load_wq();
        } else {
            bar_sync(0, 256);
            if (warp == 5 && elect()) issue_w(IC<0>{}, 1);
            __syncwarp();
            fresh(); calc_offsets();
            load_wq();
#pragma unroll 1
            for (int ph = 0; ph < 3; ph++) {
                bar_sync(ph + 2, 256);
                c0 = clk();
                if (ph == 2) {
                    msq = sum5(ldsf(sb + SM_PART + 12), ldsf(sb + SM_PART + 268), ldsf(sb + SM_PART + 524), ldsf(sb + SM_PART + 780), ldsf(sb + SM_PART + 1036)) * (1.f / D_MODEL);
                    bar_arrive(5, 256);
                }
                if (elect()) {
                    if (ph == 0) asm volatile("fence.proxy.async.shared::cta;" ::: "memory");
                    const uint32_t gap = ph == 0 ? WG1 : ph == 1 ? WG2 : WG3;
                    uint32_t c1 = c0 + (ph == 0 ? WD1 : 0) + (warp - 5) * gap;
#pragma unroll 1
                    for (int k = warp + (ph == 0 ? -5 : ph == 1 ? 9 : 1); k < (ph == 0 ? 9 : ph == 1 ? 20 : 14); k += 3, c1 += 3 * gap) {
                        const int i = ph == 0 && k >= 6 ? k + 23 : k;
                        const uint32_t bar = sb + SM_BAR + (i & 7) * 96 + 32 + (i & 24);
                        while ((int)(clk() - c1) < 0);
                        mbar_expect(bar, SUB);
                        tma_v(sb + SM_RING + i * SUB, tmk,
                              rowc * 3 + (i & 7) * 24 + ((UC<SCH.st[0].unit | SCH.st[1].unit << 8 | SCH.st[2].unit << 16 | SCH.st[3].unit << 24>::value >> (i & 24)) & 15) * 768, bar);
                    }
                }
                __syncwarp();
            }
            c0 += PCD;
        }
        {
            constexpr IC<1> L{};
            fresh();
            const int col = xcol(g & 3, t), cw = j40 + (col >> 2);
            const unsigned char* xa = pin(accg + ACC_BYTES + ((cw >> 3) + (col & 2) * 10) * acc_pitch(1) + (cw & 7) * 8);
            const uint32_t pst = pin(prow + (g * 8 + (t & 1) * 4 + (t & 2)) * 4);
            const float inv = pinf(fx2_inv(msq));
            sts64f(sb + SM_MSQ, msq, inv);
            rap = pin(accg + ACC_BYTES + (c4() >> 3) * acc_pitch(1) + (c4() & 7) * 8);
            fresh();
            maskA = pin(maskA); maskB = pin(maskB);
            u64 w[1];
            uint32_t x1[1], x2[3];
            auto look = [&]() { w[0] = ld_rlx(xa); };
            if (warp < 5) bar_sync(5, 256);
            while ((int)(clk() - c0) < ARDELAY);
            look();
            while ((int)(clk() - c0) < ARDELAY + DPOST);
            if (warp < 5 && elect()) {
                issue_v(IC<3>{}, 0);
                if (warp < 4) issue_v(IC<2>{}, 4);
            }
            __syncwarp();
            fx2_wait<1>([&](int) { return xa; }, look, w, sb + SM_MSQ, inv, x1);
            if (warp < 5) look_rw(); else rw[0] = rw[1] = 96;
#pragma unroll
            for (int i = 0; i < 3; i++) x2[i] = __shfl_sync(~0u, x1[0], 4 * i + t);
            TSTAMP(9);
            CSTAMP(22, x2[2]);
            q_proj(L, x2, pst);
            pass2();
            out_proj(L);
            if (warp >= 5) {
                bar_arrive(0, 256);
                if (warp == 5 && elect()) issue_w(L, 1);
                TDUMP();
                return;
            }
            mlp_part(L);
            u64 old[2];
            auto add = [&]() {
#pragma unroll
                for (int k = 0; k < 2; k++) asm volatile("atom.relaxed.gpu.global.add.u64 %0, [%1], %2;" : "=l"(old[k]) : "l"(rap + k * 20 * acc_pitch(3)), "l"(yw[k]) : "memory");
            };
            add();
            uint32_t* op = pin(reinterpret_cast<uint32_t*>(P.out) + 2 * c4());
            const float inv2 = pinf(fx2_inv(msq));
            if (wide) { send_wide(acc_pitch(3)); add(); }
            TSTAMP(18);
            CSTAMP(17, hi32(yw[1]));
            __syncwarp();
            CSTAMP(18, lo32(old[0]) ^ lo32(old[1]));
#pragma unroll
            for (int k = 0; k < 2; k++) {
                yw[k] += old[k];
                asm volatile("{\n.reg .pred p;\nsetp.eq.u32 p, %2, 96;\n@p st.global.u32 [%0], %1;\n}"
                             :: "l"(op + k), "r"(fx2_get(yw[k], inv2)), "r"(lo32(yw[k]) & 511) : "memory");
            }
            if ((lo32(yw[0]) & 255) == 96 && tid == 0) P.g->epoch = lds32(sb + SM_EPOCH) + 1;
#pragma unroll
            for (int k = 0; k < 2; k++) if ((lo32(yw[k]) & 511) == 256 + 96) op[k] = fx2_wide(rap + k * 20 * acc_pitch(3), msq);
            TSTAMP(19);
            CSTAMP(19, lo32(yw[1]));
            TDUMP();
        }
    }
}

typedef CUresult (*EncodeFn)(CUtensorMap*, CUtensorMapDataType, cuuint32_t, void*, const cuuint64_t*, const cuuint64_t*, const cuuint32_t*,
                             const cuuint32_t*, CUtensorMapInterleave, CUtensorMapSwizzle, CUtensorMapL2promotion, CUtensorMapFloatOOBfill);

}

extern "C" void kernel_launch(void* const* d_in, const int* in_sizes, int n_in, void* d_out, int out_size) {
    (void)in_sizes; (void)n_in; (void)out_size;
    static EncodeFn enc = nullptr;
    static void* scratch = nullptr;
    if (!enc) {
        void* fn = nullptr;
        cudaDriverEntryPointQueryResult qr;
        cudaGetDriverEntryPoint("cuTensorMapEncodeTiled", &fn, cudaEnableDefault, &qr);
        enc = (EncodeFn)fn;
        cudaGetSymbolAddress(&scratch, g_scratch);
        cudaFuncSetAttribute(fused_kernel, cudaFuncAttributeMaxDynamicSharedMemorySize, SM_TOTAL);
    }
    Params P = {};
    auto map3 = [&](int m, int in, cuuint64_t d0, cuuint64_t d1, cuuint64_t d2, cuuint64_t s1, cuuint64_t s2, cuuint32_t b0, cuuint32_t b1, cuuint32_t b2,
                    CUtensorMapSwizzle sw, int promo) {
        const cuuint64_t dim[3] = {d0, d1, d2}, str[2] = {s1, s2};
        const cuuint32_t box[3] = {b0, b1, b2}, ones[3] = {1, 1, 1};
        enc(&P.tm[m], CU_TENSOR_MAP_DATA_TYPE_BFLOAT16, d2 ? 3 : 2, d_in[in], dim, str, box, ones, CU_TENSOR_MAP_INTERLEAVE_NONE, sw, (CUtensorMapL2promotion)promo,
            CU_TENSOR_MAP_FLOAT_OOB_FILL_NONE);
    };
    map3(TM_KH, 1, 64, 3, NHEAD * SK, 128, DH * 2, 64, 3, 32, CU_TENSOR_MAP_SWIZZLE_128B, 0);
    map3(TM_VH, 2, 64, 3, NHEAD * SK, 128, DH * 2, 64, 3, 32, CU_TENSOR_MAP_SWIZZLE_128B, 0);
    map3(TM_VP, 2, 64, 3, NHEAD * SK, 128, DH * 2, 8, 3, 32, CU_TENSOR_MAP_SWIZZLE_NONE, 0);
    map3(TM_V, 2, 64, NHEAD * SK * 3, 0, 128, 0, 64, 24, 0, CU_TENSOR_MAP_SWIZZLE_128B, 0);
    map3(TM_WO, 4, 32, 20, NHEAD * DH, 64, D_MODEL * 2, 32, 1, DH, CU_TENSOR_MAP_SWIZZLE_64B, 2);
    map3(TM_WOP, 4, 32, 20, NHEAD * DH, 64, D_MODEL * 2, 8, 1, DH, CU_TENSOR_MAP_SWIZZLE_NONE, 0);
    map3(TM_WQ, 3, 64, NHEAD * 3, D_MODEL, 128, NHEAD * DH * 2, 64, 3, 32, CU_TENSOR_MAP_SWIZZLE_128B, 0);
    map3(TM_W1, 6, DFF, 128, 5, DFF * 2, DFF * 256, 16, 128, 5, CU_TENSOR_MAP_SWIZZLE_32B, 2);
    map3(TM_W2, 8, 64, 10, DFF, 128, D_MODEL * 2, 64, 10, 16, CU_TENSOR_MAP_SWIZZLE_128B, 0);
    P.x = (const __nv_bfloat16*)d_in[0];
    P.k = (const __nv_bfloat16*)d_in[1];
    P.b1 = (const __nv_bfloat16*)d_in[7];
    P.b2 = (const __nv_bfloat16*)d_in[9];
    P.w1 = (const __nv_bfloat16*)d_in[6];
    P.out = (__nv_bfloat16*)d_out;
    P.g = (Scratch*)(((uintptr_t)scratch + ACC_BYTES - 1) & ~(uintptr_t)(ACC_BYTES - 1));
    for (int i = 0; i < 64; i++) P.tile[i] = make_uint4(SCH.tile[i][0], SCH.tile[i][1], SCH.tile[i][2], 0);
    fused_kernel<<<NCTA, NTHR, SM_TOTAL, cudaStreamPerThread>>>(P);
}
```

```cpp
#include <cuda_runtime.h>
#include <cuda_bf16.h>
#include <cuda.h>
#include <stdint.h>

namespace {

constexpr int D_MODEL = 640, NHEAD = 32, SK = 32768, DH = 192, WIN = 4096, DFF = 1536;
constexpr int NCTA = 128, NTHR = 256;
constexpr int TILE = 64 * DH * 2;
constexpr int HALF = TILE / 2;
constexpr int SUB = 8 * DH * 2;
constexpr int SM_RING = 4 * TILE;
constexpr int SM_W2 = SM_RING + 20480, SM_W1 = SM_W2 + 20480;
constexpr int SM_WQR = 6 * TILE + HALF, SM_WQ = 7 * TILE;
constexpr int SM_PART = 9 * TILE;
constexpr int SM_EXC = SM_PART + 6144;
constexpr int SM_SC = SM_EXC + 1024;
constexpr int SM_BAR = SM_SC + 1024;
constexpr int SM_VEC = SM_BAR + 768;
constexpr int SM_CS = SM_VEC + 384;
constexpr int SM_FAC = SM_CS + 768;
constexpr int SM_ML = SM_FAC + 32;
constexpr int SM_B1 = SM_ML + 64;
constexpr int SM_STAT = SM_B1 + 64;
constexpr int NCB = 28;
constexpr int CB_WO = 18, CB_W1 = 23, CB_W2 = 24, CB_SNAP = 25, CB_REL = 26, CB_WQ = 27;
constexpr int SM_CBAR = SM_STAT + 48;
constexpr int SM_CNT = SM_CBAR + NCB * 8;
constexpr int SM_ZERO = SM_CNT + NCB * 8;
constexpr int SM_EPOCH = SM_ZERO + 64;
constexpr int SM_FXS = SM_EPOCH + 4;
constexpr int SM_T0 = SM_FXS + 4;
constexpr int SM_M1 = SM_T0 + 4;
constexpr int SM_MSQ = SM_M1 + 4;
constexpr int SM_TS = SM_MSQ + 8;
constexpr int SM_TOTAL = 232448;
static_assert(SM_TS + 320 <= SM_TOTAL && SM_ZERO % 16 == 0, "smem");
constexpr int NEXC = 16;

constexpr int SPIN = 1 << 20;
enum { TM_V = 0, TM_KH = 1, TM_VH = 2, TM_WO = 3, TM_VP = 4, TM_WOP = 5, TM_W1 = 6, TM_W2 = 7, TM_WQ = 8 };
constexpr uint32_t POL_NORMAL = 0x16F00000u, POL_FIRST = 0x12F00000u;

#define PACE 980
#define PACE0 1500
#define PACES 1300
#define NI1 6
#define ETRIG 0x54321000
#define PFREE 66
#define SNAPAT 2
#define LATEAT 5
#define PUBAT 28
#define HW0 30
#define HW1 31
#define AR1D 250
#define ARDELAY 720
#define DPOST 200
#define PCD 350
#define WD1 100
#define W2T 1200
#define WG1 140
#define WG2 120
#define WG3 65
#define VORD2 0x7685943a2b1cd0efull
#define VSLOT 0x1087654321087654ull
#define VTRIG 0xba73210
#define PARKS 0xa5
#define RF0 1
#define RF1 2
#define M1D 1
#define LAG0 12
#define NMMA 2
#define HWAT 12
#define WOP 0x44433
#define NWO1 4
#define FX1LIM 524288.f
#define FX2LIM 524288.f

constexpr uint32_t G_A = 1u << 28, G_B = 1u << 29, G_C = 1u << 30;
__host__ __device__ constexpr int ring_hs(int j) { return (j + 4) % 5; }
__host__ __device__ constexpr uint32_t load_word(int j) {
    if (j >= 64) return (uint32_t)(j - 64) << 20 | (SM_RING + ring_hs(j) * HALF) | TM_WO << 8 | (CB_WO + j - 64) << 3 | 2;
    const int e = j >> 1, isv = e >= 16, unit = e & 15;
    return (uint32_t)(unit * 256 + (j & 1) * 32) << 20 | (j < 8 ? j * HALF : SM_RING + ring_hs(j) * HALF) | (TM_KH + isv) << 8 | (j < 8 ? 10 + j : (j - 8) % 10) << 3 | 2 | !isv;
}
__host__ __device__ constexpr int popc(int v) { return v ? (v & 1) + popc(v >> 1) : 0; }
constexpr int NPARK = popc(PARKS), NPRE = 2;
constexpr int SM_SNAP = SM_RING + ring_hs(12) * HALF, SM_CSP = SM_RING + ring_hs(11) * HALF;
struct Step { int unit, slot, par, next, mma0, nmma; };
struct Sched { uint32_t tile[64][3]; Step st[16]; };
constexpr Sched make_sched() {
    Sched s{};
    for (int j = 0; j < 64; j++) {
        const int e = j >> 1;
        const uint32_t d = load_word(j);
        uint32_t w = (uint32_t)(j < 8 ? 0 : (j - 8) / 10 & 1) << 31 | (e & 15) * 4 << 20 | ((d & 0x3f000) - (j & 1) * HALF) | (d & 0xf8);
        if (e == PUBAT || e == SNAPAT) w |= G_A;
        if (e == HW0 || e == 4) w |= G_B;
        if ((e >= LATEAT && e < LATEAT + 4) || e == HW1) w |= G_C;
        s.tile[j][0] = w;
    }
    for (int j = NI1; j < 69; j++) {
        if (j == 12) continue;
        const int at = j < 12 ? (ETRIG >> (4 * (j - 4)) & 15) : j - 5;
        s.tile[at][1] = load_word(j);
        s.tile[at][2] = j >= PFREE ? 0 : PACE0 + j * PACE / 2;
    }
    int done = 0;
    for (int p = 0; p < 16; p++) {
        Step& c = s.st[p];
        c.unit = (int)(VORD2 >> (4 * p) & 15); c.slot = (int)(VSLOT >> (4 * p) & 15); c.par = p >= 9; c.next = -1;
        c.mma0 = done;
        if (p >= NPARK) { const int avail = p - done + (p >= LAG0); c.nmma = p == 15 ? 16 - done : (avail < NMMA ? avail : NMMA); done += c.nmma; }
    }
    for (int p = 9; p < 16; p++) s.st[VTRIG >> (4 * (p - 9)) & 15].next = p;
    return s;
}
constexpr Sched SCH = make_sched();
__host__ __device__ constexpr int kunit(int o) { return o < 5 ? o + 11 : o == 5 ? 10 : o - 6; }

template <int I> struct IC { static constexpr int value = I; };
template <uint32_t I> struct UC { static constexpr uint32_t value = I; };
template <int A, int B, class F> __device__ __forceinline__ void static_for(F&& f) {
    if constexpr (A < B) { f(IC<A>{}); static_for<A + 1, B>(f); }
}

typedef unsigned long long u64;
constexpr int ACC_BYTES = 65536;
__host__ __device__ constexpr int acc_pitch(int r) { return (r & 1) ? 832 : 256; }
struct alignas(1024) Scratch {
    unsigned char acc[4 * ACC_BYTES];
    u64 l0[NCTA][384];
    u64 ll[NCTA][256];
    alignas(128) unsigned epoch;
    alignas(128) unsigned zeroed;
};
__device__ __align__(1024) unsigned char g_scratch[sizeof(Scratch) + ACC_BYTES];

struct Params {
    CUtensorMap tm[9];
    const __nv_bfloat16 *x, *k, *b1, *b2, *w1;
    __nv_bfloat16* out;
    Scratch* g;
    uint4 tile[66];
};

#define TSTAMP(i)
#define TSTAMP2(i)
#define TSTAMPL(i)
#define TDUMP()
#define CSTAMP(i, x)
#define TRACE(i)

__device__ __forceinline__ void mbar_wait(uint32_t bar, uint32_t parity) {
    asm volatile("{\n.reg .pred p;\nLOOP:\nmbarrier.try_wait.parity.shared::cta.b64 p, [%0], %1;\n@!p bra.uni LOOP;\n}" :: "r"(bar), "r"(parity) : "memory");
}
__device__ __forceinline__ bool mbar_test(uint32_t bar, uint32_t parity) {
    uint32_t r;
    asm volatile("{\n.reg .pred p;\nmbarrier.test_wait.parity.shared::cta.b64 p, [%1], %2;\nselp.u32 %0, 1, 0, p;\n}" : "=r"(r) : "r"(bar), "r"(parity) : "memory");
    return __all_sync(~0u, r);
}
__device__ __forceinline__ bool elect() {
    uint32_t r;
    asm volatile("{\n.reg .pred p;\nelect.sync _|p, 0xffffffff;\nselp.u32 %0, 1, 0, p;\n}" : "=r"(r));
    return r != 0;
}
__device__ __forceinline__ void mbar_expect(uint32_t bar, uint32_t bytes) {
    asm volatile("mbarrier.arrive.expect_tx.shared::cta.b64 _, [%0], %1;" :: "r"(bar), "r"(bytes) : "memory");
}
__device__ __forceinline__ uint4 lds128(uint32_t a) {
    uint4 v; asm volatile("ld.shared.v4.u32 {%0,%1,%2,%3}, [%4];" : "=r"(v.x), "=r"(v.y), "=r"(v.z), "=r"(v.w) : "r"(a) : "memory"); return v;
}
__device__ __forceinline__ uint4 ldsm_t(uint32_t a) {
    uint4 v; asm volatile("ldmatrix.sync.aligned.m8n8.x4.trans.shared.b16 {%0,%1,%2,%3}, [%4];" : "=r"(v.x), "=r"(v.y), "=r"(v.z), "=r"(v.w) : "r"(a) : "memory"); return v;
}
__device__ __forceinline__ uint2 lds64(uint32_t a) {
    uint2 v; asm volatile("ld.shared.v2.u32 {%0,%1}, [%2];" : "=r"(v.x), "=r"(v.y) : "r"(a) : "memory"); return v;
}
__device__ __forceinline__ float2 lds64f(uint32_t a) { const uint2 v = lds64(a); return make_float2(__uint_as_float(v.x), __uint_as_float(v.y)); }
__device__ __forceinline__ uint32_t lds32(uint32_t a) {
    uint32_t v; asm volatile("ld.shared.u32 %0, [%1];" : "=r"(v) : "r"(a) : "memory"); return v;
}
__device__ __forceinline__ float ldsf(uint32_t a) { return __uint_as_float(lds32(a)); }
__device__ __forceinline__ void sts32(uint32_t a, uint32_t v) { asm volatile("st.shared.u32 [%0], %1;" :: "r"(a), "r"(v) : "memory"); }
__device__ __forceinline__ void stsf(uint32_t a, float v) { sts32(a, __float_as_uint(v)); }
__device__ __forceinline__ void sts16(uint32_t a, uint32_t v) { asm volatile("st.shared.u16 [%0], %1;" :: "r"(a), "h"((uint16_t)v) : "memory"); }
__device__ __forceinline__ void sts64(uint32_t a, uint32_t x, uint32_t y) { asm volatile("st.shared.v2.u32 [%0], {%1,%2};" :: "r"(a), "r"(x), "r"(y) : "memory"); }
__device__ __forceinline__ void sts64f(uint32_t a, float x, float y) { sts64(a, __float_as_uint(x), __float_as_uint(y)); }
__device__ __forceinline__ void sts128f(uint32_t a, float x, float y, float z, float w) {
    asm volatile("st.shared.v4.f32 [%0], {%1,%2,%3,%4};" :: "r"(a), "f"(x), "f"(y), "f"(z), "f"(w) : "memory");
}
__device__ __forceinline__ void mma(float (&c)[4], const uint4& a, uint32_t b0, uint32_t b1) {
    asm volatile("mma.sync.aligned.m16n8k16.row.col.f32.bf16.bf16.f32 {%0,%1,%2,%3}, {%4,%5,%6,%7}, {%8,%9}, {%0,%1,%2,%3};"
                 : "+f"(c[0]), "+f"(c[1]), "+f"(c[2]), "+f"(c[3]) : "r"(a.x), "r"(a.y), "r"(a.z), "r"(a.w), "r"(b0), "r"(b1));
}
__device__ __forceinline__ u64 ld_rlx(const void* p) {
    u64 a; asm volatile("ld.relaxed.gpu.global.u64 %0, [%1];" : "=l"(a) : "l"(p) : "memory"); return a;
}
__device__ __forceinline__ void ld_rlx2(const void* p, u64& a, u64& b) {
    asm volatile("ld.relaxed.gpu.global.v2.u64 {%0,%1}, [%2];" : "=l"(a), "=l"(b) : "l"(p) : "memory");
}
__device__ __forceinline__ void st_rlx(void* p, u64 a) { asm volatile("st.relaxed.gpu.global.u64 [%0], %1;" :: "l"(p), "l"(a) : "memory"); }
__device__ __forceinline__ u64 ll_pack(float v, uint32_t tag) { return ((u64)tag << 32) | __float_as_uint(v); }
__device__ __forceinline__ float ll_val(u64 w) { return __uint_as_float((uint32_t)w); }
__device__ __forceinline__ uint32_t ll_tag(u64 w) { return (uint32_t)(w >> 32); }
__device__ __forceinline__ float bf_lo(uint32_t u) { return __uint_as_float(u << 16); }
__device__ __forceinline__ float bf_hi(uint32_t u) { return __uint_as_float(u & 0xffff0000u); }
__device__ __forceinline__ uint32_t pack_bf(float lo, float hi) {
    uint32_t r; asm("cvt.rn.bf16x2.f32 %0, %1, %2;" : "=r"(r) : "f"(hi), "f"(lo)); return r;
}
__device__ __forceinline__ float ex2(float v) { float r; asm("ex2.approx.ftz.f32 %0, %1;" : "=f"(r) : "f"(v)); return r; }
__device__ __forceinline__ float rcp(float v) { float r; asm("rcp.approx.ftz.f32 %0, %1;" : "=f"(r) : "f"(v)); return r; }
__device__ __forceinline__ float rsq(float v) { float r; asm("rsqrt.approx.ftz.f32 %0, %1;" : "=f"(r) : "f"(v)); return r; }
__device__ __forceinline__ void bar_sync(int id, int n) { asm volatile("bar.sync %0, %1;" :: "r"(id), "r"(n) : "memory"); }
__device__ __forceinline__ uint32_t clk() { uint32_t c; asm volatile("mov.u32 %0, %clock;" : "=r"(c)); return c; }
__device__ __forceinline__ void sched_fence() { __syncwarp(); while (clk() == 0x9e3779b9u); }
__device__ __forceinline__ uint32_t pin(uint32_t v) { return __shfl_xor_sync(~0u, v, 0); }
__device__ __forceinline__ float shx(float v, int o) { return __shfl_xor_sync(~0u, v, o); }

__device__ __forceinline__ u64 fx_pack(float v, float scale) { return ((u64)__float2ll_rn(v * scale) & ~255ull) | 1ull; }
__device__ __forceinline__ float fx_scale(float meansq) {
    const int e = max(((int)(__float_as_uint(meansq) >> 23) - 127) >> 1, -6);
    return __uint_as_float((uint32_t)(127 + 32 - e) << 23);
}
__device__ __forceinline__ float fx_inv(float scale) { return __uint_as_float((254u << 23) - __float_as_uint(scale)); }
__device__ __forceinline__ uint32_t lo32(u64 w) { uint32_t l; asm("mov.b64 {%0, _}, %1;" : "=r"(l) : "l"(w)); return l; }
__device__ __forceinline__ int hi32(u64 w) { int h; asm("mov.b64 {_, %0}, %1;" : "=r"(h) : "l"(w)); return h; }
__device__ __forceinline__ float fx_val(u64 w) { return (float)hi32(w) * 4294967296.f + (float)lo32(w); }
constexpr float FX2_ONE = 12582912.f;
__device__ __forceinline__ float fx2_scale(float meansq) { return __uint_as_float((uint32_t)(127 + 16 - max(((int)(__float_as_uint(meansq) >> 23) - 127) >> 1, -100)) << 23); }
__device__ __forceinline__ u64 fx2_pack(float a, float b) {
    const uint32_t lo = __float_as_uint(a) * 512u + (1u - 0x4b400000u * 512u);
    return lo | (u64)(__float_as_uint(b) * 16u - 0x4b400000u * 16u + (uint32_t)((int)lo >> 31)) << 32;
}
__device__ __forceinline__ float fx2_lo(u64 w, float inv) { return (float)(int)(__funnelshift_r(lo32(w), hi32(w), 4) & ~31u) * (inv * 0.5f); }
__device__ __forceinline__ float fx2_hi(u64 w, float inv) { return (float)((hi32(w) + 8) & ~15) * inv; }
__device__ __forceinline__ uint32_t fx2_get(u64 w, float inv) {
    return pack_bf((float)(int)__funnelshift_r(lo32(w), hi32(w), 4) * (inv * 0.5f) - inv * 3.f, (float)hi32(w) * inv);
}
__device__ __forceinline__ float fx2_inv(float meansq) { return fx_inv(fx2_scale(meansq)) * 0.0625f; }
__device__ __noinline__ uint32_t fx2_wide(const unsigned char* a, float meansq) {
    __threadfence();
    const u64 w = ld_rlx(a);
    const float inv = fx_inv(fx_scale(meansq));
    return pack_bf(fx2_lo(w, fx2_inv(meansq)) + fx_val(ld_rlx(a + 64)) * inv, fx2_hi(w, fx2_inv(meansq)) + fx_val(ld_rlx(a + 128)) * inv);
}
__device__ __noinline__ uint32_t fx1_wide(const unsigned char* a, float meansq) {
    __threadfence();
    const u64 w = ld_rlx(a);
    const unsigned char* b = a + 64 + (reinterpret_cast<u64>(a) & 63);
    const float inv = fx_inv(fx_scale(meansq)), inv1 = fx2_inv(meansq) * 0.5f;
    return pack_bf((float)(int)(lo32(w) & ~127u) * inv1 + fx_val(ld_rlx(b)) * inv, (float)(hi32(w) & ~127) * inv1 + fx_val(ld_rlx(b + 8)) * inv);
}
__device__ __noinline__ void fx_send(const unsigned char* wide, float v, float meansq, const unsigned char* a, uint32_t flag) {
    asm volatile("red.relaxed.gpu.global.add.u64 [%0], %1;" :: "l"(wide), "l"(fx_pack(v, fx_scale(meansq))) : "memory");
    __threadfence();
    asm volatile("red.relaxed.gpu.global.or.b32 [%0], %1;" :: "l"(a), "r"(flag) : "memory");
}
template <int N, class A, class F> __device__ __forceinline__ void fx2_wait(A a, F look, u64 (&w)[N], uint32_t msqa, float inv, uint32_t (&x)[N]) {
    auto miss = [&]() {
#pragma unroll
        for (int i = 0; i < N; i++) x[i] = fx2_get(w[i], inv);
        return __any_sync(~0u, ((lo32(w[0]) ^ 96) | (lo32(w[N - 1]) ^ 96)) & 0x160);
    };
    if (miss()) {
        int it = 0;
#pragma unroll 1
        do {
            if (__all_sync(~0u, (lo32(w[0]) & lo32(w[N - 1]) & 96) == 96)) {
#pragma unroll
                for (int i = 0; i < N; i++) x[i] = fx2_wide(a(i), ldsf(msqa));
                break;
            }
            look();
        } while (miss() & (++it < SPIN));
    }
}
__device__ __forceinline__ void st_rlx_if(bool p, void* a, u64 v) {
    asm volatile("{\n.reg .pred p;\nsetp.ne.u32 p, %2, 0;\n@p st.relaxed.gpu.global.u64 [%0], %1;\n}" :: "l"(a), "l"(v), "r"((uint32_t)p) : "memory");
}
__device__ __forceinline__ void sts128f(uint32_t a, const float (&v)[4]) { sts128f(a, v[0], v[1], v[2], v[3]); }
__device__ __forceinline__ void bar_arrive(int id, int n) { asm volatile("bar.arrive %0, %1;" :: "r"(id), "r"(n) : "memory"); }
template <class T> __device__ __forceinline__ T* pin(T* p) { return reinterpret_cast<T*>(__shfl_xor_sync(~0u, (u64)p, 0)); }

__device__ __forceinline__ void tma3(uint32_t dst, const CUtensorMap* tm, int c1, int c2, uint32_t bar, uint32_t pol) {
    asm volatile("cp.async.bulk.tensor.3d.shared::cluster.global.mbarrier::complete_tx::bytes.L2::cache_hint [%0], [%1, {%2, %3, %4}], [%5], %6;"
                 :: "r"(dst), "l"(tm), "r"(0), "r"(c1), "r"(c2), "r"(bar), "l"((u64)pol << 32) : "memory");
}
__device__ __forceinline__ void tma_v(uint32_t dst, const CUtensorMap* tm, int line, uint32_t bar) {
    asm volatile("cp.async.bulk.tensor.2d.shared::cluster.global.mbarrier::complete_tx::bytes.L2::cache_hint [%0], [%1, {%2, %3}], [%4], %5;"
                 :: "r"(dst), "l"(tm), "r"(0), "r"(line), "r"(bar), "l"((u64)POL_FIRST << 32) : "memory");
}
__device__ __forceinline__ void tma3_pf(const CUtensorMap* tm, int c1, int c2, uint32_t pol) {
    asm volatile("cp.async.bulk.prefetch.tensor.3d.L2.global.tile.L2::cache_hint [%0, {%1, %2, %3}], %4;"
                 :: "l"(tm), "r"(0), "r"(c1), "r"(c2), "l"((u64)pol << 32) : "memory");
}
__device__ __forceinline__ void issue_half(uint32_t d, uint32_t sb, int rowc, int cta, const CUtensorMap* tm0) {
    const uint32_t bar = sb + SM_CBAR + (d & 0xf8);
    const CUtensorMap* tm = tm0 + ((d >> 8) & 3);
    const bool wo = (d & 0x300) == TM_WO << 8;
    const int c1 = wo ? (cta & 3) + 4 * (d >> 20) : 0, c2 = wo ? (cta >> 2) * DH : rowc + (d >> 20);
    mbar_expect(bar, HALF);
    tma3(sb + (d & 0x3f000), tm, c1, c2, bar, POL_FIRST);
    if (!(d & 1)) tma3_pf(tm + 2, c1, c2, POL_NORMAL);
}
__device__ __forceinline__ uint32_t cnt_inc(uint32_t a, uint32_t last) {
    uint32_t old; asm volatile("atom.relaxed.cta.shared.inc.u32 %0, [%1], %2;" : "=r"(old) : "r"(a), "r"(last) : "memory"); return old;
}
__device__ __forceinline__ void wait_until(uint32_t due) {
#pragma unroll 1
    for (int it = 0; it < 4096; it++) { uint32_t now; asm volatile("mov.u32 %0, %globaltimer_lo;" : "=r"(now)); if ((int)(now - due) >= 0) break; }
}
__device__ __forceinline__ uint32_t bf2_mul(uint32_t a, uint32_t b) { uint32_t r; asm("mul.rn.bf16x2 %0, %1, %2;" : "=r"(r) : "r"(a), "r"(b)); return r; }
__device__ __forceinline__ uint32_t bf2_fma(uint32_t a, uint32_t b, uint32_t c) { uint32_t r; asm("fma.rn.bf16x2 %0, %1, %2, %3;" : "=r"(r) : "r"(a), "r"(b), "r"(c)); return r; }
__device__ __forceinline__ uint32_t bf2_amax(uint32_t a, uint32_t b) { uint32_t r; asm("max.NaN.xorsign.abs.bf16x2 %0, %1, %2;" : "=r"(r) : "r"(a), "r"(b)); return r; }
__device__ __forceinline__ uint4 k_unpack(uint32_t l0, uint32_t l1, uint32_t h, uint32_t m1) {
    const uint32_t ha = h & 0x87878787u, hc = ha * m1 + h, hb = __funnelshift_l(hc, hc, 4);
    return make_uint4(__byte_perm(l0, ha, 0x5140), __byte_perm(l0, ha, 0x7362), __byte_perm(l1, hb, 0x5140), __byte_perm(l1, hb, 0x7362));
}
#define KR4(u, i) "+r"(kr[u][i].x), "+r"(kr[u][i].y), "+r"(kr[u][i].z), "+r"(kr[u][i].w)
#define KR6(u) KR4(u, 0), KR4(u, 1), KR4(u, 2), KR4(u, 3), KR4(u, 4), KR4(u, 5)
__device__ __forceinline__ void k_keep(uint4 (&kr)[8][6], const uint32_t (&c)[18], int e, uint32_t a) {
    asm volatile("{\nKT: .branchtargets K0, K1, K2, K3, K4, K5, K6, K7, K8, K9, K10, K11, K12, K13, K14, K15;\nbrx.idx.uni %210, KT;\n"
                 "K0: mov.b32 %12, %192; mov.b32 %13, %193; mov.b32 %14, %194; mov.b32 %15, %195; mov.b32 %16, %196; mov.b32 %17, %197; mov.b32 %18, %198; mov.b32 %19, %199; mov.b32 %20, %200; mov.b32 %21, %201; mov.b32 %22, %202; mov.b32 %23, %203; mov.b32 %24, %204; mov.b32 %25, %205; mov.b32 %26, %206; mov.b32 %27, %207; mov.b32 %28, %208; mov.b32 %29, %209; bra.uni KE;\n"
                 "K1: mov.b32 %30, %192; mov.b32 %31, %193; mov.b32 %32, %194; mov.b32 %33, %195; mov.b32 %34, %196; mov.b32 %35, %197; mov.b32 %36, %198; mov.b32 %37, %199; mov.b32 %38, %200; mov.b32 %39, %201; mov.b32 %40, %202; mov.b32 %41, %203; mov.b32 %42, %204; mov.b32 %43, %205; mov.b32 %44, %206; mov.b32 %45, %207; mov.b32 %46, %208; mov.b32 %47, %209; bra.uni KE;\n"
                 "K2: mov.b32 %48, %192; mov.b32 %49, %193; mov.b32 %50, %194; mov.b32 %51, %195; mov.b32 %52, %196; mov.b32 %53, %197; mov.b32 %54, %198; mov.b32 %55, %199; mov.b32 %56, %200; mov.b32 %57, %201; mov.b32 %58, %202; mov.b32 %59, %203; mov.b32 %60, %204; mov.b32 %61, %205; mov.b32 %62, %206; mov.b32 %63, %207; mov.b32 %64, %208; mov.b32 %65, %209; bra.uni KE;\n"
                 "K3: mov.b32 %66, %192; mov.b32 %67, %193; mov.b32 %68, %194; mov.b32 %69, %195; mov.b32 %70, %196; mov.b32 %71, %197; mov.b32 %72, %198; mov.b32 %73, %199; mov.b32 %74, %200; mov.b32 %75, %201; mov.b32 %76, %202; mov.b32 %77, %203; mov.b32 %78, %204; mov.b32 %79, %205; mov.b32 %80, %206; mov.b32 %81, %207; mov.b32 %82, %208; mov.b32 %83, %209; bra.uni KE;\n"
                 "K4: mov.b32 %84, %192; mov.b32 %85, %193; mov.b32 %86, %194; mov.b32 %87, %195; mov.b32 %88, %196; mov.b32 %89, %197; mov.b32 %90, %198; mov.b32 %91, %199; mov.b32 %92, %200; mov.b32 %93, %201; mov.b32 %94, %202; mov.b32 %95, %203; mov.b32 %96, %204; mov.b32 %97, %205; mov.b32 %98, %206; mov.b32 %99, %207; mov.b32 %100, %208; mov.b32 %101, %209; bra.uni KE;\n"
                 "K5: mov.b32 %102, %192; mov.b32 %103, %193; mov.b32 %104, %194; mov.b32 %105, %195; mov.b32 %106, %196; mov.b32 %107, %197; mov.b32 %108, %198; mov.b32 %109, %199; mov.b32 %110, %200; mov.b32 %111, %201; mov.b32 %112, %202; mov.b32 %113, %203; mov.b32 %114, %204; mov.b32 %115, %205; mov.b32 %116, %206; mov.b32 %117, %207; mov.b32 %118, %208; mov.b32 %119, %209; bra.uni KE;\n"
                 "K6: mov.b32 %120, %192; mov.b32 %121, %193; mov.b32 %122, %194; mov.b32 %123, %195; mov.b32 %124, %196; mov.b32 %125, %197; mov.b32 %126, %198; mov.b32 %127, %199; mov.b32 %128, %200; mov.b32 %129, %201; mov.b32 %130, %202; mov.b32 %131, %203; mov.b32 %132, %204; mov.b32 %133, %205; mov.b32 %134, %206; mov.b32 %135, %207; mov.b32 %136, %208; mov.b32 %137, %209; bra.uni KE;\n"
                 "K7: mov.b32 %138, %192; mov.b32 %139, %193; mov.b32 %140, %194; mov.b32 %141, %195; mov.b32 %142, %196; mov.b32 %143, %197; mov.b32 %144, %198; mov.b32 %145, %199; mov.b32 %146, %200; mov.b32 %147, %201; mov.b32 %148, %202; mov.b32 %149, %203; mov.b32 %150, %204; mov.b32 %151, %205; mov.b32 %152, %206; mov.b32 %153, %207; mov.b32 %154, %208; mov.b32 %155, %209; bra.uni KE;\n"
                 "K8: mov.b32 %156, %192; mov.b32 %157, %193; mov.b32 %158, %194; mov.b32 %159, %195; mov.b32 %160, %196; mov.b32 %161, %197; mov.b32 %162, %198; mov.b32 %163, %199; mov.b32 %164, %200; mov.b32 %165, %201; mov.b32 %166, %202; mov.b32 %167, %203; mov.b32 %168, %204; mov.b32 %169, %205; mov.b32 %170, %206; mov.b32 %171, %207; mov.b32 %172, %208; mov.b32 %173, %209; bra.uni KE;\n"
                 "K9: mov.b32 %174, %192; mov.b32 %175, %193; mov.b32 %176, %194; mov.b32 %177, %195; mov.b32 %178, %196; mov.b32 %179, %197; mov.b32 %180, %198; mov.b32 %181, %199; mov.b32 %182, %200; mov.b32 %183, %201; mov.b32 %184, %202; mov.b32 %185, %203; mov.b32 %186, %204; mov.b32 %187, %205; mov.b32 %188, %206; mov.b32 %189, %207; mov.b32 %190, %208; mov.b32 %191, %209; bra.uni KE;\n"
                 "K10: st.shared.v2.b32 [%211+75784], {%192, %193}; st.shared.v2.b32 [%211+76288], {%194, %195}; st.shared.v2.b32 [%211+76296], {%196, %197}; mov.b32 %0, %198; mov.b32 %1, %199; mov.b32 %2, %200; mov.b32 %3, %201; mov.b32 %4, %202; mov.b32 %5, %203; mov.b32 %6, %204; mov.b32 %7, %205; mov.b32 %8, %206; mov.b32 %9, %207; mov.b32 %10, %208; mov.b32 %11, %209; bra.uni KE;\n"
                 "K11: st.shared.v2.b32 [%211+0], {%192, %193}; st.shared.v2.b32 [%211+8], {%194, %195}; st.shared.v2.b32 [%211+512], {%196, %197}; st.shared.v2.b32 [%211+520], {%198, %199}; st.shared.v2.b32 [%211+1024], {%200, %201}; st.shared.v2.b32 [%211+1032], {%202, %203}; st.shared.v2.b32 [%211+1536], {%204, %205}; st.shared.v2.b32 [%211+1544], {%206, %207}; st.shared.v2.b32 [%211+2048], {%208, %209}; bra.uni KE;\n"
                 "K12: st.shared.v2.b32 [%211+2056], {%192, %193}; st.shared.v2.b32 [%211+2560], {%194, %195}; st.shared.v2.b32 [%211+2568], {%196, %197}; st.shared.v2.b32 [%211+24576], {%198, %199}; st.shared.v2.b32 [%211+24584], {%200, %201}; st.shared.v2.b32 [%211+25088], {%202, %203}; st.shared.v2.b32 [%211+25096], {%204, %205}; st.shared.v2.b32 [%211+25600], {%206, %207}; st.shared.v2.b32 [%211+25608], {%208, %209}; bra.uni KE;\n"
                 "K13: st.shared.v2.b32 [%211+26112], {%192, %193}; st.shared.v2.b32 [%211+26120], {%194, %195}; st.shared.v2.b32 [%211+26624], {%196, %197}; st.shared.v2.b32 [%211+26632], {%198, %199}; st.shared.v2.b32 [%211+27136], {%200, %201}; st.shared.v2.b32 [%211+27144], {%202, %203}; st.shared.v2.b32 [%211+49152], {%204, %205}; st.shared.v2.b32 [%211+49160], {%206, %207}; st.shared.v2.b32 [%211+49664], {%208, %209}; bra.uni KE;\n"
                 "K14: st.shared.v2.b32 [%211+49672], {%192, %193}; st.shared.v2.b32 [%211+50176], {%194, %195}; st.shared.v2.b32 [%211+50184], {%196, %197}; st.shared.v2.b32 [%211+50688], {%198, %199}; st.shared.v2.b32 [%211+50696], {%200, %201}; st.shared.v2.b32 [%211+51200], {%202, %203}; st.shared.v2.b32 [%211+51208], {%204, %205}; st.shared.v2.b32 [%211+51712], {%206, %207}; st.shared.v2.b32 [%211+51720], {%208, %209}; bra.uni KE;\n"
                 "K15: st.shared.v2.b32 [%211+73728], {%192, %193}; st.shared.v2.b32 [%211+73736], {%194, %195}; st.shared.v2.b32 [%211+74240], {%196, %197}; st.shared.v2.b32 [%211+74248], {%198, %199}; st.shared.v2.b32 [%211+74752], {%200, %201}; st.shared.v2.b32 [%211+74760], {%202, %203}; st.shared.v2.b32 [%211+75264], {%204, %205}; st.shared.v2.b32 [%211+75272], {%206, %207}; st.shared.v2.b32 [%211+75776], {%208, %209}; \nKE:\n}"
                 : KR6(0), KR6(1), KR6(2), KR6(3), KR6(4), KR6(5), KR6(6), KR6(7)
                 : "r"(c[0]), "r"(c[1]), "r"(c[2]), "r"(c[3]), "r"(c[4]), "r"(c[5]), "r"(c[6]), "r"(c[7]), "r"(c[8]), "r"(c[9]), "r"(c[10]), "r"(c[11]), "r"(c[12]), "r"(c[13]), "r"(c[14]), "r"(c[15]), "r"(c[16]), "r"(c[17]), "r"(e), "r"(a) : "memory");
}
__device__ __forceinline__ uint32_t smem_base() { extern __shared__ __align__(1024) unsigned char smem[]; return (uint32_t)__cvta_generic_to_shared(smem); }
__device__ __forceinline__ void k_rare(uint4 v0, uint4 v1, uint4 v2, uint4 v3, uint4 v4, uint4 v5, uint32_t odd, int e, int warp, int lane) {
    const uint32_t sb = smem_base(), g = lane >> 2, t = lane & 3, st = sb + SM_BAR + warp * 96 + 80;
    uint32_t lt; asm volatile("mov.u32 %0, %lanemask_lt;" : "=r"(lt));
    const uint4 v[6] = {v0, v1, v2, v3, v4, v5};
    odd <<= 6;
#pragma unroll
    for (int i = 0; i < 6; i++) if (v[i].x | v[i].y | v[i].z | v[i].w) odd |= 1u << i;
    odd = __reduce_or_sync(~0u, odd);
    uint32_t n = odd >= 64 ? NEXC + 1 : __shfl_sync(~0u, lds32(st), 0);
#pragma unroll 1
    for (; odd && n <= NEXC; odd &= odd - 1) {
        const int i = __ffs(odd) - 1;
#pragma unroll
        for (int k = 1; k < 6; k++) if (i == k) v0 = v[k];
#pragma unroll 1
        for (int k = 0; k < 4; k++, v0.x = v0.y, v0.y = v0.z, v0.z = v0.w) {
            const uint32_t who = __ballot_sync(~0u, v0.x), at = n + __popc(who & lt);
            sts64(v0.x && at < NEXC ? sb + SM_EXC + warp * 128 + at * 8 : st + 8, v0.x, (e * 32 + g * 4) << 16 | (((k & 1) * 4 + t) * 48 + i * 8 + (k >> 1) * 4));
            n += __popc(who);
        }
    }
    const uint32_t bad = lds32(st + 4);
    __syncwarp();
    if (n <= NEXC) sts32(st, n);
    else {
        sts32(st + 4, bad | 1u << e);
        asm volatile("st.shared.u8 [%0], %1;" :: "r"(sb + SM_SC + warp * 128 + g * 16 + (e & 3) * 4 + (e >> 2)), "r"(0) : "memory");
    }
    __syncwarp();
}
template <int K> __device__ __forceinline__ uint32_t& word(uint4& v) { if constexpr (K == 0) return v.x; else if constexpr (K == 1) return v.y; else if constexpr (K == 2) return v.z; else return v.w; }
__device__ __forceinline__ void add_if(bool p, float& d, float a, float b) {
    asm volatile("{\n.reg .pred p;\nsetp.ne.u32 p, %3, 0;\n@p add.f32 %0, %1, %2;\n}" : "+f"(d) : "f"(a), "f"(b), "r"((uint32_t)p));
}
__device__ __forceinline__ float warp_max(float v) {
#pragma unroll
    for (int o = 16; o; o >>= 1) v = fmaxf(v, shx(v, o));
    return v;
}
__device__ __forceinline__ float warp_sum(float v) {
#pragma unroll
    for (int o = 16; o; o >>= 1) v += shx(v, o);
    return v;
}
template <int PITCH> __device__ __forceinline__ void ll_look(const u64* buf, u64 (&w)[4]) {
#pragma unroll
    for (int i = 0; i < 4; i++) w[i] = ld_rlx(buf + i * PITCH);
}
template <int PITCH> __device__ __forceinline__ float ll_gather(const u64* buf, uint32_t tag, u64 (&w)[4]) {
    auto miss = [&]() {
        uint32_t a, b;
        asm("lop3.b32 %0, %1, %2, %3, 0x7e;" : "=r"(a) : "r"(ll_tag(w[0])), "r"(ll_tag(w[1])), "r"(tag));
        asm("lop3.b32 %0, %1, %2, %3, 0x7e;" : "=r"(b) : "r"(ll_tag(w[2])), "r"(ll_tag(w[3])), "r"(tag));
        return __any_sync(~0u, a | b);
    };
    int it = 0;
    goto check;
again:
    ll_look<PITCH>(buf, w);
check:
    if (miss() & (++it < SPIN)) goto again;
    return (ll_val(w[0]) + ll_val(w[1])) + (ll_val(w[2]) + ll_val(w[3]));
}
__device__ __forceinline__ float sum8(uint32_t a, int pitch) {
    float s[8];
#pragma unroll
    for (int w = 0; w < 8; w++) s[w] = ldsf(a + w * pitch);
    return ((s[0] + s[1]) + (s[2] + s[3])) + ((s[4] + s[5]) + (s[6] + s[7]));
}
__device__ __forceinline__ float sum5(float a, float b, float c, float d, float e) { return ((a + b) + (c + d)) + e; }
__device__ __forceinline__ float ln_part(uint2 xp, int lane) {
    const float x0 = bf_lo(xp.x), x1 = bf_hi(xp.x), x2 = bf_lo(xp.y), x3 = bf_hi(xp.y);
    const float s1 = (x0 + x1) + (x2 + x3), s2 = (x0 * x0 + x1 * x1) + (x2 * x2 + x3 * x3);
    return ((lane & 16) ? s2 : s1) + shx((lane & 16) ? s1 : s2, 16);
}
__device__ __forceinline__ float ln_rstd(float mean, float msq) { return rsq(fmaxf(msq - mean * mean, 0.f) + 1e-5f); }
__device__ __forceinline__ float score(const uint4 (&v)[6], const uint4 (&qf)[3]) {
    float d[2][4];
#pragma unroll
    for (int j = 0; j < 2; j++) d[j][0] = d[j][1] = d[j][2] = d[j][3] = 0.f;
#pragma unroll
    for (int i = 0; i < 3; i++) { mma(d[0], v[2 * i], qf[i].x, qf[i].y); mma(d[1], v[2 * i + 1], qf[i].z, qf[i].w); }
    return (d[0][0] + d[0][3]) + (d[1][0] + d[1][3]);
}
__device__ __forceinline__ float k_side(uint32_t sb, uint2 x) {
    const uint32_t qq = lds32(sb + SM_VEC + (x.y & 0xffff));
    return (bf_lo(x.x) * bf_lo(qq) + bf_hi(x.x) * bf_hi(qq)) * 0x1p-64f;
}
__device__ __forceinline__ void k_fix(const __nv_bfloat16* k, uint32_t bad, int warp, int lane) {
    const uint32_t sb = smem_base(), g = lane >> 2, sa = sb + SM_PART + warp * 768 + 256;
    const uint2 x = lds64(sb + SM_EXC + warp * 128 + (lane & 15) * 8);
    if ((int)x.y >= 0x40000000 && lane < 16) asm volatile("red.shared.add.f32 [%0], %1;" :: "r"(sa + ((x.y >> 16) & 511)), "f"(k_side(sb, x)) : "memory");
    __syncwarp();
#pragma unroll 1
    for (bad &= 0xffff; bad; bad &= bad - 1) {
        const int e = __ffs(bad) - 1;
        const __nv_bfloat16* kp = k + (e * 256 + (g >> 1) + 4 * (g & 1)) * DH + (lane & 3) * 8;
        uint4 v[6], qf[3];
#pragma unroll
        for (int i = 0; i < 6; i++) v[i] = *reinterpret_cast<const uint4*>(kp + i * 32);
#pragma unroll
        for (int i = 0; i < 3; i++) qf[i] = lds128(sb + SM_VEC + (lane & 7) * 48 + i * 16);
        stsf(sa + e * 32 + g * 4, score(v, qf) * 0x1p-64f);
    }
    __syncwarp();
}
constexpr float CS = 0.07216878364870322f * 1.4426950408889634f;
__device__ __forceinline__ void head_weight(const u64* a, u64 pm, u64 pl, int layer, int lane) {
    const uint32_t sb = smem_base(), tag = lds32(sb + SM_EPOCH) * 4 + 2 + 2 * layer;
#pragma unroll 1
    for (int it = 0; it < SPIN; it++) {
        if (__all_sync(~0u, ll_tag(pm) == tag && ll_tag(pl) == tag)) break;
        ld_rlx2(a, pm, pl);
    }
    const float f = ex2((ll_val(pm) - warp_max(ll_val(pm))) * CS);
    const float w = f * rcp(warp_sum(f * ll_val(pl)));
    if (lane < 8) stsf(sb + SM_FAC + lane * 4, w);
}
constexpr uint32_t ONES = 0x3f803f80u;

__global__ void __launch_bounds__(NTHR, 1) fused_kernel(const __grid_constant__ Params P) {
    const uint32_t sb = smem_base();
    const int bx = blockIdx.x;
    if (__all_sync(~0u, threadIdx.x >= NTHR - 32) && elect()) {
        asm volatile("mbarrier.init.shared::cta.b64 [%0], 1;" :: "r"(sb + SM_CBAR + CB_WQ * 8));
        asm volatile("mbarrier.init.shared::cta.b64 [%0], 1;" :: "r"(sb + SM_CBAR + 80));
        asm volatile("fence.mbarrier_init.release.cluster;" ::: "memory");
        mbar_expect(sb + SM_CBAR + CB_WQ * 8, 5 * HALF);
        mbar_expect(sb + SM_CBAR + 80, HALF);
        tma3(sb, &P.tm[TM_KH], 0, (bx >> 2) * SK + (SK - WIN) + (bx & 3) * 64, sb + SM_CBAR + 80, POL_FIRST);
#pragma unroll 1
        for (int i = 0; i < 5; i++) tma3(sb + SM_WQR + (i == 4 ? 0 : i + 1) * HALF, &P.tm[TM_WQ], (bx >> 2) * 3, (bx & 3) * 160 + i * 32, sb + SM_CBAR + CB_WQ * 8, POL_FIRST);
    }
    __syncwarp();
    int id = bx * NTHR + threadIdx.x, tid, lane, g, t, key, warp, cta, mlp, rowc, roww, j40;
    uint32_t maskA, maskB, barw, subw, prow;
    auto fresh = [&]() {
        const int cw = __shfl_sync(~0u, id >> 5, 0);
        id = pin(id); tid = id & 255; lane = id & 31; g = lane >> 2; t = lane & 3; key = (g >> 1) + 4 * (g & 1);
        const uint32_t m = (g & 1) ? 0xffff0000u : 0x0000ffffu;
        maskA = (g & 2) ? 0u : m; maskB = (g & 2) ? m : 0u;
        warp = cw & 7; cta = cw >> 3;
        mlp = (cta & 3) == 3 ? 96 : (cta >> 2) * 3 + (cta & 3);
        rowc = (cta >> 2) * SK + (SK - WIN) + (cta & 3) * 64; roww = rowc + warp * 8;
        j40 = (cta & 3) * 40;
        barw = sb + SM_BAR + warp * 96; subw = sb + warp * SUB; prow = sb + SM_PART + warp * 768;
    };
    fresh();
    auto fresh_lane = [&]() { id = pin(id); tid = id & 255; lane = id & 31; g = lane >> 2; t = lane & 3; };
    auto pinf = [&](float v) { return __uint_as_float(pin(__float_as_uint(v) | (id >> 16))); };

    TSTAMP(0);
    if (tid == 64) { uint32_t now; asm volatile("mov.u32 %0, %globaltimer_lo;" : "=r"(now)); sts32(sb + SM_T0, now); }

    const CUtensorMap* tmk = reinterpret_cast<const CUtensorMap*>(__shfl_sync(~0u, (u64)&P.tm[0] + (lane >> 5), 0));
    auto c4 = [&]() { return 32 * min(warp, 4) + 16 * (t >> 1) + 2 * g + (t & 1); };
    auto xcol = [&](int i, int tt) { return (i < 2 ? 64 * i + 8 * warp : 128 + 8 * (warp >> 1)) + 2 * tt; };
    uint2 xp;
    uint32_t px[3], small;
    if (elect()) {
        if (warp != 2) asm volatile("mbarrier.init.shared::cta.b64 [%0], 1;" :: "r"(sb + SM_CBAR + 64 + warp * 8));
#pragma unroll
        for (int i = 0; i < 9; i++) asm volatile("mbarrier.init.shared::cta.b64 [%0], 1;" :: "r"(barw + i * 8));
        asm volatile("mbarrier.init.shared::cta.b64 [%0], 1;" :: "r"(sb + SM_CBAR + warp * 8));
        asm volatile("mbarrier.init.shared::cta.b64 [%0], 1;" :: "r"(sb + SM_CBAR + 128 + warp * 8));
        if (warp < 3) asm volatile("mbarrier.init.shared::cta.b64 [%0], %1;" :: "r"(sb + SM_CBAR + 192 + warp * 8), "r"(warp == 2 ? 8 : 1));
        sts64(barw + 80, 0, 0);
        asm volatile("fence.mbarrier_init.release.cluster;" ::: "memory");
        asm volatile("prefetch.tensormap [%0];" :: "l"(tmk + warp) : "memory");
    }
    __syncwarp();
    asm volatile("ld.global.nc.v2.u32 {%0,%1}, [%2];" : "=r"(xp.x), "=r"(xp.y) : "l"(P.x + 4 * c4()) : "memory");
#pragma unroll
    for (int i = 0; i < 3; i++) asm volatile("ld.global.nc.u32 %0, [%1];" : "=r"(px[i]) : "l"(P.x + 4 * j40 + xcol(i, t)) : "memory");
    asm volatile("ld.relaxed.gpu.global.u32 %0, [%1];" : "=r"(small) : "l"(lane < 16 ? (const void*)(P.b1 + min(mlp, 95) * 16 + (lane & 14)) : (const void*)&P.g->epoch) : "memory");
    if (tid < NCB + 8) sts64(sb + SM_CNT + tid * 8, 0, 0);
    unsigned char* accg = reinterpret_cast<unsigned char*>(__shfl_sync(~0u, (u64)P.g->acc + (lane >> 5), 0));
    auto release = [&](const uint4& tw) {
        uint32_t old;
        __syncwarp();
        asm volatile("atom.relaxed.cta.shared.add.u32 %0, [%1], 1;" : "=r"(old) : "r"(sb + SM_CNT + (tw.x & 0xf8)) : "memory");
        return old;
    };
    auto refill = [&](const uint4& tw, uint32_t old) {
        if (__any_sync(~0u, (old & 127) == 127 && (tw.y & 2))) {
            wait_until(lds32(sb + SM_T0) + tw.z);
            if (elect()) issue_half(tw.y, sb, rowc, cta, tmk);
            __syncwarp();
        }
    };
    __syncthreads();

    uint32_t offV0, offV2;
    auto calc_offsets = [&]() {
        offV0 = subw + (6 * t) * 128 + ((g ^ ((6 * t) & 7)) << 4);
        offV2 = subw + (6 * t + 2) * 128 + ((g ^ ((6 * t + 2) & 7)) << 4);
    };
    calc_offsets();

    auto load_v = [&](uint4 (&v)[6], uint32_t so) {
        v[0] = lds128(offV0 + so); v[1] = lds128((offV0 ^ 16) + so + 128); v[2] = lds128(offV2 + so);
        v[3] = lds128((offV2 ^ 16) + so + 128); v[4] = lds128((offV0 ^ 64) + so + 512); v[5] = lds128((offV0 ^ 80) + so + 640);
    };
    auto issue_v = [&](auto I, int dw, uint32_t done = ~0u) {
        constexpr Step c = SCH.st[I.value];
        const uint32_t bar = barw + dw * 96 + c.slot * 8;
        mbar_expect(bar, done & SUB);
        tma_v(subw + dw * SUB + c.slot * TILE, tmk, roww * 3 + dw * 24 + c.unit * 768, bar);
    };
    auto reads_done = [&]() { __syncwarp(); return lds32(sb + SM_M1); };
    auto refill2 = [&](auto I, uint32_t done = ~0u) { __syncwarp(); if (elect()) issue_v(I, 0, done); };
    uint4 wq0[6], wqh[3], wq1[6];
    auto load_wq1 = [&](int i) { wq1[i] = lds128((i == 2 ? offV2 : i == 3 ? (offV2 ^ 16) + 128 : (offV0 ^ (i * 16)) + i * 128) + SM_WQ + TILE); };
    auto load_wq = [&]() {
        load_v(wq0, SM_WQ);
        const uint32_t so = SM_WQR - ((warp + 1) >> 1) * SUB;
        wqh[0] = lds128(((warp & 1) ? (offV2 ^ 16) + 128 : offV0) + so);
        wqh[1] = lds128(((warp & 1) ? (offV0 ^ 64) + 512 : (offV0 ^ 16) + 128) + so);
        wqh[2] = lds128(((warp & 1) ? (offV0 ^ 80) + 640 : offV2) + so);
    };
    uint4 kr[8][6];
    const unsigned char* rap;
    u64 rw[2];
    auto look_rw = [&]() { rw[0] = ld_rlx(rap); rw[1] = ld_rlx(rap + 20 * acc_pitch(1)); };
    auto q_proj = [&](auto L, uint32_t (&p)[3], uint32_t pst) {
        if (L.value == 0 && g >= 4) p[0] = p[1] = p[2] = ONES;
        float a[3][4], b[3][4];
        const uint32_t dH = __byte_perm(p[2], 0, (warp & 1) ? 0x3232 : 0x1010);
        const uint32_t dA = __byte_perm(p[0], 0, 0x1010), dB = __byte_perm(p[0], 0, 0x3232), dC = __byte_perm(p[1], 0, 0x1010), dD = __byte_perm(p[1], 0, 0x3232);
#pragma unroll
        for (int i = 0; i < 3; i++) load_wq1(i);
#pragma unroll
        for (int j = 0; j < 3; j++) { a[j][0] = a[j][1] = a[j][2] = a[j][3] = 0.f; mma(a[j], wq0[j], dA & maskA, dA & maskB); }
#pragma unroll
        for (int j = 0; j < 3; j++) { b[j][0] = b[j][1] = b[j][2] = b[j][3] = 0.f; mma(b[j], wq0[j + 3], dB & maskA, dB & maskB); }
#pragma unroll
        for (int j = 0; j < 3; j++) mma(a[j], wqh[j], dH & maskA, dH & maskB);
#pragma unroll
        for (int i = 3; i < 6; i++) load_wq1(i);
#pragma unroll
        for (int j = 0; j < 3; j++) mma(b[j], wq1[j], dC & maskA, dC & maskB);
#pragma unroll
        for (int j = 0; j < 3; j++) mma(a[j], wq1[j + 3], dD & maskA, dD & maskB);
#pragma unroll
        for (int j = 0; j < 3; j++) {
            if (L.value) {
#pragma unroll
                for (int k = 0; k < 2; k++) { a[j][k] += b[j][k]; add_if(t & 2, a[j][k], a[j][k + 2], b[j][k + 2]); }
                sts64f(pst + j * 256, a[j][0], a[j][1]);
            } else sts128f(pst + j * 256, a[j][0] + b[j][0], a[j][1] + b[j][1], a[j][2] + b[j][2], a[j][3] + b[j][3]);
        }
        CSTAMP(23, __float_as_uint(a[2][1]));
        uint32_t tag;
        if (L.value) tag = lds32(sb + SM_EPOCH) * 4 + 3;
        u64* pub = L.value ? &P.g->ll[cta][tid] : &P.g->l0[cta][tid];
        if (L.value == 0) asm volatile("fence.proxy.async.shared::cta;" ::: "memory");
        TSTAMPL(21);
        __syncthreads();
        if (!L.value) tag = lds32(sb + SM_EPOCH) * 4 + 1;
#pragma unroll 1
        for (int k = 0; k < 2 - L.value; k++) st_rlx_if(tid < 192, pub + k * 192, ll_pack(sum8(sb + (k ? SM_CSP : SM_PART) + tid * 4, 768), tag));
        TSTAMPL(23);
            CSTAMP(24, tag);
    };
    auto ln_stats = [&]() {
        float ss = ln_part(xp, lane);
        ss += shx(ss, 8); ss += shx(ss, 4); ss += shx(ss, 2); ss += shx(ss, 1);
        stsf(sb + SM_STAT + min(warp, 5) * 8 + (lane >> 4) * 4, ss);
    };
    auto ln_final = [&](float& mean, float& rstd) {
        float2 v[5];
#pragma unroll
        for (int w = 0; w < 5; w++) v[w] = lds64f(sb + SM_STAT + w * 8);
        mean = sum5(v[0].x, v[1].x, v[2].x, v[3].x, v[4].x) * (1.f / D_MODEL);
        const float msq = sum5(v[0].y, v[1].y, v[2].y, v[3].y, v[4].y) * (1.f / D_MODEL);
        rstd = ln_rstd(mean, msq);
        stsf(sb + SM_FXS, msq);
    };
    auto q_addr = [&](int d) { return sb + SM_VEC + (((d >> 1) & 1) * 4 + ((d >> 3) & 3)) * 48 + (d >> 5) * 8 + ((d >> 2) & 1) * 4 + (d & 1) * 2; };
    {
#pragma unroll
        for (int u = 0; u < 8; u++)
#pragma unroll
            for (int i = 0; i < 6; i++) kr[u][i] = lds128(sb + SM_CS + (u * 6 + i) * 16);
        if (warp >= 1 && warp < NI1) {
            wait_until(lds32(sb + SM_T0) + PACES + warp * PACE / 2);
            if (elect()) {
                mbar_expect(sb + SM_CBAR + 80 + warp * 8, HALF);
                tma3(sb + warp * HALF, tmk + TM_KH, 0, rowc + (warp >> 1) * 256 + (warp & 1) * 32, sb + SM_CBAR + 80 + warp * 8, POL_FIRST);
            }
            __syncwarp();
        }
        ln_stats();
        if (tid == 16) { sts32(sb + SM_EPOCH, small); sts32(sb + SM_M1, ~0u); }
        else if (tid < 16) sts32(sb + SM_B1 + tid * 4, (tid & 1) ? small & 0xffff0000u : small << 16);
        mbar_wait(sb + SM_CBAR + CB_WQ * 8, 0);
        load_wq();
        q_proj(IC<0>{}, px, sb + (t < 2 ? SM_PART : SM_CSP) + warp * 768 + (8 * g + 4 * (t & 1)) * 4);
    }
    {
        uint32_t offQ, offL;
        auto calc_ql = [&]() {
            offQ = pin(sb + SM_VEC + (lane & 7) * 48);
            offL = pin(subw + lane * 16);
        };

        auto issue_w = [&](auto L, int which) {
            const uint32_t bar = sb + SM_CBAR + (CB_W1 + which) * 8;
            if (mlp == 96) asm volatile("mbarrier.arrive.shared::cta.b64 _, [%0];" :: "r"(bar) : "memory");
            else {
                mbar_expect(bar, 20480);
                if (which) {
                    tma3(sb + (L.value ? 3 * TILE : SM_W2), tmk + TM_W2, 0, mlp * 16, bar, POL_FIRST);
                    if (!L.value) tma3_pf(tmk + TM_W2, 0, mlp * 16, POL_NORMAL);
                }
                else asm volatile("cp.async.bulk.tensor.3d.shared::cluster.global.mbarrier::complete_tx::bytes.L2::cache_hint [%0], [%1, {%2, %3, %3}], [%4], %5;"
                                  :: "r"(sb + (L.value ? 2 * TILE : SM_W1)), "l"(tmk + TM_W1), "r"(mlp * 16), "r"(0), "r"(bar), "l"((u64)POL_FIRST << 32) : "memory");
            }
        };
        float acc[3][4];
        auto load_q = [&](uint4 (&qf)[3]) {
#pragma unroll
            for (int i = 0; i < 3; i++) qf[i] = lds128(offQ + i * 16);
        };
        auto softmax = [&](float S0, float S1, float S2, float S3) {
            int mi = __float_as_int(fmaxf(fmaxf(S0, S1), fmaxf(S2, S3)));
            mi = __reduce_max_sync(~0u, mi ^ ((mi >> 31) & 0x7fffffff));
            const float mrun = __int_as_float(mi ^ ((mi >> 31) & 0x7fffffff));
            const float p0 = ex2((S0 - mrun) * CS), p1 = ex2((S1 - mrun) * CS), p2 = ex2((S2 - mrun) * CS), p3 = ex2((S3 - mrun) * CS);
            const uint32_t pa = pack_bf(p0, p1), pb = pack_bf(p2, p3), pw = prow + 256 + (key >> 1) * 80 + t * 4 + (key & 1) * 2;
            sts16(pw, pa); sts16(pw + 16, pa >> 16); sts16(pw + 32, pb); sts16(pw + 48, pb >> 16);
            __syncwarp();
#pragma unroll
            for (int j = 0; j < 3; j++) acc[j][0] = acc[j][1] = acc[j][2] = acc[j][3] = 0.f;
            return make_float2(mrun, (p0 + p1) + (p2 + p3));
        };
        auto pv = [&](const uint4 (&v)[6], uint32_t pp) {
            const uint32_t dA = __byte_perm(pp, 0, 0x1010), dB = __byte_perm(pp, 0, 0x3232);
            mma(acc[0], v[0], dA & maskA, dA & maskB); mma(acc[1], v[1], dA & maskA, dA & maskB); mma(acc[2], v[2], dA & maskA, dA & maskB);
            mma(acc[0], v[3], dB & maskA, dB & maskB); mma(acc[1], v[4], dB & maskA, dB & maskB); mma(acc[2], v[5], dB & maskA, dB & maskB);
        };
        auto sa = [&]() { return prow + 256 + t * 32 + g * 4; };
        auto pass1 = [&]() {
            fresh();
            calc_ql();
            __syncthreads();
            sts64(prow + lane * 8, xp.x, xp.y);
            int e = 0;
            const uint4* tab = P.tile + (warp >> 2);
            uint4 tw = tab[0];
            uint32_t ka[3];
#pragma unroll
            for (int j = 0; j < 3; j++) ka[j] = pin(subw + key * 384 + j * 128 + ((t ^ ((3 * key + j) & 7)) << 4));
            auto load_k = [&](uint4 (&v)[6], uint32_t so) {
#pragma unroll
                for (int i = 0; i < 6; i++) v[i] = lds128(((i & 1) ? ka[i >> 1] ^ 64 : ka[i >> 1]) + so);
            };
            const uint32_t s0 = pin(prow + 256 + g * 4), sca = pin(sb + SM_SC + warp * 128 + g * 16);
#pragma unroll 1
            do {
                const uint4 tn = tab[2 * e + 2];
                uint4 v[6], qf[3];
                if (tw.x & (G_A | G_B | G_C)) {
                    if ((tw.x & G_A) && warp == 7 && elect()) {
                        mbar_expect(sb + SM_CBAR + CB_SNAP * 8, HALF);
                        asm volatile("cp.async.bulk.shared::cluster.global.mbarrier::complete_tx::bytes [%0], [%1], 12288, [%2];"
                                     :: "r"(sb + SM_SNAP), "l"(&P.g->l0[cta & ~3][0]), "r"(sb + SM_CBAR + CB_SNAP * 8) : "memory");
                    }
                    if (tw.x & G_B) {
                        if (warp < 6) {
                            mbar_wait(sb + SM_CBAR + CB_SNAP * 8, 0);
                            float qc[2] = {0.f, 0.f}, mean, rstd;
#pragma unroll 1
                            for (int k = 0; k < 2; k++) {
                                u64 qw[4];
#pragma unroll
                                for (int i = 0; i < 4; i++) { const uint2 x = lds64(sb + SM_SNAP + i * 3072 + k * 1536 + tid * 8); qw[i] = x.x | (u64)x.y << 32; }
                                qc[0] = qc[1];
                                qc[1] = ll_gather<384>(&P.g->l0[cta & ~3][k * 192 + tid], lds32(sb + SM_EPOCH) * 4 + 1, qw);
                            }
                            ln_final(mean, rstd);
                            stsf(sb + SM_CS + tid * 4, qc[1]);
                            const float q = (qc[0] - mean * qc[1]) * rstd;
                            sts16(q_addr(tid), pack_bf(q, q));
                        }
                        __syncthreads();
                        if (warp == 7 && elect()) issue_half(UC<load_word(12)>::value, sb, rowc, cta, tmk);
                        TSTAMP(2);
                    }
                    if (tw.x & G_C) {
                        load_k(v, (e - LATEAT) * TILE);
                        load_q(qf);
                        stsf(s0 + (e - LATEAT) * 32, score(v, qf));
                    }
                }
                load_q(qf);
                mbar_wait(sb + SM_CBAR + (tw.x & 0xf8), tw.x >> 31);
                TRACE(e);
                load_k(v, tw.x & 0x3f000);
                const uint32_t old = release(tw);
                const float s = score(v, qf);
                uint32_t m;
                {
                    uint32_t a[6];
#pragma unroll
                    for (int i = 0; i < 6; i++) a[i] = bf2_amax(bf2_amax(v[i].x, v[i].y), bf2_amax(v[i].z, v[i].w));
                    m = bf2_amax(bf2_amax(bf2_amax(a[0], a[1]), bf2_amax(a[2], a[3])), bf2_amax(a[4], a[5]));
                }
                m = bf2_amax(m, m >> 16) & 0x7f80;
                m = max(m, __shfl_xor_sync(~0u, m, 1));
                stsf(s0 + e * 32, s);
                m = max(m, __shfl_xor_sync(~0u, m, 2));
                refill(tw, old);
                const uint32_t b = min(max(m, 15u << 7) - (15u << 7), 126u << 7);
                const uint32_t dn = ((127u << 7) - b) * 0x10001u, up = ((127u << 7 | 0x8000u) + b) * 0x10001u;
                uint32_t c[18], any = m > (141u << 7);
#pragma unroll
                for (int i = 0; i < 6; i++) {
                    const uint32_t y0 = bf2_mul(v[i].x, dn), y1 = bf2_mul(v[i].y, dn), y2 = bf2_mul(v[i].z, dn), y3 = bf2_mul(v[i].w, dn);
                    v[i] = make_uint4(bf2_fma(y0, up, v[i].x), bf2_fma(y1, up, v[i].y), bf2_fma(y2, up, v[i].z), bf2_fma(y3, up, v[i].w));
                    any |= v[i].x | v[i].y;
                    any |= v[i].z | v[i].w;
                    const uint32_t hb = __byte_perm(y2, y3, 0x7531);
                    c[3 * i] = __byte_perm(y0, y1, 0x6420); c[3 * i + 1] = __byte_perm(y2, y3, 0x6420);
                    c[3 * i + 2] = __byte_perm(y0, y1, 0x7531) | __funnelshift_r(hb, hb, 4);
                }
                asm volatile("st.shared.u8 [%0], %1;" :: "r"(sca + (e & 3) * 4 + (e >> 2)), "r"((b >> 7) + 63) : "memory");
                const bool rare = __any_sync(~0u, any);
                k_keep(kr, c, e, offL);
                if (rare) k_rare(v[0], v[1], v[2], v[3], v[4], v[5], m > (141u << 7), e, warp, lane);
                tw = tn;
            } while (++e < 16);
            asm volatile("fence.proxy.async.shared::cta;" ::: "memory");
            __syncwarp();
            TSTAMP(10);
            fresh(); calc_offsets();
            offV0 = pin(offV0); offV2 = pin(offV2);
            {
                const uint2 st = lds64(barw + 80);
                const uint32_t xa = sb + SM_EXC + warp * 128 + (lane & 15) * 8 + 4;
                uint32_t pos = lds32(xa), lt;
                asm volatile("mov.u32 %0, %lanemask_lt;" : "=r"(lt));
                if (lane >= st.x) pos = 0x80000000u;
                const bool dup = (__match_any_sync(~0u, pos >> 16) & lt) && lane < st.x;
                if (lane < 16) sts32(xa, dup ? pos | 0x40000000u : pos);
                if (__any_sync(~0u, dup)) sts32(barw + 84, st.y | 0x10000u);
                const float2 ml = softmax(ldsf(sa()), ldsf(sa() + 128), ldsf(sa() + 256), ldsf(sa() + 384));
                sts64f(sb + SM_ML + warp * 8, ml.x, warp_sum(ml.y));
            }
            u64 pm = 0, pl = 0;
#pragma unroll 1
            do {
                const uint4 tn = tab[2 * e + 2];
                if (tw.x & (G_A | G_B | G_C)) {
                    if (tw.x & G_A) {
                        if (lane < 24) st_rlx(&P.g->ll[cta][warp * 24 + lane], 0ull);
                        else if (lane < 28) st_rlx(&P.g->ll[cta][168 + warp * 4 + lane], ll_pack(ldsf(sb + SM_ML + warp * 8 + (lane & 1) * 4), lds32(sb + SM_EPOCH) * 4 + 2));
                    }
                    if (warp == 0 && cta < 80 && elect()) {
                        if (tw.x & G_A) {
#pragma unroll 1
                            for (int k = 0; k < 8; k++) {
                                const int r = (cta & 1) * 2 + (k >> 2);
                                asm volatile("cp.async.bulk.global.shared::cta.bulk_group [%0], [%1], 64;"
                                             :: "l"(P.g->acc + r * ACC_BYTES + ((cta >> 1) * acc_pitch(r) & ~127) + (k & 3) * 64), "r"(sb + SM_ZERO) : "memory");
                            }
                            asm volatile("cp.async.bulk.commit_group;" ::: "memory");
                        }
                        if (tw.x & G_B) asm volatile("cp.async.bulk.wait_group 0;\nred.relaxed.gpu.global.add.u32 [%0], 1;" :: "l"(&P.g->zeroed) : "memory");
                    }
                    if (warp == 2) {
                        if (tw.x & G_B) ld_rlx2(&P.g->ll[cta ^ (lane >> 3)][192 + (lane & 7) * 4], pm, pl);
                        if (tw.x & G_C) head_weight(&P.g->ll[cta ^ (lane >> 3)][192 + (lane & 7) * 4], pm, pl, 0, lane);
                    }
                    __syncwarp();
                }
                const uint32_t pp = lds32(prow + 256 + t * 80 + ((tw.x >> 20) & 255));
                mbar_wait(sb + SM_CBAR + (tw.x & 0xf8), tw.x >> 31);
                TRACE(e);
                uint4 v[6];
                load_v(v, tw.x & 0x3f000);
                refill(tw, release(tw));
                pv(v, pp);
                tw = tn;
            } while (++e < 32);
        };
        uint32_t osa, ora, owa, orow, otag;
        u64* olb;
        float xc;
        auto o_setup = [&](auto L) {
            fresh();
            const int lz = lane, d = warp * 24 + min(lz, 23);
            osa = pin(prow + ((lz >> 2) * 8 + (lz & 1) * 4 + (lz & 2)) * 4);
            ora = pin(sb + SM_PART + d * 4);
            olb = pin(&P.g->ll[cta & ~3][d]);
            orow = pin((lz & 1) + 2 * (lz & 2) + 2 * (lz >> 4));
            owa = pin(sb + SM_RING + warp * 1536 + orow * 64 + ((((lz >> 2) & 3) ^ (orow >> 1)) << 4));
            otag = lds32(sb + SM_EPOCH) * 4 + 2 + 2 * L.value;
            uint32_t x; asm volatile("ld.shared.u16 %0, [%1];" : "=r"(x) : "r"(prow + ((cta & 1) * 16 + (lz >> 3) * 4 + (cta & 2) + ((lz >> 2) & 1)) * 8 + (lz & 3) * 2) : "memory");
            xc = bf_lo(x) * (1.f / 32);
        };
        auto wo_at = [&](auto A) {
            constexpr uint32_t x = WOP ^ A.value * 0x11111;
            if constexpr (A.value > 0 && ((x - 0x11111) & ~x & 0x88888) != 0) {
                if ((WOP >> (4 * warp) & 15) == A.value) {
                    mbar_wait(sb + SM_CBAR + CB_REL * 8, 0);
                    if (elect()) {
                        const uint32_t bar = sb + SM_CBAR + (CB_WO + warp) * 8;
                        mbar_expect(bar, HALF);
                        tma3(sb + SM_RING + (warp + (warp < 2 ? 3 : -2)) * HALF, tmk + TM_WO, (cta & 3) + 4 * warp, (cta >> 2) * DH, bar, POL_FIRST);
                    }
                    __syncwarp();
                }
            }
        };
        static_assert(ring_hs(64) == 3, "wo");
        auto pass2 = [&]() {
            constexpr IC<1> L{};
            refill2(IC<4>{});
            uint4 tb[8][3];
            auto load_tb = [&](auto I) {
#pragma unroll
                for (int i = 0; i < 3; i++) tb[I.value][i] = lds128(offL + (I.value >> 1) * TILE + ((I.value & 1) * 3 + i) * 512);
            };
            uint32_t m1, m1n, done;
            const u64* qb = &P.g->ll[cta & ~3][min(tid, 191)];
            {
                uint32_t x[2];
                fx2_wait<2>([&](int i) { return rap + i * 20 * acc_pitch(1); }, look_rw, rw, sb + SM_MSQ, ldsf(sb + SM_MSQ + 4), x);
                xp = make_uint2(x[0], x[1]);
                CSTAMP(25, xp.y);
            }
            ln_stats();
            u64 qw[4];
            offL = subw + lane * 16;
            static_for<0, NPRE>(load_tb);
            m1n = m1 = reads_done();
            ll_look<256>(qb, qw);
            const float cs = ldsf(sb + SM_CS + min(tid, 191) * 4);
            const uint32_t qtag = lds32(sb + SM_EPOCH) * 4 + 3, qa = pin(q_addr(min(tid, 191)));
            fresh_lane();
            offQ = sb + SM_VEC + (lane & 7) * 48; offL = subw + lane * 16;
            __syncthreads();
            auto vwait = [&](auto I) { mbar_wait(barw + IC<SCH.st[I.value].slot>::value * 8, IC<SCH.st[I.value].par>::value); };
            bool ok;
            {
                float mean, rstd;
                ln_final(mean, rstd);
                const float sq = shx(rstd * 0x1p64f, 0), q0 = shx(-mean * cs * sq, 0);
                CSTAMP(26, __float_as_uint(q0));
                refill2(IC<5>{}, m1);
                sts64(prow + lane * 8, xp.x, xp.y);
                sts128f(prow + 256 + lane * 16, 0.f, 0.f, 0.f, 0.f);
                const float q = ll_gather<256>(qb, qtag, qw) * sq + q0;
                sts16(qa, pack_bf(q, q));
                TSTAMPL(24);
                CSTAMP(27, __float_as_uint(q));
            }
            __syncthreads();
            uint4 qf[3];
            load_q(qf);
            CSTAMP(28, qf[0].x);
            float S[4], d[2][4];
            auto vload = [&](auto I) {
                constexpr int p = I.value;
                constexpr Step c = SCH.st[p];
                load_v(kr[p & 7], c.slot * TILE);
                if constexpr (c.next >= 0 && p >= NPARK) {
                    static_assert(c.next - 9 < c.mma0, "the slot's last tile has been multiplied");
                    refill2(IC<c.next>{});
                }
                if constexpr (p == 11) { __syncwarp(); if (elect()) asm volatile("mbarrier.arrive.shared::cta.b64 _, [%0];" :: "r"(sb + SM_CBAR + CB_REL * 8) : "memory"); }
            };
            static_for<0, 96>([&](auto F) {
                constexpr int f = F.value, i = f % 6, u = kunit(f / 6), w = 3 * f % 12;
                uint4 (&src)[3] = *reinterpret_cast<uint4 (*)[3]>(f < 32 ? &tb[f / 4 & 7][0] : &kr[(f / 8 + 4) & 7][(f / 4 & 1) * 3]);
                const uint4 a = k_unpack(word<w % 4>(src[w / 4]), word<(w + 1) % 4>(src[(w + 1) / 4]), word<(w + 2) % 4>(src[(w + 2) / 4]), m1);
                if constexpr (f % 8 == (f < 32 ? RF0 : RF1) + M1D) m1 = m1n;
                if constexpr (f % 4 == 3 && f / 4 + NPRE < 8) {
                    load_tb(IC<f / 4 + NPRE>{});
                    if constexpr (f % 8 == 7) done = reads_done();
                }
                if constexpr (f >= 8 && f < 32 && f % 8 == RF0) { refill2(IC<5 + f / 8>{}, done); m1n = lds32(sb + SM_M1); }
                if constexpr (f >= 40 && f % 8 == RF1) {
                    if constexpr (PARKS >> (f / 8 - 5) & 1) { refill2(IC<SCH.st[popc(PARKS & ((1 << (f / 8 - 5)) - 1))].next>{}, done); m1n = lds32(sb + SM_M1); }
                }
                if constexpr (i < 2) d[i][0] = d[i][1] = d[i][2] = d[i][3] = 0.f;
                mma(d[i & 1], a, (i & 1) ? qf[i / 2].z : qf[i / 2].x, (i & 1) ? qf[i / 2].w : qf[i / 2].y);
                if constexpr (i == 5) {
                    if constexpr (u == 11 || ((u & 3) == 0 && u != 8)) S[u >> 2] = (d[0][0] + d[0][3]) + (d[1][0] + d[1][3]);
                    else add_if(t == (u & 3), S[u >> 2], d[0][0] + d[0][3], d[1][0] + d[1][3]);
                    if constexpr (f < 64) S[u >> 2] = shx(S[u >> 2], 0);
                }
                if constexpr (f == 31) { fresh(); calc_offsets(); ok = mbar_test(barw + IC<SCH.st[0].slot>::value * 8, 0); }
                if constexpr (f == 48) {
                    const uint2 x = lds64(sb + SM_EXC + warp * 128 + (lane & 15) * 8);
                    const float c = k_side(sb, x);
                    if (x.y < 0x40000000u) stsf(prow + 256 + (x.y >> 16), c);
                }
                if constexpr (f >= 32 && f % 8 == 7) {
                    if constexpr (PARKS >> (f / 8 - 4) & 1) {
                        constexpr int p = popc(PARKS & ((1 << (f / 8 - 4)) - 1));
                        if (!ok) vwait(IC<p>{});
                        vload(IC<p>{});
                        done = reads_done();
                        ok = mbar_test(barw + IC<SCH.st[p + 1].slot>::value * 8, IC<SCH.st[p + 1].par>::value);
                    }
                }
            });
            if constexpr (PARKS & 0x80) refill2(IC<SCH.st[NPARK - 1].next>{}, done);
            uint32_t bad = lds32(barw + 84);
            const uint32_t sc = lds32(sb + SM_SC + tid * 4);
            __syncwarp();
            if (bad) k_fix(P.k + (size_t)roww * DH, bad, warp, lane);
            TSTAMP(30);
            CSTAMP(29, __float_as_uint(S[2]));
            const float2 ml = softmax(S[0] * __uint_as_float((sc & 255) << 23) + ldsf(sa()), S[1] * __uint_as_float((sc & 0xff00) << 15) + ldsf(sa() + 128),
                                      S[2] * __uint_as_float((sc & 0xff0000) << 7) + ldsf(sa() + 256), S[3] * __uint_as_float((sc >> 24) << 23) + ldsf(sa() + 384));
            uint4 pq[4];
#pragma unroll
            for (int j = 0; j < 4; j++) pq[j] = lds128(prow + 256 + t * 80 + j * 16);
            TSTAMP(1);
            CSTAMP(30, pq[3].w);
            if (!ok) vwait(IC<NPARK>{});
            float ac2[3][4];
#pragma unroll
            for (int j = 0; j < 3; j++) ac2[j][0] = ac2[j][1] = ac2[j][2] = ac2[j][3] = 0.f;
            const uint32_t sl = (g & 1) ? 0x1044 : 0x4410, sh = (g & 1) ? 0x3244 : 0x4432;
            const uint32_t sA0 = (g & 2) ? 0x4444 : sl, sA1 = (g & 2) ? sl : 0x4444, sB0 = (g & 2) ? 0x4444 : sh, sB1 = (g & 2) ? sh : 0x4444;
            u64 pm = 0, pl = 0;
            static_for<NPARK, 16>([&](auto I) {
                constexpr int p = I.value;
                static_assert(p - SCH.st[p].mma0 < 8, "buffer in use");
                vload(I);
                if constexpr (p < 15) ok = mbar_test(barw + IC<SCH.st[p + 1].slot>::value * 8, IC<SCH.st[p + 1].par>::value);
                static_for<SCH.st[p].mma0, SCH.st[p].mma0 + SCH.st[p].nmma>([&](auto J) {
                    constexpr int u = SCH.st[J.value].unit;
                    const uint32_t pp = word<u & 3>(pq[u >> 2]), a0 = __byte_perm(pp, 0, sA0), a1 = __byte_perm(pp, 0, sA1), b0 = __byte_perm(pp, 0, sB0), b1 = __byte_perm(pp, 0, sB1);
#pragma unroll
                    for (int j = 0; j < 3; j++) mma(acc[j], kr[J.value & 7][j], a0, a1);
#pragma unroll
                    for (int j = 0; j < 3; j++) mma(ac2[j], kr[J.value & 7][j + 3], b0, b1);
                });
                if constexpr (p == NPARK) {
                    const float l = warp_sum(ml.y);
                    st_rlx_if(lane < 4, &P.g->ll[cta][192 + warp * 4 + lane], ll_pack((lane & 1) ? l : ml.x, lds32(sb + SM_EPOCH) * 4 + 4));
                }
                if constexpr (p == HWAT) { if (warp == 6) ld_rlx2(&P.g->ll[cta ^ (lane >> 3)][192 + (lane & 7) * 4], pm, pl); }
                if constexpr (p == 13) o_setup(L);
                if constexpr (p == HWAT + 2) { if (warp == 6) head_weight(&P.g->ll[cta ^ (lane >> 3)][192 + (lane & 7) * 4], pm, pl, 1, lane); }
                wo_at(IC<p - 10>{});
                if constexpr (p < 15) { if (!ok) mbar_wait(barw + IC<SCH.st[p + 1].slot>::value * 8, IC<SCH.st[p + 1].par>::value); TRACE(33 + p); }
            });
#pragma unroll
            for (int j = 0; j < 3; j++)
#pragma unroll
                for (int k = 0; k < 2; k++) { acc[j][k] += ac2[j][k]; add_if(t & 2, acc[j][k], acc[j][k + 2], ac2[j][k + 2]); }
        };

        const unsigned char* ap;
        uint32_t hpa, hsa, hst, w2a, la;
        uint2 b2v;
        float b1v, cs1;
        auto mlp_global = [&](auto L) {
            const int cz = c4();
            ap = accg + 2 * L.value * ACC_BYTES + (cz >> 2) * acc_pitch(0) + (cz & 3) * 16;
            if (L.value) ap = pin(ap);
            rap = pin(accg + (2 * L.value + 1) * ACC_BYTES + (cz >> 3) * acc_pitch(2 * L.value + 1) + (cz & 7) * 8);
            asm volatile("ld.global.nc.v2.u32 {%0,%1}, [%2];" : "=r"(b2v.x), "=r"(b2v.y) : "l"(P.b2 + 4 * cz));
        };
        auto mlp_shared = [&](auto L) {
            const int lz = lane;
            hpa = pin(sb + SM_PART + warp * 256 + ((lz & 2) * 4 + (lz >> 2)) * 16 + (L.value ? 0 : (lz & 1) * 4));
            hsa = pin(sb + SM_PART + (lz & 15) * 16); hst = pin(sb + SM_PART + (lz & 15) * 16 + warp * 256 + 8 + (lz >> 4) * 4);
            w2a = pin(sb + (L.value ? 3 * TILE : SM_W2) + ((lz & 3) * 10 + 2 * warp) * 128 + (((lz >> 2) ^ ((2 * lz + 2 * warp) & 6)) << 4));
            la = sb + (L.value ? 2 * TILE : SM_W1) + warp * 4096 + (lz & 4) * 512 + (lz & 2) * 64 + (lz & 1) * 32 + (lz >> 4) * 64 + ((((lz >> 3) ^ (lz >> 1)) & 1) << 4);
            b1v = ldsf(sb + SM_B1 + (lz & 15) * 4);
            if (L.value) { la = pin(la); cs1 = ldsf(sb + SM_ML + (lz & 15) * 4); }
            else fresh();
        };
        uint32_t pa;
        unsigned char* rop;
        uint32_t wpa;
        float sc1;
        auto sum_setup = [&](auto L) {
            const int lz = lane, word = warp * 128 + (cta & 3) * 32 + lz;
            wpa = pin(sb + SM_RING + warp * 1536 + ((((lz >> 2) * 8 + (lz & 1) * 4) * 4) ^ ((((lz >> 1) ^ (lz >> 4)) & 1) ? 256 + 64 : 0)));
            sc1 = pinf(fx2_scale(ldsf(sb + SM_FXS)) * 0.25f);
            pa = pin(sb + SM_RING + warp * 256 + ((lz * 4) ^ ((warp & 1) * 64)));
            rop = pin(accg + 2 * L.value * ACC_BYTES + (word >> 4) * acc_pitch(0) + (word & 15) * 4);
        };
        auto out_proj = [&](auto L) {
            TSTAMP2(3);
            CSTAMP(0, __float_as_uint(acc[2][1]));
            __syncwarp();
#pragma unroll
            for (int j = 0; j < 3; j++) {
                if (L.value == 0 && (t & 2)) { acc[j][0] = acc[j][2]; acc[j][1] = acc[j][3]; }
                sts64f(osa + 256 * j, acc[j][0], acc[j][1]);
            }
            __syncthreads();
            {
                float s[8];
#pragma unroll
                for (int w = 0; w < 8; w++) s[w] = ldsf(ora + w * 768);
                const uint4 fa = lds128(sb + SM_FAC), fb = lds128(sb + SM_FAC + 16);
            CSTAMP(1, __float_as_uint(s[0]));
                const float own = ((s[0] * __uint_as_float(fa.x) + s[1] * __uint_as_float(fa.y)) + (s[2] * __uint_as_float(fa.z) + s[3] * __uint_as_float(fa.w))) +
                                  ((s[4] * __uint_as_float(fb.x) + s[5] * __uint_as_float(fb.y)) + (s[6] * __uint_as_float(fb.z) + s[7] * __uint_as_float(fb.w)));
                st_rlx_if(lane < 24, olb + (cta & 3) * 256, ll_pack(own, otag));
            CSTAMP(2, __float_as_uint(own));
            }
            TSTAMPL(29);
            if (L.value == 0) fresh();
            if (L.value) wo_at(IC<6>{});
            if (L.value == 0 && warp == 7) {
#pragma unroll 1
                for (int it = 0; it < SPIN; it++) {
                    uint32_t v; asm volatile("ld.acquire.gpu.global.u32 %0, [%1];" : "=r"(v) : "l"(&P.g->zeroed) : "memory");
                    if (__all_sync(~0u, v == (lds32(sb + SM_EPOCH) + 1) * 80)) break;
                }
            }
            constexpr int NW = L.value ? NWO1 : 3;
            uint4 v[5][3];
            u64 ow[4];
            auto read_wo = [&](auto J) {
#pragma unroll
                for (int p = 0; p < 3; p++) v[J.value][p] = lds128(((J.value & 1) ? owa ^ 144 : owa) + ring_hs(64 + J.value) * HALF + p * 512);
            };
            static_for<0, NW>([&](auto J) {
                if (L.value && J.value == 0) { sum_setup(L); maskA = pin(maskA); maskB = pin(maskB); }
                if (J.value == 2) { ll_look<256>(olb, ow); if (L.value) { mlp_shared(L); mlp_global(L); } }
                mbar_wait(sb + SM_CBAR + (CB_WO + J.value) * 8, L.value);
                read_wo(J);
                if (L.value == 0 && J.value == 2) {
                    __syncwarp();
                    if (elect() && cnt_inc(sb + SM_CNT + CB_W1 * 8, 7) == 7) issue_w(L, 0);
                    __syncwarp();
                }
                if (L.value == 1 && J.value == 2) {
                    if (warp == 7 && elect()) issue_w(L, 0);
                    __syncwarp();
                }
            });
            sched_fence();
            const float o = ll_gather<256>(olb, otag, ow);
            CSTAMP(3, __float_as_uint(o));
            TSTAMP2(4);
            bool ok = true;
            if constexpr (NW < 5) ok = mbar_test(sb + SM_CBAR + (CB_WO + 4) * 8, L.value);
            if constexpr (NW < 4) ok &= mbar_test(sb + SM_CBAR + (CB_WO + 3) * 8, L.value);
            const uint32_t od = pack_bf(o, o);
            uint32_t oa[3], ob[3];
#pragma unroll
            for (int p = 0; p < 3; p++) { const uint32_t op = __shfl_sync(~0u, od, 8 * p + orow); oa[p] = op & maskA; ob[p] = op & maskB; }
            CSTAMP(4, oa[2]);
            float y[5][4];
#pragma unroll
            for (int j = 0; j < 5; j++) y[j][0] = y[j][1] = y[j][2] = y[j][3] = 0.f;
            auto rest = [&]() {
                if (!ok) static_for<NW, 5>([&](auto J) { mbar_wait(sb + SM_CBAR + (CB_WO + J.value) * 8, L.value); });
                static_for<NW, 5>(read_wo);
                __syncwarp();
            };
            if (L.value) rest();
#pragma unroll
            for (int p = 0; p < 3; p++)
#pragma unroll
                for (int j = 0; j < NW; j++) mma(y[j], v[j][p], oa[p], ob[p]);
            if (!L.value) { rest(); sum_setup(L); }
#pragma unroll
            for (int p = 0; p < 3; p++)
#pragma unroll
                for (int j = NW; j < 5; j++) mma(y[j], v[j][p], oa[p], ob[p]);
            CSTAMP(5, __float_as_uint(y[4][3]));
#pragma unroll
            for (int j = 0; j < 5; j += 2) {
                if (j < 4 && (t >> 1) != (g >> 2)) { y[j][0] = y[j + 1][0]; y[j][1] = y[j + 1][1]; y[j][2] = y[j + 1][2]; y[j][3] = y[j + 1][3]; }
                sts128f(wpa + j * 256, y[j]);
            }
            TSTAMP2(5);
        };
        u64 yw[2];
        bool wide;
        float msq = 0.f, yf[4] = {};
        auto mlp_part = [&](auto L) {
            bar_sync(0, 256);
            CSTAMP(6, __float_as_uint(sc1));
            const float s = (sum8(pa, 1536) + xc) + sum8(pa + 128, 1536), sm = s * sc1 + FX2_ONE;
            CSTAMP(7, __float_as_uint(s));
            const bool wide1 = !(fabsf(sm - FX2_ONE) < FX1LIM);
            asm volatile("red.relaxed.gpu.global.add.u32 [%0], %1;" :: "l"(rop), "r"(wide1 ? 0u : __float_as_uint(sm) * 128u + (1u - 0x4b400000u * 128u)) : "memory");
            const uint32_t c0 = clk();
            TSTAMP2(6);
            if (L.value == 0) bar_arrive(2, 256);
            if (wide1) {
                fx_send(rop + 64 + (lane & 15) * 4, s, ldsf(sb + SM_FXS), rop, 64);
                asm volatile("red.relaxed.gpu.global.add.u32 [%0], 1;" :: "l"(rop) : "memory");
            }
            __syncwarp();
            if (L.value == 1 && mlp == 96) { TDUMP(); asm volatile("exit;"); }
            uint4 wf[8], w2r[8];
            uint4 w;
            auto look = [&]() { asm volatile("ld.relaxed.gpu.global.v4.u32 {%0,%1,%2,%3}, [%4];" : "=r"(w.x), "=r"(w.y), "=r"(w.z), "=r"(w.w) : "l"(ap) : "memory"); };
            auto read_w1 = [&]() {
#pragma unroll
                for (int j = 0; j < 8; j++) wf[j] = ldsm_t(la + j * 256);
            };
            auto read_w2 = [&]() {
#pragma unroll
                for (int i = 0; i < 8; i++) w2r[i] = lds128(((i & 1) ? (w2a ^ 16) + 128 : w2a) + (i >> 1) * 5120);
            };
            const float inv = pinf(fx_inv(sc1) * (1.f / 128)), off = L.value ? pinf(fx_inv(sc1) * -0.25f) : inv * -32.f;
            if (L.value == 0) { fresh(); mlp_global(L); }
            mbar_wait(sb + SM_CBAR + CB_W1 * 8, L.value);
            if (L.value == 1) read_w1();
            while (clk() - c0 < AR1D);
            look();
            if (L.value == 0) { mlp_shared(L); read_w1(); bar_arrive(3, 256); }
            else { mbar_wait(sb + SM_CBAR + CB_W2 * 8, 1); read_w2(); }
            TSTAMPL(28);
            {
                sched_fence();
                auto miss = [&]() {
                    xp = make_uint2(pack_bf((float)(int)w.x * inv + off, (float)(int)w.y * inv + off), pack_bf((float)(int)w.z * inv + off, (float)(int)w.w * inv + off));
                    uint32_t a, b;
                    asm("lop3.b32 %0, %1, %2, 32, 0x7e;" : "=r"(a) : "r"(w.x), "r"(w.y));
                    asm("lop3.b32 %0, %1, %2, 32, 0x7e;" : "=r"(b) : "r"(w.z), "r"(w.w));
                    return __any_sync(~0u, (a | b) & 96);
                };
                if (miss()) {
                    int it = 0;
#pragma unroll 1
                    do {
                        if (!__any_sync(~0u, ~(w.x & w.y & w.z & w.w) & 32)) { xp.x = fx1_wide(ap, ldsf(sb + SM_FXS)); xp.y = fx1_wide(ap + 8, ldsf(sb + SM_FXS)); break; }
                        look();
                    } while (miss() & (++it < SPIN));
                }
                CSTAMP(8, w.w);
            }
            TSTAMP2(7);
            CSTAMP(9, xp.y);
            {
                bool ok = true;
                if (L.value == 0) ok = mbar_test(sb + SM_CBAR + CB_W2 * 8, 0);
                const bool ev = L.value || !(g & 1), od = L.value || (g & 1);
                const uint32_t e0 = ev ? xp.x : ONES, e1 = ev ? xp.y : ONES, o0 = od ? xp.x : ONES, o1 = od ? xp.y : ONES;
                float d[8][4];
#pragma unroll
                for (int j = 0; j < 8; j++) { d[j][0] = d[j][1] = d[j][2] = d[j][3] = 0.f; mma(d[j], wf[j], (j & 1) ? o0 : e0, (j & 1) ? o1 : e1); }
                float ss = ln_part(xp, lane);
                ss += shx(ss, 8); ss += shx(ss, 4);
                float r[4], dd;
#pragma unroll
                for (int k = 0; k < 4; k += 1 + L.value) r[k] = d[0][k] + d[1][k ^ 1];
#pragma unroll
                for (int j = 1; j < 4; j++)
#pragma unroll
                    for (int k = 0; k < 4; k += 1 + L.value) add_if(t == j, r[k], d[2 * j][k], d[2 * j + 1][k ^ 1]);
                CSTAMP(10, __float_as_uint(r[2]));
                if (L.value) {
                    dd = ((t & 2) ? r[2] : r[0]) + shx((t & 2) ? r[0] : r[2], 2);
                    ss += shx(ss, 2);
                    dd += shx(dd, 1);
                } else {
                    const float a = ((t & 1) ? r[1] : r[0]) + shx((t & 1) ? r[0] : r[1], 1), b = ((t & 1) ? r[3] : r[2]) + shx((t & 1) ? r[2] : r[3], 1);
                    ss += shx(ss, 2);
                    dd = ((t & 2) ? b : a) + shx((t & 2) ? a : b, 2);
                }
                ss += shx(ss, 1);
                stsf(hpa, dd);
                stsf(hst, ss);
                CSTAMP(11, __float_as_uint(dd + ss));
                if (!ok) mbar_wait(sb + SM_CBAR + CB_W2 * 8, L.value);
            }
            TSTAMPL(25);
            bar_sync(1, 160);
            uint4 hp[5];
#pragma unroll
            for (int w = 0; w < 5; w++) hp[w] = lds128(hsa + w * 256);
            CSTAMP(12, hp[0].x);
            auto hs = [&](auto K) { return sum5(__uint_as_float(word<K.value>(hp[0])), __uint_as_float(word<K.value>(hp[1])), __uint_as_float(word<K.value>(hp[2])),
                                                __uint_as_float(word<K.value>(hp[3])), __uint_as_float(word<K.value>(hp[4]))); };
            const float mean = hs(IC<2>{}) * (1.f / D_MODEL);
            msq = hs(IC<3>{}) * (1.f / D_MODEL);
            if (L.value == 0) cs1 = hs(IC<1>{});
            float hv = hs(IC<0>{}) - mean * cs1;
            CSTAMP(13, __float_as_uint(hv));
            const float sc2 = fx2_scale(msq), lim = fx_inv(sc2) * FX2LIM;
            if (L.value == 0) {
                read_w2();
                bar_arrive(4, 256);
                wide = false;
                if (mlp == 96) return;
            }
            hv = hv * ln_rstd(mean, msq) + b1v;
            CSTAMP(14, __float_as_uint(hv));
            hv = hv * rcp(1.f + ex2(hv * (-2.302208198f - 0.1029432397f * hv * hv)));
            const uint32_t hd = pack_bf(hv, hv);
            CSTAMP(15, hd);
            TSTAMPL(27);
            float ym[4][4];
#pragma unroll
            for (int i = 0; i < 2; i++) {
                ym[i][0] = ym[i][1] = ym[i][2] = ym[i][3] = 0.f;
                const float f = mlp < 64 ? 1.f / 64 : 0.f;
                ym[i + 2][0] = (bf_lo(xp.x) + bf_lo(b2v.x)) * f; ym[i + 2][1] = (bf_hi(xp.x) + bf_hi(b2v.x)) * f;
                ym[i + 2][2] = (bf_lo(xp.y) + bf_lo(b2v.y)) * f; ym[i + 2][3] = (bf_hi(xp.y) + bf_hi(b2v.y)) * f;
            }
#pragma unroll
            for (int i = 0; i < 4; i++) {
                const uint32_t hh = __shfl_sync(~0u, hd, 4 * i + t);
                mma(ym[(i & 1) * 2], w2r[2 * i], hh & maskA, hh & maskB);
                mma(ym[(i & 1) * 2 + 1], w2r[2 * i + 1], hh & maskA, hh & maskB);
            }
#pragma unroll
            for (int k = 0; k < 4; k++) { yf[k] = ym[0][k] + ym[2][k]; add_if(t & 2, yf[k], ym[1][k], ym[3][k]); }
            CSTAMP(16, __float_as_uint(yf[3]));
            yw[0] = fx2_pack(yf[0] * sc2 + FX2_ONE, yf[1] * sc2 + FX2_ONE); yw[1] = fx2_pack(yf[2] * sc2 + FX2_ONE, yf[3] * sc2 + FX2_ONE);
            wide = !(fmaxf(fmaxf(fabsf(yf[0]), fabsf(yf[1])), fmaxf(fabsf(yf[2]), fabsf(yf[3]))) < lim);
            if (wide) yw[0] = yw[1] = 0;
            if (L.value == 0) {
#pragma unroll
                for (int k = 0; k < 2; k++) asm volatile("red.relaxed.gpu.global.add.u64 [%0], %1;" :: "l"(rap + k * 20 * acc_pitch(1)), "l"(yw[k]) : "memory");
            }
        };
        auto send_wide = [&](int pitch) {
#pragma unroll 1
            for (int k = 0; k < 4; k++, yf[0] = yf[1], yf[1] = yf[2], yf[2] = yf[3]) {
                const unsigned char* a = rap + (k >> 1) * 20 * pitch;
                fx_send(a + 64 + (k & 1) * 64, yf[0], msq, a, 256);
            }
            yw[0] = yw[1] = 1;
        };

        pass1();
        o_setup(IC<0>{});
        out_proj(IC<0>{});
        uint32_t c0;
        if (warp < 5) {
            mlp_part(IC<0>{});
            c0 = clk() + (mlp == 96 ? PCD : 0);
            stsf(sb + SM_ML + (lane & 15) * 4, cs1);
            TSTAMP(8);
            if (__any_sync(~0u, wide)) {
                if (wide) {
                    send_wide(acc_pitch(1));
#pragma unroll
                    for (int k = 0; k < 2; k++) asm volatile("red.relaxed.gpu.global.add.u64 [%0], 1;" :: "l"(rap + k * 20 * acc_pitch(1)) : "memory");
                }
                __syncwarp();
            }
            fresh(); calc_offsets();
            load_wq();
        } else {
            bar_sync(0, 256);
            if (warp == 5 && elect()) {
                if (mlp != 96) {
                    tma3_pf(tmk + TM_W2, 0, mlp * 16, POL_NORMAL);
                    asm volatile("cp.async.bulk.prefetch.L2.global.L2::cache_hint [%0], 20480, %1;" :: "l"(P.w1 + mlp * 10240), "l"((u64)POL_NORMAL << 32) : "memory");
                }
            }
            __syncwarp();
            fresh(); calc_offsets();
            load_wq();
#pragma unroll 1
            for (int ph = 0; ph < 3; ph++) {
                bar_sync(ph + 2, 256);
                c0 = clk();
                if (ph == 2) {
                    msq = sum5(ldsf(sb + SM_PART + 12), ldsf(sb + SM_PART + 268), ldsf(sb + SM_PART + 524), ldsf(sb + SM_PART + 780), ldsf(sb + SM_PART + 1036)) * (1.f / D_MODEL);
                    bar_arrive(5, 256);
                }
                if (elect()) {
                    if (ph == 0) asm volatile("fence.proxy.async.shared::cta;" ::: "memory");
                    const uint32_t gap = ph == 0 ? WG1 : ph == 1 ? WG2 : WG3;
                    uint32_t c1 = c0 + (ph == 0 ? WD1 : 0) + (warp - 5) * gap;
#pragma unroll 1
                    for (int k = warp + (ph == 0 ? -5 : ph == 1 ? 9 : 1); k < (ph == 0 ? 9 : ph == 1 ? 20 : 14); k += 3, c1 += 3 * gap) {
                        const int i = ph == 0 && k >= 6 ? k + 23 : k;
                        const uint32_t bar = sb + SM_BAR + (i & 7) * 96 + 32 + (i & 24);
                        while ((int)(clk() - c1) < 0);
                        mbar_expect(bar, SUB);
                        tma_v(sb + SM_RING + i * SUB, tmk,
                              rowc * 3 + (i & 7) * 24 + ((UC<SCH.st[0].unit | SCH.st[1].unit << 8 | SCH.st[2].unit << 16 | SCH.st[3].unit << 24>::value >> (i & 24)) & 15) * 768, bar);
                    }
                    if (ph == 0 && warp == 5) { while ((int)(clk() - c0) < W2T); issue_w(IC<0>{}, 1); }
                }
                __syncwarp();
            }
            c0 += PCD;
        }
        {
            constexpr IC<1> L{};
            fresh();
            const int col = xcol(g & 3, t), cw = j40 + (col >> 2);
            const unsigned char* xa = pin(accg + ACC_BYTES + ((cw >> 3) + (col & 2) * 10) * acc_pitch(1) + (cw & 7) * 8);
            const uint32_t pst = pin(prow + (g * 8 + (t & 1) * 4 + (t & 2)) * 4);
            const float inv = pinf(fx2_inv(msq));
            sts64f(sb + SM_MSQ, msq, inv);
            rap = pin(accg + ACC_BYTES + (c4() >> 3) * acc_pitch(1) + (c4() & 7) * 8);
            fresh();
            maskA = pin(maskA); maskB = pin(maskB);
            u64 w[1];
            uint32_t x1[1], x2[3];
            auto look = [&]() { w[0] = ld_rlx(xa); };
            if (warp < 5) bar_sync(5, 256);
            while ((int)(clk() - c0) < ARDELAY);
            look();
            while ((int)(clk() - c0) < ARDELAY + DPOST);
            if (warp < 5 && elect()) {
                issue_v(IC<3>{}, 0);
                if (warp < 4) issue_v(IC<2>{}, 4);
            }
            __syncwarp();
            fx2_wait<1>([&](int) { return xa; }, look, w, sb + SM_MSQ, inv, x1);
            if (warp < 5) look_rw(); else rw[0] = rw[1] = 96;
#pragma unroll
            for (int i = 0; i < 3; i++) x2[i] = __shfl_sync(~0u, x1[0], 4 * i + t);
            TSTAMP(9);
            CSTAMP(22, x2[2]);
            q_proj(L, x2, pst);
            pass2();
            out_proj(L);
            if (warp >= 5) {
                bar_arrive(0, 256);
                if (warp == 5 && elect()) issue_w(L, 1);
                TDUMP();
                return;
            }
            mlp_part(L);
            u64 old[2];
            auto add = [&]() {
#pragma unroll
                for (int k = 0; k < 2; k++) asm volatile("atom.relaxed.gpu.global.add.u64 %0, [%1], %2;" : "=l"(old[k]) : "l"(rap + k * 20 * acc_pitch(3)), "l"(yw[k]) : "memory");
            };
            add();
            uint32_t* op = pin(reinterpret_cast<uint32_t*>(P.out) + 2 * c4());
            const float inv2 = pinf(fx2_inv(msq));
            if (wide) { send_wide(acc_pitch(3)); add(); }
            TSTAMP(18);
            CSTAMP(17, hi32(yw[1]));
            __syncwarp();
            CSTAMP(18, lo32(old[0]) ^ lo32(old[1]));
#pragma unroll
            for (int k = 0; k < 2; k++) {
                yw[k] += old[k];
                asm volatile("{\n.reg .pred p;\nsetp.eq.u32 p, %2, 96;\n@p st.global.u32 [%0], %1;\n}"
                             :: "l"(op + k), "r"(fx2_get(yw[k], inv2)), "r"(lo32(yw[k]) & 511) : "memory");
            }
            if ((lo32(yw[0]) & 255) == 96 && tid == 0) P.g->epoch = lds32(sb + SM_EPOCH) + 1;
#pragma unroll
            for (int k = 0; k < 2; k++) if ((lo32(yw[k]) & 511) == 256 + 96) op[k] = fx2_wide(rap + k * 20 * acc_pitch(3), msq);
            TSTAMP(19);
            CSTAMP(19, lo32(yw[1]));
            TDUMP();
        }
    }
}

typedef CUresult (*EncodeFn)(CUtensorMap*, CUtensorMapDataType, cuuint32_t, void*, const cuuint64_t*, const cuuint64_t*, const cuuint32_t*,
                             const cuuint32_t*, CUtensorMapInterleave, CUtensorMapSwizzle, CUtensorMapL2promotion, CUtensorMapFloatOOBfill);

}

extern "C" void kernel_launch(void* const* d_in, const int* in_sizes, int n_in, void* d_out, int out_size) {
    (void)in_sizes; (void)n_in; (void)out_size;
    static EncodeFn enc = nullptr;
    static void* scratch = nullptr;
    if (!enc) {
        void* fn = nullptr;
        cudaDriverEntryPointQueryResult qr;
        cudaGetDriverEntryPoint("cuTensorMapEncodeTiled", &fn, cudaEnableDefault, &qr);
        enc = (EncodeFn)fn;
        cudaGetSymbolAddress(&scratch, g_scratch);
        cudaFuncSetAttribute(fused_kernel, cudaFuncAttributeMaxDynamicSharedMemorySize, SM_TOTAL);
    }
    Params P = {};
    auto map3 = [&](int m, int in, cuuint64_t d0, cuuint64_t d1, cuuint64_t d2, cuuint64_t s1, cuuint64_t s2, cuuint32_t b0, cuuint32_t b1, cuuint32_t b2,
                    CUtensorMapSwizzle sw, int promo) {
        const cuuint64_t dim[3] = {d0, d1, d2}, str[2] = {s1, s2};
        const cuuint32_t box[3] = {b0, b1, b2}, ones[3] = {1, 1, 1};
        enc(&P.tm[m], CU_TENSOR_MAP_DATA_TYPE_BFLOAT16, d2 ? 3 : 2, d_in[in], dim, str, box, ones, CU_TENSOR_MAP_INTERLEAVE_NONE, sw, (CUtensorMapL2promotion)promo,
            CU_TENSOR_MAP_FLOAT_OOB_FILL_NONE);
    };
    map3(TM_KH, 1, 64, 3, NHEAD * SK, 128, DH * 2, 64, 3, 32, CU_TENSOR_MAP_SWIZZLE_128B, 0);
    map3(TM_VH, 2, 64, 3, NHEAD * SK, 128, DH * 2, 64, 3, 32, CU_TENSOR_MAP_SWIZZLE_128B, 0);
    map3(TM_VP, 2, 64, 3, NHEAD * SK, 128, DH * 2, 8, 3, 32, CU_TENSOR_MAP_SWIZZLE_NONE, 0);
    map3(TM_V, 2, 64, NHEAD * SK * 3, 0, 128, 0, 64, 24, 0, CU_TENSOR_MAP_SWIZZLE_128B, 0);
    map3(TM_WO, 4, 32, 20, NHEAD * DH, 64, D_MODEL * 2, 32, 1, DH, CU_TENSOR_MAP_SWIZZLE_64B, 2);
    map3(TM_WOP, 4, 32, 20, NHEAD * DH, 64, D_MODEL * 2, 8, 1, DH, CU_TENSOR_MAP_SWIZZLE_NONE, 0);
    map3(TM_WQ, 3, 64, NHEAD * 3, D_MODEL, 128, NHEAD * DH * 2, 64, 3, 32, CU_TENSOR_MAP_SWIZZLE_128B, 0);
    map3(TM_W1, 6, DFF, 128, 5, DFF * 2, DFF * 256, 16, 128, 5, CU_TENSOR_MAP_SWIZZLE_32B, 2);
    map3(TM_W2, 8, 64, 10, DFF, 128, D_MODEL * 2, 64, 10, 16, CU_TENSOR_MAP_SWIZZLE_128B, 0);
    P.x = (const __nv_bfloat16*)d_in[0];
    P.k = (const __nv_bfloat16*)d_in[1];
    P.b1 = (const __nv_bfloat16*)d_in[7];
    P.b2 = (const __nv_bfloat16*)d_in[9];
    P.w1 = (const __nv_bfloat16*)d_in[6];
    P.out = (__nv_bfloat16*)d_out;
    P.g = (Scratch*)(((uintptr_t)scratch + ACC_BYTES - 1) & ~(uintptr_t)(ACC_BYTES - 1));
    for (int i = 0; i < 64; i++) P.tile[i] = make_uint4(SCH.tile[i][0], SCH.tile[i][1], SCH.tile[i][2], 0);
    fused_kernel<<<NCTA, NTHR, SM_TOTAL, cudaStreamPerThread>>>(P);
}
```
